```python
import torch

def _softmax(x, axis=-1):
    return torch.softmax(x, dim=axis)
def _gelu(x):
    return torch.nn.functional.gelu(x, approximate="tanh")
def _silu(x):
    return torch.nn.functional.silu(x)
def _sigmoid(x):
    return torch.sigmoid(x)
def _layernorm(x, axis=-1, eps=1e-5):
    m = x.mean(dim=axis, keepdim=True)
    v = x.var(dim=axis, keepdim=True, unbiased=False)
    return (x - m) / torch.sqrt(v + eps)
def _scatter_add(tgt, idx, src, axis=0):
    return tgt.clone().index_add_(axis, idx, src)
def _segment_sum(src, seg, n):
    out = torch.zeros((n,) + src.shape[1:], dtype=src.dtype)
    return out.index_add_(0, seg, src)
def _pad(x, pw):
    flat = tuple(v for pair in reversed(pw) for v in pair)
    return torch.nn.functional.pad(x, flat)

kernel_name = 'sequential_preLN__sliding_local_dilated__mixer_token_mlp__prompt'

def setup_inputs():

    _w = (lambda a: (lambda t: t.to(torch.bfloat16) if t.is_floating_point() else t)(torch.as_tensor(a)))
    def _A_setup():
        B, S, D = 1, 2048, 448
        return {
            "x": _w((lambda *s: torch.randn(*s, dtype=torch.bfloat16) * 0.05)(B, S, D)),
            "wqkv": _w((lambda *s: torch.randn(*s, dtype=torch.bfloat16) * 0.05)(D, 3 * D)),
            "wo": _w((lambda *s: torch.randn(*s, dtype=torch.bfloat16) * 0.05)(D, D)),
        }
    _A_in = _A_setup()

    def _B_setup():
        B, S, D, F = 1, 2048, 448, 1792
        return {
            "x": _w((lambda *s: torch.randn(*s, dtype=torch.bfloat16) * 0.05)(B, S, D)),
            "w1": _w((lambda *s: torch.randn(*s, dtype=torch.bfloat16) * 1.6)(S, F) * (S ** -0.5)),
            "b1": _w((lambda *s: torch.randn(*s, dtype=torch.bfloat16) * 12.8)(F) * 0.02),
            "w2": _w((lambda *s: torch.randn(*s, dtype=torch.bfloat16) * 0.4)(F, S) * (F ** -0.5)),
            "b2": _w((lambda *s: torch.randn(*s, dtype=torch.bfloat16) * 6.4)(S) * 0.02),
        }
    _B_in = _B_setup()

    return {
        "A_x": _A_in["x"],
        "A_wqkv": _A_in["wqkv"],
        "A_wo": _A_in["wo"],
        "B_x": _B_in["x"],
        "B_w1": _B_in["w1"],
        "B_b1": _B_in["b1"],
        "B_w2": _B_in["w2"],
        "B_b2": _B_in["b2"],
    }

def reference(A_x, A_wqkv, A_wo, B_x, B_w1, B_b1, B_w2, B_b2):
    def _A_ref(x, wqkv, wo):
        B, S, D = x.shape
        H = 16; Dh = D // H
        W, dil = 8, 2
        qkv = (lambda x, *d: x.permute(*d))((x @ wqkv).reshape(B, S, 3, H, Dh), 2, 0, 3, 1, 4)
        q, k, v = qkv[0], qkv[1], qkv[2]
        scale = Dh ** -0.5
        pos = torch.arange(S)
        off = torch.arange(W) * dil
        idx = pos[:, None] - off[None, :]
        mask = idx >= 0
        idx_c = torch.where(mask, idx, 0).reshape(-1)
        kg = k[:, :, idx_c, :].reshape(B, H, S, W, Dh)
        vg = v[:, :, idx_c, :].reshape(B, H, S, W, Dh)
        logits = torch.einsum("bhsd,bhswd->bhsw", q, kg) * scale
        logits = torch.where(mask[None, None, :, :], logits, -1e9)
        attn = _softmax(logits, axis=-1)
        o = torch.einsum("bhsw,bhswd->bhsd", attn, vg)
        return (lambda x, *d: x.permute(*d))(o, 0, 2, 1, 3).reshape(B, S, D) @ wo

    def _B_ref(x, w1, b1, w2, b2):
        B, S, D = x.shape
        h = _layernorm(x, axis=-1)
        u = torch.einsum("bsd,sf->bdf", h, w1) + b1
        u = _gelu(u)
        y = torch.einsum("bdf,fs->bds", u, w2) + b2
        return (lambda x, *d: x.permute(*d))(y, 0, 2, 1)

    x = A_x
    h = x + _A_ref(_layernorm(x, axis=-1), A_wqkv, A_wo)
    h2 = h + _B_ref(_layernorm(h, axis=-1), B_w1, B_b1, B_w2, B_b2)
    return h2
```

```cpp
#include <cuda_runtime.h>
#include <cuda.h>
#include <cuda_bf16.h>
#include <stdint.h>
#include <type_traits>

namespace {

constexpr int kS = 2048, kD = 448, kF = 1792;
constexpr float kEps = 1e-5f;

#define FS 32
__device__ __align__(1024) uint4    g_o[16 * 2 * 4 * 28 * 32];
__device__ __align__(1024) uint4    g_h[kS * kD * 2 / 16];
__device__ __align__(1024) uint4    g_hn[32 * 4 * 896];
__device__ __align__(1024) uint4    g_g[28 * 4 * 896];
__device__ __align__(1024) uint4    g_halo[16 * 8 * 2 * 7 * 32];
__device__ __align__(1024) uint4    g_stats[32 * 64 * 4];
__device__ __align__(1024) uint32_t g_flag_o[16 * 2 * 8 * FS];
__device__ __align__(1024) uint32_t g_flag_h[32 * 4 * FS];
__device__ __align__(1024) uint32_t g_flag_g[4 * 28 * 2 * FS];
__device__ uint32_t g_epoch;
#define TIMEOUT(code)
#define TR(idx)
#define TRW(idx)
#define TRG(idx)

constexpr uint32_t SM_X    = 0;
constexpr uint32_t SM_WKV  = 114688;
constexpr uint32_t SM_RED  = 81920;
constexpr uint32_t SM_B    = 110592;
constexpr uint32_t SM_AHI  = 182272;
constexpr uint32_t SM_BAR  = 231424;
constexpr uint32_t SM_TOTAL = SM_BAR + 1024;
constexpr int NB = 5;
constexpr int B_XF = 0, B_WKVF = 7, B_WQF = 14, B_WOF = 15, B_XC = 17, B_KVC = 18, B_A1D = 19, B_WOC = 20,
              B_AF = 21, B_AE = 37, B_BE = 51, B_RF = 56, B_EP = 58, B_BF = 59  , B_XRF = 69, B_HND = 70, B_COUNT = 71;
#define PFPACE 400
#define PFBAR (B_XF + 6)
constexpr uint32_t SM_EPOCH = SM_BAR + B_COUNT * 8;

constexpr int kSpinLimit = 1 << 15;
__device__ __forceinline__ bool elect_one() {
    uint32_t p;
    asm volatile("{ .reg .pred P; elect.sync _|P, 0xffffffff; selp.u32 %0, 1, 0, P; }" : "=r"(p));
    return p;
}
__device__ __forceinline__ void mbar_init(uint32_t bar, uint32_t cnt) { asm volatile("mbarrier.init.shared::cta.b64 [%0], %1;" :: "r"(bar), "r"(cnt)); }
__device__ __forceinline__ void mbar_expect(uint32_t bar, uint32_t bytes) { asm volatile("mbarrier.arrive.expect_tx.shared::cta.b64 _, [%0], %1;" :: "r"(bar), "r"(bytes) : "memory"); }
__device__ __forceinline__ void mbar_arrive(uint32_t bar) { asm volatile("mbarrier.arrive.shared::cta.b64 _, [%0];" :: "r"(bar) : "memory"); }
__device__ __forceinline__ void mbar_wait(uint32_t bar, uint32_t parity) {
    uint32_t ok; int it = 0;
    do {
        asm volatile("{ .reg .pred p; mbarrier.try_wait.parity.shared::cta.b64 p, [%1], %2; selp.u32 %0, 1, 0, p; }"
                     : "=r"(ok) : "r"(bar), "r"(parity) : "memory");
        if (++it > kSpinLimit) { TIMEOUT((bar & 1023) >> 3); break; }
    } while (!ok);
}
__device__ __forceinline__ void mbar_wait2(uint32_t bar0, uint32_t par0, uint32_t bar1, uint32_t par1) {
    uint32_t ok; int it = 0;
    do {
        asm volatile("{ .reg .pred p, q; mbarrier.try_wait.parity.shared::cta.b64 p, [%1], %2;\n"
                     "mbarrier.try_wait.parity.shared::cta.b64 q, [%3], %4; and.pred p, p, q; selp.u32 %0, 1, 0, p; }"
                     : "=r"(ok) : "r"(bar0), "r"(par0), "r"(bar1), "r"(par1) : "memory");
        if (++it > kSpinLimit) { TIMEOUT((bar0 & 1023) >> 3); break; }
    } while (!ok);
}
template <int N> __device__ __forceinline__ void reg_fence(float (&d)[N]) {
    #pragma unroll
    for (int i = 0; i < N; i++) asm volatile("" : "+f"(d[i]) :: "memory");
}
__device__ __forceinline__ void mbar_wait_cluster(uint32_t bar, uint32_t parity) {
    uint32_t ok; int it = 0;
    do {
        asm volatile("{ .reg .pred p; mbarrier.try_wait.parity.acquire.cluster.shared::cta.b64 p, [%1], %2; selp.u32 %0, 1, 0, p; }"
                     : "=r"(ok) : "r"(bar), "r"(parity) : "memory");
        if (++it > kSpinLimit) { TIMEOUT((bar & 1023) >> 3); break; }
    } while (!ok);
}
__device__ __forceinline__ void mbar_arrive_if(uint32_t bar, bool pred) {
    asm volatile("{ .reg .pred p; setp.ne.u32 p, %1, 0; @p mbarrier.arrive.shared::cta.b64 _, [%0]; }" :: "r"(bar), "r"((uint32_t)pred) : "memory");
}
__device__ __forceinline__ void warp_arrive(uint32_t bar) { __syncwarp(); if (elect_one()) mbar_arrive(bar); }
__device__ __forceinline__ void tma2d(uint32_t dst, const CUtensorMap* m, int c0, int c1, uint32_t bar) {
    asm volatile("cp.async.bulk.tensor.2d.shared::cluster.global.mbarrier::complete_tx::bytes [%0], [%1, {%3, %4}], [%2];"
                 :: "r"(dst), "l"(m), "r"(bar), "r"(c0), "r"(c1) : "memory");
}
__device__ __forceinline__ void bulk_g2s(uint32_t dst, const void* src, uint32_t bytes, uint32_t bar) {
    asm volatile("cp.async.bulk.shared::cluster.global.mbarrier::complete_tx::bytes [%0], [%1], %2, [%3];"
                 :: "r"(dst), "l"(src), "r"(bytes), "r"(bar) : "memory");
}
__device__ __forceinline__ void wg_fence()  { asm volatile("wgmma.fence.sync.aligned;" ::: "memory"); }
__device__ __forceinline__ void wg_commit() { asm volatile("wgmma.commit_group.sync.aligned;" ::: "memory"); }
template <int N> __device__ __forceinline__ void wg_wait() { asm volatile("wgmma.wait_group.sync.aligned %0;" :: "n"(N) : "memory"); }
__device__ __forceinline__ void named_bar(int id, int n) { asm volatile("bar.sync %0, %1;" :: "r"(id), "r"(n) : "memory"); }
__device__ __forceinline__ void fence_gpu() { asm volatile("fence.acq_rel.gpu;" ::: "memory"); }
__device__ __forceinline__ void fence_async_global() { asm volatile("fence.proxy.async.global;" ::: "memory"); }
__device__ __forceinline__ void fence_async_smem() { asm volatile("fence.proxy.async.shared::cta;" ::: "memory"); }
__device__ __forceinline__ void st_flag(uint32_t* p, uint32_t v) { asm volatile("st.relaxed.gpu.global.u32 [%0], %1;" :: "l"(p), "r"(v) : "memory"); }
__device__ __forceinline__ uint32_t ld_acq(const uint32_t* p) { uint32_t v; asm volatile("ld.acquire.gpu.global.u32 %0, [%1];" : "=r"(v) : "l"(p) : "memory"); return v; }
__device__ __forceinline__ uint4 ld_rlx4(const uint4* p) {
    uint4 v; asm volatile("ld.relaxed.gpu.global.v4.u32 {%0,%1,%2,%3}, [%4];" : "=r"(v.x), "=r"(v.y), "=r"(v.z), "=r"(v.w) : "l"(p) : "memory"); return v;
}
__device__ __forceinline__ void st_ll(uint4* p, uint32_t a, uint32_t b, uint32_t tag) {
    uint64_t lo = ((uint64_t)tag << 32) | a, hi = ((uint64_t)tag << 32) | b;
    asm volatile("st.relaxed.gpu.global.v2.u64 [%0], {%1,%2};" :: "l"(p), "l"(lo), "l"(hi) : "memory");
}
__device__ __forceinline__ bool ld_ll(const uint4* p, uint32_t& a, uint32_t& b, uint32_t tag) {
    uint64_t lo, hi;
    asm volatile("ld.relaxed.gpu.global.v2.u64 {%0,%1}, [%2];" : "=l"(lo), "=l"(hi) : "l"(p) : "memory");
    a = (uint32_t)lo; b = (uint32_t)hi;
    return (uint32_t)(lo >> 32) == tag && (uint32_t)(hi >> 32) == tag;
}
__device__ __forceinline__ uint2 ld_rlx2(const uint2* p) {
    uint2 v; asm volatile("ld.relaxed.gpu.global.v2.u32 {%0,%1}, [%2];" : "=r"(v.x), "=r"(v.y) : "l"(p) : "memory"); return v;
}
__device__ __forceinline__ void sts4(uint32_t a, uint32_t x, uint32_t y, uint32_t z, uint32_t w) { asm volatile("st.shared.v4.u32 [%0], {%1,%2,%3,%4};" :: "r"(a), "r"(x), "r"(y), "r"(z), "r"(w) : "memory"); }
__device__ __forceinline__ uint4 lds4(uint32_t a) { uint4 v; asm volatile("ld.shared.v4.u32 {%0,%1,%2,%3}, [%4];" : "=r"(v.x), "=r"(v.y), "=r"(v.z), "=r"(v.w) : "r"(a) : "memory"); return v; }
__device__ __forceinline__ uint32_t pack_bf16(float lo, float hi) { uint32_t r; asm("cvt.rn.bf16x2.f32 %0, %1, %2;" : "=r"(r) : "f"(hi), "f"(lo)); return r; }
__device__ __forceinline__ float bf_lo(uint32_t v) { return __uint_as_float(v << 16); }
__device__ __forceinline__ float bf_hi(uint32_t v) { return __uint_as_float(v & 0xffff0000u); }
__device__ __forceinline__ uint32_t sub_bf16x2(uint32_t a, uint32_t b) { uint32_t r; asm("sub.rn.bf16x2 %0, %1, %2;" : "=r"(r) : "r"(a), "r"(b)); return r; }
__device__ __forceinline__ uint32_t movm(uint32_t a) { uint32_t r; asm volatile("movmatrix.sync.aligned.m8n8.trans.b16 %0, %1;" : "=r"(r) : "r"(a)); return r; }
__device__ __forceinline__ float ex2(float x) { float r; asm("ex2.approx.ftz.f32 %0, %1;" : "=f"(r) : "f"(x)); return r; }
__device__ __forceinline__ float rcp(float x) { float r; asm("rcp.approx.ftz.f32 %0, %1;" : "=f"(r) : "f"(x)); return r; }
__device__ __forceinline__ void mma16816(float (&c)[4], uint32_t a0, uint32_t a1, uint32_t a2, uint32_t a3, uint32_t b0, uint32_t b1) {
    asm("mma.sync.aligned.m16n8k16.row.col.f32.bf16.bf16.f32 {%0,%1,%2,%3}, {%4,%5,%6,%7}, {%8,%9}, {%0,%1,%2,%3};"
        : "+f"(c[0]), "+f"(c[1]), "+f"(c[2]), "+f"(c[3]) : "r"(a0), "r"(a1), "r"(a2), "r"(a3), "r"(b0), "r"(b1));
}
__device__ __forceinline__ void mma1688(float (&c)[4], uint32_t a0, uint32_t a1, uint32_t b0) {
    asm("mma.sync.aligned.m16n8k8.row.col.f32.bf16.bf16.f32 {%0,%1,%2,%3}, {%4,%5}, {%6}, {%0,%1,%2,%3};"
        : "+f"(c[0]), "+f"(c[1]), "+f"(c[2]), "+f"(c[3]) : "r"(a0), "r"(a1), "r"(b0));
}
__device__ __forceinline__ float quad_sum(float v) { v += __shfl_xor_sync(~0u, v, 1); v += __shfl_xor_sync(~0u, v, 2); return v; }
__device__ __forceinline__ float quad_max(float v) { v = fmaxf(v, __shfl_xor_sync(~0u, v, 1)); v = fmaxf(v, __shfl_xor_sync(~0u, v, 2)); return v; }
__device__ __forceinline__ uint32_t desc_lo(uint32_t addr, uint32_t lbo) { return ((addr & 0x3FFFF) >> 4) | ((lbo >> 4) << 16); }
template <int I, int N, class F> __device__ __forceinline__ void static_for(F&& f) {
    if constexpr (I < N) { f(std::integral_constant<int, I>{}); static_for<I + 1, N>(f); }
}
__device__ __forceinline__ uint32_t opaque(uint32_t v) { asm volatile("" : "+r"(v)); return v; }
template <int BOFF, int SCALE_D>
__device__ __forceinline__ void wgmma_rs_n56(float (&d)[28], uint32_t a0, uint32_t a1, uint32_t a2, uint32_t a3, uint32_t blo) {
    asm volatile("{ .reg .b32 lb; .reg .b64 db;\n"
        "add.u32 lb, %32, %33; mov.b64 db, {lb, 0x40000040};\n"
        "wgmma.mma_async.sync.aligned.m64n56k16.f32.bf16.bf16 "
        "{%0, %1, %2, %3, %4, %5, %6, %7, %8, %9, %10, %11, %12, %13, %14, %15, %16, %17, %18, %19, %20, %21, %22, %23, %24, %25, %26, %27}, "
        "{%28, %29, %30, %31}, db, %34, 1, 1, 1; }"
        : "+f"(d[0]), "+f"(d[1]), "+f"(d[2]), "+f"(d[3]), "+f"(d[4]), "+f"(d[5]), "+f"(d[6]), "+f"(d[7]),
        "+f"(d[8]), "+f"(d[9]), "+f"(d[10]), "+f"(d[11]), "+f"(d[12]), "+f"(d[13]), "+f"(d[14]), "+f"(d[15]),
        "+f"(d[16]), "+f"(d[17]), "+f"(d[18]), "+f"(d[19]), "+f"(d[20]), "+f"(d[21]), "+f"(d[22]), "+f"(d[23]),
        "+f"(d[24]), "+f"(d[25]), "+f"(d[26]), "+f"(d[27])
        : "r"(a0), "r"(a1), "r"(a2), "r"(a3), "r"(blo), "n"(BOFF >> 4), "n"(SCALE_D));
}
template <int BOFF, int SCALE_D>
__device__ __forceinline__ void wgmma_rs_n128(float (&d)[64], uint32_t a0, uint32_t a1, uint32_t a2, uint32_t a3, uint32_t blo) {
    asm volatile("{ .reg .b32 lb; .reg .b64 db;\n"
        "add.u32 lb, %68, %69; mov.b64 db, {lb, 0x40000040};\n"
        "wgmma.mma_async.sync.aligned.m64n128k16.f32.bf16.bf16 "
        "{%0, %1, %2, %3, %4, %5, %6, %7, %8, %9, %10, %11, %12, %13, %14, %15, %16, %17, %18, %19, %20, %21, %22, %23, %24, %25, %26, %27, %28, %29, %30, %31, %32, %33, %34, %35, %36, %37, %38, %39, %40, %41, %42, %43, %44, %45, %46, %47, %48, %49, %50, %51, %52, %53, %54, %55, %56, %57, %58, %59, %60, %61, %62, %63}, "
        "{%64, %65, %66, %67}, db, %70, 1, 1, 1; }"
        : "+f"(d[0]), "+f"(d[1]), "+f"(d[2]), "+f"(d[3]), "+f"(d[4]), "+f"(d[5]), "+f"(d[6]), "+f"(d[7]),
        "+f"(d[8]), "+f"(d[9]), "+f"(d[10]), "+f"(d[11]), "+f"(d[12]), "+f"(d[13]), "+f"(d[14]), "+f"(d[15]),
        "+f"(d[16]), "+f"(d[17]), "+f"(d[18]), "+f"(d[19]), "+f"(d[20]), "+f"(d[21]), "+f"(d[22]), "+f"(d[23]),
        "+f"(d[24]), "+f"(d[25]), "+f"(d[26]), "+f"(d[27]), "+f"(d[28]), "+f"(d[29]), "+f"(d[30]), "+f"(d[31]),
        "+f"(d[32]), "+f"(d[33]), "+f"(d[34]), "+f"(d[35]), "+f"(d[36]), "+f"(d[37]), "+f"(d[38]), "+f"(d[39]),
        "+f"(d[40]), "+f"(d[41]), "+f"(d[42]), "+f"(d[43]), "+f"(d[44]), "+f"(d[45]), "+f"(d[46]), "+f"(d[47]),
        "+f"(d[48]), "+f"(d[49]), "+f"(d[50]), "+f"(d[51]), "+f"(d[52]), "+f"(d[53]), "+f"(d[54]), "+f"(d[55]),
        "+f"(d[56]), "+f"(d[57]), "+f"(d[58]), "+f"(d[59]), "+f"(d[60]), "+f"(d[61]), "+f"(d[62]), "+f"(d[63])
        : "r"(a0), "r"(a1), "r"(a2), "r"(a3), "r"(blo), "n"(BOFF >> 4), "n"(SCALE_D));
}
template <int AOFF, int BOFF, int SCALE_D>
__device__ __forceinline__ void wgmma_ss_n112(float (&d)[56], uint32_t alo, uint32_t blo) {
    asm volatile("{ .reg .b32 la, lb; .reg .b64 da, db;\n"
        "add.u32 la, %56, %58; add.u32 lb, %57, %59;\n"
        "mov.b64 da, {la, 0x40000040}; mov.b64 db, {lb, 8};\n"
        "wgmma.mma_async.sync.aligned.m64n112k16.f32.bf16.bf16 "
        "{%0, %1, %2, %3, %4, %5, %6, %7, %8, %9, %10, %11, %12, %13, %14, %15, %16, %17, %18, %19, %20, %21, %22, %23, %24, %25, %26, %27, %28, %29, %30, %31, %32, %33, %34, %35, %36, %37, %38, %39, %40, %41, %42, %43, %44, %45, %46, %47, %48, %49, %50, %51, %52, %53, %54, %55}, "
        "da, db, %60, 1, 1, 1, 1; }"
        : "+f"(d[0]), "+f"(d[1]), "+f"(d[2]), "+f"(d[3]), "+f"(d[4]), "+f"(d[5]), "+f"(d[6]), "+f"(d[7]),
        "+f"(d[8]), "+f"(d[9]), "+f"(d[10]), "+f"(d[11]), "+f"(d[12]), "+f"(d[13]), "+f"(d[14]), "+f"(d[15]),
        "+f"(d[16]), "+f"(d[17]), "+f"(d[18]), "+f"(d[19]), "+f"(d[20]), "+f"(d[21]), "+f"(d[22]), "+f"(d[23]),
        "+f"(d[24]), "+f"(d[25]), "+f"(d[26]), "+f"(d[27]), "+f"(d[28]), "+f"(d[29]), "+f"(d[30]), "+f"(d[31]),
        "+f"(d[32]), "+f"(d[33]), "+f"(d[34]), "+f"(d[35]), "+f"(d[36]), "+f"(d[37]), "+f"(d[38]), "+f"(d[39]),
        "+f"(d[40]), "+f"(d[41]), "+f"(d[42]), "+f"(d[43]), "+f"(d[44]), "+f"(d[45]), "+f"(d[46]), "+f"(d[47]),
        "+f"(d[48]), "+f"(d[49]), "+f"(d[50]), "+f"(d[51]), "+f"(d[52]), "+f"(d[53]), "+f"(d[54]), "+f"(d[55])
        : "r"(alo), "r"(blo), "n"(AOFF >> 4), "n"(BOFF >> 4), "n"(SCALE_D));
}

struct Params {
    const __nv_bfloat16 *x, *w1, *w2, *b1, *b2;
    __nv_bfloat16* out;
};

__global__ void __cluster_dims__(2, 1, 1) __launch_bounds__(384, 1)
fused_kernel(const __grid_constant__ CUtensorMap mX, const __grid_constant__ CUtensorMap mWqkv,
             const __grid_constant__ CUtensorMap mWo, const __grid_constant__ CUtensorMap mW1,
             const __grid_constant__ CUtensorMap mW2, const Params prm)
{
    extern __shared__ __align__(1024) unsigned char smem_raw[];
    uint32_t sb = (uint32_t)__cvta_generic_to_shared(smem_raw);
    asm volatile("mov.u32 %0, %0;" : "+r"(sb));
    const uint32_t bar0 = sb + SM_BAR;
    auto BAR = [&](int i) { return bar0 + 8u * i; };

    const int tid = threadIdx.x, lane = tid & 31;
    const int warp = __shfl_sync(~0u, tid >> 5, 0);
    const int b = blockIdx.x;
    const int rank = b & 1;
    const int res = (b >> 1) & 7, rnd = b >> 4;
    const int hg = (res & 1) * 4 + (rnd & 3);
    const int ti = (res >> 1) * 4 + (rnd >> 2) * 2 + rank;
    const int a2p = res & 1, a2j = rnd & 3;
    const int gj = res & 1;
    const bool g1_on = rnd != 7;
    const int g1f = (res >> 1) * 7 + rnd;
    const int g2j = rnd & 1, g2s = res * 4 + (rnd >> 1);

    if (tid == 32) { TRG(60); TRW(59); }
    if (tid == 0) {
        if (sb & 1023) __trap();
        for (int i = 0; i < B_COUNT; i++) {
            uint32_t cnt = 1;
            if (i >= B_XC && i <= B_WOC) cnt = 8;
            if (i >= B_AE && i < B_AE + 14) cnt = 4;
            if (i >= B_BE && i < B_BE + NB) cnt = 4;
            mbar_init(BAR(i), cnt);
        }
        asm volatile("fence.mbarrier_init.release.cluster;" ::: "memory");
    }
    __syncthreads();
    if (tid < 256) TR(0);
    if (tid == 0) TRG(61);

    if (warp >= 8) {
        asm volatile("setmaxnreg.dec.sync.aligned.u32 40;");
        if (warp < 10) asm volatile("barrier.cluster.arrive.relaxed.aligned;" ::: "memory");
        if (warp == 8) {
            const int wcol = hg * 56 - (hg & 1) * 8;
            if (elect_one()) {
                #pragma unroll 1
                for (int kb = 0; kb < 7; kb++) {
                    mbar_expect(BAR(B_XF + kb), 16384);
                    tma2d(sb + SM_X + kb * 8192, &mX, kb * 64, ti * 64, BAR(B_XF + kb));
                    tma2d(sb + SM_X + 57344 + kb * 8192, &mX, kD + kb * 64, ti * 64, BAR(B_XF + kb));
                }
                #pragma unroll 1
                for (int s = 0; s < 7; s++) {
                    mbar_expect(BAR(B_WKVF + s), 16384);
                    tma2d(sb + SM_WKV + s * 16384, &mWqkv, kD + wcol, s * 64, BAR(B_WKVF + s));
                    tma2d(sb + SM_WKV + s * 16384 + 8192, &mWqkv, 2 * kD + wcol, s * 64, BAR(B_WKVF + s));
                }
            }
            __syncwarp();
            mbar_wait(BAR(B_XC), 0);
            if (elect_one()) {
                mbar_expect(BAR(B_WQF), 57344);
                #pragma unroll 1
                for (int s = 0; s < 7; s++)
                    tma2d(sb + SM_X + s * 8192, &mWqkv, wcol, s * 64, BAR(B_WQF));
                mbar_expect(BAR(B_XRF), a2j == 3 ? 8192 : 16384);
                tma2d(sb + SM_X + 8 * 8192, &mX, a2p * kD + a2j * 128, ti * 64, BAR(B_XRF));
                if (a2j != 3) tma2d(sb + SM_X + 9 * 8192, &mX, a2p * kD + a2j * 128 + 64, ti * 64, BAR(B_XRF));
            }
            __syncwarp();
            const CUtensorMap* mA = g1_on ? &mW1 : &mW2;
            auto load_slab = [&](int s, bool second) {
                if (elect_one()) {
                    mbar_expect(BAR(B_AF + s), 8192);
                    const uint32_t dst = sb + (s < 10 ? s * 8192 : SM_AHI + (s - 10) * 8192);
                    if (g1_on && !second) tma2d(dst, &mW1, (s & 1) * kF + g1f * 64, (rank * 8 + (s >> 1)) * 64, BAR(B_AF + s));
                    else                  tma2d(dst, &mW2, g2s * 64, (rank * 14 + s) * 64, BAR(B_AF + s));
                }
                __syncwarp();
            };
            (void)mA;
            mbar_wait(BAR(B_KVC), 0);
            if (elect_one()) {
                #pragma unroll 1
                for (int h = 0; h < 2; h++) {
                    mbar_expect(BAR(B_WOF + h), a2j == 3 ? 28672 : 57344);
                    tma2d(sb + SM_WKV + h * 57344, &mWo, a2j * 128, h * 224, BAR(B_WOF + h));
                    if (a2j != 3) tma2d(sb + SM_WKV + h * 57344 + 28672, &mWo, a2j * 128 + 64, h * 224, BAR(B_WOF + h));
                }
            }
            __syncwarp();
            mbar_wait(BAR(B_A1D), 0);
            #pragma unroll 1
            for (int s = 0; s < (g1_on ? 16 : 14); s++) {
                if (s == 8) mbar_wait(BAR(B_WOC), 0);
                load_slab(s, false);
                if (s >= 2) mbar_wait(BAR(B_AF + s - 2), 0);
            }
            if (g1_on) {
                #pragma unroll 1
                for (int s = 0; s < 14; s++) { mbar_wait(BAR(B_AE + s), 0); load_slab(s, true); }
            }
        } else if (warp == 9) {
            mbar_wait(BAR(B_EP), 0);
            uint32_t tag; asm volatile("ld.shared.u32 %0, [%1];" : "=r"(tag) : "r"(sb + SM_EPOCH) : "memory");
            mbar_wait(BAR(B_HND), 0);
            int slot = 0; uint32_t ph = 1;
            #pragma unroll 1
            for (int e = g1_on ? 0 : 2; e < 4; e++) {
                const int str = e & 1;
                const bool g2 = e >= 2;
                const int nst = g2 ? 14 : 16;
                const int dsub = (g2 ? g2j : gj) + 2 * str;
                const uint32_t* fp = g2 ? &g_flag_g[((dsub * 28 + rank * 14) * 2 + min(lane, 27)) * FS]
                                        : &g_flag_h[((rank * 16 + (lane >> 1)) * 4 + max(dsub - (lane & 1), 0)) * FS];
                const uint4* src = g2 ? &g_g[(rank * 14 * 4 + dsub) * 896] : &g_hn[(rank * 16 * 4 + dsub) * 896];
                uint32_t ready = 0;
                #pragma unroll 1
                for (int s = 0; s < nst; s++) {
                    const uint32_t need = ~0u;
                    int it = 0;
                    while ((ready & need) != need) {
                        ready = __ballot_sync(~0u, ld_acq(fp) == tag);
                        if (++it > kSpinLimit) { TIMEOUT(100); break; }
                    }
                    if (s == 0) TRW(40 + e);
                    mbar_wait(BAR(B_BE + slot), ph);
                    if (elect_one()) {
                        mbar_expect(BAR(B_BF + str * NB + slot), 14336);
                        bulk_g2s(sb + SM_B + slot * 14336, src + s * 4 * 896, 14336, BAR(B_BF + str * NB + slot));
                    }
                    __syncwarp();
                    if (++slot == NB) { slot = 0; ph ^= 1; }
                }
            }
        } else if (warp == 10) {
            mbar_wait(BAR(PFBAR), 0);
            const char* p1 = (const char*)prm.w1 + (size_t)b * 57344 + lane * 128;
            const char* p2 = (const char*)prm.w2 + (size_t)b * 57344 + lane * 128;
            uint32_t tnext = (uint32_t)clock();
            #pragma unroll 1
            for (int i = 0; i < 28; i++) {
                asm volatile("prefetch.global.L2 [%0];" :: "l"(i < 14 ? p1 + i * 4096 : p2 + (i - 14) * 4096));
                tnext += PFPACE;
                while ((int)((uint32_t)clock() - tnext) < 0) __nanosleep(40);
            }
        } else {
            if (lane == 0) {
                uint32_t e = *(volatile uint32_t*)&g_epoch + 1;
                asm volatile("st.shared.u32 [%0], %1;" :: "r"(sb + SM_EPOCH), "r"(e) : "memory");
                mbar_arrive(BAR(B_EP));
                mbar_expect(BAR(B_RF + 0), 14336);
                mbar_expect(BAR(B_RF + 1), 14336);
            }
        }
        if (warp < 10) asm volatile("barrier.cluster.wait.aligned;" ::: "memory");
    } else {
        asm volatile("setmaxnreg.inc.sync.aligned.u32 232;");
        const int wg = warp >> 2, w = warp & 3;
        const int g = lane >> 2, t = lane & 3;
        uint32_t tag;
        {
            uint32_t a[28][4];
            float sm0[4] = {0.f, 0.f, 0.f, 0.f}, sm1[4] = {0.f, 0.f, 0.f, 0.f};
            {
                const int r = w * 16 + (lane & 15);
                const uint32_t rowa = sb + SM_X + wg * 57344 + r * 128;
                #pragma unroll
                for (int kb = 0; kb < 7; kb++) {
                    mbar_wait(BAR(B_XF + kb), 0);
                    #pragma unroll
                    for (int q = 0; q < 4; q++) {
                        const uint32_t addr = rowa + kb * 8192 + (((q * 2 + (lane >> 4)) ^ (r & 7)) << 4);
                        uint32_t (&f)[4] = a[kb * 4 + q];
                        asm volatile("ldmatrix.sync.aligned.m8n8.x4.shared.b16 {%0,%1,%2,%3}, [%4];"
                                     : "=r"(f[0]), "=r"(f[1]), "=r"(f[2]), "=r"(f[3]) : "r"(addr) : "memory");
                        if (q & 1) mma16816(sm1, f[0], f[1], f[2], f[3], 0x3F803F80u, 0x3F803F80u);
                        else       mma16816(sm0, f[0], f[1], f[2], f[3], 0x3F803F80u, 0x3F803F80u);
                    }
                }
            }
            const float mean0 = (sm0[0] + sm1[0]) * (1.f / kD), mean1 = (sm0[2] + sm1[2]) * (1.f / kD);
            const uint32_t mb0 = pack_bf16(mean0, mean0), mb1 = pack_bf16(mean1, mean1);
            warp_arrive(BAR(B_XC));
            TR(1);
            float ak[28], av[28], aq[28];
            float ss0 = 0.f, ss1 = 0.f, ss2 = 0.f, ss3 = 0.f;
            const uint32_t dw = desc_lo(sb + (hg & 1) * 16, 0);
            static_for<0, 7>([&](auto S_) {
                constexpr int s = decltype(S_)::value;
                #pragma unroll
                for (int q = 0; q < 4; q++) {
                    uint32_t (&f)[4] = a[s * 4 + q];
                    f[0] = sub_bf16x2(f[0], mb0); f[1] = sub_bf16x2(f[1], mb1);
                    f[2] = sub_bf16x2(f[2], mb0); f[3] = sub_bf16x2(f[3], mb1);
                    ss0 = fmaf(bf_lo(f[0]), bf_lo(f[0]), ss0); ss2 = fmaf(bf_hi(f[0]), bf_hi(f[0]), ss2);
                    ss1 = fmaf(bf_lo(f[1]), bf_lo(f[1]), ss1); ss3 = fmaf(bf_hi(f[1]), bf_hi(f[1]), ss3);
                    ss0 = fmaf(bf_lo(f[2]), bf_lo(f[2]), ss0); ss2 = fmaf(bf_hi(f[2]), bf_hi(f[2]), ss2);
                    ss1 = fmaf(bf_lo(f[3]), bf_lo(f[3]), ss1); ss3 = fmaf(bf_hi(f[3]), bf_hi(f[3]), ss3);
                }
                mbar_wait(BAR(B_WKVF + s), 0);
                wg_fence();
                static_for<0, 4>([&](auto Q_) {
                    constexpr int q = decltype(Q_)::value;
                    uint32_t (&f)[4] = a[s * 4 + q];
                    wgmma_rs_n56<SM_WKV + s * 16384 + q * 2048, (s | q) != 0>(ak, f[0], f[1], f[2], f[3], dw);
                    wgmma_rs_n56<SM_WKV + s * 16384 + q * 2048 + 8192, (s | q) != 0>(av, f[0], f[1], f[2], f[3], dw);
                });
                wg_commit();
            });
            auto q_chunk = [&](auto C_) {
                wg_fence();
                static_for<0, 7>([&](auto K_) {
                    constexpr int k = decltype(C_)::value * 7 + decltype(K_)::value;
                    wgmma_rs_n56<SM_X + k * 2048, k != 0>(aq, a[k][0], a[k][1], a[k][2], a[k][3], dw);
                });
                wg_commit();
            };
            const float dl0 = mean0 - bf_lo(mb0), dl1 = mean1 - bf_lo(mb1);
            const float rs0 = rsqrtf(fmaxf(quad_sum(ss0 + ss2) * (1.f / kD) - dl0 * dl0, 0.f) + kEps);
            const float rs1 = rsqrtf(fmaxf(quad_sum(ss1 + ss3) * (1.f / kD) - dl1 * dl1, 0.f) + kEps);
            mbar_wait(BAR(B_EP), 0);
            asm volatile("ld.shared.u32 %0, [%1];" : "=r"(tag) : "r"(sb + SM_EPOCH) : "memory");
            mbar_wait(BAR(B_WQF), 0);
            q_chunk(std::integral_constant<int, 0>{});
            wg_wait<1>();
            reg_fence(ak); reg_fence(av);
            TR(2);
            warp_arrive(BAR(B_KVC));
            uint32_t kf[3][7], vf[3][7];
            #pragma unroll
            for (int c = 0; c < 7; c++) {
                kf[1][c] = pack_bf16(ak[4 * c] * rs0, ak[4 * c + 1] * rs0);
                kf[2][c] = pack_bf16(ak[4 * c + 2] * rs1, ak[4 * c + 3] * rs1);
                vf[1][c] = movm(pack_bf16(av[4 * c] * rs0, av[4 * c + 1] * rs0));
                vf[2][c] = movm(pack_bf16(av[4 * c + 2] * rs1, av[4 * c + 3] * rs1));
            }
            const uint32_t stg = sb + SM_RED + (1 - wg) * 16384 + lane * 16;
            if (w == 3) {
                uint4* hp = &g_halo[((ti * 8 + hg) * 2 + wg) * 7 * 32 + lane];
                #pragma unroll
                for (int c = 0; c < 7; c++) st_ll(hp + c * 32, kf[2][c], vf[2][c], tag);
            } else {
                sts4(stg + w * 2048 + 0,    kf[2][0], kf[2][1], kf[2][2], kf[2][3]);
                sts4(stg + w * 2048 + 512,  kf[2][4], kf[2][5], kf[2][6], vf[2][0]);
                sts4(stg + w * 2048 + 1024, vf[2][1], vf[2][2], vf[2][3], vf[2][4]);
                sts4(stg + w * 2048 + 1536, vf[2][5], vf[2][6], 0u, 0u);
            }
            q_chunk(std::integral_constant<int, 1>{});
            named_bar(1 + wg, 128);
            q_chunk(std::integral_constant<int, 2>{});
            q_chunk(std::integral_constant<int, 3>{});
            if (w == 0) {
                if (ti > 0) {
                    const uint4* hp = &g_halo[(((ti - 1) * 8 + hg) * 2 + wg) * 7 * 32 + lane];
                    int it = 0; bool ok;
                    do {
                        ok = true;
                        #pragma unroll
                        for (int c = 0; c < 7; c++) ok &= ld_ll(hp + c * 32, kf[0][c], vf[0][c], tag);
                        if (++it > kSpinLimit) { TIMEOUT(101); break; }
                    } while (!__all_sync(~0u, ok));
                } else {
                    #pragma unroll
                    for (int c = 0; c < 7; c++) { kf[0][c] = 0u; vf[0][c] = 0u; }
                }
            } else {
                const uint4 u0 = lds4(stg + (w - 1) * 2048), u1 = lds4(stg + (w - 1) * 2048 + 512),
                            u2 = lds4(stg + (w - 1) * 2048 + 1024), u3 = lds4(stg + (w - 1) * 2048 + 1536);
                kf[0][0] = u0.x; kf[0][1] = u0.y; kf[0][2] = u0.z; kf[0][3] = u0.w;
                kf[0][4] = u1.x; kf[0][5] = u1.y; kf[0][6] = u1.z; vf[0][0] = u1.w;
                vf[0][1] = u2.x; vf[0][2] = u2.y; vf[0][3] = u2.z; vf[0][4] = u2.w;
                vf[0][5] = u3.x; vf[0][6] = u3.y;
            }
            TR(3);
            wg_wait<0>();
            reg_fence(aq);
            TR(4);
            fence_async_smem();
            warp_arrive(BAR(B_A1D));
            uint32_t qf[7][2];
            #pragma unroll
            for (int c = 0; c < 7; c++) {
                qf[c][0] = pack_bf16(aq[4 * c] * rs0, aq[4 * c + 1] * rs0);
                qf[c][1] = pack_bf16(aq[4 * c + 2] * rs1, aq[4 * c + 3] * rs1);
            }
            const bool has_prev = (ti > 0) || (w > 0);
            const float sc = 0.18898223650461362f * 1.4426950408889634f;
            const float NEG = -__int_as_float(0x7f800000);
            uint32_t ow[7][2];
            #pragma unroll
            for (int hd = 0; hd < 2; hd++) {
                const int c0 = hd * 3;
                const bool keep = hd == 0 ? (t < 2) : (t >= 2);
                const uint32_t q3a = keep ? qf[3][0] : 0u, q3b = keep ? qf[3][1] : 0u;
                float sc_[3][4];
                #pragma unroll
                for (int n = 0; n < 3; n++) {
                    sc_[n][0] = sc_[n][1] = sc_[n][2] = sc_[n][3] = 0.f;
                    if (hd == 0) {
                        mma16816(sc_[n], qf[0][0], qf[0][1], qf[1][0], qf[1][1], kf[n][0], kf[n][1]);
                        mma16816(sc_[n], qf[2][0], qf[2][1], q3a, q3b, kf[n][2], kf[n][3]);
                    } else {
                        mma16816(sc_[n], q3a, q3b, qf[4][0], qf[4][1], kf[n][3], kf[n][4]);
                        mma16816(sc_[n], qf[5][0], qf[5][1], qf[6][0], qf[6][1], kf[n][5], kf[n][6]);
                    }
                }
                const bool gt0 = 2 * t > g, gt1 = 2 * t + 1 > g;
                const float e0 = (gt0 && has_prev) ? sc_[0][0] : NEG, e1 = (gt1 && has_prev) ? sc_[0][1] : NEG;
                const float e2 = gt0 ? NEG : sc_[1][0], e3 = gt1 ? NEG : sc_[1][1];
                const float f0 = gt0 ? sc_[1][2] : NEG, f1 = gt1 ? sc_[1][3] : NEG;
                const float f2 = gt0 ? NEG : sc_[2][2], f3 = gt1 ? NEG : sc_[2][3];
                const float me = quad_max(fmaxf(fmaxf(e0, e1), fmaxf(e2, e3))) * sc;
                const float mf = quad_max(fmaxf(fmaxf(f0, f1), fmaxf(f2, f3))) * sc;
                const float p0 = ex2(fmaf(e0, sc, -me)), p1 = ex2(fmaf(e1, sc, -me)), p2 = ex2(fmaf(e2, sc, -me)), p3 = ex2(fmaf(e3, sc, -me));
                const float r0 = ex2(fmaf(f0, sc, -mf)), r1 = ex2(fmaf(f1, sc, -mf)), r2 = ex2(fmaf(f2, sc, -mf)), r3 = ex2(fmaf(f3, sc, -mf));
                const float ie = rcp(quad_sum((p0 + p1) + (p2 + p3))), jf = rcp(quad_sum((r0 + r1) + (r2 + r3)));
                const uint32_t pa0 = pack_bf16(p0 * ie, p1 * ie), pa2 = pack_bf16(p2 * ie, p3 * ie);
                const uint32_t pa3 = pack_bf16(r0 * jf, r1 * jf), pb1 = pack_bf16(r2 * jf, r3 * jf);
                #pragma unroll
                for (int c = 0; c < 4; c++) {
                    float o[4] = {0.f, 0.f, 0.f, 0.f};
                    mma16816(o, pa0, 0u, pa2, pa3, vf[0][c0 + c], vf[1][c0 + c]);
                    mma1688(o, 0u, pb1, vf[2][c0 + c]);
                    const uint32_t lo = pack_bf16(o[0], o[1]), hi = pack_bf16(o[2], o[3]);
                    if (hd == 1 && c == 0) { if (t >= 2) { ow[3][0] = lo; ow[3][1] = hi; } }
                    else { ow[c0 + c][0] = lo; ow[c0 + c][1] = hi; }
                }
            }
            {
                uint4* op = &g_o[(((ti * 2 + wg) * 4 + w) * 28 + ((7 * hg) >> 1)) * 32 + lane];
                if (hg & 1) {
                    ((uint2*)(op - lane))[32 + lane] = make_uint2(ow[0][0], ow[0][1]);
                    op[32] = make_uint4(ow[1][0], ow[1][1], ow[2][0], ow[2][1]);
                    op[64] = make_uint4(ow[3][0], ow[3][1], ow[4][0], ow[4][1]);
                    op[96] = make_uint4(ow[5][0], ow[5][1], ow[6][0], ow[6][1]);
                } else {
                    op[0]  = make_uint4(ow[0][0], ow[0][1], ow[1][0], ow[1][1]);
                    op[32] = make_uint4(ow[2][0], ow[2][1], ow[3][0], ow[3][1]);
                    op[64] = make_uint4(ow[4][0], ow[4][1], ow[5][0], ow[5][1]);
                    ((uint2*)(op + 96 - lane))[lane] = make_uint2(ow[6][0], ow[6][1]);
                }
                TR(5);
                named_bar(3, 256);
                if (tid == 0) { fence_gpu(); st_flag(&g_flag_o[((ti * 2) * 8 + hg) * FS], tag); st_flag(&g_flag_o[((ti * 2 + 1) * 8 + hg) * FS], tag); }
                __syncwarp();
                named_bar(3, 256);
                TR(19);
            }
        }
        {
            float acc2[64];
            const int row = w * 16 + wg * 8 + g;
            const bool wide = a2j != 3;
            uint32_t xr[16];
            {
                mbar_wait(BAR(B_XRF), 0);
                const uint32_t xa = sb + SM_X + 8 * 8192 + (w * 16 + wg * 8 + (lane & 7)) * 128;
                #pragma unroll
                for (int c = 0; c < 4; c++)
                    asm volatile("ldmatrix.sync.aligned.m8n8.x4.shared.b16 {%0,%1,%2,%3}, [%4];"
                                 : "=r"(xr[4 * c]), "=r"(xr[4 * c + 1]), "=r"(xr[4 * c + 2]), "=r"(xr[4 * c + 3])
                                 : "r"(xa + (c >> 1) * 8192 + ((((c & 1) * 4 + (lane >> 3)) ^ (lane & 7)) << 4)) : "memory");
            }
            {
                const uint32_t* fp = &g_flag_o[((ti * 2 + a2p) * 8 + wg * 4 + t) * FS];
                int it = 0;
                while (!__all_sync(~0u, ld_acq(fp) == tag)) { if (++it > kSpinLimit) { TIMEOUT(102); break; } }
            }
            TR(6);
            uint4 of[14];
            const uint4* op = &g_o[(((ti * 2 + a2p) * 4 + w) * 28 + wg * 14) * 32];
            #pragma unroll
            for (int k = 0; k < 14; k++) {
                if (k % 7 == 3) {
                    const uint2 lo = ld_rlx2((const uint2*)(op + k * 32) + lane), hi = ld_rlx2((const uint2*)(op + k * 32) + 32 + lane);
                    of[k] = make_uint4(lo.x, lo.y, hi.x, hi.y);
                } else of[k] = ld_rlx4(op + k * 32 + lane);
            }
            mbar_wait(BAR(B_WOF + wg), 0);
            const uint32_t dwo = desc_lo(sb + SM_WKV + wg * 57344, 28672);
            static_for<0, 14>([&](auto K_) {
                constexpr int k = decltype(K_)::value;
                if ((k & 1) == 0) wg_fence();
                wgmma_rs_n128<k * 2048, k != 0>(acc2, of[k].x, of[k].y, of[k].z, of[k].w, dwo);
            });
            wg_commit();
            wg_wait<0>();
            reg_fence(acc2);
            TR(7);
            const uint32_t rsend = sb + SM_RED + (1 - wg) * 16384 + (tid & 127) * 16;
            const uint32_t rrecv = sb + SM_RED + wg * 16384 + (tid & 127) * 16;
            float hv[32];
            #pragma unroll
            for (int c = 0; c < 8; c++) {
                const float s0 = wg ? acc2[8 * c] : acc2[8 * c + 2], s1 = wg ? acc2[8 * c + 1] : acc2[8 * c + 3];
                const float s2 = wg ? acc2[8 * c + 4] : acc2[8 * c + 6], s3 = wg ? acc2[8 * c + 5] : acc2[8 * c + 7];
                sts4(rsend + c * 2048, __float_as_uint(s0), __float_as_uint(s1), __float_as_uint(s2), __float_as_uint(s3));
                hv[4 * c]     = wg ? acc2[8 * c + 2] : acc2[8 * c];     hv[4 * c + 1] = wg ? acc2[8 * c + 3] : acc2[8 * c + 1];
                hv[4 * c + 2] = wg ? acc2[8 * c + 6] : acc2[8 * c + 4]; hv[4 * c + 3] = wg ? acc2[8 * c + 7] : acc2[8 * c + 5];
            }
            named_bar(3, 256);
            uint32_t hw[16];
            float sum = 0.f;
            #pragma unroll
            for (int c = 0; c < 8; c++) {
                const uint4 u = lds4(rrecv + c * 2048);
                hw[2 * c]     = pack_bf16(hv[4 * c] + __uint_as_float(u.x) + bf_lo(xr[2 * c]), hv[4 * c + 1] + __uint_as_float(u.y) + bf_hi(xr[2 * c]));
                hw[2 * c + 1] = pack_bf16(hv[4 * c + 2] + __uint_as_float(u.z) + bf_lo(xr[2 * c + 1]), hv[4 * c + 3] + __uint_as_float(u.w) + bf_hi(xr[2 * c + 1]));
                if (c < 4 || wide) sum += (bf_lo(hw[2 * c]) + bf_hi(hw[2 * c])) + (bf_lo(hw[2 * c + 1]) + bf_hi(hw[2 * c + 1]));
            }
            const float ms = quad_sum(sum) * (wide ? 1.f / 128.f : 1.f / 64.f);
            fence_async_smem();
            warp_arrive(BAR(B_WOC));
            asm volatile("barrier.cluster.arrive.relaxed.aligned;" ::: "memory");
            float m2 = 0.f;
            #pragma unroll
            for (int c = 0; c < 16; c++) {
                const float d0 = bf_lo(hw[c]) - ms, d1 = bf_hi(hw[c]) - ms;
                if (c < 8 || wide) { m2 = fmaf(d0, d0, m2); m2 = fmaf(d1, d1, m2); }
            }
            m2 = quad_sum(m2);
            uint4* sp = &g_stats[((ti * 2 + a2p) * 32 + (row >> 1)) * 8 + (row & 1)];
            if (t == 0) st_ll(sp + a2j * 2, __float_as_uint(ms), __float_as_uint(m2), tag);
            {
                uint2* hp = (uint2*)g_h + (((ti * 2 + a2p) * 8 + w * 2 + wg) * 28 + a2j * 8) * 32 + lane;
                #pragma unroll
                for (int c = 0; c < 8; c++) if (c < 4 || wide) hp[c * 32] = make_uint2(hw[2 * c], hw[2 * c + 1]);
            }
            TR(8);
            uint32_t um, uv;
            {
                int it = 0;
                while (!__all_sync(~0u, ld_ll(sp + t * 2, um, uv, tag))) { if (++it > kSpinLimit) { TIMEOUT(103); break; } }
            }
            TR(9);
            const float mj = __uint_as_float(um), nj = t == 3 ? 64.f : 128.f;
            const float mean = quad_sum(mj * nj) * (1.f / kD);
            const float var = quad_sum(fmaf(nj * (mj - mean), mj - mean, __uint_as_float(uv))) * (1.f / kD);
            const float r1 = rsqrtf(var + kEps);
            const float rr = r1 * rsqrtf(fmaf(var * r1, r1, kEps));
            uint32_t* np = (uint32_t*)&g_hn[(ti * 2 + a2p) * 4 * 896] + (w * 2 + wg) * 448 + lane;
            #pragma unroll
            for (int c = 0; c < 16; c++) {
                const int blk = a2j * 2 + c;
                const int off = (blk >= 14 ? (a2j + 1) * 3584 + (blk - 14) * 32 : a2j * 3584 + blk * 32);
                if (c < 8 || wide) np[off] = pack_bf16((bf_lo(hw[c]) - mean) * rr, (bf_hi(hw[c]) - mean) * rr);
            }
            named_bar(3, 256);
            if (tid == 0) { fence_async_global(); fence_gpu(); st_flag(&g_flag_h[((ti * 2 + a2p) * 4 + a2j) * FS], tag); mbar_arrive(BAR(B_HND)); }
            TR(10);
        }
        float acc[56];
        uint32_t peer_red, peer_bar;
        asm volatile("mapa.shared::cluster.u32 %0, %1, %2;" : "=r"(peer_red) : "r"(sb + SM_RED + wg * 14336 + (tid & 127) * 16), "r"(rank ^ 1));
        asm volatile("mapa.shared::cluster.u32 %0, %1, %2;" : "=r"(peer_bar) : "r"(BAR(B_RF + wg)), "r"(rank ^ 1));
        asm volatile("barrier.cluster.wait.aligned;" ::: "memory");
        uint32_t rph = 0, bph = 0;
        #pragma unroll 1
        for (int ge = g1_on ? 0 : 1; ge < 2; ge++) {
            const int pos = (ge ? (g1_on ? 32 : 0) : 0) + wg * (ge ? 14 : 16);
            const uint32_t aph = (ge && g1_on) ? 1u : 0u;
            const int row = w * 16 + rank * 8 + g;
            const int dsub = (ge ? g2j : gj) + 2 * wg;
            const float bias = __bfloat162float(ge ? prm.b2[g2s * 64 + row] : prm.b1[g1f * 64 + row]);
            uint32_t fbar[NB], ebar[NB], sp[NB], db[NB];
            #pragma unroll
            for (int i = 0; i < NB; i++) {
                const uint32_t sl = (pos + i) % NB;
                fbar[i] = opaque(BAR(B_BF + wg * NB + sl)); ebar[i] = opaque(BAR(B_BE + sl));
                sp[i] = opaque((bph >> sl) & 1);            db[i] = desc_lo(sb + SM_B + sl * 14336, 1792);
            }
            const bool lead = elect_one();
            const bool rel_a = lead && !ge && wg == 1;
            const uint32_t da = desc_lo(sb, 0);
            auto stage = [&](auto S_) {
                constexpr int s = decltype(S_)::value;
                constexpr int aoff = s < 10 ? s * 8192 : SM_AHI + (s - 10) * 8192;
                wg_fence();
                wgmma_ss_n112<aoff,        0,     s != 0>(acc, da, db[s % NB]);
                wgmma_ss_n112<aoff + 2048, 3584,  1>(acc, da, db[s % NB]);
                wgmma_ss_n112<aoff + 4096, 7168,  1>(acc, da, db[s % NB]);
                wgmma_ss_n112<aoff + 6144, 10752, 1>(acc, da, db[s % NB]);
                wg_commit();
                if (s < 15 && !(s == 13 && ge))
                    mbar_wait2(BAR(B_AF + s + 1), aph, fbar[(s + 1) % NB], sp[(s + 1) % NB] ^ (((s + 1) / NB) & 1));
                if constexpr (s > 0) {
                    wg_wait<1>();
                    mbar_arrive_if(ebar[(s - 1) % NB], lead);
                    if (s <= 14) mbar_arrive_if(BAR(B_AE + s - 1), rel_a);
                }
            };
            mbar_wait2(BAR(B_AF), aph, fbar[0], sp[0]);
            TR(11 + ge * 4);
            static_for<0, 14>(stage);
            if (!ge) static_for<14, 16>(stage);
            const uint32_t lastbar = ge ? ebar[13 % NB] : ebar[15 % NB];
            bph ^= 31u ^ (1u << (pos % NB));
            uint2 hr[7];
            if (ge) {
                const int tok = g2s * 64 + row, pr = (tok & 127) >> 1;
                const uint2* hp = (const uint2*)g_h + ((((tok >> 7) * 2 + (tok & 1)) * 8 + (pr >> 3)) * 28 + dsub * 7) * 32 + (pr & 7) * 4 + t;
                #pragma unroll
                for (int c = 0; c < 7; c++) hr[c] = ld_rlx2(hp + c * 32);
            }
            wg_wait<0>();
            reg_fence(acc);
            TR(12 + ge * 4);
            mbar_arrive_if(lastbar, lead);
            float v[28];
            #pragma unroll
            for (int c = 0; c < 7; c++) {
                const float s0 = rank ? acc[8 * c] : acc[8 * c + 2], s1 = rank ? acc[8 * c + 1] : acc[8 * c + 3];
                const float s2 = rank ? acc[8 * c + 4] : acc[8 * c + 6], s3 = rank ? acc[8 * c + 5] : acc[8 * c + 7];
                asm volatile("st.async.shared::cluster.mbarrier::complete_tx::bytes.v4.f32 [%0], {%1,%2,%3,%4}, [%5];"
                             :: "r"(peer_red + c * 2048), "f"(s0), "f"(s1), "f"(s2), "f"(s3), "r"(peer_bar) : "memory");
                v[4 * c]     = rank ? acc[8 * c + 2] : acc[8 * c];     v[4 * c + 1] = rank ? acc[8 * c + 3] : acc[8 * c + 1];
                v[4 * c + 2] = rank ? acc[8 * c + 6] : acc[8 * c + 4]; v[4 * c + 3] = rank ? acc[8 * c + 7] : acc[8 * c + 5];
            }
            mbar_wait_cluster(BAR(B_RF + wg), rph);
            rph ^= 1;
            #pragma unroll
            for (int c = 0; c < 7; c++) {
                const uint4 u = lds4(sb + SM_RED + wg * 14336 + (tid & 127) * 16 + c * 2048);
                v[4 * c] += __uint_as_float(u.x) + bias;     v[4 * c + 1] += __uint_as_float(u.y) + bias;
                v[4 * c + 2] += __uint_as_float(u.z) + bias; v[4 * c + 3] += __uint_as_float(u.w) + bias;
            }
            TR(13 + ge * 4);
            if (!ge) {
                uint32_t* gp = (uint32_t*)&g_g[(g1f * 4 + dsub) * 896] + (w * 2 + rank) * 448 + lane;
                #pragma unroll
                for (int c = 0; c < 14; c++) {
                    float r[2];
                    #pragma unroll
                    for (int e = 0; e < 2; e++) {
                        const float u = v[2 * c + e];
                        const float z = u * fmaf(u * u, -2.302208198f * 0.044715f, -2.302208198f);
                        r[e] = u * rcp(1.f + ex2(z));
                    }
                    gp[c * 32] = pack_bf16(r[0], r[1]);
                }
                named_bar(1 + wg, 128);
                if (w == 0 && lane == 0) {
                    mbar_expect(BAR(B_RF + wg), 14336);
                    fence_async_global(); fence_gpu();
                    st_flag(&g_flag_g[((dsub * 28 + g1f) * 2 + rank) * FS], tag);
                }
            } else {
                uint32_t* op = (uint32_t*)(prm.out + (size_t)(g2s * 64 + row) * kD + dsub * 112) + t;
                #pragma unroll
                for (int c = 0; c < 7; c++) {
                    op[c * 8]     = pack_bf16(v[4 * c] + bf_lo(hr[c].x), v[4 * c + 1] + bf_hi(hr[c].x));
                    op[c * 8 + 4] = pack_bf16(v[4 * c + 2] + bf_lo(hr[c].y), v[4 * c + 3] + bf_hi(hr[c].y));
                }
            }
            TR(14 + ge * 4);
        }
        if (tid == 128) TRG(62);
        if (b == 0 && tid == 128) g_epoch = tag;
    }
}

typedef CUresult (*EncodeFn)(CUtensorMap*, CUtensorMapDataType, cuuint32_t, void*, const cuuint64_t*, const cuuint64_t*,
                             const cuuint32_t*, const cuuint32_t*, CUtensorMapInterleave, CUtensorMapSwizzle,
                             CUtensorMapL2promotion, CUtensorMapFloatOOBfill);

void make_map(EncodeFn enc, CUtensorMap* m, const void* base, uint64_t cols, uint64_t rows, uint32_t box_rows) {
    cuuint64_t dims[2] = {cols, rows};
    cuuint64_t strides[1] = {cols * 2};
    cuuint32_t box[2] = {64, box_rows};
    cuuint32_t es[2] = {1, 1};
    enc(m, CU_TENSOR_MAP_DATA_TYPE_BFLOAT16, 2, const_cast<void*>(base), dims, strides, box, es, CU_TENSOR_MAP_INTERLEAVE_NONE,
        CU_TENSOR_MAP_SWIZZLE_128B, CU_TENSOR_MAP_L2_PROMOTION_L2_128B, CU_TENSOR_MAP_FLOAT_OOB_FILL_NONE);
}

}

extern "C" void kernel_launch(void* const* d_in, const int* in_sizes, int n_in, void* d_out, int out_size) {
    (void)in_sizes; (void)n_in; (void)out_size;
    void* fn = nullptr;
    cudaDriverEntryPointQueryResult qr;
    cudaGetDriverEntryPoint("cuTensorMapEncodeTiled", &fn, cudaEnableDefault, &qr);
    EncodeFn enc = (EncodeFn)fn;
    CUtensorMap mX, mWqkv, mWo, mW1, mW2;
    make_map(enc, &mX, d_in[0], 2 * kD, kS / 2, 64);
    make_map(enc, &mWqkv, d_in[1], 3 * kD, kD, 64);
    make_map(enc, &mWo, d_in[2], kD, kD, 224);
    make_map(enc, &mW1, d_in[4], 2 * kF, kS / 2, 64);
    make_map(enc, &mW2, d_in[6], kS, kF, 64);
    Params prm;
    prm.x = (const __nv_bfloat16*)d_in[0];
    prm.w1 = (const __nv_bfloat16*)d_in[4];
    prm.b1 = (const __nv_bfloat16*)d_in[5];
    prm.w2 = (const __nv_bfloat16*)d_in[6];
    prm.b2 = (const __nv_bfloat16*)d_in[7];
    prm.out = (__nv_bfloat16*)d_out;
    cudaFuncSetAttribute(fused_kernel, cudaFuncAttributeMaxDynamicSharedMemorySize, SM_TOTAL);
    fused_kernel<<<128, 384, SM_TOTAL, cudaStreamPerThread>>>(mX, mWqkv, mWo, mW1, mW2, prm);
}
```

```cpp
#include <cuda_runtime.h>
#include <cuda.h>
#include <cuda_bf16.h>
#include <stdint.h>
#include <type_traits>

namespace {

constexpr int kS = 2048, kD = 448, kF = 1792;
constexpr float kEps = 1e-5f;

#define FS 32
__device__ __align__(1024) uint4    g_o[2][32 * 4 * 28 * 32];
__device__ __align__(1024) uint4    g_h[kS * kD * 2 / 16];
__device__ __align__(1024) uint4    g_hn[32 * 56 * 64];
__device__ __align__(1024) uint4    g_g[28 * 56 * 64];
__device__ __align__(1024) uint4    g_halo[16 * 8 * 2 * 7 * 32];
__device__ __align__(1024) uint4    g_stats[32 * 4 * 64];
__device__ __align__(1024) uint32_t g_flag_h[32 * 4 * FS];
__device__ __align__(1024) uint32_t g_flag_g[4 * 28 * 2 * FS];
__device__ uint32_t g_epoch;
#define TIMEOUT(code)
#define RETRY_COUNT(i)
#define TR(idx)
#define TRW(idx)
#define TRG(idx)

constexpr uint32_t SM_X    = 0;
constexpr uint32_t SM_WKV  = 114688;
constexpr uint32_t SM_RED  = 81920;
constexpr uint32_t SM_B    = 96256;
constexpr uint32_t SM_AHI  = 182272;
constexpr uint32_t SM_BAR  = 231424;
constexpr uint32_t SM_TOTAL = SM_BAR + 1024;
constexpr int NB = 6;
constexpr int B_XF = 0, B_WKVF = 7, B_WQF = 14, B_XRF = 15, B_WOF = 16,
              B_XC = 18, B_KV3 = 19, B_KVC = 20,
              B_A1D = 21, B_OL = 22,
              B_AE = 23, B_BE = B_AE + 14, B_RE = B_BE + NB,
              B_AF = B_RE + 3, B_BF = B_AF + 16  , B_RF = B_BF + 2 * NB,
              B_EP = B_RF + 4, B_HD = B_EP + 1, B_PD = B_HD + 1, B_GD = B_PD + 1, B_GO = B_GD + 2, B_COUNT = B_GO + 4;
#define WEARLY 6
#define PF0 126
#define TMPF 2
#define RSTE 2
#define POLLP 1
#define PROBEP 1
#define LOADP 1
#define LOADW 64
#define NOB 0
#define AEARLY 5
#define W1PACE 280
#define W2PACE 420
#define PFPACE 330
#define PFBAR (B_XF + 6)
constexpr uint32_t SM_EPOCH = SM_BAR + B_COUNT * 8;

constexpr int kSpinLimit = 1 << 15;
__device__ __forceinline__ bool elect_one() {
    uint32_t p;
    asm volatile("{ .reg .pred P; elect.sync _|P, 0xffffffff; selp.u32 %0, 1, 0, P; }" : "=r"(p));
    return p;
}
__device__ __forceinline__ void mbar_init(uint32_t bar, uint32_t cnt) { asm volatile("mbarrier.init.shared::cta.b64 [%0], %1;" :: "r"(bar), "r"(cnt)); }
__device__ __forceinline__ void mbar_expect(uint32_t bar, uint32_t bytes) { asm volatile("mbarrier.arrive.expect_tx.shared::cta.b64 _, [%0], %1;" :: "r"(bar), "r"(bytes) : "memory"); }
__device__ __forceinline__ void mbar_arrive(uint32_t bar) { asm volatile("mbarrier.arrive.shared::cta.b64 _, [%0];" :: "r"(bar) : "memory"); }
__device__ __forceinline__ void mbar_wait(uint32_t bar, uint32_t parity) {
    uint32_t ok; int it = 0;
    do {
        asm volatile("{ .reg .pred p; mbarrier.try_wait.parity.shared::cta.b64 p, [%1], %2; selp.u32 %0, 1, 0, p; }"
                     : "=r"(ok) : "r"(bar), "r"(parity) : "memory");
        if (++it > kSpinLimit) { TIMEOUT((bar & 1023) >> 3); break; }
    } while (!ok);
}
__device__ __forceinline__ void mbar_wait2(uint32_t bar0, uint32_t par0, uint32_t bar1, uint32_t par1) {
    uint32_t ok; int it = 0;
    do {
        asm volatile("{ .reg .pred p, q; mbarrier.try_wait.parity.shared::cta.b64 p, [%1], %2;\n"
                     "mbarrier.try_wait.parity.shared::cta.b64 q, [%3], %4; and.pred p, p, q; selp.u32 %0, 1, 0, p; }"
                     : "=r"(ok) : "r"(bar0), "r"(par0), "r"(bar1), "r"(par1) : "memory");
        if (++it > kSpinLimit) { TIMEOUT((bar0 & 1023) >> 3); break; }
    } while (!ok);
}
template <int N> __device__ __forceinline__ void reg_fence(float (&d)[N]) {
    #pragma unroll
    for (int i = 0; i < N; i++) asm volatile("" : "+f"(d[i]) :: "memory");
}
__device__ __forceinline__ void mbar_wait_cluster(uint32_t bar, uint32_t parity) {
    uint32_t ok; int it = 0;
    do {
        asm volatile("{ .reg .pred p; mbarrier.try_wait.parity.acquire.cluster.shared::cta.b64 p, [%1], %2; selp.u32 %0, 1, 0, p; }"
                     : "=r"(ok) : "r"(bar), "r"(parity) : "memory");
        if (++it > kSpinLimit) { TIMEOUT((bar & 1023) >> 3); break; }
    } while (!ok);
}
__device__ __forceinline__ void mbar_arrive_if(uint32_t bar, bool pred) {
    asm volatile("{ .reg .pred p; setp.ne.u32 p, %1, 0; @p mbarrier.arrive.shared::cta.b64 _, [%0]; }" :: "r"(bar), "r"((uint32_t)pred) : "memory");
}
template <int P> __device__ __forceinline__ void tick() {
    if (P > 1) { const uint32_t t = ((uint32_t)clock() | (P - 1)) + 1; while ((int)((uint32_t)clock() - t) < 0) {} }
}
__device__ __forceinline__ void warp_arrive(uint32_t bar) { __syncwarp(); if (elect_one()) mbar_arrive(bar); }
__device__ __forceinline__ void tma2d(uint32_t dst, const CUtensorMap* m, int c0, int c1, uint32_t bar) {
    asm volatile("cp.async.bulk.tensor.2d.shared::cluster.global.mbarrier::complete_tx::bytes [%0], [%1, {%3, %4}], [%2];"
                 :: "r"(dst), "l"(m), "r"(bar), "r"(c0), "r"(c1) : "memory");
}
__device__ __forceinline__ void tma2d_mc(uint32_t dst, const CUtensorMap* m, int c0, int c1, uint32_t bar) {
    asm volatile("cp.async.bulk.tensor.2d.shared::cluster.global.mbarrier::complete_tx::bytes.multicast::cluster [%0], [%1, {%3, %4}], [%2], %5;"
                 :: "r"(dst), "l"(m), "r"(bar), "r"(c0), "r"(c1), "h"((uint16_t)3) : "memory");
}
__device__ __forceinline__ void bulk_g2s_mc(uint32_t dst, const void* src, uint32_t bytes, uint32_t bar) {
    asm volatile("cp.async.bulk.shared::cluster.global.mbarrier::complete_tx::bytes.multicast::cluster [%0], [%1], %2, [%3], %4;"
                 :: "r"(dst), "l"(src), "r"(bytes), "r"(bar), "h"((uint16_t)3) : "memory");
}
__device__ __forceinline__ void mbar_arrive_remote_if(uint32_t cluster_bar, bool pred) {
    asm volatile("{ .reg .pred p; setp.ne.u32 p, %1, 0; @p mbarrier.arrive.shared::cluster.b64 _, [%0]; }" :: "r"(cluster_bar), "r"((uint32_t)pred) : "memory");
}
__device__ __forceinline__ void bulk_g2s(uint32_t dst, const void* src, uint32_t bytes, uint32_t bar) {
    asm volatile("cp.async.bulk.shared::cluster.global.mbarrier::complete_tx::bytes [%0], [%1], %2, [%3];"
                 :: "r"(dst), "l"(src), "r"(bytes), "r"(bar) : "memory");
}
__device__ __forceinline__ void wg_fence()  { asm volatile("wgmma.fence.sync.aligned;" ::: "memory"); }
__device__ __forceinline__ void wg_commit() { asm volatile("wgmma.commit_group.sync.aligned;" ::: "memory"); }
template <int N> __device__ __forceinline__ void wg_wait() { asm volatile("wgmma.wait_group.sync.aligned %0;" :: "n"(N) : "memory"); }
__device__ __forceinline__ void named_bar(int id, int n) { asm volatile("bar.sync %0, %1;" :: "r"(id), "r"(n) : "memory"); }
__device__ __forceinline__ void fence_gpu() { asm volatile("fence.acq_rel.gpu;" ::: "memory"); }
__device__ __forceinline__ void fence_async_global() { asm volatile("fence.proxy.async.global;" ::: "memory"); }
__device__ __forceinline__ void fence_async_smem() { asm volatile("fence.proxy.async.shared::cta;" ::: "memory"); }
__device__ __forceinline__ void st_flag(uint32_t* p, uint32_t v) { asm volatile("st.relaxed.gpu.global.u32 [%0], %1;" :: "l"(p), "r"(v) : "memory"); }
__device__ __forceinline__ uint32_t ld_acq(const uint32_t* p) { uint32_t v; asm volatile("ld.acquire.gpu.global.u32 %0, [%1];" : "=r"(v) : "l"(p) : "memory"); return v; }
__device__ __forceinline__ uint32_t ld_rlx(const uint32_t* p) { uint32_t v; asm volatile("ld.relaxed.gpu.global.u32 %0, [%1];" : "=r"(v) : "l"(p) : "memory"); return v; }
template <class T> __device__ __forceinline__ T* opaque_ptr(T* p) { asm volatile("" : "+l"(p)); return p; }
__device__ __forceinline__ uint4 ld_rlx4(const uint4* p) {
    uint4 v; asm volatile("ld.relaxed.gpu.global.v4.u32 {%0,%1,%2,%3}, [%4];" : "=r"(v.x), "=r"(v.y), "=r"(v.z), "=r"(v.w) : "l"(p) : "memory"); return v;
}
__device__ __forceinline__ void st_ll(uint4* p, uint32_t a, uint32_t b, uint32_t tag) {
    uint64_t lo = ((uint64_t)tag << 32) | a, hi = ((uint64_t)tag << 32) | b;
    asm volatile("st.relaxed.gpu.global.v2.u64 [%0], {%1,%2};" :: "l"(p), "l"(lo), "l"(hi) : "memory");
}
__device__ __forceinline__ bool ld_ll(const uint4* p, uint32_t& a, uint32_t& b, uint32_t tag) {
    uint64_t lo, hi;
    asm volatile("ld.relaxed.gpu.global.v2.u64 {%0,%1}, [%2];" : "=l"(lo), "=l"(hi) : "l"(p) : "memory");
    a = (uint32_t)lo; b = (uint32_t)hi;
    return (uint32_t)(lo >> 32) == tag && (uint32_t)(hi >> 32) == tag;
}
__device__ __forceinline__ uint2 ld_acq2(const uint2* p) {
    uint2 v; asm volatile("ld.acquire.gpu.global.v2.u32 {%0,%1}, [%2];" : "=r"(v.x), "=r"(v.y) : "l"(p) : "memory"); return v;
}
__device__ __forceinline__ uint2 ld_rlx2(const uint2* p) {
    uint2 v; asm volatile("ld.relaxed.gpu.global.v2.u32 {%0,%1}, [%2];" : "=r"(v.x), "=r"(v.y) : "l"(p) : "memory"); return v;
}
__device__ __forceinline__ void sts4(uint32_t a, uint32_t x, uint32_t y, uint32_t z, uint32_t w) { asm volatile("st.shared.v4.u32 [%0], {%1,%2,%3,%4};" :: "r"(a), "r"(x), "r"(y), "r"(z), "r"(w) : "memory"); }
__device__ __forceinline__ uint4 lds4(uint32_t a) { uint4 v; asm volatile("ld.shared.v4.u32 {%0,%1,%2,%3}, [%4];" : "=r"(v.x), "=r"(v.y), "=r"(v.z), "=r"(v.w) : "r"(a) : "memory"); return v; }
__device__ __forceinline__ uint32_t pack_bf16(float lo, float hi) { uint32_t r; asm("cvt.rn.bf16x2.f32 %0, %1, %2;" : "=r"(r) : "f"(hi), "f"(lo)); return r; }
__device__ __forceinline__ float bf_lo(uint32_t v) { return __uint_as_float(v << 16); }
__device__ __forceinline__ float bf_hi(uint32_t v) { return __uint_as_float(v & 0xffff0000u); }
__device__ __forceinline__ uint32_t sub_bf16x2(uint32_t a, uint32_t b) { uint32_t r; asm("sub.rn.bf16x2 %0, %1, %2;" : "=r"(r) : "r"(a), "r"(b)); return r; }
__device__ __forceinline__ uint32_t movm(uint32_t a) { uint32_t r; asm volatile("movmatrix.sync.aligned.m8n8.trans.b16 %0, %1;" : "=r"(r) : "r"(a)); return r; }
__device__ __forceinline__ float ex2(float x) { float r; asm("ex2.approx.ftz.f32 %0, %1;" : "=f"(r) : "f"(x)); return r; }
__device__ __forceinline__ float rsq(float x) { float r; asm("rsqrt.approx.ftz.f32 %0, %1;" : "=f"(r) : "f"(x)); return r; }
__device__ __forceinline__ float rcp(float x) { float r; asm("rcp.approx.ftz.f32 %0, %1;" : "=f"(r) : "f"(x)); return r; }
__device__ __forceinline__ void mma16816(float (&c)[4], uint32_t a0, uint32_t a1, uint32_t a2, uint32_t a3, uint32_t b0, uint32_t b1) {
    asm("mma.sync.aligned.m16n8k16.row.col.f32.bf16.bf16.f32 {%0,%1,%2,%3}, {%4,%5,%6,%7}, {%8,%9}, {%0,%1,%2,%3};"
        : "+f"(c[0]), "+f"(c[1]), "+f"(c[2]), "+f"(c[3]) : "r"(a0), "r"(a1), "r"(a2), "r"(a3), "r"(b0), "r"(b1));
}
__device__ __forceinline__ void mma1688(float (&c)[4], uint32_t a0, uint32_t a1, uint32_t b0) {
    asm("mma.sync.aligned.m16n8k8.row.col.f32.bf16.bf16.f32 {%0,%1,%2,%3}, {%4,%5}, {%6}, {%0,%1,%2,%3};"
        : "+f"(c[0]), "+f"(c[1]), "+f"(c[2]), "+f"(c[3]) : "r"(a0), "r"(a1), "r"(b0));
}
__device__ __forceinline__ float quad_sum(float v) { v += __shfl_xor_sync(~0u, v, 1); v += __shfl_xor_sync(~0u, v, 2); return v; }
__device__ __forceinline__ float quad_max(float v) { v = fmaxf(v, __shfl_xor_sync(~0u, v, 1)); v = fmaxf(v, __shfl_xor_sync(~0u, v, 2)); return v; }
__device__ __forceinline__ uint32_t desc_lo(uint32_t addr, uint32_t lbo) { return ((addr & 0x3FFFF) >> 4) | ((lbo >> 4) << 16); }
template <int I, int N, class F> __device__ __forceinline__ void static_for(F&& f) {
    if constexpr (I < N) { f(std::integral_constant<int, I>{}); static_for<I + 1, N>(f); }
}
__device__ __forceinline__ uint32_t opaque(uint32_t v) { asm volatile("" : "+r"(v)); return v; }
template <int BOFF, int SCALE_D>
__device__ __forceinline__ void wgmma_rs_n56(float (&d)[28], uint32_t a0, uint32_t a1, uint32_t a2, uint32_t a3, uint32_t blo) {
    asm volatile("{ .reg .b32 lb; .reg .b64 db;\n"
        "add.u32 lb, %32, %33; mov.b64 db, {lb, 0x40000040};\n"
        "wgmma.mma_async.sync.aligned.m64n56k16.f32.bf16.bf16 "
        "{%0, %1, %2, %3, %4, %5, %6, %7, %8, %9, %10, %11, %12, %13, %14, %15, %16, %17, %18, %19, %20, %21, %22, %23, %24, %25, %26, %27}, "
        "{%28, %29, %30, %31}, db, %34, 1, 1, 1; }"
        : "+f"(d[0]), "+f"(d[1]), "+f"(d[2]), "+f"(d[3]), "+f"(d[4]), "+f"(d[5]), "+f"(d[6]), "+f"(d[7]),
        "+f"(d[8]), "+f"(d[9]), "+f"(d[10]), "+f"(d[11]), "+f"(d[12]), "+f"(d[13]), "+f"(d[14]), "+f"(d[15]),
        "+f"(d[16]), "+f"(d[17]), "+f"(d[18]), "+f"(d[19]), "+f"(d[20]), "+f"(d[21]), "+f"(d[22]), "+f"(d[23]),
        "+f"(d[24]), "+f"(d[25]), "+f"(d[26]), "+f"(d[27])
        : "r"(a0), "r"(a1), "r"(a2), "r"(a3), "r"(blo), "n"(BOFF >> 4), "n"(SCALE_D));
}
template <int BOFF, int SCALE_D>
__device__ __forceinline__ void wgmma_rs_n128(float (&d)[64], uint32_t a0, uint32_t a1, uint32_t a2, uint32_t a3, uint32_t blo) {
    asm volatile("{ .reg .b32 lb; .reg .b64 db;\n"
        "add.u32 lb, %68, %69; mov.b64 db, {lb, 0x40000040};\n"
        "wgmma.mma_async.sync.aligned.m64n128k16.f32.bf16.bf16 "
        "{%0, %1, %2, %3, %4, %5, %6, %7, %8, %9, %10, %11, %12, %13, %14, %15, %16, %17, %18, %19, %20, %21, %22, %23, %24, %25, %26, %27, %28, %29, %30, %31, %32, %33, %34, %35, %36, %37, %38, %39, %40, %41, %42, %43, %44, %45, %46, %47, %48, %49, %50, %51, %52, %53, %54, %55, %56, %57, %58, %59, %60, %61, %62, %63}, "
        "{%64, %65, %66, %67}, db, %70, 1, 1, 1; }"
        : "+f"(d[0]), "+f"(d[1]), "+f"(d[2]), "+f"(d[3]), "+f"(d[4]), "+f"(d[5]), "+f"(d[6]), "+f"(d[7]),
        "+f"(d[8]), "+f"(d[9]), "+f"(d[10]), "+f"(d[11]), "+f"(d[12]), "+f"(d[13]), "+f"(d[14]), "+f"(d[15]),
        "+f"(d[16]), "+f"(d[17]), "+f"(d[18]), "+f"(d[19]), "+f"(d[20]), "+f"(d[21]), "+f"(d[22]), "+f"(d[23]),
        "+f"(d[24]), "+f"(d[25]), "+f"(d[26]), "+f"(d[27]), "+f"(d[28]), "+f"(d[29]), "+f"(d[30]), "+f"(d[31]),
        "+f"(d[32]), "+f"(d[33]), "+f"(d[34]), "+f"(d[35]), "+f"(d[36]), "+f"(d[37]), "+f"(d[38]), "+f"(d[39]),
        "+f"(d[40]), "+f"(d[41]), "+f"(d[42]), "+f"(d[43]), "+f"(d[44]), "+f"(d[45]), "+f"(d[46]), "+f"(d[47]),
        "+f"(d[48]), "+f"(d[49]), "+f"(d[50]), "+f"(d[51]), "+f"(d[52]), "+f"(d[53]), "+f"(d[54]), "+f"(d[55]),
        "+f"(d[56]), "+f"(d[57]), "+f"(d[58]), "+f"(d[59]), "+f"(d[60]), "+f"(d[61]), "+f"(d[62]), "+f"(d[63])
        : "r"(a0), "r"(a1), "r"(a2), "r"(a3), "r"(blo), "n"(BOFF >> 4), "n"(SCALE_D));
}
template <int AOFF, int BOFF, int SCALE_D>
__device__ __forceinline__ void wgmma_ss_n112(float (&d)[56], uint32_t alo, uint32_t blo) {
    asm volatile("{ .reg .b32 la, lb; .reg .b64 da, db;\n"
        "add.u32 la, %56, %58; add.u32 lb, %57, %59;\n"
        "mov.b64 da, {la, 0x40000040}; mov.b64 db, {lb, 64};\n"
        "wgmma.mma_async.sync.aligned.m64n112k16.f32.bf16.bf16 "
        "{%0, %1, %2, %3, %4, %5, %6, %7, %8, %9, %10, %11, %12, %13, %14, %15, %16, %17, %18, %19, %20, %21, %22, %23, %24, %25, %26, %27, %28, %29, %30, %31, %32, %33, %34, %35, %36, %37, %38, %39, %40, %41, %42, %43, %44, %45, %46, %47, %48, %49, %50, %51, %52, %53, %54, %55}, "
        "da, db, %60, 1, 1, 1, 1; }"
        : "+f"(d[0]), "+f"(d[1]), "+f"(d[2]), "+f"(d[3]), "+f"(d[4]), "+f"(d[5]), "+f"(d[6]), "+f"(d[7]),
        "+f"(d[8]), "+f"(d[9]), "+f"(d[10]), "+f"(d[11]), "+f"(d[12]), "+f"(d[13]), "+f"(d[14]), "+f"(d[15]),
        "+f"(d[16]), "+f"(d[17]), "+f"(d[18]), "+f"(d[19]), "+f"(d[20]), "+f"(d[21]), "+f"(d[22]), "+f"(d[23]),
        "+f"(d[24]), "+f"(d[25]), "+f"(d[26]), "+f"(d[27]), "+f"(d[28]), "+f"(d[29]), "+f"(d[30]), "+f"(d[31]),
        "+f"(d[32]), "+f"(d[33]), "+f"(d[34]), "+f"(d[35]), "+f"(d[36]), "+f"(d[37]), "+f"(d[38]), "+f"(d[39]),
        "+f"(d[40]), "+f"(d[41]), "+f"(d[42]), "+f"(d[43]), "+f"(d[44]), "+f"(d[45]), "+f"(d[46]), "+f"(d[47]),
        "+f"(d[48]), "+f"(d[49]), "+f"(d[50]), "+f"(d[51]), "+f"(d[52]), "+f"(d[53]), "+f"(d[54]), "+f"(d[55])
        : "r"(alo), "r"(blo), "n"(AOFF >> 4), "n"(BOFF >> 4), "n"(SCALE_D));
}

struct Params {
    const __nv_bfloat16 *x, *wqkv, *wo, *w1, *w2, *b1, *b2;
    __nv_bfloat16* out;
};

__global__ void __cluster_dims__(2, 1, 1) __launch_bounds__(384, 1)
fused_kernel(const __grid_constant__ CUtensorMap mX, const __grid_constant__ CUtensorMap mWqkv,
             const __grid_constant__ CUtensorMap mWo, const __grid_constant__ CUtensorMap mW1,
             const __grid_constant__ CUtensorMap mW2, const Params prm)
{
    extern __shared__ __align__(1024) unsigned char smem_raw[];
    uint32_t sb = (uint32_t)__cvta_generic_to_shared(smem_raw);
    asm volatile("mov.u32 %0, %0;" : "+r"(sb));
    const uint32_t bar0 = sb + SM_BAR;
    auto BAR = [&](int i) { return bar0 + 8u * i; };

    const int tid = threadIdx.x, lane = tid & 31;
    const int warp = __shfl_sync(~0u, tid >> 5, 0);
    const int b = __shfl_sync(~0u, (int)blockIdx.x, 0);
    const int rank = b & 1;
    const int res = (b >> 1) & 7, rnd = b >> 4;
    const int hg = (res & 1) * 4 + (rnd & 3);
    const int ti = (res >> 1) * 4 + (rnd >> 2) * 2 + rank;
    const int a2p = res & 1, a2j = rnd & 3;
    const int a2s = ti * 2 + a2p;
    const bool g1_on = rnd != 7;
    const int g1j = res & 1, g1f = (res >> 1) * 7 + rnd;
    const int g2j = rnd & 1, g2s = res * 4 + (rnd >> 1);
    uint32_t pbar0;
    asm volatile("mapa.shared::cluster.u32 %0, %1, %2;" : "=r"(pbar0) : "r"(bar0), "r"(rank ^ 1));
    auto pair_arrive = [&](int i) { __syncwarp(); const bool l = elect_one(); mbar_arrive_if(BAR(i), l); mbar_arrive_remote_if(pbar0 + 8u * i, l); };
    const int wcol = hg * 56 - (hg & 1) * 8;

    if (tid == 32) { TRG(60); TRW(59); }
    if (warp == 8) {
        if (elect_one()) {
            #pragma unroll
            for (int i = 0; i < B_WQF; i++) mbar_init(BAR(i), 1);
            asm volatile("fence.mbarrier_init.release.cluster;" ::: "memory");
            fence_async_smem();
            TRW(56);
            #pragma unroll 1
            for (int kb = 0; kb < 7; kb++) {
                mbar_expect(BAR(B_XF + kb), 16384);
                tma2d(sb + SM_X + kb * 8192, &mX, kb * 64, ti * 64, BAR(B_XF + kb));
                tma2d(sb + SM_X + 57344 + kb * 8192, &mX, kD + kb * 64, ti * 64, BAR(B_XF + kb));
                if (TMPF == 2 && kb == 0) asm volatile("prefetch.tensormap [%0];" :: "l"(&mWqkv) : "memory");
            }
        }
    } else if (warp > 8) {
        if (elect_one()) {
            if (warp == 9) {
                if (TMPF == 1) asm volatile("prefetch.tensormap [%0];" :: "l"(&mWqkv) : "memory");
                #pragma unroll
                for (int i = B_WQF; i < B_AF; i++) mbar_init(BAR(i), i < B_XC ? 1 : i < B_A1D ? 16 : i < B_AE ? 8 : 4);
            } else if (warp == 10) {
                #pragma unroll
                for (int i = B_AF; i < B_BF; i++) mbar_init(BAR(i), 1);
            } else {
                #pragma unroll
                for (int i = B_BF; i < B_COUNT; i++) mbar_init(BAR(i), 1);
            }
            asm volatile("fence.mbarrier_init.release.cluster;" ::: "memory");
            fence_async_smem();
        }
    } else {
        const char* p = tid < 112 ? (const char*)prm.x + (size_t)(ti * 8 + hg) * 14336 + tid * 128
                                  : (const char*)prm.wqkv + b * 2688 + 896 + (tid - 112) * 128;
        if (tid < PF0) asm volatile("prefetch.global.L2 [%0];" :: "l"(p));
    }
    __syncwarp();
    __syncthreads();
    asm volatile("barrier.cluster.arrive.relaxed.aligned;" ::: "memory");
    if (tid < 256) TR(0);
    if (tid == 0) TRG(61);

    if (warp >= 8) {
        asm volatile("setmaxnreg.dec.sync.aligned.u32 40;");
        asm volatile("barrier.cluster.wait.aligned;" ::: "memory");
        if (warp == 8) {
            if (elect_one()) {
                #pragma unroll 1
                for (int s = 0; s < 7; s++) {
                    mbar_expect(BAR(B_WKVF + s), 16384);
                    tma2d_mc(sb + SM_WKV + s * 16384 + rank * 8192, &mWqkv, (1 + rank) * kD + wcol, s * 64, BAR(B_WKVF + s));
                }
            }
            __syncwarp();
            mbar_wait(BAR(B_XC), 0);
            if (elect_one()) {
                asm volatile("prefetch.tensormap [%0];" :: "l"(&mWo) : "memory");
                asm volatile("prefetch.tensormap [%0];" :: "l"(&mW1) : "memory");
                asm volatile("prefetch.tensormap [%0];" :: "l"(&mW2) : "memory");
                mbar_expect(BAR(B_WQF), 57344);
                #pragma unroll 1
                for (int s = rank; s < 7; s += 2) tma2d_mc(sb + SM_X + s * 8192, &mWqkv, wcol, s * 64, BAR(B_WQF));
                mbar_expect(BAR(B_XRF), a2j == 3 ? 8192 : 16384);
                tma2d(sb + SM_X + 8 * 8192, &mX, a2p * kD + a2j * 128, ti * 64, BAR(B_XRF));
                if (a2j != 3) tma2d(sb + SM_X + 9 * 8192, &mX, a2p * kD + a2j * 128 + 64, ti * 64, BAR(B_XRF));
            }
            __syncwarp();
            #pragma unroll 1
            for (int h = 0; h < 2; h++) {
                mbar_wait(BAR(B_KV3 + h), 0);
                if (elect_one()) {
                    mbar_expect(BAR(B_WOF + h), a2j == 3 ? 28672 : 57344);
                    const int atom = rank ^ h;
                    if (a2j != 3 || atom == 0) tma2d_mc(sb + SM_WKV + h * 57344 + atom * 28672, &mWo, a2j * 128 + atom * 64, h * 224, BAR(B_WOF + h));
                }
                __syncwarp();
            }
            auto load_slab = [&](int s, bool second) {
                if (elect_one()) {
                    mbar_expect(BAR(B_AF + s), 8192);
                    const uint32_t dst = sb + (s < 10 ? s * 8192 : SM_AHI + (s - 10) * 8192);
                    if (g1_on && !second) tma2d(dst, &mW1, (s & 1) * kF + g1f * 64, (rank * 8 + (s >> 1)) * 64, BAR(B_AF + s));
                    else                  tma2d(dst, &mW2, g2s * 64, (rank * 14 + s) * 64, BAR(B_AF + s));
                }
                __syncwarp();
            };
            mbar_wait(BAR(B_A1D), 0);
            #pragma unroll 1
            for (int s = 0; s < 8; s++) {
                if (s == AEARLY) mbar_wait(BAR(B_OL), 0);
                load_slab(s, false);
            }
            mbar_wait(BAR(g1_on ? B_GO : B_HD), 0);
            {
                uint32_t tnext = (uint32_t)clock();
                #pragma unroll 1
                for (int s = 8; s < (g1_on ? 16 : 14); s++) {
                    tnext += W1PACE;
                    while ((int)((uint32_t)clock() - tnext) < 0) {}
                    load_slab(s, false);
                }
            }
            if (g1_on) {
                mbar_wait(BAR(B_AE), 0);
                uint32_t tnext = (uint32_t)clock();
                #pragma unroll 1
                for (int s = 0; s < 14; s++) {
                    mbar_wait(BAR(B_AE + s), 0);
                    while ((int)((uint32_t)clock() - tnext) < 0) {}
                    load_slab(s, true);
                    tnext += W2PACE;
                }
            }
        } else if (warp == 9) {
            int slot = 0; uint32_t ph = 1;
            #pragma unroll 1
            for (int e = g1_on ? 0 : 2; e < 4; e++) {
                const bool g2 = e >= 2;
                const int dsub = (g2 ? g2j : g1j) + 2 * (e & 1);
                const uint4* src = (g2 ? &g_g[rank * 14 * 3584] : &g_hn[rank * 16 * 3584]) + dsub * 896;
                mbar_wait(BAR(B_GO + e), 0);
                TRW(40 + e);
                #pragma unroll 1
                for (int s = g2 ? 2 : 0; s < 16; s++) {
                    mbar_wait(BAR(B_BE + slot), ph);
                    if (LOADP > 1) while (((uint32_t)clock() & (LOADP - 1)) >= LOADW) {}
                    if (elect_one()) {
                        const uint32_t fb = BAR(B_BF + (e & 1) * NB + slot);
                        if ((NOB >> e) & 1) mbar_arrive(fb); else {
                        mbar_expect(fb, 14336);
                        bulk_g2s(sb + SM_B + slot * 14336, src, 14336, fb); }
                    }
                    src += 3584;
                    if (++slot == NB) { slot = 0; ph ^= 1; }
                }
            }
        } else if (warp == 10) {
            mbar_wait(BAR(PFBAR), 0);
            const char* p1 = (const char*)prm.w1 + (size_t)b * 57344 + lane * 128;
            const char* p2 = (const char*)prm.w2 + (size_t)b * 57344 + lane * 128;
            if (lane < 25) asm volatile("prefetch.global.L2 [%0];" :: "l"((const char*)prm.wo + min(b * 25 + lane, 3135) * 128));
            uint32_t tnext = (uint32_t)clock();
            #pragma unroll 1
            for (int i = 0; i < 28; i++) {
                asm volatile("prefetch.global.L2 [%0];" :: "l"(i < 14 ? p1 + i * 4096 : p2 + (i - 14) * 4096));
                tnext += PFPACE;
                while ((int)((uint32_t)clock() - tnext) < 0) __nanosleep(40);
            }
        } else {
            const uint32_t tag = *(volatile uint32_t*)&g_epoch + 1;
            const uint4 z4 = make_uint4(0u, 0u, 0u, 0u);
            #pragma unroll 1
            for (int i = 0; i < 14; i++) g_halo[(ti * 8 + hg) * 448 + i * 32 + lane] = z4;
            g_stats[(a2s * 4 + a2j) * 64 + lane] = z4; g_stats[(a2s * 4 + a2j) * 64 + 32 + lane] = z4;
            if (lane < FS) {
                g_flag_h[(a2s * 4 + a2j) * FS + lane] = 0;
                if (g1_on) { g_flag_g[((g1j * 28 + g1f) * 2 + rank) * FS + lane] = 0; g_flag_g[(((g1j + 2) * 28 + g1f) * 2 + rank) * FS + lane] = 0; }
            }
            #pragma unroll 1
            for (int i = 0; i < 2; i++) g_o[tag & 1][(ti * 8 + i * 4 + (lane >> 3)) * 896 + hg * 112 + 104 + (lane & 7)] = z4;
            __syncwarp();
            if (lane == 0) {
                asm volatile("st.shared.u32 [%0], %1;" :: "r"(sb + SM_EPOCH), "r"(tag) : "memory");
                mbar_arrive(BAR(B_EP));
            }
            if (lane < 4) mbar_expect(BAR(B_RF + lane), 14336);
            __syncwarp();
            TRW(44);
            mbar_wait(BAR(B_HD), 0);
            #pragma unroll 1
            for (int e = g1_on ? 0 : 2; e < 4; e++) {
                const int dsub = (e >= 2 ? g2j : g1j) + 2 * (e & 1);
                const uint32_t* fp = e >= 2 ? &g_flag_g[((dsub * 28 + rank * 14) * 2 + min(lane, 27)) * FS]
                                            : &g_flag_h[((rank * 16 + (lane >> 1)) * 4 + max(dsub - (lane & 1), 0)) * FS];
                if (e == RSTE) {
                    #pragma unroll 1
                    for (int i = 0; i < 8; i++) {
                        uint4* p = &g_o[~tag & 1][(ti * 8 + i) * 896 + hg * 112 + lane];
                        p[0] = z4; p[32] = z4; p[64] = z4; if (lane < 16) p[96] = z4;
                        __nanosleep(100);
                    }
                }
                if (g1_on && e >= 2) mbar_wait(BAR(B_GD + e - 2), 0);
                int it = 0;
                while (true) {
                    tick<POLLP>();
                    if (__all_sync(~0u, ld_acq(fp) == tag)) break;
                    if (++it > kSpinLimit) { TIMEOUT(108); break; }
                }
                warp_arrive(BAR(B_GO + e));
            }
        }
    } else {
        asm volatile("setmaxnreg.inc.sync.aligned.u32 232;");
        asm volatile("barrier.cluster.wait.aligned;" ::: "memory");
        const int wg = warp >> 2, w = warp & 3;
        const int g = lane >> 2, t = lane & 3;
        uint32_t tag;
        {
            uint32_t a[28][4];
            float sm0[4] = {0.f, 0.f, 0.f, 0.f}, sm1[4] = {0.f, 0.f, 0.f, 0.f};
            {
                const int r = w * 16 + (lane & 15);
                const uint32_t rowa = sb + SM_X + wg * 57344 + r * 128;
                #pragma unroll
                for (int kb = 0; kb < 7; kb++) {
                    mbar_wait(BAR(B_XF + kb), 0);
                    #pragma unroll
                    for (int q = 0; q < 4; q++) {
                        const uint32_t addr = rowa + kb * 8192 + (((q * 2 + (lane >> 4)) ^ (r & 7)) << 4);
                        uint32_t (&f)[4] = a[kb * 4 + q];
                        asm volatile("ldmatrix.sync.aligned.m8n8.x4.shared.b16 {%0,%1,%2,%3}, [%4];"
                                     : "=r"(f[0]), "=r"(f[1]), "=r"(f[2]), "=r"(f[3]) : "r"(addr) : "memory");
                        if (q & 1) mma16816(sm1, f[0], f[1], f[2], f[3], 0x3F803F80u, 0x3F803F80u);
                        else       mma16816(sm0, f[0], f[1], f[2], f[3], 0x3F803F80u, 0x3F803F80u);
                    }
                }
            }
            const float mean0 = (sm0[0] + sm1[0]) * (1.f / kD), mean1 = (sm0[2] + sm1[2]) * (1.f / kD);
            const uint32_t mb0 = pack_bf16(mean0, mean0), mb1 = pack_bf16(mean1, mean1);
            pair_arrive(B_XC);
            TR(1);
            float ak[28], av[28], aq[28];
            float ss0 = 0.f, ss1 = 0.f, ss2 = 0.f, ss3 = 0.f;
            const uint32_t dw = desc_lo(sb + (hg & 1) * 16, 0);
            static_for<0, 7>([&](auto S_) {
                constexpr int s = decltype(S_)::value;
                #pragma unroll
                for (int q = 0; q < 4; q++) {
                    uint32_t (&f)[4] = a[s * 4 + q];
                    f[0] = sub_bf16x2(f[0], mb0); f[1] = sub_bf16x2(f[1], mb1);
                    f[2] = sub_bf16x2(f[2], mb0); f[3] = sub_bf16x2(f[3], mb1);
                    ss0 = fmaf(bf_lo(f[0]), bf_lo(f[0]), ss0); ss2 = fmaf(bf_hi(f[0]), bf_hi(f[0]), ss2);
                    ss1 = fmaf(bf_lo(f[1]), bf_lo(f[1]), ss1); ss3 = fmaf(bf_hi(f[1]), bf_hi(f[1]), ss3);
                    ss0 = fmaf(bf_lo(f[2]), bf_lo(f[2]), ss0); ss2 = fmaf(bf_hi(f[2]), bf_hi(f[2]), ss2);
                    ss1 = fmaf(bf_lo(f[3]), bf_lo(f[3]), ss1); ss3 = fmaf(bf_hi(f[3]), bf_hi(f[3]), ss3);
                }
                mbar_wait(BAR(B_WKVF + s), 0);
                wg_fence();
                static_for<0, 4>([&](auto Q_) {
                    constexpr int q = decltype(Q_)::value;
                    uint32_t (&f)[4] = a[s * 4 + q];
                    wgmma_rs_n56<SM_WKV + s * 16384 + q * 2048, (s | q) != 0>(ak, f[0], f[1], f[2], f[3], dw);
                    wgmma_rs_n56<SM_WKV + s * 16384 + q * 2048 + 8192, (s | q) != 0>(av, f[0], f[1], f[2], f[3], dw);
                });
                wg_commit();
                if (s == 4) { wg_wait<1>(); pair_arrive(B_KV3); }
            });
            auto q_chunk = [&](auto C_) {
                wg_fence();
                static_for<0, 7>([&](auto K_) {
                    constexpr int k = decltype(C_)::value * 7 + decltype(K_)::value;
                    wgmma_rs_n56<SM_X + k * 2048, k != 0>(aq, a[k][0], a[k][1], a[k][2], a[k][3], dw);
                });
                wg_commit();
            };
            const float dl0 = mean0 - bf_lo(mb0), dl1 = mean1 - bf_lo(mb1);
            const float rs0 = rsq(fmaxf(quad_sum(ss0 + ss2) * (1.f / kD) - dl0 * dl0, 0.f) + kEps);
            const float rs1 = rsq(fmaxf(quad_sum(ss1 + ss3) * (1.f / kD) - dl1 * dl1, 0.f) + kEps);
            mbar_wait2(BAR(B_EP), 0, BAR(B_WQF), 0);
            asm volatile("ld.shared.u32 %0, [%1];" : "=r"(tag) : "r"(sb + SM_EPOCH) : "memory");
            q_chunk(std::integral_constant<int, 0>{});
            wg_wait<1>();
            reg_fence(ak); reg_fence(av);
            TR(2);
            uint32_t kf[3][7], vf[3][7];
            #pragma unroll
            for (int c = 0; c < 7; c++) {
                kf[2][c] = pack_bf16(ak[4 * c + 2] * rs1, ak[4 * c + 3] * rs1);
                vf[2][c] = movm(pack_bf16(av[4 * c + 2] * rs1, av[4 * c + 3] * rs1));
            }
            const uint32_t stg = sb + SM_RED + (1 - wg) * 16384 + lane * 16;
            if (w == 3) {
                uint4* hp = &g_halo[((ti * 8 + hg) * 2 + wg) * 7 * 32 + lane];
                #pragma unroll
                for (int c = 0; c < 7; c++) st_ll(hp + c * 32, kf[2][c], vf[2][c], tag);
            } else {
                sts4(stg + w * 2048 + 0,    kf[2][0], kf[2][1], kf[2][2], kf[2][3]);
                sts4(stg + w * 2048 + 512,  kf[2][4], kf[2][5], kf[2][6], vf[2][0]);
                sts4(stg + w * 2048 + 1024, vf[2][1], vf[2][2], vf[2][3], vf[2][4]);
                sts4(stg + w * 2048 + 1536, vf[2][5], vf[2][6], 0u, 0u);
            }
            pair_arrive(B_KVC);
            q_chunk(std::integral_constant<int, 1>{});
            #pragma unroll
            for (int c = 0; c < 7; c++) {
                kf[1][c] = pack_bf16(ak[4 * c] * rs0, ak[4 * c + 1] * rs0);
                vf[1][c] = movm(pack_bf16(av[4 * c] * rs0, av[4 * c + 1] * rs0));
            }
            named_bar(1 + wg, 128);
            q_chunk(std::integral_constant<int, 2>{});
            q_chunk(std::integral_constant<int, 3>{});
            if (w == 0) {
                if (ti > 0) {
                    const uint4* hp = &g_halo[(((ti - 1) * 8 + hg) * 2 + wg) * 7 * 32 + lane];
                    int it = 0; bool ok;
                    do {
                        ok = true;
                        #pragma unroll
                        for (int c = 0; c < 7; c++) ok &= ld_ll(hp + c * 32, kf[0][c], vf[0][c], tag);
                        if (++it > kSpinLimit) { TIMEOUT(101); break; }
                    } while (!__all_sync(~0u, ok));
                } else {
                    #pragma unroll
                    for (int c = 0; c < 7; c++) { kf[0][c] = 0u; vf[0][c] = 0u; }
                }
            } else {
                const uint4 u0 = lds4(stg + (w - 1) * 2048), u1 = lds4(stg + (w - 1) * 2048 + 512),
                            u2 = lds4(stg + (w - 1) * 2048 + 1024), u3 = lds4(stg + (w - 1) * 2048 + 1536);
                kf[0][0] = u0.x; kf[0][1] = u0.y; kf[0][2] = u0.z; kf[0][3] = u0.w;
                kf[0][4] = u1.x; kf[0][5] = u1.y; kf[0][6] = u1.z; vf[0][0] = u1.w;
                vf[0][1] = u2.x; vf[0][2] = u2.y; vf[0][3] = u2.z; vf[0][4] = u2.w;
                vf[0][5] = u3.x; vf[0][6] = u3.y;
            }
            uint4* op = opaque_ptr(&g_o[tag & 1][(((ti * 2 + wg) * 4 + w) * 28 + ((7 * hg) >> 1)) * 32 + lane]);
            TR(3);
            wg_wait<0>();
            reg_fence(aq);
            warp_arrive(BAR(B_A1D));
            TR(4);
            uint32_t qf[7][2];
            #pragma unroll
            for (int c = 0; c < 7; c++) {
                qf[c][0] = pack_bf16(aq[4 * c], aq[4 * c + 1]);
                qf[c][1] = pack_bf16(aq[4 * c + 2], aq[4 * c + 3]);
            }
            const bool has_prev = (ti > 0) || (w > 0);
            const float sc0 = rs0 * (0.18898223650461362f * 1.4426950408889634f);
            const float sc1 = rs1 * (0.18898223650461362f * 1.4426950408889634f);
            const float NEG = -__int_as_float(0x7f800000);
            uint32_t ow[7][2];
            #pragma unroll
            for (int hd = 0; hd < 2; hd++) {
                const int c0 = hd * 3;
                const bool keep = hd == 0 ? (t < 2) : (t >= 2);
                const uint32_t q3a = keep ? qf[3][0] : 0u, q3b = keep ? qf[3][1] : 0u;
                float sc_[3][4];
                #pragma unroll
                for (int n = 0; n < 3; n++) {
                    sc_[n][0] = sc_[n][1] = sc_[n][2] = sc_[n][3] = 0.f;
                    if (hd == 0) {
                        mma16816(sc_[n], qf[0][0], qf[0][1], qf[1][0], qf[1][1], kf[n][0], kf[n][1]);
                        mma16816(sc_[n], qf[2][0], qf[2][1], q3a, q3b, kf[n][2], kf[n][3]);
                    } else {
                        mma16816(sc_[n], q3a, q3b, qf[4][0], qf[4][1], kf[n][3], kf[n][4]);
                        mma16816(sc_[n], qf[5][0], qf[5][1], qf[6][0], qf[6][1], kf[n][5], kf[n][6]);
                    }
                }
                const bool gt0 = 2 * t > g, gt1 = 2 * t + 1 > g;
                const float e0 = gt0 ? (has_prev ? sc_[0][0] : NEG) : sc_[1][0], e1 = gt1 ? (has_prev ? sc_[0][1] : NEG) : sc_[1][1];
                const float f0 = gt0 ? sc_[1][2] : sc_[2][2], f1 = gt1 ? sc_[1][3] : sc_[2][3];
                const float me = quad_max(fmaxf(e0, e1)) * sc0, mf = quad_max(fmaxf(f0, f1)) * sc1;
                float p0 = ex2(fmaf(e0, sc0, -me)), p1 = ex2(fmaf(e1, sc0, -me));
                float r0 = ex2(fmaf(f0, sc1, -mf)), r1 = ex2(fmaf(f1, sc1, -mf));
                const float ie = rcp(quad_sum(p0 + p1)), jf = rcp(quad_sum(r0 + r1));
                const uint32_t pp = pack_bf16(p0 * ie, p1 * ie), rp = pack_bf16(r0 * jf, r1 * jf);
                const uint32_t mk = (gt0 ? 0x0000ffffu : 0u) | (gt1 ? 0xffff0000u : 0u);
                const uint32_t sw = hg >= 4 ? ~0u : 0u;
                const uint32_t pa0 = pp & mk & ~sw, pa1 = pp & mk & sw, pb0 = rp & ~mk & sw, pb1 = rp & ~mk & ~sw;
                const uint32_t pa2 = sw ? rp & mk : pp & ~mk, pa3 = sw ? pp & ~mk : rp & mk;
                #pragma unroll
                for (int c = 0; c < 4; c++) {
                    float o[4] = {0.f, 0.f, 0.f, 0.f};
                    mma16816(o, pa0, pa1, pa2, pa3, vf[0][c0 + c], vf[1][c0 + c]);
                    mma1688(o, pb0, pb1, vf[2][c0 + c]);
                    const uint32_t lo = max(pack_bf16(o[0], o[1]), 1u), hi = pack_bf16(o[2], o[3]);
                    if (hd == 1 && c == 0) { if (t >= 2) { ow[3][0] = lo; ow[3][1] = hi; } }
                    else { ow[c0 + c][0] = lo; ow[c0 + c][1] = hi; }
                }
            }
            if (hg & 1) {
                ((uint2*)(op - lane))[32 + lane] = make_uint2(ow[0][0], ow[0][1]);
                op[32] = make_uint4(ow[1][0], ow[1][1], ow[2][0], ow[2][1]);
                op[64] = make_uint4(ow[3][0], ow[3][1], ow[4][0], ow[4][1]);
                op[96] = make_uint4(ow[5][0], ow[5][1], ow[6][0], ow[6][1]);
            } else {
                op[0]  = make_uint4(ow[0][0], ow[0][1], ow[1][0], ow[1][1]);
                op[32] = make_uint4(ow[2][0], ow[2][1], ow[3][0], ow[3][1]);
                op[64] = make_uint4(ow[4][0], ow[4][1], ow[5][0], ow[5][1]);
                ((uint2*)(op + 96 - lane))[lane] = make_uint2(ow[6][0], ow[6][1]);
            }
            TR(5);
        }
        {
            float acc2[64];
            const bool wide = a2j != 3;
            mbar_wait(BAR(B_XRF), 0);
            {
                const uint32_t xa = sb + SM_X + 8 * 8192 + (w * 16 + wg * 8 + (lane & 7)) * 128;
                #pragma unroll
                for (int c = 0; c < 4; c++) {
                    uint32_t xr[4];
                    asm volatile("ldmatrix.sync.aligned.m8n8.x4.shared.b16 {%0,%1,%2,%3}, [%4];"
                                 : "=r"(xr[0]), "=r"(xr[1]), "=r"(xr[2]), "=r"(xr[3])
                                 : "r"(xa + (c >> 1) * 8192 + ((((c & 1) * 4 + (lane >> 3)) ^ (lane & 7)) << 4)) : "memory");
                    #pragma unroll
                    for (int e = 0; e < 4; e++) {
                        acc2[16 * c + 4 * e] = bf_lo(xr[e]); acc2[16 * c + 4 * e + 1] = bf_hi(xr[e]);
                        acc2[16 * c + 4 * e + 2] = 0.f;      acc2[16 * c + 4 * e + 3] = 0.f;
                    }
                }
            }
            const uint4* op = &g_o[tag & 1][((a2s * 4 + w) * 28 + wg * 14) * 32];
            const uint32_t rsend = opaque(sb + SM_RED + (1 - wg) * 16384 + w * 4096 + lane * 16);
            const uint32_t rrecv = opaque(sb + SM_RED + wg * 16384 + w * 4096 + lane * 16);
            uint4* spw = opaque_ptr(&g_stats[(a2s * 4 + a2j) * 64 + (w * 2 + wg) * 8 + g]);
            const uint4* spr = opaque_ptr(&g_stats[(a2s * 4 + t) * 64 + (w * 2 + wg) * 8 + g]);
            uint2* hp = opaque_ptr((uint2*)g_h + ((a2s * 8 + w * 2 + wg) * 28 + a2j * 8) * 32 + lane);
            uint32_t* np = opaque_ptr((uint32_t*)&g_hn[(a2s * 56 + a2j * 16) * 64] + (w * 2 + wg) * 32 + lane);
            reg_fence(acc2);
            mbar_wait(BAR(B_WOF + wg), 0);
            {
                const uint32_t* pp = (const uint32_t*)(op + ((t >> 1) * 7 + 3 + (t & 1) * 3) * 32) + 32 + (t & 1) * 64;
                int it = 0;
                while (true) {
                    tick<PROBEP>();
                    if (!__any_sync(~0u, ld_rlx(pp) == 0u)) break;
                    if (++it > kSpinLimit) { TIMEOUT(102); break; }
                }
            }
            TR(6);
            uint4 of[14];
            auto load_o = [&](int k) {
                if (k % 7 == 3) {
                    const uint2 lo = ld_rlx2((const uint2*)(op + k * 32) + lane), hi = ld_rlx2((const uint2*)(op + k * 32) + 32 + lane);
                    of[k] = make_uint4(lo.x, lo.y, hi.x, hi.y);
                } else of[k] = ld_rlx4(op + k * 32 + lane);
            };
            #pragma unroll
            for (int k = 0; k < 14; k++) load_o(k);
            const uint32_t dwo = desc_lo(sb + SM_WKV + wg * 57344, 28672);
            static_for<0, 4>([&](auto G_) {
                constexpr int k0 = (decltype(G_)::value * 7) / 2, k1 = (decltype(G_)::value * 7 + 7) / 2;
                int it = 0;
                while (true) {
                    bool bad = false;
                    #pragma unroll
                    for (int k = k0; k < k1; k++) bad |= of[k].x == 0u || (k % 7 == 3 && of[k].z == 0u);
                    if (!__any_sync(~0u, bad)) break;
                    if (++it > kSpinLimit) { TIMEOUT(109); break; }
                    RETRY_COUNT(1);
                    #pragma unroll
                    for (int k = k0; k < k1; k++) load_o(k);
                }
                if (k1 == 14) warp_arrive(BAR(B_OL));
                wg_fence();
                static_for<k0, k1>([&](auto K_) { constexpr int k = decltype(K_)::value;
                    wgmma_rs_n128<k * 2048, 1>(acc2, of[k].x, of[k].y, of[k].z, of[k].w, dwo); });
            });
            wg_commit();
            wg_wait<0>();
            reg_fence(acc2);
            TR(7);
            #pragma unroll
            for (int c = 0; c < 8; c++)
                sts4(rsend + c * 512, __float_as_uint(acc2[8 * c + 2]), __float_as_uint(acc2[8 * c + 3]), __float_as_uint(acc2[8 * c + 6]), __float_as_uint(acc2[8 * c + 7]));
            named_bar(3, 256);
            float hv[32];
            float s0 = 0.f, s1 = 0.f, q0 = 0.f, q1 = 0.f;
            #pragma unroll
            for (int c = 0; c < 8; c++) {
                const uint4 u = lds4(rrecv + c * 512);
                hv[4 * c]     = acc2[8 * c] + __uint_as_float(u.x);     hv[4 * c + 1] = acc2[8 * c + 1] + __uint_as_float(u.y);
                hv[4 * c + 2] = acc2[8 * c + 4] + __uint_as_float(u.z); hv[4 * c + 3] = acc2[8 * c + 5] + __uint_as_float(u.w);
            }
            #pragma unroll
            for (int c = 0; c < 16; c += 2) { s0 += hv[c]; s1 += hv[c + 1]; q0 = fmaf(hv[c], hv[c], q0); q1 = fmaf(hv[c + 1], hv[c + 1], q1); }
            if (wide) {
                #pragma unroll
                for (int c = 16; c < 32; c += 2) { s0 += hv[c]; s1 += hv[c + 1]; q0 = fmaf(hv[c], hv[c], q0); q1 = fmaf(hv[c + 1], hv[c + 1], q1); }
            }
            s0 = quad_sum(s0 + s1); q0 = quad_sum(q0 + q1);
            if (t == 0) st_ll(spw, __float_as_uint(s0), __float_as_uint(q0), tag);
            TR(8);
            fence_async_smem();
            #pragma unroll
            for (int c = 0; c < 8; c++)
                if (c < 4 || wide) hp[c * 32] = make_uint2(pack_bf16(hv[4 * c], hv[4 * c + 1]), pack_bf16(hv[4 * c + 2], hv[4 * c + 3]));
            uint32_t um, uv;
            {
                int it = 0;
                while (!__all_sync(~0u, ld_ll(spr, um, uv, tag))) { if (++it > kSpinLimit) { TIMEOUT(103); break; } }
            }
            TR(9);
            const float mean = quad_sum(__uint_as_float(um)) * (1.f / kD);
            const float var = fmaxf(fmaf(quad_sum(__uint_as_float(uv)), 1.f / kD, -mean * mean), 0.f);
            const float r1 = rsq(var + kEps);
            const float rr = r1 * rsq(fmaf(var * r1, r1, kEps));
            const float mr = -mean * rr;
            #pragma unroll
            for (int c = 0; c < 16; c++)
                if (c < 8 || wide) np[c * 256] = pack_bf16(fmaf(hv[2 * c], rr, mr), fmaf(hv[2 * c + 1], rr, mr));
            named_bar(3, 256);
            mbar_arrive_remote_if(pbar0 + 8u * B_PD, tid == 0);
            if (tid == 128) { fence_async_global(); fence_gpu(); st_flag(&g_flag_h[(a2s * 4 + a2j) * FS], tag); mbar_arrive(BAR(B_HD)); }
            __syncwarp();
            TR(10);
        }
        float acc[56];
        const uint32_t red = opaque(sb + SM_RED + w * 3584 + lane * 16);
        uint32_t peer_red; const uint32_t peer_bar = pbar0;
        asm volatile("mapa.shared::cluster.u32 %0, %1, %2;" : "=r"(peer_red) : "r"(red), "r"(rank ^ 1));
        uint32_t bph = 0;
        #pragma unroll 1
        for (int ge = g1_on ? 0 : 1; ge < 2; ge++) {
            const int pos = (ge ? (g1_on ? 32 : 0) : 0) + wg * (ge ? 14 : 16);
            const uint32_t aph = (ge && g1_on) ? 1u : 0u;
            const int row = w * 16 + rank * 8 + g;
            const int dsub = (ge ? g2j : g1j) + 2 * wg;
            const float bias = __bfloat162float(ge ? prm.b2[g2s * 64 + row] : prm.b1[g1f * 64 + row]);
            const int tok = g2s * 64 + row, pr = (tok & 127) >> 1;
            const uint2* hp = opaque_ptr((const uint2*)g_h + ((((tok >> 7) * 2 + (tok & 1)) * 8 + (pr >> 3)) * 28 + dsub * 7) * 32 + (pr & 7) * 4 + t);
            uint32_t fbar[NB], ebar[NB], sp[NB], db[NB];
            #pragma unroll
            for (int i = 0; i < NB; i++) {
                const uint32_t sl = (pos + i) % NB;
                fbar[i] = opaque(BAR(B_BF + wg * NB + sl)); ebar[i] = opaque(BAR(B_BE + sl));
                sp[i] = opaque((bph >> sl) & 1);            db[i] = desc_lo(sb + SM_B + sl * 14336, 128);
            }
            uint32_t* gp = opaque_ptr(ge ? (uint32_t*)(prm.out + (size_t)(g2s * 64 + w * 16 + rank * 8) * kD + dsub * 112)
                                         : (uint32_t*)&g_g[(g1f * 56 + dsub * 14) * 64] + (w * 2 + rank) * 32 + lane);
            const bool lead = elect_one();
            const bool rel_a = lead && !ge && wg == 1;
            const uint32_t da = desc_lo(sb, 0);
            auto stage = [&](auto S_) {
                constexpr int s = decltype(S_)::value;
                constexpr int aoff = s < 10 ? s * 8192 : SM_AHI + (s - 10) * 8192;
                wg_fence();
                wgmma_ss_n112<aoff,        0,   s != 0>(acc, da, db[s % NB]);
                wgmma_ss_n112<aoff + 2048, 256, 1>(acc, da, db[s % NB]);
                wgmma_ss_n112<aoff + 4096, 512, 1>(acc, da, db[s % NB]);
                wgmma_ss_n112<aoff + 6144, 768, 1>(acc, da, db[s % NB]);
                wg_commit();
                if (s < 15 && !(s == 13 && ge))
                    mbar_wait2(BAR(B_AF + s + 1), aph, fbar[(s + 1) % NB], sp[(s + 1) % NB] ^ (((s + 1) / NB) & 1));
                if constexpr (s > 0) {
                    wg_wait<1>();
                    mbar_arrive_if(ebar[(s - 1) % NB], lead);
                    if (s <= 14) mbar_arrive_if(BAR(B_AE + s - 1), rel_a);
                }
            };
            mbar_wait2(BAR(B_AF), aph, fbar[0], sp[0]);
            TR(11 + ge * 4);
            static_for<0, 14>(stage);
            if (!ge) static_for<14, 16>(stage);
            const uint32_t lastbar = ge ? ebar[13 % NB] : ebar[15 % NB];
            #pragma unroll
            for (int i = 0; i < NB; i++) if (((16 - i + NB - 1) / NB) & 1) bph ^= 1u << ((pos + i) % NB);
            uint2 hr[7];
            #pragma unroll
            for (int c = 0; c < 7; c++) hr[c] = ge ? ld_rlx2(hp + c * 32) : make_uint2(0u, 0u);
            const int use = ge * 2 + wg;
            mbar_wait(BAR(use > (g1_on ? 0 : 2) ? B_RE + use - 1 : B_PD), 0);
            wg_wait<0>();
            reg_fence(acc);
            TR(12 + ge * 4);
            mbar_arrive_if(lastbar, lead);
            float v[28];
            auto send = [&](auto R_) {
                constexpr int o = decltype(R_)::value * 2;
                #pragma unroll
                for (int c = 0; c < 7; c++) {
                    asm volatile("st.async.shared::cluster.mbarrier::complete_tx::bytes.v4.f32 [%0], {%1,%2,%3,%4}, [%5];"
                                 :: "r"(peer_red + c * 512), "f"(acc[8 * c + 2 - o]), "f"(acc[8 * c + 3 - o]), "f"(acc[8 * c + 6 - o]), "f"(acc[8 * c + 7 - o]),
                                    "r"(peer_bar + (B_RF + use) * 8) : "memory");
                    v[4 * c] = acc[8 * c + o]; v[4 * c + 1] = acc[8 * c + 1 + o]; v[4 * c + 2] = acc[8 * c + 4 + o]; v[4 * c + 3] = acc[8 * c + 5 + o];
                }
            };
            if (rank) send(std::integral_constant<int, 1>{}); else send(std::integral_constant<int, 0>{});
            #pragma unroll
            for (int c = 0; c < 7; c++) {
                v[4 * c] += bf_lo(hr[c].x) + bias;     v[4 * c + 1] += bf_hi(hr[c].x) + bias;
                v[4 * c + 2] += bf_lo(hr[c].y) + bias; v[4 * c + 3] += bf_hi(hr[c].y) + bias;
            }
            reg_fence(v);
            mbar_wait_cluster(BAR(B_RF + use), 0);
            #pragma unroll
            for (int c = 0; c < 7; c++) {
                const uint4 u = lds4(red + c * 512);
                v[4 * c] += __uint_as_float(u.x);     v[4 * c + 1] += __uint_as_float(u.y);
                v[4 * c + 2] += __uint_as_float(u.z); v[4 * c + 3] += __uint_as_float(u.w);
            }
            TR(13 + ge * 4);
            if (!ge) {
                reg_fence(v);
                __syncwarp();
                if (lead) asm volatile("mbarrier.arrive.shared::cluster.b64 _, [%0];" :: "r"(peer_bar + (B_RE + use) * 8) : "memory");
                #pragma unroll
                for (int c = 0; c < 14; c++) {
                    float r[2];
                    #pragma unroll
                    for (int e = 0; e < 2; e++) {
                        const float u = v[2 * c + e];
                        const float z = u * fmaf(u * u, -2.302208198f * 0.044715f, -2.302208198f);
                        r[e] = u * rcp(1.f + ex2(z));
                    }
                    gp[c * 256] = pack_bf16(r[0], r[1]);
                }
                named_bar(1 + wg, 128);
                if (w == 0 && lane == 0) {
                    fence_async_global(); fence_gpu();
                    st_flag(&g_flag_g[((dsub * 28 + g1f) * 2 + rank) * FS], tag);
                    mbar_arrive(BAR(B_GD + wg));
                }
                __syncwarp();
            } else {
                const uint32_t stw = red - lane * 16;
                uint32_t pk[14];
                #pragma unroll
                for (int c = 0; c < 14; c++) pk[c] = pack_bf16(v[2 * c], v[2 * c + 1]);
                __syncwarp();
                const uint32_t sa = stw + (lane & 7) * 240 + (lane >> 3) * 16;
                #pragma unroll
                for (int m = 0; m < 3; m++)
                    asm volatile("stmatrix.sync.aligned.m8n8.x4.shared.b16 [%0], {%1,%2,%3,%4};"
                                 :: "r"(sa + m * 64), "r"(pk[4 * m]), "r"(pk[4 * m + 1]), "r"(pk[4 * m + 2]), "r"(pk[4 * m + 3]) : "memory");
                asm volatile("stmatrix.sync.aligned.m8n8.x2.shared.b16 [%0], {%1,%2};" :: "r"(sa + 192), "r"(pk[12]), "r"(pk[13]) : "memory");
                __syncwarp();
                #pragma unroll
                for (int i = 0; i < 4; i++) {
                    const int r = 2 * i + (lane >> 4), ch = lane & 15;
                    if (ch < 14) *(uint4*)(gp + r * 224 + ch * 4) = lds4(stw + r * 240 + ch * 16);
                }
                __syncwarp();
                if (lead && wg == 0) asm volatile("mbarrier.arrive.shared::cluster.b64 _, [%0];" :: "r"(peer_bar + (B_RE + 2) * 8) : "memory");
            }
            TR(14 + ge * 4);
        }
        if (tid == 128) TRG(62);
        if (b == 0 && tid == 128) g_epoch = tag;
    }
}

typedef CUresult (*EncodeFn)(CUtensorMap*, CUtensorMapDataType, cuuint32_t, void*, const cuuint64_t*, const cuuint64_t*,
                             const cuuint32_t*, const cuuint32_t*, CUtensorMapInterleave, CUtensorMapSwizzle,
                             CUtensorMapL2promotion, CUtensorMapFloatOOBfill);

void make_map(EncodeFn enc, CUtensorMap* m, const void* base, uint64_t cols, uint64_t rows, uint32_t box_rows) {
    cuuint64_t dims[2] = {cols, rows};
    cuuint64_t strides[1] = {cols * 2};
    cuuint32_t box[2] = {64, box_rows};
    cuuint32_t es[2] = {1, 1};
    enc(m, CU_TENSOR_MAP_DATA_TYPE_BFLOAT16, 2, const_cast<void*>(base), dims, strides, box, es, CU_TENSOR_MAP_INTERLEAVE_NONE,
        CU_TENSOR_MAP_SWIZZLE_128B, CU_TENSOR_MAP_L2_PROMOTION_L2_128B, CU_TENSOR_MAP_FLOAT_OOB_FILL_NONE);
}

}

extern "C" void kernel_launch(void* const* d_in, const int* in_sizes, int n_in, void* d_out, int out_size) {
    (void)in_sizes; (void)n_in; (void)out_size;
    void* fn = nullptr;
    cudaDriverEntryPointQueryResult qr;
    cudaGetDriverEntryPoint("cuTensorMapEncodeTiled", &fn, cudaEnableDefault, &qr);
    EncodeFn enc = (EncodeFn)fn;
    CUtensorMap mX, mWqkv, mWo, mW1, mW2;
    make_map(enc, &mX, d_in[0], 2 * kD, kS / 2, 64);
    make_map(enc, &mWqkv, d_in[1], 3 * kD, kD, 64);
    make_map(enc, &mWo, d_in[2], kD, kD, 224);
    make_map(enc, &mW1, d_in[4], 2 * kF, kS / 2, 64);
    make_map(enc, &mW2, d_in[6], kS, kF, 64);
    Params prm;
    prm.x = (const __nv_bfloat16*)d_in[0];
    prm.wqkv = (const __nv_bfloat16*)d_in[1];
    prm.wo = (const __nv_bfloat16*)d_in[2];
    prm.w1 = (const __nv_bfloat16*)d_in[4];
    prm.b1 = (const __nv_bfloat16*)d_in[5];
    prm.w2 = (const __nv_bfloat16*)d_in[6];
    prm.b2 = (const __nv_bfloat16*)d_in[7];
    prm.out = (__nv_bfloat16*)d_out;
    cudaFuncSetAttribute(fused_kernel, cudaFuncAttributeMaxDynamicSharedMemorySize, SM_TOTAL);
    fused_kernel<<<128, 384, SM_TOTAL, cudaStreamPerThread>>>(mX, mWqkv, mWo, mW1, mW2, prm);
}
```

```cpp
#include <cuda_runtime.h>
#include <cuda.h>
#include <cuda_bf16.h>
#include <stdint.h>
#include <type_traits>

namespace {

constexpr int kS = 2048, kD = 448, kF = 1792;
constexpr float kEps = 1e-5f;

#define FS 32
__device__ __align__(1024) uint4    g_o[2][32 * 4 * 28 * 32];
__device__ __align__(1024) uint4    g_h[kS * kD * 2 / 16];
__device__ __align__(1024) uint4    g_hn[32 * 56 * 64];
__device__ __align__(1024) uint4    g_g[28 * 56 * 64];
__device__ __align__(1024) uint4    g_halo[16 * 8 * 2 * 7 * 32];
__device__ __align__(1024) uint4    g_stats[32 * 4 * 64];
__device__ __align__(1024) uint32_t g_flag_h[32 * 4 * FS];
__device__ __align__(1024) uint32_t g_flag_g[4 * 28 * 2 * FS];
__device__ uint32_t g_epoch;
#define TIMEOUT(code)
#define RETRY_COUNT(i)
#define TR(idx)
#define TRW(idx)
#define TRG(idx)

constexpr uint32_t SM_X    = 0;
constexpr uint32_t SM_WKV  = 114688;
constexpr uint32_t SM_RED  = 81920;
constexpr uint32_t SM_B    = 96256;
constexpr uint32_t SM_AHI  = 182272;
constexpr uint32_t SM_BAR  = 231424;
constexpr uint32_t SM_TOTAL = SM_BAR + 1024;
constexpr int NB = 6;
constexpr int B_XF = 0, B_WKVF = 7, B_WQF = 14, B_XRF = 15, B_WOF = 16,
              B_XC = 18, B_KV3 = 19, B_KVC = 20,
              B_A1D = 21, B_OL = 22,
              B_AE = 23, B_BE = B_AE + 14, B_RE = B_BE + NB,
              B_AF = B_RE + 3, B_BF = B_AF + 16  , B_RF = B_BF + 2 * NB,
              B_EP = B_RF + 4, B_HD = B_EP + 1, B_PD = B_HD + 1, B_GD = B_PD + 1, B_GO = B_GD + 2, B_COUNT = B_GO + 4;
#define WEARLY 6
#define PF0 126
#define TMPF 2
#define RSTE 2
#define POLLP 1
#define PROBEP 1
#define LOADP 1
#define LOADW 64
#define NOB 0
#define AEARLY 5
#define W1PACE 280
#define W2PACE 420
#define PFPACE 330
#define PFBAR (B_XF + 6)
constexpr uint32_t SM_EPOCH = SM_BAR + B_COUNT * 8;

constexpr int kSpinLimit = 1 << 15;
__device__ __forceinline__ bool elect_one() {
    uint32_t p;
    asm volatile("{ .reg .pred P; elect.sync _|P, 0xffffffff; selp.u32 %0, 1, 0, P; }" : "=r"(p));
    return p;
}
__device__ __forceinline__ void mbar_init(uint32_t bar, uint32_t cnt) { asm volatile("mbarrier.init.shared::cta.b64 [%0], %1;" :: "r"(bar), "r"(cnt)); }
__device__ __forceinline__ void mbar_expect(uint32_t bar, uint32_t bytes) { asm volatile("mbarrier.arrive.expect_tx.shared::cta.b64 _, [%0], %1;" :: "r"(bar), "r"(bytes) : "memory"); }
__device__ __forceinline__ void mbar_arrive(uint32_t bar) { asm volatile("mbarrier.arrive.shared::cta.b64 _, [%0];" :: "r"(bar) : "memory"); }
__device__ __forceinline__ void mbar_wait(uint32_t bar, uint32_t parity) {
    uint32_t ok; int it = 0;
    do {
        asm volatile("{ .reg .pred p; mbarrier.try_wait.parity.shared::cta.b64 p, [%1], %2; selp.u32 %0, 1, 0, p; }"
                     : "=r"(ok) : "r"(bar), "r"(parity) : "memory");
        if (++it > kSpinLimit) { TIMEOUT((bar & 1023) >> 3); break; }
    } while (!ok);
}
__device__ __forceinline__ void mbar_wait2(uint32_t bar0, uint32_t par0, uint32_t bar1, uint32_t par1) {
    uint32_t ok; int it = 0;
    do {
        asm volatile("{ .reg .pred p, q; mbarrier.try_wait.parity.shared::cta.b64 p, [%1], %2;\n"
                     "mbarrier.try_wait.parity.shared::cta.b64 q, [%3], %4; and.pred p, p, q; selp.u32 %0, 1, 0, p; }"
                     : "=r"(ok) : "r"(bar0), "r"(par0), "r"(bar1), "r"(par1) : "memory");
        if (++it > kSpinLimit) { TIMEOUT((bar0 & 1023) >> 3); break; }
    } while (!ok);
}
template <int N> __device__ __forceinline__ void reg_fence(float (&d)[N]) {
    #pragma unroll
    for (int i = 0; i < N; i++) asm volatile("" : "+f"(d[i]) :: "memory");
}
__device__ __forceinline__ void mbar_wait_cluster(uint32_t bar, uint32_t parity) {
    uint32_t ok; int it = 0;
    do {
        asm volatile("{ .reg .pred p; mbarrier.try_wait.parity.acquire.cluster.shared::cta.b64 p, [%1], %2; selp.u32 %0, 1, 0, p; }"
                     : "=r"(ok) : "r"(bar), "r"(parity) : "memory");
        if (++it > kSpinLimit) { TIMEOUT((bar & 1023) >> 3); break; }
    } while (!ok);
}
__device__ __forceinline__ void mbar_arrive_if(uint32_t bar, bool pred) {
    asm volatile("{ .reg .pred p; setp.ne.u32 p, %1, 0; @p mbarrier.arrive.shared::cta.b64 _, [%0]; }" :: "r"(bar), "r"((uint32_t)pred) : "memory");
}
template <int P> __device__ __forceinline__ void tick() {
    if (P > 1) { const uint32_t t = ((uint32_t)clock() | (P - 1)) + 1; while ((int)((uint32_t)clock() - t) < 0) {} }
}
__device__ __forceinline__ void warp_arrive(uint32_t bar) { __syncwarp(); if (elect_one()) mbar_arrive(bar); }
__device__ __forceinline__ void tma2d(uint32_t dst, const CUtensorMap* m, int c0, int c1, uint32_t bar) {
    asm volatile("cp.async.bulk.tensor.2d.shared::cluster.global.mbarrier::complete_tx::bytes [%0], [%1, {%3, %4}], [%2];"
                 :: "r"(dst), "l"(m), "r"(bar), "r"(c0), "r"(c1) : "memory");
}
__device__ __forceinline__ void tma2d_mc(uint32_t dst, const CUtensorMap* m, int c0, int c1, uint32_t bar) {
    asm volatile("cp.async.bulk.tensor.2d.shared::cluster.global.mbarrier::complete_tx::bytes.multicast::cluster [%0], [%1, {%3, %4}], [%2], %5;"
                 :: "r"(dst), "l"(m), "r"(bar), "r"(c0), "r"(c1), "h"((uint16_t)3) : "memory");
}
__device__ __forceinline__ void bulk_g2s_mc(uint32_t dst, const void* src, uint32_t bytes, uint32_t bar) {
    asm volatile("cp.async.bulk.shared::cluster.global.mbarrier::complete_tx::bytes.multicast::cluster [%0], [%1], %2, [%3], %4;"
                 :: "r"(dst), "l"(src), "r"(bytes), "r"(bar), "h"((uint16_t)3) : "memory");
}
__device__ __forceinline__ void mbar_arrive_remote_if(uint32_t cluster_bar, bool pred) {
    asm volatile("{ .reg .pred p; setp.ne.u32 p, %1, 0; @p mbarrier.arrive.shared::cluster.b64 _, [%0]; }" :: "r"(cluster_bar), "r"((uint32_t)pred) : "memory");
}
__device__ __forceinline__ void bulk_g2s(uint32_t dst, const void* src, uint32_t bytes, uint32_t bar) {
    asm volatile("cp.async.bulk.shared::cluster.global.mbarrier::complete_tx::bytes [%0], [%1], %2, [%3];"
                 :: "r"(dst), "l"(src), "r"(bytes), "r"(bar) : "memory");
}
__device__ __forceinline__ void wg_fence()  { asm volatile("wgmma.fence.sync.aligned;" ::: "memory"); }
__device__ __forceinline__ void wg_commit() { asm volatile("wgmma.commit_group.sync.aligned;" ::: "memory"); }
template <int N> __device__ __forceinline__ void wg_wait() { asm volatile("wgmma.wait_group.sync.aligned %0;" :: "n"(N) : "memory"); }
__device__ __forceinline__ void named_bar(int id, int n) { asm volatile("bar.sync %0, %1;" :: "r"(id), "r"(n) : "memory"); }
__device__ __forceinline__ void fence_gpu() { asm volatile("fence.acq_rel.gpu;" ::: "memory"); }
__device__ __forceinline__ void fence_async_global() { asm volatile("fence.proxy.async.global;" ::: "memory"); }
__device__ __forceinline__ void fence_async_smem() { asm volatile("fence.proxy.async.shared::cta;" ::: "memory"); }
__device__ __forceinline__ void st_flag(uint32_t* p, uint32_t v) { asm volatile("st.relaxed.gpu.global.u32 [%0], %1;" :: "l"(p), "r"(v) : "memory"); }
__device__ __forceinline__ uint32_t ld_acq(const uint32_t* p) { uint32_t v; asm volatile("ld.acquire.gpu.global.u32 %0, [%1];" : "=r"(v) : "l"(p) : "memory"); return v; }
__device__ __forceinline__ uint32_t ld_rlx(const uint32_t* p) { uint32_t v; asm volatile("ld.relaxed.gpu.global.u32 %0, [%1];" : "=r"(v) : "l"(p) : "memory"); return v; }
template <class T> __device__ __forceinline__ T* opaque_ptr(T* p) { asm volatile("" : "+l"(p)); return p; }
__device__ __forceinline__ uint4 ld_rlx4(const uint4* p) {
    uint4 v; asm volatile("ld.relaxed.gpu.global.v4.u32 {%0,%1,%2,%3}, [%4];" : "=r"(v.x), "=r"(v.y), "=r"(v.z), "=r"(v.w) : "l"(p) : "memory"); return v;
}
__device__ __forceinline__ void st_ll(uint4* p, uint32_t a, uint32_t b, uint32_t tag) {
    uint64_t lo = ((uint64_t)tag << 32) | a, hi = ((uint64_t)tag << 32) | b;
    asm volatile("st.relaxed.gpu.global.v2.u64 [%0], {%1,%2};" :: "l"(p), "l"(lo), "l"(hi) : "memory");
}
__device__ __forceinline__ bool ld_ll(const uint4* p, uint32_t& a, uint32_t& b, uint32_t tag) {
    uint64_t lo, hi;
    asm volatile("ld.relaxed.gpu.global.v2.u64 {%0,%1}, [%2];" : "=l"(lo), "=l"(hi) : "l"(p) : "memory");
    a = (uint32_t)lo; b = (uint32_t)hi;
    return (uint32_t)(lo >> 32) == tag && (uint32_t)(hi >> 32) == tag;
}
__device__ __forceinline__ uint2 ld_acq2(const uint2* p) {
    uint2 v; asm volatile("ld.acquire.gpu.global.v2.u32 {%0,%1}, [%2];" : "=r"(v.x), "=r"(v.y) : "l"(p) : "memory"); return v;
}
__device__ __forceinline__ uint2 ld_rlx2(const uint2* p) {
    uint2 v; asm volatile("ld.relaxed.gpu.global.v2.u32 {%0,%1}, [%2];" : "=r"(v.x), "=r"(v.y) : "l"(p) : "memory"); return v;
}
__device__ __forceinline__ void sts4(uint32_t a, uint32_t x, uint32_t y, uint32_t z, uint32_t w) { asm volatile("st.shared.v4.u32 [%0], {%1,%2,%3,%4};" :: "r"(a), "r"(x), "r"(y), "r"(z), "r"(w) : "memory"); }
__device__ __forceinline__ uint4 lds4(uint32_t a) { uint4 v; asm volatile("ld.shared.v4.u32 {%0,%1,%2,%3}, [%4];" : "=r"(v.x), "=r"(v.y), "=r"(v.z), "=r"(v.w) : "r"(a) : "memory"); return v; }
__device__ __forceinline__ uint32_t pack_bf16(float lo, float hi) { uint32_t r; asm("cvt.rn.bf16x2.f32 %0, %1, %2;" : "=r"(r) : "f"(hi), "f"(lo)); return r; }
__device__ __forceinline__ float bf_lo(uint32_t v) { return __uint_as_float(v << 16); }
__device__ __forceinline__ float bf_hi(uint32_t v) { return __uint_as_float(v & 0xffff0000u); }
__device__ __forceinline__ uint32_t sub_bf16x2(uint32_t a, uint32_t b) { uint32_t r; asm("sub.rn.bf16x2 %0, %1, %2;" : "=r"(r) : "r"(a), "r"(b)); return r; }
__device__ __forceinline__ uint32_t movm(uint32_t a) { uint32_t r; asm volatile("movmatrix.sync.aligned.m8n8.trans.b16 %0, %1;" : "=r"(r) : "r"(a)); return r; }
__device__ __forceinline__ float ex2(float x) { float r; asm("ex2.approx.ftz.f32 %0, %1;" : "=f"(r) : "f"(x)); return r; }
__device__ __forceinline__ float rsq(float x) { float r; asm("rsqrt.approx.ftz.f32 %0, %1;" : "=f"(r) : "f"(x)); return r; }
__device__ __forceinline__ float rcp(float x) { float r; asm("rcp.approx.ftz.f32 %0, %1;" : "=f"(r) : "f"(x)); return r; }
__device__ __forceinline__ void mma16816(float (&c)[4], uint32_t a0, uint32_t a1, uint32_t a2, uint32_t a3, uint32_t b0, uint32_t b1) {
    asm("mma.sync.aligned.m16n8k16.row.col.f32.bf16.bf16.f32 {%0,%1,%2,%3}, {%4,%5,%6,%7}, {%8,%9}, {%0,%1,%2,%3};"
        : "+f"(c[0]), "+f"(c[1]), "+f"(c[2]), "+f"(c[3]) : "r"(a0), "r"(a1), "r"(a2), "r"(a3), "r"(b0), "r"(b1));
}
__device__ __forceinline__ void mma1688(float (&c)[4], uint32_t a0, uint32_t a1, uint32_t b0) {
    asm("mma.sync.aligned.m16n8k8.row.col.f32.bf16.bf16.f32 {%0,%1,%2,%3}, {%4,%5}, {%6}, {%0,%1,%2,%3};"
        : "+f"(c[0]), "+f"(c[1]), "+f"(c[2]), "+f"(c[3]) : "r"(a0), "r"(a1), "r"(b0));
}
__device__ __forceinline__ float quad_sum(float v) { v += __shfl_xor_sync(~0u, v, 1); v += __shfl_xor_sync(~0u, v, 2); return v; }
__device__ __forceinline__ float quad_max(float v) { v = fmaxf(v, __shfl_xor_sync(~0u, v, 1)); v = fmaxf(v, __shfl_xor_sync(~0u, v, 2)); return v; }
__device__ __forceinline__ uint32_t desc_lo(uint32_t addr, uint32_t lbo) { return ((addr & 0x3FFFF) >> 4) | ((lbo >> 4) << 16); }
template <int I, int N, class F> __device__ __forceinline__ void static_for(F&& f) {
    if constexpr (I < N) { f(std::integral_constant<int, I>{}); static_for<I + 1, N>(f); }
}
__device__ __forceinline__ uint32_t opaque(uint32_t v) { asm volatile("" : "+r"(v)); return v; }
template <int BOFF, int SCALE_D>
__device__ __forceinline__ void wgmma_rs_n56(float (&d)[28], uint32_t a0, uint32_t a1, uint32_t a2, uint32_t a3, uint32_t blo) {
    asm volatile("{ .reg .b32 lb; .reg .b64 db;\n"
        "add.u32 lb, %32, %33; mov.b64 db, {lb, 0x40000040};\n"
        "wgmma.mma_async.sync.aligned.m64n56k16.f32.bf16.bf16 "
        "{%0, %1, %2, %3, %4, %5, %6, %7, %8, %9, %10, %11, %12, %13, %14, %15, %16, %17, %18, %19, %20, %21, %22, %23, %24, %25, %26, %27}, "
        "{%28, %29, %30, %31}, db, %34, 1, 1, 1; }"
        : "+f"(d[0]), "+f"(d[1]), "+f"(d[2]), "+f"(d[3]), "+f"(d[4]), "+f"(d[5]), "+f"(d[6]), "+f"(d[7]),
        "+f"(d[8]), "+f"(d[9]), "+f"(d[10]), "+f"(d[11]), "+f"(d[12]), "+f"(d[13]), "+f"(d[14]), "+f"(d[15]),
        "+f"(d[16]), "+f"(d[17]), "+f"(d[18]), "+f"(d[19]), "+f"(d[20]), "+f"(d[21]), "+f"(d[22]), "+f"(d[23]),
        "+f"(d[24]), "+f"(d[25]), "+f"(d[26]), "+f"(d[27])
        : "r"(a0), "r"(a1), "r"(a2), "r"(a3), "r"(blo), "n"(BOFF >> 4), "n"(SCALE_D));
}
template <int BOFF, int SCALE_D>
__device__ __forceinline__ void wgmma_rs_n128(float (&d)[64], uint32_t a0, uint32_t a1, uint32_t a2, uint32_t a3, uint32_t blo) {
    asm volatile("{ .reg .b32 lb; .reg .b64 db;\n"
        "add.u32 lb, %68, %69; mov.b64 db, {lb, 0x40000040};\n"
        "wgmma.mma_async.sync.aligned.m64n128k16.f32.bf16.bf16 "
        "{%0, %1, %2, %3, %4, %5, %6, %7, %8, %9, %10, %11, %12, %13, %14, %15, %16, %17, %18, %19, %20, %21, %22, %23, %24, %25, %26, %27, %28, %29, %30, %31, %32, %33, %34, %35, %36, %37, %38, %39, %40, %41, %42, %43, %44, %45, %46, %47, %48, %49, %50, %51, %52, %53, %54, %55, %56, %57, %58, %59, %60, %61, %62, %63}, "
        "{%64, %65, %66, %67}, db, %70, 1, 1, 1; }"
        : "+f"(d[0]), "+f"(d[1]), "+f"(d[2]), "+f"(d[3]), "+f"(d[4]), "+f"(d[5]), "+f"(d[6]), "+f"(d[7]),
        "+f"(d[8]), "+f"(d[9]), "+f"(d[10]), "+f"(d[11]), "+f"(d[12]), "+f"(d[13]), "+f"(d[14]), "+f"(d[15]),
        "+f"(d[16]), "+f"(d[17]), "+f"(d[18]), "+f"(d[19]), "+f"(d[20]), "+f"(d[21]), "+f"(d[22]), "+f"(d[23]),
        "+f"(d[24]), "+f"(d[25]), "+f"(d[26]), "+f"(d[27]), "+f"(d[28]), "+f"(d[29]), "+f"(d[30]), "+f"(d[31]),
        "+f"(d[32]), "+f"(d[33]), "+f"(d[34]), "+f"(d[35]), "+f"(d[36]), "+f"(d[37]), "+f"(d[38]), "+f"(d[39]),
        "+f"(d[40]), "+f"(d[41]), "+f"(d[42]), "+f"(d[43]), "+f"(d[44]), "+f"(d[45]), "+f"(d[46]), "+f"(d[47]),
        "+f"(d[48]), "+f"(d[49]), "+f"(d[50]), "+f"(d[51]), "+f"(d[52]), "+f"(d[53]), "+f"(d[54]), "+f"(d[55]),
        "+f"(d[56]), "+f"(d[57]), "+f"(d[58]), "+f"(d[59]), "+f"(d[60]), "+f"(d[61]), "+f"(d[62]), "+f"(d[63])
        : "r"(a0), "r"(a1), "r"(a2), "r"(a3), "r"(blo), "n"(BOFF >> 4), "n"(SCALE_D));
}
template <int AOFF, int BOFF, int SCALE_D>
__device__ __forceinline__ void wgmma_ss_n112(float (&d)[56], uint32_t alo, uint32_t blo) {
    asm volatile("{ .reg .b32 la, lb; .reg .b64 da, db;\n"
        "add.u32 la, %56, %58; add.u32 lb, %57, %59;\n"
        "mov.b64 da, {la, 0x40000040}; mov.b64 db, {lb, 64};\n"
        "wgmma.mma_async.sync.aligned.m64n112k16.f32.bf16.bf16 "
        "{%0, %1, %2, %3, %4, %5, %6, %7, %8, %9, %10, %11, %12, %13, %14, %15, %16, %17, %18, %19, %20, %21, %22, %23, %24, %25, %26, %27, %28, %29, %30, %31, %32, %33, %34, %35, %36, %37, %38, %39, %40, %41, %42, %43, %44, %45, %46, %47, %48, %49, %50, %51, %52, %53, %54, %55}, "
        "da, db, %60, 1, 1, 1, 1; }"
        : "+f"(d[0]), "+f"(d[1]), "+f"(d[2]), "+f"(d[3]), "+f"(d[4]), "+f"(d[5]), "+f"(d[6]), "+f"(d[7]),
        "+f"(d[8]), "+f"(d[9]), "+f"(d[10]), "+f"(d[11]), "+f"(d[12]), "+f"(d[13]), "+f"(d[14]), "+f"(d[15]),
        "+f"(d[16]), "+f"(d[17]), "+f"(d[18]), "+f"(d[19]), "+f"(d[20]), "+f"(d[21]), "+f"(d[22]), "+f"(d[23]),
        "+f"(d[24]), "+f"(d[25]), "+f"(d[26]), "+f"(d[27]), "+f"(d[28]), "+f"(d[29]), "+f"(d[30]), "+f"(d[31]),
        "+f"(d[32]), "+f"(d[33]), "+f"(d[34]), "+f"(d[35]), "+f"(d[36]), "+f"(d[37]), "+f"(d[38]), "+f"(d[39]),
        "+f"(d[40]), "+f"(d[41]), "+f"(d[42]), "+f"(d[43]), "+f"(d[44]), "+f"(d[45]), "+f"(d[46]), "+f"(d[47]),
        "+f"(d[48]), "+f"(d[49]), "+f"(d[50]), "+f"(d[51]), "+f"(d[52]), "+f"(d[53]), "+f"(d[54]), "+f"(d[55])
        : "r"(alo), "r"(blo), "n"(AOFF >> 4), "n"(BOFF >> 4), "n"(SCALE_D));
}

struct Params {
    const __nv_bfloat16 *x, *wqkv, *wo, *w1, *w2, *b1, *b2;
    __nv_bfloat16* out;
};

__global__ void __cluster_dims__(2, 1, 1) __launch_bounds__(384, 1)
fused_kernel(const __grid_constant__ CUtensorMap mX, const __grid_constant__ CUtensorMap mWqkv,
             const __grid_constant__ CUtensorMap mWo, const __grid_constant__ CUtensorMap mW1,
             const __grid_constant__ CUtensorMap mW2, const Params prm)
{
    extern __shared__ __align__(1024) unsigned char smem_raw[];
    uint32_t sb = (uint32_t)__cvta_generic_to_shared(smem_raw);
    asm volatile("mov.u32 %0, %0;" : "+r"(sb));
    const uint32_t bar0 = sb + SM_BAR;
    auto BAR = [&](int i) { return bar0 + 8u * i; };

    const int tid = threadIdx.x, lane = tid & 31;
    const int warp = __shfl_sync(~0u, tid >> 5, 0);
    const int b = __shfl_sync(~0u, (int)blockIdx.x, 0);
    const int rank = b & 1;
    const int cl = b >> 1;
    const int res = cl < 4 ? 0 : cl < 36 ? (cl - 4) & 7 : 1 + (cl - 36) % 7;
    const int rnd = cl < 4 ? 4 + cl : cl < 36 ? (cl - 4) >> 3 : 4 + (cl - 36) / 7;
    const int hg = (res & 1) * 4 + (rnd & 3);
    const int ti = (res >> 1) * 4 + (rnd >> 2) * 2 + rank;
    const int a2p = res & 1, a2j = rnd & 3;
    const int a2s = ti * 2 + a2p;
    const bool g1_on = rnd != 7;
    const int g1j = (rnd < 6 ? rnd : res) & 1, g1f = rnd < 6 ? res * 3 + (rnd >> 1) : 24 + (res >> 1);
    const int g2j = rnd & 1, g2s = res * 4 + (rnd >> 1);
    uint32_t pbar0;
    asm volatile("mapa.shared::cluster.u32 %0, %1, %2;" : "=r"(pbar0) : "r"(bar0), "r"(rank ^ 1));
    auto pair_arrive = [&](int i) { __syncwarp(); const bool l = elect_one(); mbar_arrive_if(BAR(i), l); mbar_arrive_remote_if(pbar0 + 8u * i, l); };
    const int wcol = hg * 56 - (hg & 1) * 8;

    if (tid == 32) { TRG(60); TRW(59); }
    if (warp == 8) {
        if (elect_one()) {
            #pragma unroll
            for (int i = 0; i < B_WQF; i++) mbar_init(BAR(i), 1);
            asm volatile("fence.mbarrier_init.release.cluster;" ::: "memory");
            fence_async_smem();
            TRW(56);
            #pragma unroll 1
            for (int kb = 0; kb < 7; kb++) {
                mbar_expect(BAR(B_XF + kb), 16384);
                tma2d(sb + SM_X + kb * 8192, &mX, kb * 64, ti * 64, BAR(B_XF + kb));
                tma2d(sb + SM_X + 57344 + kb * 8192, &mX, kD + kb * 64, ti * 64, BAR(B_XF + kb));
                if (TMPF == 2 && kb == 0) asm volatile("prefetch.tensormap [%0];" :: "l"(&mWqkv) : "memory");
            }
        }
    } else if (warp > 8) {
        if (elect_one()) {
            if (warp == 9) {
                if (TMPF == 1) asm volatile("prefetch.tensormap [%0];" :: "l"(&mWqkv) : "memory");
                #pragma unroll
                for (int i = B_WQF; i < B_AF; i++) mbar_init(BAR(i), i < B_XC ? 1 : i < B_A1D ? 16 : i < B_AE ? 8 : 4);
            } else if (warp == 10) {
                #pragma unroll
                for (int i = B_AF; i < B_BF; i++) mbar_init(BAR(i), 1);
            } else {
                #pragma unroll
                for (int i = B_BF; i < B_COUNT; i++) mbar_init(BAR(i), 1);
            }
            asm volatile("fence.mbarrier_init.release.cluster;" ::: "memory");
            fence_async_smem();
        }
    } else {
        const char* p = tid < 112 ? (const char*)prm.x + (size_t)(ti * 8 + hg) * 14336 + tid * 128
                                  : (const char*)prm.wqkv + b * 2688 + 896 + (tid - 112) * 128;
        if (tid < PF0) asm volatile("prefetch.global.L2 [%0];" :: "l"(p));
    }
    __syncwarp();
    __syncthreads();
    asm volatile("barrier.cluster.arrive.relaxed.aligned;" ::: "memory");
    if (tid < 256) TR(0);
    if (tid == 0) TRG(61);

    if (warp >= 8) {
        asm volatile("setmaxnreg.dec.sync.aligned.u32 40;");
        asm volatile("barrier.cluster.wait.aligned;" ::: "memory");
        if (warp == 8) {
            if (elect_one()) {
                #pragma unroll 1
                for (int s = 0; s < 7; s++) {
                    mbar_expect(BAR(B_WKVF + s), 16384);
                    tma2d_mc(sb + SM_WKV + s * 16384 + rank * 8192, &mWqkv, (1 + rank) * kD + wcol, s * 64, BAR(B_WKVF + s));
                }
            }
            __syncwarp();
            mbar_wait(BAR(B_XC), 0);
            if (elect_one()) {
                asm volatile("prefetch.tensormap [%0];" :: "l"(&mWo) : "memory");
                asm volatile("prefetch.tensormap [%0];" :: "l"(&mW1) : "memory");
                asm volatile("prefetch.tensormap [%0];" :: "l"(&mW2) : "memory");
                mbar_expect(BAR(B_WQF), 57344);
                #pragma unroll 1
                for (int s = rank; s < 7; s += 2) tma2d_mc(sb + SM_X + s * 8192, &mWqkv, wcol, s * 64, BAR(B_WQF));
                mbar_expect(BAR(B_XRF), a2j == 3 ? 8192 : 16384);
                tma2d(sb + SM_X + 8 * 8192, &mX, a2p * kD + a2j * 128, ti * 64, BAR(B_XRF));
                if (a2j != 3) tma2d(sb + SM_X + 9 * 8192, &mX, a2p * kD + a2j * 128 + 64, ti * 64, BAR(B_XRF));
            }
            __syncwarp();
            #pragma unroll 1
            for (int h = 0; h < 2; h++) {
                mbar_wait(BAR(B_KV3 + h), 0);
                if (elect_one()) {
                    mbar_expect(BAR(B_WOF + h), a2j == 3 ? 28672 : 57344);
                    const int atom = rank ^ h;
                    if (a2j != 3 || atom == 0) tma2d_mc(sb + SM_WKV + h * 57344 + atom * 28672, &mWo, a2j * 128 + atom * 64, h * 224, BAR(B_WOF + h));
                }
                __syncwarp();
            }
            auto load_slab = [&](int s, bool second) {
                if (elect_one()) {
                    mbar_expect(BAR(B_AF + s), 8192);
                    const uint32_t dst = sb + (s < 10 ? s * 8192 : SM_AHI + (s - 10) * 8192);
                    if (g1_on && !second) tma2d(dst, &mW1, (s & 1) * kF + g1f * 64, (rank * 8 + (s >> 1)) * 64, BAR(B_AF + s));
                    else                  tma2d(dst, &mW2, g2s * 64, (rank * 14 + s) * 64, BAR(B_AF + s));
                }
                __syncwarp();
            };
            mbar_wait(BAR(B_A1D), 0);
            #pragma unroll 1
            for (int s = 0; s < 8; s++) {
                if (s == AEARLY) mbar_wait(BAR(B_OL), 0);
                load_slab(s, false);
            }
            mbar_wait(BAR(g1_on ? B_GO : B_HD), 0);
            {
                uint32_t tnext = (uint32_t)clock();
                #pragma unroll 1
                for (int s = 8; s < (g1_on ? 16 : 14); s++) {
                    tnext += W1PACE;
                    while ((int)((uint32_t)clock() - tnext) < 0) {}
                    load_slab(s, false);
                }
            }
            if (g1_on) {
                mbar_wait(BAR(B_AE), 0);
                uint32_t tnext = (uint32_t)clock();
                #pragma unroll 1
                for (int s = 0; s < 14; s++) {
                    mbar_wait(BAR(B_AE + s), 0);
                    while ((int)((uint32_t)clock() - tnext) < 0) {}
                    load_slab(s, true);
                    tnext += W2PACE;
                }
            }
        } else if (warp == 9) {
            int slot = 0; uint32_t ph = 1;
            #pragma unroll 1
            for (int e = g1_on ? 0 : 2; e < 4; e++) {
                const bool g2 = e >= 2;
                const int dsub = (g2 ? g2j : g1j) + 2 * (e & 1);
                const uint4* src = (g2 ? &g_g[rank * 14 * 3584] : &g_hn[rank * 16 * 3584]) + dsub * 896;
                mbar_wait(BAR(B_GO + e), 0);
                TRW(40 + e);
                #pragma unroll 1
                for (int s = g2 ? 2 : 0; s < 16; s++) {
                    mbar_wait(BAR(B_BE + slot), ph);
                    if (LOADP > 1) while (((uint32_t)clock() & (LOADP - 1)) >= LOADW) {}
                    if (elect_one()) {
                        const uint32_t fb = BAR(B_BF + (e & 1) * NB + slot);
                        if ((NOB >> e) & 1) mbar_arrive(fb); else {
                        mbar_expect(fb, 14336);
                        bulk_g2s(sb + SM_B + slot * 14336, src, 14336, fb); }
                    }
                    src += 3584;
                    if (++slot == NB) { slot = 0; ph ^= 1; }
                }
            }
        } else if (warp == 10) {
            mbar_wait(BAR(PFBAR), 0);
            const char* p1 = (const char*)prm.w1 + (size_t)b * 57344 + lane * 128;
            const char* p2 = (const char*)prm.w2 + (size_t)b * 57344 + lane * 128;
            if (lane < 25) asm volatile("prefetch.global.L2 [%0];" :: "l"((const char*)prm.wo + min(b * 25 + lane, 3135) * 128));
            uint32_t tnext = (uint32_t)clock();
            #pragma unroll 1
            for (int i = 0; i < 28; i++) {
                asm volatile("prefetch.global.L2 [%0];" :: "l"(i < 14 ? p1 + i * 4096 : p2 + (i - 14) * 4096));
                tnext += PFPACE;
                while ((int)((uint32_t)clock() - tnext) < 0) __nanosleep(40);
            }
        } else {
            const uint32_t tag = *(volatile uint32_t*)&g_epoch + 1;
            const uint4 z4 = make_uint4(0u, 0u, 0u, 0u);
            #pragma unroll 1
            for (int i = 0; i < 14; i++) g_halo[(ti * 8 + hg) * 448 + i * 32 + lane] = z4;
            g_stats[(a2s * 4 + a2j) * 64 + lane] = z4; g_stats[(a2s * 4 + a2j) * 64 + 32 + lane] = z4;
            if (lane < FS) {
                g_flag_h[(a2s * 4 + a2j) * FS + lane] = 0;
                if (g1_on) { g_flag_g[((g1j * 28 + g1f) * 2 + rank) * FS + lane] = 0; g_flag_g[(((g1j + 2) * 28 + g1f) * 2 + rank) * FS + lane] = 0; }
            }
            #pragma unroll 1
            for (int i = 0; i < 2; i++) g_o[tag & 1][(ti * 8 + i * 4 + (lane >> 3)) * 896 + hg * 112 + 104 + (lane & 7)] = z4;
            __syncwarp();
            if (lane == 0) {
                asm volatile("st.shared.u32 [%0], %1;" :: "r"(sb + SM_EPOCH), "r"(tag) : "memory");
                mbar_arrive(BAR(B_EP));
            }
            if (lane < 4) mbar_expect(BAR(B_RF + lane), 14336);
            __syncwarp();
            TRW(44);
            mbar_wait(BAR(B_HD), 0);
            #pragma unroll 1
            for (int e = g1_on ? 0 : 2; e < 4; e++) {
                const int dsub = (e >= 2 ? g2j : g1j) + 2 * (e & 1);
                const uint32_t* fp = e >= 2 ? &g_flag_g[((dsub * 28 + rank * 14) * 2 + min(lane, 27)) * FS]
                                            : &g_flag_h[((rank * 16 + (lane >> 1)) * 4 + max(dsub - (lane & 1), 0)) * FS];
                if (e == RSTE) {
                    #pragma unroll 1
                    for (int i = 0; i < 8; i++) {
                        uint4* p = &g_o[~tag & 1][(ti * 8 + i) * 896 + hg * 112 + lane];
                        p[0] = z4; p[32] = z4; p[64] = z4; if (lane < 16) p[96] = z4;
                        __nanosleep(100);
                    }
                }
                if (g1_on && e >= 2) mbar_wait(BAR(B_GD + e - 2), 0);
                int it = 0;
                while (true) {
                    tick<POLLP>();
                    if (__all_sync(~0u, ld_acq(fp) == tag)) break;
                    if (++it > kSpinLimit) { TIMEOUT(108); break; }
                }
                warp_arrive(BAR(B_GO + e));
            }
        }
    } else {
        asm volatile("setmaxnreg.inc.sync.aligned.u32 232;");
        asm volatile("barrier.cluster.wait.aligned;" ::: "memory");
        const int wg = warp >> 2, w = warp & 3;
        const int g = lane >> 2, t = lane & 3;
        uint32_t tag;
        {
            uint32_t a[28][4];
            float sm0[4] = {0.f, 0.f, 0.f, 0.f}, sm1[4] = {0.f, 0.f, 0.f, 0.f};
            {
                const int r = w * 16 + (lane & 15);
                const uint32_t rowa = sb + SM_X + wg * 57344 + r * 128;
                #pragma unroll
                for (int kb = 0; kb < 7; kb++) {
                    mbar_wait(BAR(B_XF + kb), 0);
                    #pragma unroll
                    for (int q = 0; q < 4; q++) {
                        const uint32_t addr = rowa + kb * 8192 + (((q * 2 + (lane >> 4)) ^ (r & 7)) << 4);
                        uint32_t (&f)[4] = a[kb * 4 + q];
                        asm volatile("ldmatrix.sync.aligned.m8n8.x4.shared.b16 {%0,%1,%2,%3}, [%4];"
                                     : "=r"(f[0]), "=r"(f[1]), "=r"(f[2]), "=r"(f[3]) : "r"(addr) : "memory");
                        if (q & 1) mma16816(sm1, f[0], f[1], f[2], f[3], 0x3F803F80u, 0x3F803F80u);
                        else       mma16816(sm0, f[0], f[1], f[2], f[3], 0x3F803F80u, 0x3F803F80u);
                    }
                }
            }
            const float mean0 = (sm0[0] + sm1[0]) * (1.f / kD), mean1 = (sm0[2] + sm1[2]) * (1.f / kD);
            const uint32_t mb0 = pack_bf16(mean0, mean0), mb1 = pack_bf16(mean1, mean1);
            pair_arrive(B_XC);
            TR(1);
            float ak[28], av[28], aq[28];
            float ss0 = 0.f, ss1 = 0.f, ss2 = 0.f, ss3 = 0.f;
            const uint32_t dw = desc_lo(sb + (hg & 1) * 16, 0);
            static_for<0, 7>([&](auto S_) {
                constexpr int s = decltype(S_)::value;
                #pragma unroll
                for (int q = 0; q < 4; q++) {
                    uint32_t (&f)[4] = a[s * 4 + q];
                    f[0] = sub_bf16x2(f[0], mb0); f[1] = sub_bf16x2(f[1], mb1);
                    f[2] = sub_bf16x2(f[2], mb0); f[3] = sub_bf16x2(f[3], mb1);
                    ss0 = fmaf(bf_lo(f[0]), bf_lo(f[0]), ss0); ss2 = fmaf(bf_hi(f[0]), bf_hi(f[0]), ss2);
                    ss1 = fmaf(bf_lo(f[1]), bf_lo(f[1]), ss1); ss3 = fmaf(bf_hi(f[1]), bf_hi(f[1]), ss3);
                    ss0 = fmaf(bf_lo(f[2]), bf_lo(f[2]), ss0); ss2 = fmaf(bf_hi(f[2]), bf_hi(f[2]), ss2);
                    ss1 = fmaf(bf_lo(f[3]), bf_lo(f[3]), ss1); ss3 = fmaf(bf_hi(f[3]), bf_hi(f[3]), ss3);
                }
                mbar_wait(BAR(B_WKVF + s), 0);
                wg_fence();
                static_for<0, 4>([&](auto Q_) {
                    constexpr int q = decltype(Q_)::value;
                    uint32_t (&f)[4] = a[s * 4 + q];
                    wgmma_rs_n56<SM_WKV + s * 16384 + q * 2048, (s | q) != 0>(ak, f[0], f[1], f[2], f[3], dw);
                    wgmma_rs_n56<SM_WKV + s * 16384 + q * 2048 + 8192, (s | q) != 0>(av, f[0], f[1], f[2], f[3], dw);
                });
                wg_commit();
                if (s == 4) { wg_wait<1>(); pair_arrive(B_KV3); }
            });
            auto q_chunk = [&](auto C_) {
                wg_fence();
                static_for<0, 7>([&](auto K_) {
                    constexpr int k = decltype(C_)::value * 7 + decltype(K_)::value;
                    wgmma_rs_n56<SM_X + k * 2048, k != 0>(aq, a[k][0], a[k][1], a[k][2], a[k][3], dw);
                });
                wg_commit();
            };
            const float dl0 = mean0 - bf_lo(mb0), dl1 = mean1 - bf_lo(mb1);
            const float rs0 = rsq(fmaxf(quad_sum(ss0 + ss2) * (1.f / kD) - dl0 * dl0, 0.f) + kEps);
            const float rs1 = rsq(fmaxf(quad_sum(ss1 + ss3) * (1.f / kD) - dl1 * dl1, 0.f) + kEps);
            mbar_wait2(BAR(B_EP), 0, BAR(B_WQF), 0);
            asm volatile("ld.shared.u32 %0, [%1];" : "=r"(tag) : "r"(sb + SM_EPOCH) : "memory");
            q_chunk(std::integral_constant<int, 0>{});
            wg_wait<1>();
            reg_fence(ak); reg_fence(av);
            TR(2);
            uint32_t kf[3][7], vf[3][7];
            #pragma unroll
            for (int c = 0; c < 7; c++) {
                kf[2][c] = pack_bf16(ak[4 * c + 2] * rs1, ak[4 * c + 3] * rs1);
                vf[2][c] = movm(pack_bf16(av[4 * c + 2] * rs1, av[4 * c + 3] * rs1));
            }
            const uint32_t stg = sb + SM_RED + (1 - wg) * 16384 + lane * 16;
            if (w == 3) {
                uint4* hp = &g_halo[((ti * 8 + hg) * 2 + wg) * 7 * 32 + lane];
                #pragma unroll
                for (int c = 0; c < 7; c++) st_ll(hp + c * 32, kf[2][c], vf[2][c], tag);
            } else {
                sts4(stg + w * 2048 + 0,    kf[2][0], kf[2][1], kf[2][2], kf[2][3]);
                sts4(stg + w * 2048 + 512,  kf[2][4], kf[2][5], kf[2][6], vf[2][0]);
                sts4(stg + w * 2048 + 1024, vf[2][1], vf[2][2], vf[2][3], vf[2][4]);
                sts4(stg + w * 2048 + 1536, vf[2][5], vf[2][6], 0u, 0u);
            }
            pair_arrive(B_KVC);
            q_chunk(std::integral_constant<int, 1>{});
            #pragma unroll
            for (int c = 0; c < 7; c++) {
                kf[1][c] = pack_bf16(ak[4 * c] * rs0, ak[4 * c + 1] * rs0);
                vf[1][c] = movm(pack_bf16(av[4 * c] * rs0, av[4 * c + 1] * rs0));
            }
            named_bar(1 + wg, 128);
            q_chunk(std::integral_constant<int, 2>{});
            q_chunk(std::integral_constant<int, 3>{});
            if (w == 0) {
                if (ti > 0) {
                    const uint4* hp = &g_halo[(((ti - 1) * 8 + hg) * 2 + wg) * 7 * 32 + lane];
                    int it = 0; bool ok;
                    do {
                        ok = true;
                        #pragma unroll
                        for (int c = 0; c < 7; c++) ok &= ld_ll(hp + c * 32, kf[0][c], vf[0][c], tag);
                        if (++it > kSpinLimit) { TIMEOUT(101); break; }
                    } while (!__all_sync(~0u, ok));
                } else {
                    #pragma unroll
                    for (int c = 0; c < 7; c++) { kf[0][c] = 0u; vf[0][c] = 0u; }
                }
            } else {
                const uint4 u0 = lds4(stg + (w - 1) * 2048), u1 = lds4(stg + (w - 1) * 2048 + 512),
                            u2 = lds4(stg + (w - 1) * 2048 + 1024), u3 = lds4(stg + (w - 1) * 2048 + 1536);
                kf[0][0] = u0.x; kf[0][1] = u0.y; kf[0][2] = u0.z; kf[0][3] = u0.w;
                kf[0][4] = u1.x; kf[0][5] = u1.y; kf[0][6] = u1.z; vf[0][0] = u1.w;
                vf[0][1] = u2.x; vf[0][2] = u2.y; vf[0][3] = u2.z; vf[0][4] = u2.w;
                vf[0][5] = u3.x; vf[0][6] = u3.y;
            }
            uint4* op = opaque_ptr(&g_o[tag & 1][(((ti * 2 + wg) * 4 + w) * 28 + ((7 * hg) >> 1)) * 32 + lane]);
            TR(3);
            wg_wait<0>();
            reg_fence(aq);
            warp_arrive(BAR(B_A1D));
            TR(4);
            uint32_t qf[7][2];
            #pragma unroll
            for (int c = 0; c < 7; c++) {
                qf[c][0] = pack_bf16(aq[4 * c], aq[4 * c + 1]);
                qf[c][1] = pack_bf16(aq[4 * c + 2], aq[4 * c + 3]);
            }
            const bool has_prev = (ti > 0) || (w > 0);
            const float sc0 = rs0 * (0.18898223650461362f * 1.4426950408889634f);
            const float sc1 = rs1 * (0.18898223650461362f * 1.4426950408889634f);
            const float NEG = -__int_as_float(0x7f800000);
            uint32_t ow[7][2];
            #pragma unroll
            for (int hd = 0; hd < 2; hd++) {
                const int c0 = hd * 3;
                const bool keep = hd == 0 ? (t < 2) : (t >= 2);
                const uint32_t q3a = keep ? qf[3][0] : 0u, q3b = keep ? qf[3][1] : 0u;
                float sc_[3][4];
                #pragma unroll
                for (int n = 0; n < 3; n++) {
                    sc_[n][0] = sc_[n][1] = sc_[n][2] = sc_[n][3] = 0.f;
                    if (hd == 0) {
                        mma16816(sc_[n], qf[0][0], qf[0][1], qf[1][0], qf[1][1], kf[n][0], kf[n][1]);
                        mma16816(sc_[n], qf[2][0], qf[2][1], q3a, q3b, kf[n][2], kf[n][3]);
                    } else {
                        mma16816(sc_[n], q3a, q3b, qf[4][0], qf[4][1], kf[n][3], kf[n][4]);
                        mma16816(sc_[n], qf[5][0], qf[5][1], qf[6][0], qf[6][1], kf[n][5], kf[n][6]);
                    }
                }
                const bool gt0 = 2 * t > g, gt1 = 2 * t + 1 > g;
                const float e0 = gt0 ? (has_prev ? sc_[0][0] : NEG) : sc_[1][0], e1 = gt1 ? (has_prev ? sc_[0][1] : NEG) : sc_[1][1];
                const float f0 = gt0 ? sc_[1][2] : sc_[2][2], f1 = gt1 ? sc_[1][3] : sc_[2][3];
                const float me = quad_max(fmaxf(e0, e1)) * sc0, mf = quad_max(fmaxf(f0, f1)) * sc1;
                float p0 = ex2(fmaf(e0, sc0, -me)), p1 = ex2(fmaf(e1, sc0, -me));
                float r0 = ex2(fmaf(f0, sc1, -mf)), r1 = ex2(fmaf(f1, sc1, -mf));
                const float ie = rcp(quad_sum(p0 + p1)), jf = rcp(quad_sum(r0 + r1));
                const uint32_t pp = pack_bf16(p0 * ie, p1 * ie), rp = pack_bf16(r0 * jf, r1 * jf);
                const uint32_t mk = (gt0 ? 0x0000ffffu : 0u) | (gt1 ? 0xffff0000u : 0u);
                const uint32_t sw = hg >= 4 ? ~0u : 0u;
                const uint32_t pa0 = pp & mk & ~sw, pa1 = pp & mk & sw, pb0 = rp & ~mk & sw, pb1 = rp & ~mk & ~sw;
                const uint32_t pa2 = sw ? rp & mk : pp & ~mk, pa3 = sw ? pp & ~mk : rp & mk;
                #pragma unroll
                for (int c = 0; c < 4; c++) {
                    float o[4] = {0.f, 0.f, 0.f, 0.f};
                    mma16816(o, pa0, pa1, pa2, pa3, vf[0][c0 + c], vf[1][c0 + c]);
                    mma1688(o, pb0, pb1, vf[2][c0 + c]);
                    const uint32_t lo = max(pack_bf16(o[0], o[1]), 1u), hi = pack_bf16(o[2], o[3]);
                    if (hd == 1 && c == 0) { if (t >= 2) { ow[3][0] = lo; ow[3][1] = hi; } }
                    else { ow[c0 + c][0] = lo; ow[c0 + c][1] = hi; }
                }
            }
            if (hg & 1) {
                ((uint2*)(op - lane))[32 + lane] = make_uint2(ow[0][0], ow[0][1]);
                op[32] = make_uint4(ow[1][0], ow[1][1], ow[2][0], ow[2][1]);
                op[64] = make_uint4(ow[3][0], ow[3][1], ow[4][0], ow[4][1]);
                op[96] = make_uint4(ow[5][0], ow[5][1], ow[6][0], ow[6][1]);
            } else {
                op[0]  = make_uint4(ow[0][0], ow[0][1], ow[1][0], ow[1][1]);
                op[32] = make_uint4(ow[2][0], ow[2][1], ow[3][0], ow[3][1]);
                op[64] = make_uint4(ow[4][0], ow[4][1], ow[5][0], ow[5][1]);
                ((uint2*)(op + 96 - lane))[lane] = make_uint2(ow[6][0], ow[6][1]);
            }
            TR(5);
        }
        {
            float acc2[64];
            const bool wide = a2j != 3;
            mbar_wait(BAR(B_XRF), 0);
            {
                const uint32_t xa = sb + SM_X + 8 * 8192 + (w * 16 + wg * 8 + (lane & 7)) * 128;
                #pragma unroll
                for (int c = 0; c < 4; c++) {
                    uint32_t xr[4];
                    asm volatile("ldmatrix.sync.aligned.m8n8.x4.shared.b16 {%0,%1,%2,%3}, [%4];"
                                 : "=r"(xr[0]), "=r"(xr[1]), "=r"(xr[2]), "=r"(xr[3])
                                 : "r"(xa + (c >> 1) * 8192 + ((((c & 1) * 4 + (lane >> 3)) ^ (lane & 7)) << 4)) : "memory");
                    #pragma unroll
                    for (int e = 0; e < 4; e++) {
                        acc2[16 * c + 4 * e] = bf_lo(xr[e]); acc2[16 * c + 4 * e + 1] = bf_hi(xr[e]);
                        acc2[16 * c + 4 * e + 2] = 0.f;      acc2[16 * c + 4 * e + 3] = 0.f;
                    }
                }
            }
            const uint4* op = &g_o[tag & 1][((a2s * 4 + w) * 28 + wg * 14) * 32];
            const uint32_t rsend = opaque(sb + SM_RED + (1 - wg) * 16384 + w * 4096 + lane * 16);
            const uint32_t rrecv = opaque(sb + SM_RED + wg * 16384 + w * 4096 + lane * 16);
            uint4* spw = opaque_ptr(&g_stats[(a2s * 4 + a2j) * 64 + (w * 2 + wg) * 8 + g]);
            const uint4* spr = opaque_ptr(&g_stats[(a2s * 4 + t) * 64 + (w * 2 + wg) * 8 + g]);
            uint2* hp = opaque_ptr((uint2*)g_h + ((a2s * 8 + w * 2 + wg) * 28 + a2j * 8) * 32 + lane);
            uint32_t* np = opaque_ptr((uint32_t*)&g_hn[(a2s * 56 + a2j * 16) * 64] + (w * 2 + wg) * 32 + lane);
            reg_fence(acc2);
            mbar_wait(BAR(B_WOF + wg), 0);
            {
                const uint32_t* pp = (const uint32_t*)(op + ((t >> 1) * 7 + 3 + (t & 1) * 3) * 32) + 32 + (t & 1) * 64;
                int it = 0;
                while (true) {
                    tick<PROBEP>();
                    if (!__any_sync(~0u, ld_rlx(pp) == 0u)) break;
                    if (++it > kSpinLimit) { TIMEOUT(102); break; }
                }
            }
            TR(6);
            uint4 of[14];
            auto load_o = [&](int k) {
                if (k % 7 == 3) {
                    const uint2 lo = ld_rlx2((const uint2*)(op + k * 32) + lane), hi = ld_rlx2((const uint2*)(op + k * 32) + 32 + lane);
                    of[k] = make_uint4(lo.x, lo.y, hi.x, hi.y);
                } else of[k] = ld_rlx4(op + k * 32 + lane);
            };
            #pragma unroll
            for (int k = 0; k < 14; k++) load_o(k);
            const uint32_t dwo = desc_lo(sb + SM_WKV + wg * 57344, 28672);
            static_for<0, 4>([&](auto G_) {
                constexpr int k0 = (decltype(G_)::value * 7) / 2, k1 = (decltype(G_)::value * 7 + 7) / 2;
                int it = 0;
                while (true) {
                    bool bad = false;
                    #pragma unroll
                    for (int k = k0; k < k1; k++) bad |= of[k].x == 0u || (k % 7 == 3 && of[k].z == 0u);
                    if (!__any_sync(~0u, bad)) break;
                    if (++it > kSpinLimit) { TIMEOUT(109); break; }
                    RETRY_COUNT(1);
                    #pragma unroll
                    for (int k = k0; k < k1; k++) load_o(k);
                }
                if (k1 == 14) warp_arrive(BAR(B_OL));
                wg_fence();
                static_for<k0, k1>([&](auto K_) { constexpr int k = decltype(K_)::value;
                    wgmma_rs_n128<k * 2048, 1>(acc2, of[k].x, of[k].y, of[k].z, of[k].w, dwo); });
            });
            wg_commit();
            wg_wait<0>();
            reg_fence(acc2);
            TR(7);
            #pragma unroll
            for (int c = 0; c < 8; c++)
                sts4(rsend + c * 512, __float_as_uint(acc2[8 * c + 2]), __float_as_uint(acc2[8 * c + 3]), __float_as_uint(acc2[8 * c + 6]), __float_as_uint(acc2[8 * c + 7]));
            named_bar(3, 256);
            float hv[32];
            float s0 = 0.f, s1 = 0.f, q0 = 0.f, q1 = 0.f;
            #pragma unroll
            for (int c = 0; c < 8; c++) {
                const uint4 u = lds4(rrecv + c * 512);
                hv[4 * c]     = acc2[8 * c] + __uint_as_float(u.x);     hv[4 * c + 1] = acc2[8 * c + 1] + __uint_as_float(u.y);
                hv[4 * c + 2] = acc2[8 * c + 4] + __uint_as_float(u.z); hv[4 * c + 3] = acc2[8 * c + 5] + __uint_as_float(u.w);
            }
            #pragma unroll
            for (int c = 0; c < 16; c += 2) { s0 += hv[c]; s1 += hv[c + 1]; q0 = fmaf(hv[c], hv[c], q0); q1 = fmaf(hv[c + 1], hv[c + 1], q1); }
            if (wide) {
                #pragma unroll
                for (int c = 16; c < 32; c += 2) { s0 += hv[c]; s1 += hv[c + 1]; q0 = fmaf(hv[c], hv[c], q0); q1 = fmaf(hv[c + 1], hv[c + 1], q1); }
            }
            s0 = quad_sum(s0 + s1); q0 = quad_sum(q0 + q1);
            if (t == 0) st_ll(spw, __float_as_uint(s0), __float_as_uint(q0), tag);
            TR(8);
            fence_async_smem();
            #pragma unroll
            for (int c = 0; c < 8; c++)
                if (c < 4 || wide) hp[c * 32] = make_uint2(pack_bf16(hv[4 * c], hv[4 * c + 1]), pack_bf16(hv[4 * c + 2], hv[4 * c + 3]));
            uint32_t um, uv;
            {
                int it = 0;
                while (!__all_sync(~0u, ld_ll(spr, um, uv, tag))) { if (++it > kSpinLimit) { TIMEOUT(103); break; } }
            }
            TR(9);
            const float mean = quad_sum(__uint_as_float(um)) * (1.f / kD);
            const float var = fmaxf(fmaf(quad_sum(__uint_as_float(uv)), 1.f / kD, -mean * mean), 0.f);
            const float r1 = rsq(var + kEps);
            const float rr = r1 * rsq(fmaf(var * r1, r1, kEps));
            const float mr = -mean * rr;
            #pragma unroll
            for (int c = 0; c < 16; c++)
                if (c < 8 || wide) np[c * 256] = pack_bf16(fmaf(hv[2 * c], rr, mr), fmaf(hv[2 * c + 1], rr, mr));
            named_bar(3, 256);
            mbar_arrive_remote_if(pbar0 + 8u * B_PD, tid == 0);
            if (tid == 128) { fence_async_global(); fence_gpu(); st_flag(&g_flag_h[(a2s * 4 + a2j) * FS], tag); mbar_arrive(BAR(B_HD)); }
            __syncwarp();
            TR(10);
        }
        float acc[56];
        const uint32_t red = opaque(sb + SM_RED + w * 3584 + lane * 16);
        uint32_t peer_red; const uint32_t peer_bar = pbar0;
        asm volatile("mapa.shared::cluster.u32 %0, %1, %2;" : "=r"(peer_red) : "r"(red), "r"(rank ^ 1));
        uint32_t bph = 0;
        #pragma unroll 1
        for (int ge = g1_on ? 0 : 1; ge < 2; ge++) {
            const int pos = (ge ? (g1_on ? 32 : 0) : 0) + wg * (ge ? 14 : 16);
            const uint32_t aph = (ge && g1_on) ? 1u : 0u;
            const int row = w * 16 + rank * 8 + g;
            const int dsub = (ge ? g2j : g1j) + 2 * wg;
            const float bias = __bfloat162float(ge ? prm.b2[g2s * 64 + row] : prm.b1[g1f * 64 + row]);
            const int tok = g2s * 64 + row, pr = (tok & 127) >> 1;
            const uint2* hp = opaque_ptr((const uint2*)g_h + ((((tok >> 7) * 2 + (tok & 1)) * 8 + (pr >> 3)) * 28 + dsub * 7) * 32 + (pr & 7) * 4 + t);
            uint32_t fbar[NB], ebar[NB], sp[NB], db[NB];
            #pragma unroll
            for (int i = 0; i < NB; i++) {
                const uint32_t sl = (pos + i) % NB;
                fbar[i] = opaque(BAR(B_BF + wg * NB + sl)); ebar[i] = opaque(BAR(B_BE + sl));
                sp[i] = opaque((bph >> sl) & 1);            db[i] = desc_lo(sb + SM_B + sl * 14336, 128);
            }
            uint32_t* gp = opaque_ptr(ge ? (uint32_t*)(prm.out + (size_t)(g2s * 64 + w * 16 + rank * 8) * kD + dsub * 112)
                                         : (uint32_t*)&g_g[(g1f * 56 + dsub * 14) * 64] + (w * 2 + rank) * 32 + lane);
            const bool lead = elect_one();
            const bool rel_a = lead && !ge && wg == 1;
            const uint32_t da = desc_lo(sb, 0);
            auto stage = [&](auto S_) {
                constexpr int s = decltype(S_)::value;
                constexpr int aoff = s < 10 ? s * 8192 : SM_AHI + (s - 10) * 8192;
                wg_fence();
                wgmma_ss_n112<aoff,        0,   s != 0>(acc, da, db[s % NB]);
                wgmma_ss_n112<aoff + 2048, 256, 1>(acc, da, db[s % NB]);
                wgmma_ss_n112<aoff + 4096, 512, 1>(acc, da, db[s % NB]);
                wgmma_ss_n112<aoff + 6144, 768, 1>(acc, da, db[s % NB]);
                wg_commit();
                if (s < 15 && !(s == 13 && ge))
                    mbar_wait2(BAR(B_AF + s + 1), aph, fbar[(s + 1) % NB], sp[(s + 1) % NB] ^ (((s + 1) / NB) & 1));
                if constexpr (s > 0) {
                    wg_wait<1>();
                    mbar_arrive_if(ebar[(s - 1) % NB], lead);
                    if (s <= 14) mbar_arrive_if(BAR(B_AE + s - 1), rel_a);
                }
            };
            mbar_wait2(BAR(B_AF), aph, fbar[0], sp[0]);
            TR(11 + ge * 4);
            static_for<0, 14>(stage);
            if (!ge) static_for<14, 16>(stage);
            const uint32_t lastbar = ge ? ebar[13 % NB] : ebar[15 % NB];
            #pragma unroll
            for (int i = 0; i < NB; i++) if (((16 - i + NB - 1) / NB) & 1) bph ^= 1u << ((pos + i) % NB);
            uint2 hr[7];
            #pragma unroll
            for (int c = 0; c < 7; c++) hr[c] = ge ? ld_rlx2(hp + c * 32) : make_uint2(0u, 0u);
            const int use = ge * 2 + wg;
            mbar_wait(BAR(use > (g1_on ? 0 : 2) ? B_RE + use - 1 : B_PD), 0);
            wg_wait<0>();
            reg_fence(acc);
            TR(12 + ge * 4);
            mbar_arrive_if(lastbar, lead);
            float v[28];
            auto send = [&](auto R_) {
                constexpr int o = decltype(R_)::value * 2;
                #pragma unroll
                for (int c = 0; c < 7; c++) {
                    asm volatile("st.async.shared::cluster.mbarrier::complete_tx::bytes.v4.f32 [%0], {%1,%2,%3,%4}, [%5];"
                                 :: "r"(peer_red + c * 512), "f"(acc[8 * c + 2 - o]), "f"(acc[8 * c + 3 - o]), "f"(acc[8 * c + 6 - o]), "f"(acc[8 * c + 7 - o]),
                                    "r"(peer_bar + (B_RF + use) * 8) : "memory");
                    v[4 * c] = acc[8 * c + o]; v[4 * c + 1] = acc[8 * c + 1 + o]; v[4 * c + 2] = acc[8 * c + 4 + o]; v[4 * c + 3] = acc[8 * c + 5 + o];
                }
            };
            if (rank) send(std::integral_constant<int, 1>{}); else send(std::integral_constant<int, 0>{});
            #pragma unroll
            for (int c = 0; c < 7; c++) {
                v[4 * c] += bf_lo(hr[c].x) + bias;     v[4 * c + 1] += bf_hi(hr[c].x) + bias;
                v[4 * c + 2] += bf_lo(hr[c].y) + bias; v[4 * c + 3] += bf_hi(hr[c].y) + bias;
            }
            reg_fence(v);
            mbar_wait_cluster(BAR(B_RF + use), 0);
            #pragma unroll
            for (int c = 0; c < 7; c++) {
                const uint4 u = lds4(red + c * 512);
                v[4 * c] += __uint_as_float(u.x);     v[4 * c + 1] += __uint_as_float(u.y);
                v[4 * c + 2] += __uint_as_float(u.z); v[4 * c + 3] += __uint_as_float(u.w);
            }
            TR(13 + ge * 4);
            if (!ge) {
                reg_fence(v);
                __syncwarp();
                if (lead) asm volatile("mbarrier.arrive.shared::cluster.b64 _, [%0];" :: "r"(peer_bar + (B_RE + use) * 8) : "memory");
                #pragma unroll
                for (int c = 0; c < 14; c++) {
                    float r[2];
                    #pragma unroll
                    for (int e = 0; e < 2; e++) {
                        const float u = v[2 * c + e];
                        const float z = u * fmaf(u * u, -2.302208198f * 0.044715f, -2.302208198f);
                        r[e] = u * rcp(1.f + ex2(z));
                    }
                    gp[c * 256] = pack_bf16(r[0], r[1]);
                }
                named_bar(1 + wg, 128);
                if (w == 0 && lane == 0) {
                    fence_async_global(); fence_gpu();
                    st_flag(&g_flag_g[((dsub * 28 + g1f) * 2 + rank) * FS], tag);
                    mbar_arrive(BAR(B_GD + wg));
                }
                __syncwarp();
            } else {
                const uint32_t stw = red - lane * 16;
                uint32_t pk[14];
                #pragma unroll
                for (int c = 0; c < 14; c++) pk[c] = pack_bf16(v[2 * c], v[2 * c + 1]);
                __syncwarp();
                const uint32_t sa = stw + (lane & 7) * 240 + (lane >> 3) * 16;
                #pragma unroll
                for (int m = 0; m < 3; m++)
                    asm volatile("stmatrix.sync.aligned.m8n8.x4.shared.b16 [%0], {%1,%2,%3,%4};"
                                 :: "r"(sa + m * 64), "r"(pk[4 * m]), "r"(pk[4 * m + 1]), "r"(pk[4 * m + 2]), "r"(pk[4 * m + 3]) : "memory");
                asm volatile("stmatrix.sync.aligned.m8n8.x2.shared.b16 [%0], {%1,%2};" :: "r"(sa + 192), "r"(pk[12]), "r"(pk[13]) : "memory");
                __syncwarp();
                #pragma unroll
                for (int i = 0; i < 4; i++) {
                    const int r = 2 * i + (lane >> 4), ch = lane & 15;
                    if (ch < 14) *(uint4*)(gp + r * 224 + ch * 4) = lds4(stw + r * 240 + ch * 16);
                }
                __syncwarp();
                if (lead && wg == 0) asm volatile("mbarrier.arrive.shared::cluster.b64 _, [%0];" :: "r"(peer_bar + (B_RE + 2) * 8) : "memory");
            }
            TR(14 + ge * 4);
        }
        if (tid == 128) TRG(62);
        if (b == 0 && tid == 128) g_epoch = tag;
    }
}

typedef CUresult (*EncodeFn)(CUtensorMap*, CUtensorMapDataType, cuuint32_t, void*, const cuuint64_t*, const cuuint64_t*,
                             const cuuint32_t*, const cuuint32_t*, CUtensorMapInterleave, CUtensorMapSwizzle,
                             CUtensorMapL2promotion, CUtensorMapFloatOOBfill);

void make_map(EncodeFn enc, CUtensorMap* m, const void* base, uint64_t cols, uint64_t rows, uint32_t box_rows) {
    cuuint64_t dims[2] = {cols, rows};
    cuuint64_t strides[1] = {cols * 2};
    cuuint32_t box[2] = {64, box_rows};
    cuuint32_t es[2] = {1, 1};
    enc(m, CU_TENSOR_MAP_DATA_TYPE_BFLOAT16, 2, const_cast<void*>(base), dims, strides, box, es, CU_TENSOR_MAP_INTERLEAVE_NONE,
        CU_TENSOR_MAP_SWIZZLE_128B, CU_TENSOR_MAP_L2_PROMOTION_L2_128B, CU_TENSOR_MAP_FLOAT_OOB_FILL_NONE);
}

}

extern "C" void kernel_launch(void* const* d_in, const int* in_sizes, int n_in, void* d_out, int out_size) {
    (void)in_sizes; (void)n_in; (void)out_size;
    void* fn = nullptr;
    cudaDriverEntryPointQueryResult qr;
    cudaGetDriverEntryPoint("cuTensorMapEncodeTiled", &fn, cudaEnableDefault, &qr);
    EncodeFn enc = (EncodeFn)fn;
    CUtensorMap mX, mWqkv, mWo, mW1, mW2;
    make_map(enc, &mX, d_in[0], 2 * kD, kS / 2, 64);
    make_map(enc, &mWqkv, d_in[1], 3 * kD, kD, 64);
    make_map(enc, &mWo, d_in[2], kD, kD, 224);
    make_map(enc, &mW1, d_in[4], 2 * kF, kS / 2, 64);
    make_map(enc, &mW2, d_in[6], kS, kF, 64);
    Params prm;
    prm.x = (const __nv_bfloat16*)d_in[0];
    prm.wqkv = (const __nv_bfloat16*)d_in[1];
    prm.wo = (const __nv_bfloat16*)d_in[2];
    prm.w1 = (const __nv_bfloat16*)d_in[4];
    prm.b1 = (const __nv_bfloat16*)d_in[5];
    prm.w2 = (const __nv_bfloat16*)d_in[6];
    prm.b2 = (const __nv_bfloat16*)d_in[7];
    prm.out = (__nv_bfloat16*)d_out;
    cudaFuncSetAttribute(fused_kernel, cudaFuncAttributeMaxDynamicSharedMemorySize, SM_TOTAL);
    fused_kernel<<<128, 384, SM_TOTAL, cudaStreamPerThread>>>(mX, mWqkv, mWo, mW1, mW2, prm);
}
```

```cpp
#include <cuda_runtime.h>
#include <cuda.h>
#include <cuda_bf16.h>
#include <stdint.h>
#include <type_traits>

namespace {

constexpr int kS = 2048, kD = 448, kF = 1792;
constexpr float kEps = 1e-5f;

#define FS 32
__device__ __align__(1024) uint4    g_o[32 * 4 * 28 * 32];
__device__ __align__(1024) uint4    g_h[kS * kD * 2 / 16];
__device__ __align__(1024) uint4    g_hn[32 * 56 * 64];
__device__ __align__(1024) uint4    g_g[28 * 56 * 64];
__device__ __align__(1024) uint4    g_halo[16 * 8 * 2 * 7 * 32];
__device__ __align__(1024) uint4    g_stats[32 * 4 * 64];
__device__ __align__(1024) uint32_t g_flag_o[32 * 4 * 8 * FS];
__device__ __align__(1024) uint32_t g_flag_h[32 * 4 * FS];
__device__ uint32_t g_epoch;
#define TIMEOUT(code)
#define RETRY_COUNT(i)
#define CAP_DECL(n, k)
#define CAP(n)
#define CAP_SKIP(n)
#define TR2(idx)
#define TR(idx)
#define TRW(idx)
#define TRG(idx)

constexpr uint32_t SM_X    = 0;
constexpr uint32_t SM_WKV  = 114688;
constexpr uint32_t SM_RED  = 81920;
constexpr uint32_t SM_XCH  = 131072;
constexpr uint32_t SM_B    = 139264;
constexpr uint32_t SM_BAR  = 231424;
constexpr uint32_t SM_TOTAL = SM_BAR + 1024;
constexpr int NB = 6;
#define SH1 0
#define SH2 0
#define SH2N 5
#define SH3 0
#define NSPEC 4
#define XSPEC 900
#define C2 0
#define C3 0
#define CN2 8000
#define CN3 12000
constexpr int B_XF = 0, B_WKVF = 7, B_WQF = 14, B_XRF = 15, B_WOF = 16,
              B_XC = 18, B_KV3 = 19, B_KVC = 20,
              B_A1D = 21, B_OL = 22,
              B_AE = 23, B_BE = B_AE + 14, B_RE = B_BE + NB,
              B_AF = B_RE + 3, B_BL = B_AF + 16  , B_BF = B_BL + NB  , B_RF = B_BF + NB,
              B_EP = B_RF + 4, B_PD = B_EP + 1, B_RT = B_PD + 1,
              B_HD = B_RT + 2, B_GO = B_HD + 1, B_GD = B_GO + 1, B_COUNT = B_GD + 2;
#define WEARLY 6
#define PF0 126
#define TMPF 2
#define RSTE 2
#define POLLP 1
#define PROBEP 1
#define LOADP 1
#define LOADW 64
#define NOB 0
#define AEARLY 5
#define W1PACE 400
#define W2PACE 420
#define PFPACE 330
#define PFBAR (B_XF + 6)
#define DELTA 640
#define DELTA2 DELTA
#define BPACE 230
#define BURST 2
#define W1OFF 350
#define W2OFF 5200
#define XPACE 0
#define PSTAG 200
constexpr uint32_t SM_EPOCH = SM_BAR + B_COUNT * 8, SM_TG = SM_EPOCH + 4  , SM_TR = 225280;

constexpr int kSpinLimit = 1 << 15;
__device__ __forceinline__ bool elect_one() {
    uint32_t p;
    asm volatile("{ .reg .pred P; elect.sync _|P, 0xffffffff; selp.u32 %0, 1, 0, P; }" : "=r"(p));
    return p;
}
__device__ __forceinline__ void mbar_init(uint32_t bar, uint32_t cnt) { asm volatile("mbarrier.init.shared::cta.b64 [%0], %1;" :: "r"(bar), "r"(cnt)); }
__device__ __forceinline__ void mbar_expect(uint32_t bar, uint32_t bytes) { asm volatile("mbarrier.arrive.expect_tx.shared::cta.b64 _, [%0], %1;" :: "r"(bar), "r"(bytes) : "memory"); }
__device__ __forceinline__ void mbar_arrive(uint32_t bar) { asm volatile("mbarrier.arrive.shared::cta.b64 _, [%0];" :: "r"(bar) : "memory"); }
__device__ __forceinline__ void mbar_wait(uint32_t bar, uint32_t parity) {
    uint32_t ok; int it = 0;
    do {
        asm volatile("{ .reg .pred p; mbarrier.try_wait.parity.shared::cta.b64 p, [%1], %2; selp.u32 %0, 1, 0, p; }"
                     : "=r"(ok) : "r"(bar), "r"(parity) : "memory");
        if (++it > kSpinLimit) { TIMEOUT((bar & 1023) >> 3); break; }
    } while (!ok);
}
__device__ __forceinline__ bool mbar_try(uint32_t bar, uint32_t parity) {
    uint32_t ok;
    asm volatile("{ .reg .pred p; mbarrier.try_wait.parity.shared::cta.b64 p, [%1], %2; selp.u32 %0, 1, 0, p; }" : "=r"(ok) : "r"(bar), "r"(parity) : "memory");
    return ok;
}
__device__ __forceinline__ bool mbar_test(uint32_t bar, uint32_t parity) {
    uint32_t ok;
    asm volatile("{ .reg .pred p; mbarrier.test_wait.parity.shared::cta.b64 p, [%1], %2; selp.u32 %0, 1, 0, p; }" : "=r"(ok) : "r"(bar), "r"(parity) : "memory");
    return ok;
}
__device__ __forceinline__ void mbar_wait2(uint32_t bar0, uint32_t par0, uint32_t bar1, uint32_t par1) {
    uint32_t ok; int it = 0;
    do {
        asm volatile("{ .reg .pred p, q; mbarrier.try_wait.parity.shared::cta.b64 p, [%1], %2;\n"
                     "mbarrier.try_wait.parity.shared::cta.b64 q, [%3], %4; and.pred p, p, q; selp.u32 %0, 1, 0, p; }"
                     : "=r"(ok) : "r"(bar0), "r"(par0), "r"(bar1), "r"(par1) : "memory");
        if (++it > kSpinLimit) { TIMEOUT((bar0 & 1023) >> 3); break; }
    } while (!ok);
}
template <int N> __device__ __forceinline__ void reg_fence(float (&d)[N]) {
    #pragma unroll
    for (int i = 0; i < N; i++) asm volatile("" : "+f"(d[i]) :: "memory");
}
__device__ __forceinline__ void mbar_wait_cluster(uint32_t bar, uint32_t parity) {
    uint32_t ok; int it = 0;
    do {
        asm volatile("{ .reg .pred p; mbarrier.try_wait.parity.acquire.cluster.shared::cta.b64 p, [%1], %2; selp.u32 %0, 1, 0, p; }"
                     : "=r"(ok) : "r"(bar), "r"(parity) : "memory");
        if (++it > kSpinLimit) { TIMEOUT((bar & 1023) >> 3); break; }
    } while (!ok);
}
__device__ __forceinline__ void mbar_arrive_if(uint32_t bar, bool pred) {
    asm volatile("{ .reg .pred p; setp.ne.u32 p, %1, 0; @p mbarrier.arrive.shared::cta.b64 _, [%0]; }" :: "r"(bar), "r"((uint32_t)pred) : "memory");
}
template <int P> __device__ __forceinline__ void tick() {
    if (P > 1) { const uint32_t t = ((uint32_t)clock() | (P - 1)) + 1; while ((int)((uint32_t)clock() - t) < 0) {} }
}
__device__ __forceinline__ void warp_arrive(uint32_t bar) { __syncwarp(); if (elect_one()) mbar_arrive(bar); }
__device__ __forceinline__ void tma2d(uint32_t dst, const CUtensorMap* m, int c0, int c1, uint32_t bar) {
    asm volatile("cp.async.bulk.tensor.2d.shared::cluster.global.mbarrier::complete_tx::bytes [%0], [%1, {%3, %4}], [%2];"
                 :: "r"(dst), "l"(m), "r"(bar), "r"(c0), "r"(c1) : "memory");
}
__device__ __forceinline__ void tma2d_mc(uint32_t dst, const CUtensorMap* m, int c0, int c1, uint32_t bar) {
    asm volatile("cp.async.bulk.tensor.2d.shared::cluster.global.mbarrier::complete_tx::bytes.multicast::cluster [%0], [%1, {%3, %4}], [%2], %5;"
                 :: "r"(dst), "l"(m), "r"(bar), "r"(c0), "r"(c1), "h"((uint16_t)3) : "memory");
}
__device__ __forceinline__ void bulk_g2s_mc(uint32_t dst, const void* src, uint32_t bytes, uint32_t bar) {
    asm volatile("cp.async.bulk.shared::cluster.global.mbarrier::complete_tx::bytes.multicast::cluster [%0], [%1], %2, [%3], %4;"
                 :: "r"(dst), "l"(src), "r"(bytes), "r"(bar), "h"((uint16_t)3) : "memory");
}
__device__ __forceinline__ void mbar_arrive_remote_if(uint32_t cluster_bar, bool pred) {
    asm volatile("{ .reg .pred p; setp.ne.u32 p, %1, 0; @p mbarrier.arrive.shared::cluster.b64 _, [%0]; }" :: "r"(cluster_bar), "r"((uint32_t)pred) : "memory");
}
__device__ __forceinline__ void bulk_g2s(uint32_t dst, const void* src, uint32_t bytes, uint32_t bar) {
    asm volatile("cp.async.bulk.shared::cluster.global.mbarrier::complete_tx::bytes [%0], [%1], %2, [%3];"
                 :: "r"(dst), "l"(src), "r"(bytes), "r"(bar) : "memory");
}
__device__ __forceinline__ void wg_fence()  { asm volatile("wgmma.fence.sync.aligned;" ::: "memory"); }
__device__ __forceinline__ void wg_commit() { asm volatile("wgmma.commit_group.sync.aligned;" ::: "memory"); }
template <int N> __device__ __forceinline__ void wg_wait() { asm volatile("wgmma.wait_group.sync.aligned %0;" :: "n"(N) : "memory"); }
__device__ __forceinline__ void named_bar(int id, int n) { asm volatile("bar.sync %0, %1;" :: "r"(id), "r"(n) : "memory"); }
__device__ __forceinline__ void named_arrive(int id, int n) { asm volatile("bar.arrive %0, %1;" :: "r"(id), "r"(n) : "memory"); }
__device__ __forceinline__ bool mbar_try2(uint32_t bar0, uint32_t par0, uint32_t bar1, uint32_t par1) {
    uint32_t ok;
    asm volatile("{ .reg .pred p, q; mbarrier.test_wait.parity.shared::cta.b64 p, [%1], %2;\n"
                 "mbarrier.test_wait.parity.shared::cta.b64 q, [%3], %4; and.pred p, p, q; selp.u32 %0, 1, 0, p; }"
                 : "=r"(ok) : "r"(bar0), "r"(par0), "r"(bar1), "r"(par1) : "memory");
    return ok;
}
__device__ __forceinline__ void fence_gpu() { asm volatile("fence.release.gpu;" ::: "memory"); }
__device__ __forceinline__ void fence_async_global() { asm volatile("fence.proxy.async.global;" ::: "memory"); }
__device__ __forceinline__ void fence_async_smem() { asm volatile("fence.proxy.async.shared::cta;" ::: "memory"); }
__device__ __forceinline__ uint32_t gtime32() { uint64_t t; asm volatile("mov.u64 %0, %%globaltimer;" : "=l"(t) :: "memory"); return (uint32_t)t; }
__device__ __forceinline__ uint32_t clk32() { uint64_t t; asm volatile("mov.u64 %0, %%clock64;" : "=l"(t) :: "memory"); return (uint32_t)t; }
__device__ __forceinline__ void spin_until(uint32_t t) { while ((int)(clk32() - t) < 0) {} }
#define SLEEPNS 20
__device__ __forceinline__ void sleep_until(uint32_t t) { while ((int)(clk32() - t) < 0) { if (SLEEPNS) __nanosleep(SLEEPNS); } }
__device__ __forceinline__ void st_flag(uint32_t* p, uint32_t v) {
    const uint64_t w = ((uint64_t)gtime32() << 32) | v;
    asm volatile("st.relaxed.gpu.global.u64 [%0], %1;" :: "l"(p), "l"(w) : "memory");
}
__device__ __forceinline__ void ld_flag_if(uint64_t& v, const uint32_t* p, bool pred) {
    asm volatile("{ .reg .pred p; setp.ne.u32 p, %2, 0; @p ld.relaxed.gpu.global.u64 %0, [%1]; }" : "+l"(v) : "l"(p), "r"((uint32_t)pred) : "memory");
}
__device__ __forceinline__ uint32_t ld_acq(const uint32_t* p) { uint32_t v; asm volatile("ld.acquire.gpu.global.u32 %0, [%1];" : "=r"(v) : "l"(p) : "memory"); return v; }
__device__ __forceinline__ uint32_t ld_rlx(const uint32_t* p) { uint32_t v; asm volatile("ld.relaxed.gpu.global.u32 %0, [%1];" : "=r"(v) : "l"(p) : "memory"); return v; }
template <class T> __device__ __forceinline__ T* opaque_ptr(T* p) { asm volatile("" : "+l"(p)); return p; }
__device__ __forceinline__ uint4 ld_rlx4(const uint4* p) {
    uint4 v; asm volatile("ld.relaxed.gpu.global.v4.u32 {%0,%1,%2,%3}, [%4];" : "=r"(v.x), "=r"(v.y), "=r"(v.z), "=r"(v.w) : "l"(p) : "memory"); return v;
}
__device__ __forceinline__ void st_ll(uint4* p, uint32_t a, uint32_t b, uint32_t tag) {
    uint64_t lo = ((uint64_t)tag << 32) | a, hi = ((uint64_t)tag << 32) | b;
    asm volatile("st.relaxed.gpu.global.v2.u64 [%0], {%1,%2};" :: "l"(p), "l"(lo), "l"(hi) : "memory");
}
__device__ __forceinline__ bool ld_ll(const uint4* p, uint32_t& a, uint32_t& b, uint32_t tag) {
    uint64_t lo, hi;
    asm volatile("ld.relaxed.gpu.global.v2.u64 {%0,%1}, [%2];" : "=l"(lo), "=l"(hi) : "l"(p) : "memory");
    a = (uint32_t)lo; b = (uint32_t)hi;
    return (uint32_t)(lo >> 32) == tag && (uint32_t)(hi >> 32) == tag;
}
__device__ __forceinline__ uint2 ld_acq2(const uint2* p) {
    uint2 v; asm volatile("ld.acquire.gpu.global.v2.u32 {%0,%1}, [%2];" : "=r"(v.x), "=r"(v.y) : "l"(p) : "memory"); return v;
}
__device__ __forceinline__ uint2 ld_rlx2(const uint2* p) {
    uint2 v; asm volatile("ld.relaxed.gpu.global.v2.u32 {%0,%1}, [%2];" : "=r"(v.x), "=r"(v.y) : "l"(p) : "memory"); return v;
}
__device__ __forceinline__ void stg1(uint32_t* p, uint32_t v) { asm volatile("st.global.u32 [%0], %1;" :: "l"(p), "r"(v) : "memory"); }
__device__ __forceinline__ void stg2(void* p, uint32_t x, uint32_t y) { asm volatile("st.global.v2.u32 [%0], {%1,%2};" :: "l"(p), "r"(x), "r"(y) : "memory"); }
__device__ __forceinline__ void stg4(void* p, uint32_t x, uint32_t y, uint32_t z, uint32_t w) { asm volatile("st.global.v4.u32 [%0], {%1,%2,%3,%4};" :: "l"(p), "r"(x), "r"(y), "r"(z), "r"(w) : "memory"); }
__device__ __forceinline__ uint32_t lds1(uint32_t a) { uint32_t v; asm volatile("ld.shared.u32 %0, [%1];" : "=r"(v) : "r"(a) : "memory"); return v; }
__device__ __forceinline__ uint2 lds2(uint32_t a) { uint2 v; asm volatile("ld.shared.v2.u32 {%0,%1}, [%2];" : "=r"(v.x), "=r"(v.y) : "r"(a) : "memory"); return v; }
__device__ __forceinline__ uint32_t set_par(uint32_t v, uint32_t mask, uint32_t par) { return (v & ~mask) | (par & mask); }
__device__ __forceinline__ float tanh_hw(float x) { float r; asm("tanh.approx.f32 %0, %1;" : "=f"(r) : "f"(x)); return r; }
__device__ __forceinline__ bool bar_any(int id, int n, bool v) {
    uint32_t r;
    asm volatile("{ .reg .pred p, q; setp.ne.u32 p, %3, 0; bar.red.or.pred q, %1, %2, p; selp.u32 %0, 1, 0, q; }" : "=r"(r) : "r"(id), "r"(n), "r"((uint32_t)v) : "memory");
    return r;
}
__device__ __forceinline__ void sts4(uint32_t a, uint32_t x, uint32_t y, uint32_t z, uint32_t w) { asm volatile("st.shared.v4.u32 [%0], {%1,%2,%3,%4};" :: "r"(a), "r"(x), "r"(y), "r"(z), "r"(w) : "memory"); }
__device__ __forceinline__ uint4 lds4(uint32_t a) { uint4 v; asm volatile("ld.shared.v4.u32 {%0,%1,%2,%3}, [%4];" : "=r"(v.x), "=r"(v.y), "=r"(v.z), "=r"(v.w) : "r"(a) : "memory"); return v; }
__device__ __forceinline__ uint32_t pack_bf16(float lo, float hi) { uint32_t r; asm("cvt.rn.bf16x2.f32 %0, %1, %2;" : "=r"(r) : "f"(hi), "f"(lo)); return r; }
__device__ __forceinline__ float bf_lo(uint32_t v) { return __uint_as_float(v << 16); }
__device__ __forceinline__ float bf_hi(uint32_t v) { return __uint_as_float(v & 0xffff0000u); }
__device__ __forceinline__ uint32_t sub_bf16x2(uint32_t a, uint32_t b) { uint32_t r; asm("sub.rn.bf16x2 %0, %1, %2;" : "=r"(r) : "r"(a), "r"(b)); return r; }
__device__ __forceinline__ uint32_t movm(uint32_t a) { uint32_t r; asm volatile("movmatrix.sync.aligned.m8n8.trans.b16 %0, %1;" : "=r"(r) : "r"(a)); return r; }
__device__ __forceinline__ float ex2(float x) { float r; asm("ex2.approx.ftz.f32 %0, %1;" : "=f"(r) : "f"(x)); return r; }
__device__ __forceinline__ float rsq(float x) { float r; asm("rsqrt.approx.ftz.f32 %0, %1;" : "=f"(r) : "f"(x)); return r; }
__device__ __forceinline__ float rcp(float x) { float r; asm("rcp.approx.ftz.f32 %0, %1;" : "=f"(r) : "f"(x)); return r; }
__device__ __forceinline__ void mma16816(float (&c)[4], uint32_t a0, uint32_t a1, uint32_t a2, uint32_t a3, uint32_t b0, uint32_t b1) {
    asm("mma.sync.aligned.m16n8k16.row.col.f32.bf16.bf16.f32 {%0,%1,%2,%3}, {%4,%5,%6,%7}, {%8,%9}, {%0,%1,%2,%3};"
        : "+f"(c[0]), "+f"(c[1]), "+f"(c[2]), "+f"(c[3]) : "r"(a0), "r"(a1), "r"(a2), "r"(a3), "r"(b0), "r"(b1));
}
__device__ __forceinline__ void mma1688(float (&c)[4], uint32_t a0, uint32_t a1, uint32_t b0) {
    asm("mma.sync.aligned.m16n8k8.row.col.f32.bf16.bf16.f32 {%0,%1,%2,%3}, {%4,%5}, {%6}, {%0,%1,%2,%3};"
        : "+f"(c[0]), "+f"(c[1]), "+f"(c[2]), "+f"(c[3]) : "r"(a0), "r"(a1), "r"(b0));
}
__device__ __forceinline__ float quad_sum(float v) { v += __shfl_xor_sync(~0u, v, 1); v += __shfl_xor_sync(~0u, v, 2); return v; }
__device__ __forceinline__ float quad_max(float v) { v = fmaxf(v, __shfl_xor_sync(~0u, v, 1)); v = fmaxf(v, __shfl_xor_sync(~0u, v, 2)); return v; }
__device__ __forceinline__ uint32_t desc_lo(uint32_t addr, uint32_t lbo) { return ((addr & 0x3FFFF) >> 4) | ((lbo >> 4) << 16); }
template <int I, int N, class F> __device__ __forceinline__ void static_for(F&& f) {
    if constexpr (I < N) { f(std::integral_constant<int, I>{}); static_for<I + 1, N>(f); }
}
__device__ __forceinline__ uint32_t opaque(uint32_t v) { asm volatile("" : "+r"(v)); return v; }
template <int BOFF, int SCALE_D>
__device__ __forceinline__ void wgmma_rs_n56(float (&d)[28], uint32_t a0, uint32_t a1, uint32_t a2, uint32_t a3, uint32_t blo) {
    asm volatile("{ .reg .b32 lb; .reg .b64 db;\n"
        "add.u32 lb, %32, %33; mov.b64 db, {lb, 0x40000040};\n"
        "wgmma.mma_async.sync.aligned.m64n56k16.f32.bf16.bf16 "
        "{%0, %1, %2, %3, %4, %5, %6, %7, %8, %9, %10, %11, %12, %13, %14, %15, %16, %17, %18, %19, %20, %21, %22, %23, %24, %25, %26, %27}, "
        "{%28, %29, %30, %31}, db, %34, 1, 1, 1; }"
        : "+f"(d[0]), "+f"(d[1]), "+f"(d[2]), "+f"(d[3]), "+f"(d[4]), "+f"(d[5]), "+f"(d[6]), "+f"(d[7]),
        "+f"(d[8]), "+f"(d[9]), "+f"(d[10]), "+f"(d[11]), "+f"(d[12]), "+f"(d[13]), "+f"(d[14]), "+f"(d[15]),
        "+f"(d[16]), "+f"(d[17]), "+f"(d[18]), "+f"(d[19]), "+f"(d[20]), "+f"(d[21]), "+f"(d[22]), "+f"(d[23]),
        "+f"(d[24]), "+f"(d[25]), "+f"(d[26]), "+f"(d[27])
        : "r"(a0), "r"(a1), "r"(a2), "r"(a3), "r"(blo), "n"(BOFF >> 4), "n"(SCALE_D));
}
template <int BOFF, int SCALE_D>
__device__ __forceinline__ void wgmma_rs_n128(float (&d)[64], uint32_t a0, uint32_t a1, uint32_t a2, uint32_t a3, uint32_t blo) {
    asm volatile("{ .reg .b32 lb; .reg .b64 db;\n"
        "add.u32 lb, %68, %69; mov.b64 db, {lb, 0x40000040};\n"
        "wgmma.mma_async.sync.aligned.m64n128k16.f32.bf16.bf16 "
        "{%0, %1, %2, %3, %4, %5, %6, %7, %8, %9, %10, %11, %12, %13, %14, %15, %16, %17, %18, %19, %20, %21, %22, %23, %24, %25, %26, %27, %28, %29, %30, %31, %32, %33, %34, %35, %36, %37, %38, %39, %40, %41, %42, %43, %44, %45, %46, %47, %48, %49, %50, %51, %52, %53, %54, %55, %56, %57, %58, %59, %60, %61, %62, %63}, "
        "{%64, %65, %66, %67}, db, %70, 1, 1, 1; }"
        : "+f"(d[0]), "+f"(d[1]), "+f"(d[2]), "+f"(d[3]), "+f"(d[4]), "+f"(d[5]), "+f"(d[6]), "+f"(d[7]),
        "+f"(d[8]), "+f"(d[9]), "+f"(d[10]), "+f"(d[11]), "+f"(d[12]), "+f"(d[13]), "+f"(d[14]), "+f"(d[15]),
        "+f"(d[16]), "+f"(d[17]), "+f"(d[18]), "+f"(d[19]), "+f"(d[20]), "+f"(d[21]), "+f"(d[22]), "+f"(d[23]),
        "+f"(d[24]), "+f"(d[25]), "+f"(d[26]), "+f"(d[27]), "+f"(d[28]), "+f"(d[29]), "+f"(d[30]), "+f"(d[31]),
        "+f"(d[32]), "+f"(d[33]), "+f"(d[34]), "+f"(d[35]), "+f"(d[36]), "+f"(d[37]), "+f"(d[38]), "+f"(d[39]),
        "+f"(d[40]), "+f"(d[41]), "+f"(d[42]), "+f"(d[43]), "+f"(d[44]), "+f"(d[45]), "+f"(d[46]), "+f"(d[47]),
        "+f"(d[48]), "+f"(d[49]), "+f"(d[50]), "+f"(d[51]), "+f"(d[52]), "+f"(d[53]), "+f"(d[54]), "+f"(d[55]),
        "+f"(d[56]), "+f"(d[57]), "+f"(d[58]), "+f"(d[59]), "+f"(d[60]), "+f"(d[61]), "+f"(d[62]), "+f"(d[63])
        : "r"(a0), "r"(a1), "r"(a2), "r"(a3), "r"(blo), "n"(BOFF >> 4), "n"(SCALE_D));
}
template <int AOFF, int BOFF, int SCALE_D>
__device__ __forceinline__ void wgmma_ss_n112(float (&d)[56], uint32_t alo, uint32_t blo) {
    asm volatile("{ .reg .b32 la, lb; .reg .b64 da, db;\n"
        "add.u32 la, %56, %58; add.u32 lb, %57, %59;\n"
        "mov.b64 da, {la, 0x40000040}; mov.b64 db, {lb, 64};\n"
        "wgmma.mma_async.sync.aligned.m64n112k16.f32.bf16.bf16 "
        "{%0, %1, %2, %3, %4, %5, %6, %7, %8, %9, %10, %11, %12, %13, %14, %15, %16, %17, %18, %19, %20, %21, %22, %23, %24, %25, %26, %27, %28, %29, %30, %31, %32, %33, %34, %35, %36, %37, %38, %39, %40, %41, %42, %43, %44, %45, %46, %47, %48, %49, %50, %51, %52, %53, %54, %55}, "
        "da, db, %60, 1, 1, 1, 1; }"
        : "+f"(d[0]), "+f"(d[1]), "+f"(d[2]), "+f"(d[3]), "+f"(d[4]), "+f"(d[5]), "+f"(d[6]), "+f"(d[7]),
        "+f"(d[8]), "+f"(d[9]), "+f"(d[10]), "+f"(d[11]), "+f"(d[12]), "+f"(d[13]), "+f"(d[14]), "+f"(d[15]),
        "+f"(d[16]), "+f"(d[17]), "+f"(d[18]), "+f"(d[19]), "+f"(d[20]), "+f"(d[21]), "+f"(d[22]), "+f"(d[23]),
        "+f"(d[24]), "+f"(d[25]), "+f"(d[26]), "+f"(d[27]), "+f"(d[28]), "+f"(d[29]), "+f"(d[30]), "+f"(d[31]),
        "+f"(d[32]), "+f"(d[33]), "+f"(d[34]), "+f"(d[35]), "+f"(d[36]), "+f"(d[37]), "+f"(d[38]), "+f"(d[39]),
        "+f"(d[40]), "+f"(d[41]), "+f"(d[42]), "+f"(d[43]), "+f"(d[44]), "+f"(d[45]), "+f"(d[46]), "+f"(d[47]),
        "+f"(d[48]), "+f"(d[49]), "+f"(d[50]), "+f"(d[51]), "+f"(d[52]), "+f"(d[53]), "+f"(d[54]), "+f"(d[55])
        : "r"(alo), "r"(blo), "n"(AOFF >> 4), "n"(BOFF >> 4), "n"(SCALE_D));
}

struct Params {
    const __nv_bfloat16 *x, *wqkv, *wo, *w1, *w2, *b1, *b2;
    __nv_bfloat16* out;
};

__global__ void __cluster_dims__(2, 1, 1) __launch_bounds__(384, 1)
fused_kernel(const __grid_constant__ CUtensorMap mX, const __grid_constant__ CUtensorMap mWqkv,
             const __grid_constant__ CUtensorMap mWo, const __grid_constant__ CUtensorMap mW1,
             const __grid_constant__ CUtensorMap mW2, const Params prm)
{
    extern __shared__ __align__(1024) unsigned char smem_raw[];
    uint32_t sb = (uint32_t)__cvta_generic_to_shared(smem_raw);
    asm volatile("mov.u32 %0, %0;" : "+r"(sb));
    const uint32_t bar0 = sb + SM_BAR;
    auto BAR = [&](int i) { return bar0 + 8u * i; };

    const int tid = threadIdx.x, lane = tid & 31;
    const int warp = __shfl_sync(~0u, tid >> 5, 0);
    const int b = __shfl_sync(~0u, (int)blockIdx.x, 0);
    const int rank = b & 1;
    const int cl = (b >> 1) - 4, cq = ((cl - 32) * 37) >> 8;
    const int res = cl < 0 ? 0 : cl < 32 ? cl & 7 : cl - 31 - 7 * cq;
    const int rnd = cl < 0 ? cl + 8 : cl < 32 ? cl >> 3 : 4 + cq;
    const int hg = (res & 1) * 4 + (rnd & 3);
    const int ti = (res >> 1) * 4 + (rnd >> 2) * 2 + rank;
    const int a2p = res & 1, a2j = rnd & 3;
    const int a2s = ti * 2 + a2p;
    const bool g1_on = rnd != 7;
    const int g1j = (rnd < 6 ? rnd : res) & 1, g1f = rnd < 6 ? res * 3 + (rnd >> 1) : 24 + (res >> 1);
    const int g2j = rnd & 1, g2s = res * 4 + (rnd >> 1);
    uint32_t pbar0;
    asm volatile("mapa.shared::cluster.u32 %0, %1, %2;" : "=r"(pbar0) : "r"(bar0), "r"(rank ^ 1));
    auto pair_arrive = [&](int i) { __syncwarp(); const bool l = elect_one(); mbar_arrive_if(BAR(i), l); mbar_arrive_remote_if(pbar0 + 8u * i, l); };
    const int wcol = hg * 56 - (hg & 1) * 8;

    if (tid == 32) { TRG(60); TRW(59); }
    if (warp == 8) {
        if (elect_one()) {
            #pragma unroll
            for (int i = 0; i < B_WQF; i++) mbar_init(BAR(i), 1);
            asm volatile("fence.mbarrier_init.release.cluster;" ::: "memory");
            fence_async_smem();
            TRW(56);
            #pragma unroll 1
            for (int kb = 0; kb < 7; kb++) {
                mbar_expect(BAR(B_XF + kb), 16384);
                tma2d(sb + SM_X + kb * 8192, &mX, kb * 64, ti * 64, BAR(B_XF + kb));
                tma2d(sb + SM_X + 57344 + kb * 8192, &mX, kD + kb * 64, ti * 64, BAR(B_XF + kb));
                if (TMPF == 2 && kb == 0) asm volatile("prefetch.tensormap [%0];" :: "l"(&mWqkv) : "memory");
            }
        }
    } else if (warp > 8) {
        if (elect_one()) {
            if (warp == 9) {
                if (TMPF == 1) asm volatile("prefetch.tensormap [%0];" :: "l"(&mWqkv) : "memory");
                #pragma unroll
                for (int i = B_WQF; i < B_AF; i++) mbar_init(BAR(i), i < B_XC ? 1 : i < B_A1D ? 16 : i < B_AE ? 8 : 4);
            } else if (warp == 10) {
                #pragma unroll
                for (int i = B_AF; i < B_BL; i++) mbar_init(BAR(i), 1);
            } else {
                #pragma unroll
                for (int i = B_BL; i < B_COUNT; i++) mbar_init(BAR(i), 1);
            }
            asm volatile("fence.mbarrier_init.release.cluster;" ::: "memory");
            fence_async_smem();
        }
    } else {
        const char* p = tid < 112 ? (const char*)prm.x + (size_t)(ti * 8 + hg) * 14336 + tid * 128
                                  : (const char*)prm.wqkv + b * 2688 + 896 + (tid - 112) * 128;
        if (tid < PF0) asm volatile("prefetch.global.L2 [%0];" :: "l"(p));
    }
    __syncwarp();
    __syncthreads();
    asm volatile("barrier.cluster.arrive.relaxed.aligned;" ::: "memory");
    if (tid < 256) TR(0);
    if (tid == 0) TRG(61);

    if (warp >= 8) {
        asm volatile("setmaxnreg.dec.sync.aligned.u32 40;");
        asm volatile("barrier.cluster.wait.aligned;" ::: "memory");
        if (warp == 8) {
            if (elect_one()) {
                #pragma unroll 1
                for (int s = 0; s < 7; s++) {
                    mbar_expect(BAR(B_WKVF + s), 16384);
                    tma2d_mc(sb + SM_WKV + s * 16384 + rank * 8192, &mWqkv, (1 + rank) * kD + wcol, s * 64, BAR(B_WKVF + s));
                }
            }
            __syncwarp();
            mbar_wait(BAR(B_XC), 0);
            if (elect_one()) {
                asm volatile("prefetch.tensormap [%0];" :: "l"(&mWo) : "memory");
                asm volatile("prefetch.tensormap [%0];" :: "l"(&mW1) : "memory");
                asm volatile("prefetch.tensormap [%0];" :: "l"(&mW2) : "memory");
                mbar_expect(BAR(B_WQF), 57344);
                #pragma unroll 1
                for (int s = rank; s < 7; s += 2) tma2d_mc(sb + SM_X + s * 8192, &mWqkv, wcol, s * 64, BAR(B_WQF));
                mbar_expect(BAR(B_XRF), a2j == 3 ? 8192 : 16384);
                tma2d(sb + SM_X + 8 * 8192, &mX, a2p * kD + a2j * 128, ti * 64, BAR(B_XRF));
                if (a2j != 3) tma2d(sb + SM_X + 9 * 8192, &mX, a2p * kD + a2j * 128 + 64, ti * 64, BAR(B_XRF));
            }
            __syncwarp();
            #pragma unroll 1
            for (int h = 0; h < 2; h++) {
                mbar_wait(BAR(B_KV3 + h), 0);
                if (elect_one()) {
                    mbar_expect(BAR(B_WOF + h), a2j == 3 ? 28672 : 57344);
                    const int atom = rank ^ h;
                    if (a2j != 3 || atom == 0) tma2d_mc(sb + SM_WKV + h * 57344 + atom * 28672, &mWo, a2j * 128 + atom * 64, h * 224, BAR(B_WOF + h));
                }
                __syncwarp();
            }
            auto load_slab = [&](int s, bool second) {
                if (elect_one()) {
                    mbar_expect(BAR(B_AF + s), 8192);
                    const uint32_t dst = sb + s * 8192;
                    if (!second) tma2d(dst, &mW1, (s & 1) * kF + g1f * 64, (rank * 8 + (s >> 1)) * 64, BAR(B_AF + s));
                    else         tma2d(dst, &mW2, g2s * 64, (rank * 14 + s) * 64, BAR(B_AF + s));
                }
                __syncwarp();
            };
            if (g1_on) {
                mbar_wait(BAR(B_A1D), 0);
                #pragma unroll 1
                for (int s = 0; s < 8; s++) {
                    if (s == AEARLY) mbar_wait(BAR(B_OL), 0);
                    load_slab(s, false);
                }
            }
            mbar_wait(BAR(B_GO), 0);
            const uint32_t t0 = lds1(sb + SM_TG + 4);
            if (g1_on) {
                #pragma unroll 1
                for (int s = 8; s < 16; s++) {
                    sleep_until(t0 + W1OFF + (s - 8) * W1PACE);
                    load_slab(s, false);
                    TR2(128 + s);
                }
            }
            #pragma unroll 1
            for (int s = 0; s < 14; s++) {
                if (g1_on) mbar_wait(BAR(B_AE + s), 0);
                sleep_until(t0 + W2OFF + s * W2PACE);
                load_slab(s, true);
                TR2(144 + s);
            }
        } else if (warp == 9) {
            if (elect_one()) {
                const char* src1 = (const char*)&g_hn[rank * 16 * 3584 + g1j * 896];
                const char* src2 = (const char*)&g_g[rank * 14 * 3584 + g2j * 896];
                const long long jump = src2 - src1 - (16 * 57344 + 2 * 14336);
                const char* src = g1_on ? src1 - 2 * 57344 : src2;
                uint32_t pair = g1_on ? 2 : 0, ph = g1_on ? 0 : 1, gate = g1_on ? 0 : 2;
                CAP_DECL(ti_, 0);
                #pragma unroll 1
                for (int q = g1_on ? 0 : 17; q < 31; q++) {
                    const uint32_t dst = sb + SM_B + pair * 28672, eb = q ? BAR(B_BE) + pair * 16 : BAR(B_XF), f = BAR(B_BL) + pair * 16;
                    if ((0x1020003u >> q) & 1) {
                        mbar_wait(BAR(B_HD + gate), 0);
                        spin_until(lds1(sb + SM_TG + gate * 4));
                        gate++;
                    }
                    #pragma unroll
                    for (int h = 0; h < 2; h++) {
                        if (!mbar_try(eb + h * 8, ph)) mbar_wait(eb + h * 8, ph);
                        if (q) {
                            bulk_g2s(dst + h * 14336, src + h * 57344, 14336, f + h * 8);
                            mbar_expect(f + h * 8, 14336);
                            CAP(ti_);
                        }
                    }
                    src += 2 * 57344 + (q == 8 ? 2 * 14336 - 16 * 57344 : q == 16 ? jump : q == 23 ? 2 * 14336 - 14 * 57344 : 0);
                    if (++pair == NB / 2) { pair = 0; ph ^= 1; }
                }
            }
        } else {
          uint32_t tag;
          if (warp == 10) {
            mbar_wait(BAR(PFBAR), 0);
            const char* p1 = (const char*)prm.w1 + (size_t)b * 57344 + lane * 128;
            const char* p2 = (const char*)prm.w2 + (size_t)b * 57344 + lane * 128;
            if (lane < 25) asm volatile("prefetch.global.L2 [%0];" :: "l"((const char*)prm.wo + min(b * 25 + lane, 3135) * 128));
            uint32_t tnext = (uint32_t)clock();
            #pragma unroll 1
            for (int i = 0; i < 28; i++) {
                asm volatile("prefetch.global.L2 [%0];" :: "l"(i < 14 ? p1 + i * 4096 : p2 + (i - 14) * 4096));
                tnext += PFPACE;
                while ((int)((uint32_t)clock() - tnext) < 0) __nanosleep(40);
            }
            mbar_wait(BAR(B_EP), 0);
            tag = lds1(sb + SM_EPOCH);
          } else {
            tag = *(volatile uint32_t*)&g_epoch + 1;
            const uint4 z4 = make_uint4(0u, 0u, 0u, 0u);
            #pragma unroll 1
            for (int i = 0; i < 14; i++) g_halo[(ti * 8 + hg) * 448 + i * 32 + lane] = z4;
            g_stats[(a2s * 4 + a2j) * 64 + lane] = z4; g_stats[(a2s * 4 + a2j) * 64 + 32 + lane] = z4;
            g_flag_h[(a2s * 4 + a2j) * FS + lane] = 0;
            #pragma unroll 1
            for (int i = 0; i < 2; i++) ((uint4*)g_flag_o)[((ti * 8 + i * 4 + (lane >> 3)) * 8 + hg) * 8 + (lane & 7)] = z4;
            __syncwarp();
            if (lane == 0) {
                asm volatile("st.shared.u32 [%0], %1;" :: "r"(sb + SM_EPOCH), "r"(tag) : "memory");
                mbar_arrive(BAR(B_EP));
            }
            if (lane < 4) mbar_expect(BAR(B_RF + lane), 7168);
            __syncwarp();
            TRW(44);
            const uint32_t* fp = &g_flag_h[(rank * 64 + lane) * FS];
            mbar_wait(BAR(B_HD), 0);
            uint64_t v0 = 0, v1 = 0;
            int it = 0;
            do {
                ld_flag_if(v0, fp, (uint32_t)v0 != tag); ld_flag_if(v1, fp + 32 * FS, (uint32_t)v1 != tag);
                if (++it > kSpinLimit) { TIMEOUT(108); break; }
            } while (__any_sync(~0u, (uint32_t)v0 != tag || (uint32_t)v1 != tag));
            const uint32_t gbase = __shfl_sync(~0u, (uint32_t)(v0 >> 32), 0);
            const uint32_t tg = gbase + DELTA + __reduce_max_sync(~0u, max((int)((uint32_t)(v0 >> 32) - gbase), (int)((uint32_t)(v1 >> 32) - gbase)));
            TRW(57);
            uint32_t late;
            it = 0;
            while ((int)(late = gtime32() - tg) < 0 && ++it < 64) {}
            const uint32_t t0 = clk32() - (it ? 0u : min(late + 16u, 4096u) * 7u / 4u);
            if (lane < (g1_on ? 1 : 3)) {
                asm volatile("st.shared.u32 [%0], %1;" :: "r"(sb + SM_TG + 4 + lane * 4), "r"(t0 + (lane == 0 ? 0 : lane == 1 ? CN2 : CN3)) : "memory");
                mbar_arrive(BAR(B_GO + lane));
            }
            __syncwarp();
            TRW(40);
          }
          const int h = warp & 1;
          const bool lead = elect_one();
          const uint32_t w2o = lane * 128 + ((lane + 16 * g2j) & 31) * 4, l3 = lane < 16 ? 12288 : 0;
          uint32_t wo = g1_on ? w2o ^ ((g1j ^ g2j) << 6) : w2o, pair = 0, ph = 0, rph = 0;
          CAP_DECL(ta_, 1); CAP_DECL(tc_, 2);
          #pragma unroll 1
          for (int q = g1_on ? 1 : 17; q < 31; q++) {
              const uint32_t rb = bar0 + pair * 16 + h * 8, dst = sb + SM_B + pair * 28672 + h * 14336;
              auto stale = [&]() {
                  uint32_t d;
                  asm volatile("{ .reg .b32 x, y, z, u;\n"
                               "ld.shared.u32 x, [%1]; ld.shared.u32 y, [%1 + 4096]; ld.shared.u32 z, [%1 + 8192]; ld.shared.u32 u, [%2];\n"
                               "lop3.b32 x, x, y, %3, 0x7e; lop3.b32 z, z, u, %3, 0x7e; lop3.b32 %0, x, z, 1, 0xa8; }"
                               : "=r"(d) : "r"(dst + wo), "r"(dst + wo + l3), "r"(tag) : "memory");
                  return __any_sync(~0u, d);
              };
              mbar_wait(rb + B_BL * 8, ph);
              bool bad = stale();
              mbar_arrive_if(rb + B_BF * 8, lead && !bad);
              if (bad) {
                  RETRY_COUNT(2);
                  const int e = (q > 8) + (q > 16) + (q > 23), s = (q - (e < 3 ? 1 + 8 * e : 24)) * 2 + h;
                  const char* src = (const char*)(e < 2 ? &g_hn[(rank * 16 + s) * 3584 + (g1j + 2 * e) * 896] : &g_g[(rank * 14 + s) * 3584 + (g2j + 2 * e - 4) * 896]);
                  int it = 0;
                  do {
                      if (++it > kSpinLimit) { TIMEOUT(111); break; }
                      const uint32_t* p = (const uint32_t*)(src + wo);
                      if (__any_sync(~0u, ((ld_rlx(p) ^ tag) | (ld_rlx(p + 1024) ^ tag) | (ld_rlx(p + 2048) ^ tag) | (ld_rlx(p + l3 / 4) ^ tag)) & 1)) continue;
                      if (lead) {
                          mbar_expect(BAR(B_RT + h), 14336);
                          bulk_g2s(dst, src, 14336, BAR(B_RT + h));
                      }
                      __syncwarp();
                      mbar_wait(BAR(B_RT + h), rph);
                      rph ^= 1;
                      bad = stale();
                  } while (bad);
                  mbar_arrive_if(rb + B_BF * 8, lead);
              }
              if (q == 16) wo = w2o;
              if (++pair == NB / 2) { pair = 0; ph ^= 1; }
          }
        }
    } else {
        asm volatile("setmaxnreg.inc.sync.aligned.u32 232;");
        asm volatile("barrier.cluster.wait.aligned;" ::: "memory");
        const int wg = warp >> 2, w = warp & 3;
        const int g = lane >> 2, t = lane & 3;
        uint32_t tag;
        __nv_bfloat16 bias1, bias2;
        {
            uint32_t a[28][4];
            float sm0[4] = {0.f, 0.f, 0.f, 0.f}, sm1[4] = {0.f, 0.f, 0.f, 0.f};
            {
                const int r = w * 16 + (lane & 15);
                const uint32_t rowa = sb + SM_X + wg * 57344 + r * 128;
                #pragma unroll
                for (int kb = 0; kb < 7; kb++) {
                    mbar_wait(BAR(B_XF + kb), 0);
                    #pragma unroll
                    for (int q = 0; q < 4; q++) {
                        const uint32_t addr = rowa + kb * 8192 + (((q * 2 + (lane >> 4)) ^ (r & 7)) << 4);
                        uint32_t (&f)[4] = a[kb * 4 + q];
                        asm volatile("ldmatrix.sync.aligned.m8n8.x4.shared.b16 {%0,%1,%2,%3}, [%4];"
                                     : "=r"(f[0]), "=r"(f[1]), "=r"(f[2]), "=r"(f[3]) : "r"(addr) : "memory");
                        if (q & 1) mma16816(sm1, f[0], f[1], f[2], f[3], 0x3F803F80u, 0x3F803F80u);
                        else       mma16816(sm0, f[0], f[1], f[2], f[3], 0x3F803F80u, 0x3F803F80u);
                    }
                }
            }
            const float mean0 = (sm0[0] + sm1[0]) * (1.f / kD), mean1 = (sm0[2] + sm1[2]) * (1.f / kD);
            const uint32_t mb0 = pack_bf16(mean0, mean0), mb1 = pack_bf16(mean1, mean1);
            pair_arrive(B_XC);
            TR(1);
            float ak[28], av[28], aq[28];
            float ss0 = 0.f, ss1 = 0.f, ss2 = 0.f, ss3 = 0.f;
            const uint32_t dw = desc_lo(sb + (hg & 1) * 16, 0);
            static_for<0, 7>([&](auto S_) {
                constexpr int s = decltype(S_)::value;
                #pragma unroll
                for (int q = 0; q < 4; q++) {
                    uint32_t (&f)[4] = a[s * 4 + q];
                    f[0] = sub_bf16x2(f[0], mb0); f[1] = sub_bf16x2(f[1], mb1);
                    f[2] = sub_bf16x2(f[2], mb0); f[3] = sub_bf16x2(f[3], mb1);
                    ss0 = fmaf(bf_lo(f[0]), bf_lo(f[0]), ss0); ss2 = fmaf(bf_hi(f[0]), bf_hi(f[0]), ss2);
                    ss1 = fmaf(bf_lo(f[1]), bf_lo(f[1]), ss1); ss3 = fmaf(bf_hi(f[1]), bf_hi(f[1]), ss3);
                    ss0 = fmaf(bf_lo(f[2]), bf_lo(f[2]), ss0); ss2 = fmaf(bf_hi(f[2]), bf_hi(f[2]), ss2);
                    ss1 = fmaf(bf_lo(f[3]), bf_lo(f[3]), ss1); ss3 = fmaf(bf_hi(f[3]), bf_hi(f[3]), ss3);
                }
                mbar_wait(BAR(B_WKVF + s), 0);
                wg_fence();
                static_for<0, 4>([&](auto Q_) {
                    constexpr int q = decltype(Q_)::value;
                    uint32_t (&f)[4] = a[s * 4 + q];
                    wgmma_rs_n56<SM_WKV + s * 16384 + q * 2048, (s | q) != 0>(ak, f[0], f[1], f[2], f[3], dw);
                    wgmma_rs_n56<SM_WKV + s * 16384 + q * 2048 + 8192, (s | q) != 0>(av, f[0], f[1], f[2], f[3], dw);
                });
                wg_commit();
                if (s == 4) { wg_wait<1>(); pair_arrive(B_KV3); }
            });
            auto q_chunk = [&](auto C_) {
                wg_fence();
                static_for<0, 7>([&](auto K_) {
                    constexpr int k = decltype(C_)::value * 7 + decltype(K_)::value;
                    wgmma_rs_n56<SM_X + k * 2048, k != 0>(aq, a[k][0], a[k][1], a[k][2], a[k][3], dw);
                });
                wg_commit();
            };
            const float dl0 = mean0 - bf_lo(mb0), dl1 = mean1 - bf_lo(mb1);
            const float rs0 = rsq(fmaxf(quad_sum(ss0 + ss2) * (1.f / kD) - dl0 * dl0, 0.f) + kEps);
            const float rs1 = rsq(fmaxf(quad_sum(ss1 + ss3) * (1.f / kD) - dl1 * dl1, 0.f) + kEps);
            mbar_wait2(BAR(B_EP), 0, BAR(B_WQF), 0);
            asm volatile("ld.shared.u32 %0, [%1];" : "=r"(tag) : "r"(sb + SM_EPOCH) : "memory");
            q_chunk(std::integral_constant<int, 0>{});
            wg_wait<1>();
            reg_fence(ak); reg_fence(av);
            TR(2);
            uint32_t kf[3][7], vf[3][7];
            #pragma unroll
            for (int c = 0; c < 7; c++) {
                kf[2][c] = pack_bf16(ak[4 * c + 2] * rs1, ak[4 * c + 3] * rs1);
                vf[2][c] = movm(pack_bf16(av[4 * c + 2] * rs1, av[4 * c + 3] * rs1));
            }
            const uint32_t stg = sb + SM_RED + (1 - wg) * 16384 + lane * 16;
            if (w == 3) {
                uint4* hp = &g_halo[((ti * 8 + hg) * 2 + wg) * 7 * 32 + lane];
                #pragma unroll
                for (int c = 0; c < 7; c++) st_ll(hp + c * 32, kf[2][c], vf[2][c], tag);
            } else {
                sts4(stg + w * 2048 + 0,    kf[2][0], kf[2][1], kf[2][2], kf[2][3]);
                sts4(stg + w * 2048 + 512,  kf[2][4], kf[2][5], kf[2][6], vf[2][0]);
                sts4(stg + w * 2048 + 1024, vf[2][1], vf[2][2], vf[2][3], vf[2][4]);
                sts4(stg + w * 2048 + 1536, vf[2][5], vf[2][6], 0u, 0u);
            }
            pair_arrive(B_KVC);
            q_chunk(std::integral_constant<int, 1>{});
            #pragma unroll
            for (int c = 0; c < 7; c++) {
                kf[1][c] = pack_bf16(ak[4 * c] * rs0, ak[4 * c + 1] * rs0);
                vf[1][c] = movm(pack_bf16(av[4 * c] * rs0, av[4 * c + 1] * rs0));
            }
            named_bar(1 + wg, 128);
            q_chunk(std::integral_constant<int, 2>{});
            q_chunk(std::integral_constant<int, 3>{});
            if (w == 0) {
                if (ti > 0) {
                    const uint4* hp = &g_halo[(((ti - 1) * 8 + hg) * 2 + wg) * 7 * 32 + lane];
                    int it = 0; bool ok;
                    do {
                        ok = true;
                        #pragma unroll
                        for (int c = 0; c < 7; c++) ok &= ld_ll(hp + c * 32, kf[0][c], vf[0][c], tag);
                        if (++it > kSpinLimit) { TIMEOUT(101); break; }
                    } while (!__all_sync(~0u, ok));
                } else {
                    #pragma unroll
                    for (int c = 0; c < 7; c++) { kf[0][c] = 0u; vf[0][c] = 0u; }
                }
            } else {
                const uint4 u0 = lds4(stg + (w - 1) * 2048), u1 = lds4(stg + (w - 1) * 2048 + 512),
                            u2 = lds4(stg + (w - 1) * 2048 + 1024), u3 = lds4(stg + (w - 1) * 2048 + 1536);
                kf[0][0] = u0.x; kf[0][1] = u0.y; kf[0][2] = u0.z; kf[0][3] = u0.w;
                kf[0][4] = u1.x; kf[0][5] = u1.y; kf[0][6] = u1.z; vf[0][0] = u1.w;
                vf[0][1] = u2.x; vf[0][2] = u2.y; vf[0][3] = u2.z; vf[0][4] = u2.w;
                vf[0][5] = u3.x; vf[0][6] = u3.y;
            }
            uint4* op = opaque_ptr(&g_o[(((ti * 2 + wg) * 4 + w) * 28 + ((7 * hg) >> 1)) * 32 + lane]);
            uint32_t* ofl = opaque_ptr(&g_flag_o[(((ti * 2 + wg) * 4 + w) * 8 + hg) * FS]);
            TR(3);
            wg_wait<0>();
            reg_fence(aq);
            warp_arrive(BAR(B_A1D));
            TR(4);
            uint32_t qf[7][2];
            #pragma unroll
            for (int c = 0; c < 7; c++) {
                qf[c][0] = pack_bf16(aq[4 * c], aq[4 * c + 1]);
                qf[c][1] = pack_bf16(aq[4 * c + 2], aq[4 * c + 3]);
            }
            const bool has_prev = (ti > 0) || (w > 0);
            const float sc0 = rs0 * (0.18898223650461362f * 1.4426950408889634f);
            const float sc1 = rs1 * (0.18898223650461362f * 1.4426950408889634f);
            const float NEG = -__int_as_float(0x7f800000);
            uint32_t ow[7][2];
            #pragma unroll
            for (int hd = 0; hd < 2; hd++) {
                const int c0 = hd * 3;
                const bool keep = hd == 0 ? (t < 2) : (t >= 2);
                const uint32_t q3a = keep ? qf[3][0] : 0u, q3b = keep ? qf[3][1] : 0u;
                float sc_[3][4];
                #pragma unroll
                for (int n = 0; n < 3; n++) {
                    sc_[n][0] = sc_[n][1] = sc_[n][2] = sc_[n][3] = 0.f;
                    if (hd == 0) {
                        mma16816(sc_[n], qf[0][0], qf[0][1], qf[1][0], qf[1][1], kf[n][0], kf[n][1]);
                        mma16816(sc_[n], qf[2][0], qf[2][1], q3a, q3b, kf[n][2], kf[n][3]);
                    } else {
                        mma16816(sc_[n], q3a, q3b, qf[4][0], qf[4][1], kf[n][3], kf[n][4]);
                        mma16816(sc_[n], qf[5][0], qf[5][1], qf[6][0], qf[6][1], kf[n][5], kf[n][6]);
                    }
                }
                const bool gt0 = 2 * t > g, gt1 = 2 * t + 1 > g;
                const float e0 = gt0 ? (has_prev ? sc_[0][0] : NEG) : sc_[1][0], e1 = gt1 ? (has_prev ? sc_[0][1] : NEG) : sc_[1][1];
                const float f0 = gt0 ? sc_[1][2] : sc_[2][2], f1 = gt1 ? sc_[1][3] : sc_[2][3];
                const float me = quad_max(fmaxf(e0, e1)) * sc0, mf = quad_max(fmaxf(f0, f1)) * sc1;
                float p0 = ex2(fmaf(e0, sc0, -me)), p1 = ex2(fmaf(e1, sc0, -me));
                float r0 = ex2(fmaf(f0, sc1, -mf)), r1 = ex2(fmaf(f1, sc1, -mf));
                const float ie = rcp(quad_sum(p0 + p1)), jf = rcp(quad_sum(r0 + r1));
                const uint32_t pp = pack_bf16(p0 * ie, p1 * ie), rp = pack_bf16(r0 * jf, r1 * jf);
                const uint32_t mk = (gt0 ? 0x0000ffffu : 0u) | (gt1 ? 0xffff0000u : 0u);
                const uint32_t sw = hg >= 4 ? ~0u : 0u;
                const uint32_t pa0 = pp & mk & ~sw, pa1 = pp & mk & sw, pb0 = rp & ~mk & sw, pb1 = rp & ~mk & ~sw;
                const uint32_t pa2 = sw ? rp & mk : pp & ~mk, pa3 = sw ? pp & ~mk : rp & mk;
                #pragma unroll
                for (int c = 0; c < 4; c++) {
                    float o[4] = {0.f, 0.f, 0.f, 0.f};
                    mma16816(o, pa0, pa1, pa2, pa3, vf[0][c0 + c], vf[1][c0 + c]);
                    mma1688(o, pb0, pb1, vf[2][c0 + c]);
                    const uint32_t lo = pack_bf16(o[0], o[1]), hi = pack_bf16(o[2], o[3]);
                    if (hd == 1 && c == 0) { if (t >= 2) { ow[3][0] = lo; ow[3][1] = hi; } }
                    else { ow[c0 + c][0] = lo; ow[c0 + c][1] = hi; }
                }
            }
            const uint32_t om = ~lane & 1;
            if (hg & 1) {
                stg2((uint2*)(op - lane) + 32 + lane, set_par(ow[0][0], om, tag), ow[0][1]);
                stg4(op + 32, set_par(ow[1][0], om, tag), ow[1][1], ow[2][0], ow[2][1]);
                stg4(op + 64, set_par(ow[3][0], om, tag), ow[3][1], ow[4][0], ow[4][1]);
                stg4(op + 96, set_par(ow[5][0], om, tag), ow[5][1], ow[6][0], ow[6][1]);
            } else {
                stg4(op,      set_par(ow[0][0], om, tag), ow[0][1], ow[1][0], ow[1][1]);
                stg4(op + 32, set_par(ow[2][0], om, tag), ow[2][1], ow[3][0], ow[3][1]);
                stg4(op + 64, set_par(ow[4][0], om, tag), ow[4][1], ow[5][0], ow[5][1]);
                stg2((uint2*)(op + 96 - lane) + lane, set_par(ow[6][0], om, tag), ow[6][1]);
            }
            if (lane == 0) asm volatile("st.relaxed.gpu.global.u32 [%0], %1;" :: "l"(ofl), "r"(tag) : "memory");
            TR(5);
        }
        {
            float acc2[64];
            const bool wide = a2j != 3;
            mbar_wait(BAR(B_XRF), 0);
            {
                const uint32_t xa = sb + SM_X + 8 * 8192 + (w * 16 + wg * 8 + (lane & 7)) * 128;
                #pragma unroll
                for (int c = 0; c < 4; c++) {
                    uint32_t xr[4];
                    asm volatile("ldmatrix.sync.aligned.m8n8.x4.shared.b16 {%0,%1,%2,%3}, [%4];"
                                 : "=r"(xr[0]), "=r"(xr[1]), "=r"(xr[2]), "=r"(xr[3])
                                 : "r"(xa + (c >> 1) * 8192 + ((((c & 1) * 4 + (lane >> 3)) ^ (lane & 7)) << 4)) : "memory");
                    #pragma unroll
                    for (int e = 0; e < 4; e++) {
                        acc2[16 * c + 4 * e] = bf_lo(xr[e]); acc2[16 * c + 4 * e + 1] = bf_hi(xr[e]);
                        acc2[16 * c + 4 * e + 2] = 0.f;      acc2[16 * c + 4 * e + 3] = 0.f;
                    }
                }
            }
            const uint4* op = &g_o[((a2s * 4 + w) * 28 + wg * 14) * 32];
            const uint32_t rsend = opaque(sb + SM_RED + (1 - wg) * 16384 + w * 4096 + lane * 16);
            const uint32_t rrecv = opaque(sb + SM_RED + wg * 16384 + w * 4096 + lane * 16);
            uint4* spw = opaque_ptr(&g_stats[(a2s * 4 + a2j) * 64 + (w * 2 + wg) * 8 + g]);
            const uint4* spr = opaque_ptr(&g_stats[(a2s * 4 + t) * 64 + (w * 2 + wg) * 8 + g]);
            uint2* hp = opaque_ptr((uint2*)g_h + ((a2s * 8 + w * 2 + wg) * 28 + a2j * 8) * 32 + lane);
            uint32_t* np = opaque_ptr((uint32_t*)&g_hn[(a2s * 56 + a2j * 16) * 64] + (w * 2 + wg) * 32 + lane);
            uint32_t* nfl = opaque_ptr(&g_flag_h[(a2s * 4 + a2j) * FS]);
            bias1 = prm.b1[g1f * 64 + w * 16 + rank * 8 + g]; bias2 = prm.b2[g2s * 64 + w * 16 + rank * 8 + g];
            reg_fence(acc2);
            mbar_wait(BAR(B_WOF + wg), 0);
            {
                const uint32_t* pp = &g_flag_o[((a2s * 4 + w) * 8 + wg * 4 + t) * FS];
                int it = 0;
                while (__any_sync(~0u, ld_rlx(pp) != tag)) { if (++it > kSpinLimit) { TIMEOUT(102); break; } }
            }
            TR(6);
            uint4 of[14];
            auto load_o = [&](int k) {
                if (k % 7 == 3) {
                    const uint2 lo = ld_rlx2((const uint2*)(op + k * 32) + lane), hi = ld_rlx2((const uint2*)(op + k * 32) + 32 + lane);
                    of[k] = make_uint4(lo.x, lo.y, hi.x, hi.y);
                } else of[k] = ld_rlx4(op + k * 32 + lane);
            };
            #pragma unroll
            for (int k = 0; k < 14; k++) load_o(k);
            const uint32_t dwo = desc_lo(sb + SM_WKV + wg * 57344, 28672);
            static_for<0, 4>([&](auto G_) {
                constexpr int k0 = (decltype(G_)::value * 7) / 2, k1 = (decltype(G_)::value * 7 + 7) / 2;
                int it = 0;
                while (true) {
                    uint32_t bad = 0;
                    #pragma unroll
                    for (int k = k0; k < k1; k++) bad |= (of[k].x ^ tag) | (k % 7 == 3 ? of[k].z ^ tag : 0u);
                    if (!__any_sync(~0u, bad & ~lane & 1)) break;
                    if (++it > kSpinLimit) { TIMEOUT(109); break; }
                    RETRY_COUNT(1);
                    #pragma unroll
                    for (int k = k0; k < k1; k++) load_o(k);
                }
                if (k1 == 14) warp_arrive(BAR(B_OL));
                wg_fence();
                static_for<k0, k1>([&](auto K_) { constexpr int k = decltype(K_)::value;
                    wgmma_rs_n128<k * 2048, 1>(acc2, of[k].x, of[k].y, of[k].z, of[k].w, dwo); });
            });
            wg_commit();
            wg_wait<0>();
            reg_fence(acc2);
            TR(7);
            #pragma unroll
            for (int c = 0; c < 8; c++)
                sts4(rsend + c * 512, __float_as_uint(acc2[8 * c + 2]), __float_as_uint(acc2[8 * c + 3]), __float_as_uint(acc2[8 * c + 6]), __float_as_uint(acc2[8 * c + 7]));
            named_bar(3, 256);
            float hv[32];
            float s0 = 0.f, s1 = 0.f, q0 = 0.f, q1 = 0.f;
            #pragma unroll
            for (int c = 0; c < 8; c++) {
                const uint4 u = lds4(rrecv + c * 512);
                hv[4 * c]     = acc2[8 * c] + __uint_as_float(u.x);     hv[4 * c + 1] = acc2[8 * c + 1] + __uint_as_float(u.y);
                hv[4 * c + 2] = acc2[8 * c + 4] + __uint_as_float(u.z); hv[4 * c + 3] = acc2[8 * c + 5] + __uint_as_float(u.w);
            }
            #pragma unroll
            for (int c = 0; c < 16; c += 2) { s0 += hv[c]; s1 += hv[c + 1]; q0 = fmaf(hv[c], hv[c], q0); q1 = fmaf(hv[c + 1], hv[c + 1], q1); }
            if (wide) {
                #pragma unroll
                for (int c = 16; c < 32; c += 2) { s0 += hv[c]; s1 += hv[c + 1]; q0 = fmaf(hv[c], hv[c], q0); q1 = fmaf(hv[c + 1], hv[c + 1], q1); }
            }
            s0 = quad_sum(s0 + s1); q0 = quad_sum(q0 + q1);
            if (t == 0) st_ll(spw, __float_as_uint(s0), __float_as_uint(q0), tag);
            TR(8);
            fence_async_smem();
            #pragma unroll
            for (int c = 0; c < 8; c++)
                if (c < 4 || wide) stg2(hp + c * 32, set_par(pack_bf16(hv[4 * c], hv[4 * c + 1]), t == 0, tag), pack_bf16(hv[4 * c + 2], hv[4 * c + 3]));
            const uint32_t nm = opaque((lane & 7) == w * 2 + wg ? 1u << (lane >> 3) : 0u);
            uint32_t um, uv;
            {
                int it = 0;
                while (!__all_sync(~0u, ld_ll(spr, um, uv, tag))) { if (++it > kSpinLimit) { TIMEOUT(103); break; } }
            }
            TR(9);
            const float mean = quad_sum(__uint_as_float(um)) * (1.f / kD);
            const float var = fmaxf(fmaf(quad_sum(__uint_as_float(uv)), 1.f / kD, -mean * mean), 0.f);
            const float r1 = rsq(var + kEps);
            const float rr = r1 * rsq(fmaf(var * r1, r1, kEps));
            const float mr = -mean * rr;
            #pragma unroll
            for (int c = 0; c < 16; c++)
                if (c < 8 || wide) stg1(np + c * 256, set_par(pack_bf16(fmaf(hv[2 * c], rr, mr), fmaf(hv[2 * c + 1], rr, mr)), (nm >> (c & 3)) & 1, tag));
            named_bar(3, 256);
            mbar_arrive_remote_if(pbar0 + 8u * B_PD, tid == 0);
            if (tid == 128) {
                st_flag(nfl, tag);
                asm volatile("st.shared.u32 [%0], %1;" :: "r"(sb + SM_TG), "r"(clk32()) : "memory");
                mbar_arrive(BAR(B_HD));
            }
            __syncwarp();
            TR(10);
        }
        float acc[56];
        const uint32_t xch = opaque(sb + SM_XCH + w * 1920 + lane * 16);
        uint32_t peer_xch; const uint32_t peer_bar = pbar0;
        asm volatile("mapa.shared::cluster.u32 %0, %1, %2;" : "=r"(peer_xch) : "r"(xch), "r"(rank ^ 1));
        uint2 hr[7];
        const int tok = g2s * 64 + w * 16 + rank * 8 + g, pr = (tok & 127) >> 1;
        const uint2* hp = (const uint2*)g_h + ((((tok >> 7) * 2 + (tok & 1)) * 8 + (pr >> 3)) * 28 + (g2j + 2 * wg) * 7) * 32 + (pr & 7) * 4 + t;
        auto load_h = [&]() {
            #pragma unroll
            for (int c = 0; c < 7; c++) hr[c] = ld_rlx2(hp + c * 32);
        };
        #pragma unroll
        for (int c = 0; c < 7; c++) hr[c] = make_uint2(0u, 0u);
        if (!g1_on) { mbar_wait(BAR(B_GO), 0); load_h(); }
        #pragma unroll 1
        for (int ge = g1_on ? 0 : 1; ge < 2; ge++) {
            const int pos = (ge ? (g1_on ? 32 : 0) : 0) + wg * (ge ? 14 : 16);
            const uint32_t aph = (ge && g1_on) ? 1u : 0u;
            const int dsub = (ge ? g2j : g1j) + 2 * wg;
            auto init_acc = [&]() {
                const float bias = __bfloat162float(ge ? bias2 : bias1);
                if (ge) {
                    int it = 0;
                    while (true) {
                        uint32_t bad = 0;
                        #pragma unroll
                        for (int c = 0; c < 7; c++) bad |= hr[c].x ^ tag;
                        if (!__any_sync(~0u, t == 0 && (bad & 1))) break;
                        if (++it > kSpinLimit) { TIMEOUT(110); break; }
                        load_h();
                    }
                }
                #pragma unroll
                for (int c = 0; c < 14; c++) {
                    const uint32_t hw = c & 1 ? hr[c >> 1].y : hr[c >> 1].x;
                    const float lo = bf_lo(hw) + bias, hi = bf_hi(hw) + bias;
                    acc[4 * c]     = rank ? 0.f : lo; acc[4 * c + 1] = rank ? 0.f : hi;
                    acc[4 * c + 2] = rank ? lo : 0.f; acc[4 * c + 3] = rank ? hi : 0.f;
                }
            };
            init_acc();
            uint32_t rbar[3], sp[3], db[3];
            #pragma unroll
            for (int i = 0; i < 3; i++) {
                const uint32_t sl = (pos + 2 * i) % NB;
                rbar[i] = bar0 + sl * 8;                   sp[i] = ((pos + 2 * i) / NB) & 1;
                db[i] = desc_lo(sb + SM_B + sl * 14336, 128);
            }
            uint32_t* gp = opaque_ptr(ge ? (uint32_t*)(prm.out + (size_t)(g2s * 64 + w * 16 + rank * 8) * kD + dsub * 112)
                                         : (uint32_t*)&g_g[(g1f * 56 + dsub * 14) * 64] + (w * 2 + rank) * 32 + lane);
            const bool lead = elect_one();
            const bool rel_a = lead && !ge && wg == 1;
            const uint32_t da = desc_lo(sb, 0);
            auto stage = [&](auto S_) {
                constexpr int s = decltype(S_)::value, i = (s / 2) % 3, bs = (s & 1) * 14336;
                wg_fence();
                wgmma_ss_n112<s * 8192,        bs,       1>(acc, da, db[i]);
                wgmma_ss_n112<s * 8192 + 2048, bs + 256, 1>(acc, da, db[i]);
                wgmma_ss_n112<s * 8192 + 4096, bs + 512, 1>(acc, da, db[i]);
                wgmma_ss_n112<s * 8192 + 6144, bs + 768, 1>(acc, da, db[i]);
                wg_commit();
                if (s == 15 || (s == 13 && ge && wg == 0)) named_arrive(4 + wg, 256);
                if constexpr (s > 0) {
                    wg_wait<1>();
                    mbar_arrive_if(rbar[((s - 1) / 2) % 3] + (B_BE + ((s - 1) & 1)) * 8, lead);
                    if (s <= 14) mbar_arrive_if(BAR(B_AE + s - 1), rel_a);
                }
                if (s < 15 && !(s == 13 && ge))
                    mbar_wait2(BAR(B_AF + s + 1), aph, rbar[((s + 1) / 2) % 3] + (B_BF + ((s + 1) & 1)) * 8, sp[((s + 1) / 2) % 3] ^ (((s + 1) / NB) & 1));
            };
            reg_fence(acc);
            mbar_wait(BAR(B_AF), aph);
            if (wg == 1 || (ge && g1_on)) named_bar(5 - wg, 256);
            mbar_wait(rbar[0] + B_BF * 8, sp[0]);
            TR(11 + ge * 4);
            static_for<0, 14>(stage);
            if (!ge) static_for<14, 16>(stage);
            const uint32_t lastbar = (ge ? rbar[0] : rbar[1]) + (B_BE + 1) * 8;
            const int use = ge * 2 + wg;
            mbar_wait(BAR(use > (g1_on ? 0 : 2) ? B_RE + use - 1 : B_PD), 0);
            wg_wait<0>();
            reg_fence(acc);
            TR(12 + ge * 4);
            mbar_arrive_if(lastbar, lead);
            float v[28];
            auto reduce = [&](auto R_) {
                constexpr int o = decltype(R_)::value * 2;
                const uint32_t rf = peer_bar + (B_RF + use) * 8;
                float dly = __uint_as_float(0x3f800000u | lane); uint32_t pa = peer_xch;
                #pragma unroll
                for (int c = 0; c < 4; c++) {
                    const uint32_t p0 = pack_bf16(acc[16 * c + 2 - o], acc[16 * c + 3 - o]), p1 = pack_bf16(acc[16 * c + 6 - o], acc[16 * c + 7 - o]);
                    if (c < 3) {
                        const uint32_t p2 = pack_bf16(acc[16 * c + 10 - o], acc[16 * c + 11 - o]), p3 = pack_bf16(acc[16 * c + 14 - o], acc[16 * c + 15 - o]);
                        asm volatile("st.async.shared::cluster.mbarrier::complete_tx::bytes.v4.b32 [%0], {%1,%2,%3,%4}, [%5];"
                                     :: "r"(pa + c * 512), "r"(p0), "r"(p1), "r"(p2), "r"(p3), "r"(rf) : "memory");
                        if (use != 3) {
                            #pragma unroll
                            for (int i = 0; i < XPACE; i++) asm volatile("tanh.approx.f32 %0, %0;" : "+f"(dly) :: "memory");
                            pa += __float_as_uint(dly) >> 30;
                        }
                    } else {
                        asm volatile("st.async.shared::cluster.mbarrier::complete_tx::bytes.v2.b32 [%0], {%1,%2}, [%3];"
                                     :: "r"(pa + 1536 - lane * 8), "r"(p0), "r"(p1), "r"(rf) : "memory");
                    }
                }
                if (!ge) load_h();
                mbar_wait(BAR(B_RF + use), 0);
                #pragma unroll
                for (int c = 0; c < 4; c++) {
                    uint4 u;
                    if (c < 3) u = lds4(xch + c * 512); else { const uint2 u2 = lds2(xch + 1536 - lane * 8); u.x = u2.x; u.y = u2.y; }
                    v[8 * c]     = acc[16 * c + o] + bf_lo(u.x);     v[8 * c + 1] = acc[16 * c + 1 + o] + bf_hi(u.x);
                    v[8 * c + 2] = acc[16 * c + 4 + o] + bf_lo(u.y); v[8 * c + 3] = acc[16 * c + 5 + o] + bf_hi(u.y);
                    if (c < 3) {
                        v[8 * c + 4] = acc[16 * c + 8 + o] + bf_lo(u.z);  v[8 * c + 5] = acc[16 * c + 9 + o] + bf_hi(u.z);
                        v[8 * c + 6] = acc[16 * c + 12 + o] + bf_lo(u.w); v[8 * c + 7] = acc[16 * c + 13 + o] + bf_hi(u.w);
                    }
                }
            };
            if (rank) reduce(std::integral_constant<int, 1>{}); else reduce(std::integral_constant<int, 0>{});
            TR(13 + ge * 4);
            if (!ge) {
                uint32_t gm[4];
                #pragma unroll
                for (int i = 0; i < 4; i++) gm[i] = lane == ((dsub * 2 + i) & 3) * 8 + w * 2 + rank;
                #pragma unroll
                for (int c = 0; c < 14; c++) {
                    float r[2];
                    #pragma unroll
                    for (int e = 0; e < 2; e++) {
                        const float u = v[2 * c + e], hu = 0.5f * u;
                        r[e] = fmaf(hu, tanh_hw(u * fmaf(u * u, 0.7978845608f * 0.044715f, 0.7978845608f)), hu);
                    }
                    stg1(gp + c * 256, set_par(pack_bf16(r[0], r[1]), gm[c & 3], tag));
                }
                named_bar(1 + wg, 128);
                if (w == 0 && lane == 0) {
                    asm volatile("st.shared.u32 [%0], %1;" :: "r"(sb + SM_TG + 8 + wg * 4), "r"(clk32() + XSPEC) : "memory");
                    mbar_arrive(BAR(B_GD + wg));
                }
                mbar_arrive_remote_if(peer_bar + (B_RE + use) * 8, lead);
            } else {
                const uint32_t stw = xch - lane * 16;
                uint32_t pk[14];
                #pragma unroll
                for (int c = 0; c < 14; c++) pk[c] = pack_bf16(v[2 * c], v[2 * c + 1]);
                __syncwarp();
                const uint32_t sa = stw + (lane & 7) * 240 + (lane >> 3) * 16;
                #pragma unroll
                for (int m = 0; m < 3; m++)
                    asm volatile("stmatrix.sync.aligned.m8n8.x4.shared.b16 [%0], {%1,%2,%3,%4};"
                                 :: "r"(sa + m * 64), "r"(pk[4 * m]), "r"(pk[4 * m + 1]), "r"(pk[4 * m + 2]), "r"(pk[4 * m + 3]) : "memory");
                asm volatile("stmatrix.sync.aligned.m8n8.x2.shared.b16 [%0], {%1,%2};" :: "r"(sa + 192), "r"(pk[12]), "r"(pk[13]) : "memory");
                __syncwarp();
                #pragma unroll
                for (int i = 0; i < 4; i++) {
                    const int r = 2 * i + (lane >> 4), ch = lane & 15;
                    if (ch < 14) { const uint4 u = lds4(stw + r * 240 + ch * 16); stg4(gp + r * 224 + ch * 4, u.x, u.y, u.z, u.w); }
                }
                __syncwarp();
                mbar_arrive_remote_if(peer_bar + (B_RE + 2) * 8, lead && wg == 0);
            }
            TR(14 + ge * 4);
        }
        if (tid == 128) TRG(62);
        if (b == 0 && tid == 128) g_epoch = tag;
    }
}

typedef CUresult (*EncodeFn)(CUtensorMap*, CUtensorMapDataType, cuuint32_t, void*, const cuuint64_t*, const cuuint64_t*,
                             const cuuint32_t*, const cuuint32_t*, CUtensorMapInterleave, CUtensorMapSwizzle,
                             CUtensorMapL2promotion, CUtensorMapFloatOOBfill);

void make_map(EncodeFn enc, CUtensorMap* m, const void* base, uint64_t cols, uint64_t rows, uint32_t box_rows) {
    cuuint64_t dims[2] = {cols, rows};
    cuuint64_t strides[1] = {cols * 2};
    cuuint32_t box[2] = {64, box_rows};
    cuuint32_t es[2] = {1, 1};
    enc(m, CU_TENSOR_MAP_DATA_TYPE_BFLOAT16, 2, const_cast<void*>(base), dims, strides, box, es, CU_TENSOR_MAP_INTERLEAVE_NONE,
        CU_TENSOR_MAP_SWIZZLE_128B, CU_TENSOR_MAP_L2_PROMOTION_L2_128B, CU_TENSOR_MAP_FLOAT_OOB_FILL_NONE);
}

}

extern "C" void kernel_launch(void* const* d_in, const int* in_sizes, int n_in, void* d_out, int out_size) {
    (void)in_sizes; (void)n_in; (void)out_size;
    void* fn = nullptr;
    cudaDriverEntryPointQueryResult qr;
    cudaGetDriverEntryPoint("cuTensorMapEncodeTiled", &fn, cudaEnableDefault, &qr);
    EncodeFn enc = (EncodeFn)fn;
    CUtensorMap mX, mWqkv, mWo, mW1, mW2;
    make_map(enc, &mX, d_in[0], 2 * kD, kS / 2, 64);
    make_map(enc, &mWqkv, d_in[1], 3 * kD, kD, 64);
    make_map(enc, &mWo, d_in[2], kD, kD, 224);
    make_map(enc, &mW1, d_in[4], 2 * kF, kS / 2, 64);
    make_map(enc, &mW2, d_in[6], kS, kF, 64);
    Params prm;
    prm.x = (const __nv_bfloat16*)d_in[0];
    prm.wqkv = (const __nv_bfloat16*)d_in[1];
    prm.wo = (const __nv_bfloat16*)d_in[2];
    prm.w1 = (const __nv_bfloat16*)d_in[4];
    prm.b1 = (const __nv_bfloat16*)d_in[5];
    prm.w2 = (const __nv_bfloat16*)d_in[6];
    prm.b2 = (const __nv_bfloat16*)d_in[7];
    prm.out = (__nv_bfloat16*)d_out;
    cudaFuncSetAttribute(fused_kernel, cudaFuncAttributeMaxDynamicSharedMemorySize, SM_TOTAL);
    fused_kernel<<<128, 384, SM_TOTAL, cudaStreamPerThread>>>(mX, mWqkv, mWo, mW1, mW2, prm);
}
```

```cpp
#include <cuda_runtime.h>
#include <cuda.h>
#include <cuda_bf16.h>
#include <stdint.h>
#include <type_traits>

namespace {

constexpr int kS = 2048, kD = 448, kF = 1792;
constexpr float kEps = 1e-5f;

#define FS 32
__device__ __align__(1024) uint4    g_o[32 * 4 * 28 * 32];
__device__ __align__(1024) uint4    g_h[kS * kD * 2 / 16];
__device__ __align__(1024) uint4    g_hn[32 * 56 * 64];
__device__ __align__(1024) uint4    g_g[28 * 56 * 64];
__device__ __align__(1024) uint4    g_halo[16 * 8 * 2 * 7 * 32];
__device__ __align__(1024) uint4    g_stats[32 * 4 * 64];
__device__ __align__(1024) uint32_t g_flag_o[32 * 4 * 8 * FS];
__device__ __align__(1024) uint32_t g_flag_h[32 * 4 * FS];
__device__ uint32_t g_epoch;
#define TIMEOUT(code)
#define RETRY_COUNT(i)
#define CAP_DECL(n, k)
#define CAP(n)
#define CAP_SKIP(n)
#define TR2(idx)
#define TR(idx)
#define TRW(idx)
#define TRG(idx)

constexpr uint32_t SM_X    = 0;
constexpr uint32_t SM_WKV  = 114688;
constexpr uint32_t SM_RED  = 81920;
constexpr uint32_t SM_XCH  = 131072;
constexpr uint32_t SM_B    = 139264;
constexpr uint32_t SM_BAR  = 231424;
constexpr uint32_t SM_TOTAL = SM_BAR + 1024;
constexpr int NB = 6;
#define SH1 0
#define SH2 0
#define SH2N 5
#define SH3 0
#define NSPEC 4
#define XSPEC 900
#define C2 0
#define C3 0
#define CN2 8000
#define CN3 12000
constexpr int B_XF = 0, B_WKVF = 7, B_WQF = 14, B_XRF = 15, B_WOF = 16,
              B_XC = 18, B_KV3 = 19, B_KVC = 20,
              B_A1D = 21, B_OL = 22,
              B_BE = 23, B_RE = B_BE + NB,
              B_AE = B_RE + 3, B_AF = B_AE + 14, B_BL = B_AF + 16  , B_BF = B_BL + NB  , B_RF = B_BF + NB,
              B_EP = B_RF + 4, B_PD = B_EP + 1, B_RT = B_PD + 1,
              B_HD = B_RT + 2, B_GO = B_HD + 1, B_GD = B_GO + 1, B_COUNT = B_GD + 2;
#define WEARLY 6
#define PF0 126
#define TMPF 2
#define RSTE 2
#define POLLP 1
#define PROBEP 1
#define LOADP 1
#define LOADW 64
#define NOB 0
#define AEARLY 5
#define W1PACE 400
#define W2PACE 420
#define PFPACE 330
#define PFBAR (B_XF + 6)
#define DELTA 640
#define DELTA2 DELTA
#define BPACE 230
#define BURST 2
#define W1OFF 350
#define W2OFF 5200
#define XPACE 0
#define PSTAG 200
constexpr uint32_t SM_EPOCH = SM_BAR + B_COUNT * 8, SM_TG = SM_EPOCH + 4  , SM_TR = 225280;

constexpr int kSpinLimit = 1 << 15;
__device__ __forceinline__ bool elect_one() {
    uint32_t p;
    asm volatile("{ .reg .pred P; elect.sync _|P, 0xffffffff; selp.u32 %0, 1, 0, P; }" : "=r"(p));
    return p;
}
__device__ __forceinline__ void mbar_init(uint32_t bar, uint32_t cnt) { asm volatile("mbarrier.init.shared::cta.b64 [%0], %1;" :: "r"(bar), "r"(cnt)); }
__device__ __forceinline__ void mbar_expect(uint32_t bar, uint32_t bytes) { asm volatile("mbarrier.arrive.expect_tx.shared::cta.b64 _, [%0], %1;" :: "r"(bar), "r"(bytes) : "memory"); }
__device__ __forceinline__ void mbar_arrive(uint32_t bar) { asm volatile("mbarrier.arrive.shared::cta.b64 _, [%0];" :: "r"(bar) : "memory"); }
__device__ __forceinline__ void mbar_wait(uint32_t bar, uint32_t parity) {
    uint32_t ok; int it = 0;
    do {
        asm volatile("{ .reg .pred p; mbarrier.try_wait.parity.shared::cta.b64 p, [%1], %2; selp.u32 %0, 1, 0, p; }"
                     : "=r"(ok) : "r"(bar), "r"(parity) : "memory");
        if (++it > kSpinLimit) { TIMEOUT((bar & 1023) >> 3); break; }
    } while (!ok);
}
__device__ __forceinline__ bool mbar_try(uint32_t bar, uint32_t parity) {
    uint32_t ok;
    asm volatile("{ .reg .pred p; mbarrier.try_wait.parity.shared::cta.b64 p, [%1], %2; selp.u32 %0, 1, 0, p; }" : "=r"(ok) : "r"(bar), "r"(parity) : "memory");
    return ok;
}
__device__ __forceinline__ bool mbar_test(uint32_t bar, uint32_t parity) {
    uint32_t ok;
    asm volatile("{ .reg .pred p; mbarrier.test_wait.parity.shared::cta.b64 p, [%1], %2; selp.u32 %0, 1, 0, p; }" : "=r"(ok) : "r"(bar), "r"(parity) : "memory");
    return ok;
}
__device__ __forceinline__ void mbar_wait2(uint32_t bar0, uint32_t par0, uint32_t bar1, uint32_t par1) {
    uint32_t ok; int it = 0;
    do {
        asm volatile("{ .reg .pred p, q; mbarrier.try_wait.parity.shared::cta.b64 p, [%1], %2;\n"
                     "mbarrier.try_wait.parity.shared::cta.b64 q, [%3], %4; and.pred p, p, q; selp.u32 %0, 1, 0, p; }"
                     : "=r"(ok) : "r"(bar0), "r"(par0), "r"(bar1), "r"(par1) : "memory");
        if (++it > kSpinLimit) { TIMEOUT((bar0 & 1023) >> 3); break; }
    } while (!ok);
}
template <int N> __device__ __forceinline__ void reg_fence(float (&d)[N]) {
    #pragma unroll
    for (int i = 0; i < N; i++) asm volatile("" : "+f"(d[i]) :: "memory");
}
__device__ __forceinline__ void mbar_wait_cluster(uint32_t bar, uint32_t parity) {
    uint32_t ok; int it = 0;
    do {
        asm volatile("{ .reg .pred p; mbarrier.try_wait.parity.acquire.cluster.shared::cta.b64 p, [%1], %2; selp.u32 %0, 1, 0, p; }"
                     : "=r"(ok) : "r"(bar), "r"(parity) : "memory");
        if (++it > kSpinLimit) { TIMEOUT((bar & 1023) >> 3); break; }
    } while (!ok);
}
__device__ __forceinline__ void mbar_arrive_if(uint32_t bar, bool pred) {
    asm volatile("{ .reg .pred p; setp.ne.u32 p, %1, 0; @p mbarrier.arrive.shared::cta.b64 _, [%0]; }" :: "r"(bar), "r"((uint32_t)pred) : "memory");
}
template <int P> __device__ __forceinline__ void tick() {
    if (P > 1) { const uint32_t t = ((uint32_t)clock() | (P - 1)) + 1; while ((int)((uint32_t)clock() - t) < 0) {} }
}
__device__ __forceinline__ void warp_arrive(uint32_t bar) { __syncwarp(); if (elect_one()) mbar_arrive(bar); }
__device__ __forceinline__ void tma2d(uint32_t dst, const CUtensorMap* m, int c0, int c1, uint32_t bar) {
    asm volatile("cp.async.bulk.tensor.2d.shared::cluster.global.mbarrier::complete_tx::bytes [%0], [%1, {%3, %4}], [%2];"
                 :: "r"(dst), "l"(m), "r"(bar), "r"(c0), "r"(c1) : "memory");
}
__device__ __forceinline__ void tma2d_mc(uint32_t dst, const CUtensorMap* m, int c0, int c1, uint32_t bar) {
    asm volatile("cp.async.bulk.tensor.2d.shared::cluster.global.mbarrier::complete_tx::bytes.multicast::cluster [%0], [%1, {%3, %4}], [%2], %5;"
                 :: "r"(dst), "l"(m), "r"(bar), "r"(c0), "r"(c1), "h"((uint16_t)3) : "memory");
}
__device__ __forceinline__ void bulk_g2s_mc(uint32_t dst, const void* src, uint32_t bytes, uint32_t bar) {
    asm volatile("cp.async.bulk.shared::cluster.global.mbarrier::complete_tx::bytes.multicast::cluster [%0], [%1], %2, [%3], %4;"
                 :: "r"(dst), "l"(src), "r"(bytes), "r"(bar), "h"((uint16_t)3) : "memory");
}
__device__ __forceinline__ void mbar_arrive_remote_if(uint32_t cluster_bar, bool pred) {
    asm volatile("{ .reg .pred p; setp.ne.u32 p, %1, 0; @p mbarrier.arrive.shared::cluster.b64 _, [%0]; }" :: "r"(cluster_bar), "r"((uint32_t)pred) : "memory");
}
__device__ __forceinline__ void bulk_g2s(uint32_t dst, const void* src, uint32_t bytes, uint32_t bar) {
    asm volatile("cp.async.bulk.shared::cluster.global.mbarrier::complete_tx::bytes [%0], [%1], %2, [%3];"
                 :: "r"(dst), "l"(src), "r"(bytes), "r"(bar) : "memory");
}
__device__ __forceinline__ void wg_fence()  { asm volatile("wgmma.fence.sync.aligned;" ::: "memory"); }
__device__ __forceinline__ void wg_commit() { asm volatile("wgmma.commit_group.sync.aligned;" ::: "memory"); }
template <int N> __device__ __forceinline__ void wg_wait() { asm volatile("wgmma.wait_group.sync.aligned %0;" :: "n"(N) : "memory"); }
__device__ __forceinline__ void named_bar(int id, int n) { asm volatile("bar.sync %0, %1;" :: "r"(id), "r"(n) : "memory"); }
__device__ __forceinline__ void named_arrive(int id, int n) { asm volatile("bar.arrive %0, %1;" :: "r"(id), "r"(n) : "memory"); }
__device__ __forceinline__ bool mbar_try2(uint32_t bar0, uint32_t par0, uint32_t bar1, uint32_t par1) {
    uint32_t ok;
    asm volatile("{ .reg .pred p, q; mbarrier.test_wait.parity.shared::cta.b64 p, [%1], %2;\n"
                 "mbarrier.test_wait.parity.shared::cta.b64 q, [%3], %4; and.pred p, p, q; selp.u32 %0, 1, 0, p; }"
                 : "=r"(ok) : "r"(bar0), "r"(par0), "r"(bar1), "r"(par1) : "memory");
    return ok;
}
__device__ __forceinline__ void fence_gpu() { asm volatile("fence.release.gpu;" ::: "memory"); }
__device__ __forceinline__ void fence_async_global() { asm volatile("fence.proxy.async.global;" ::: "memory"); }
__device__ __forceinline__ void fence_async_smem() { asm volatile("fence.proxy.async.shared::cta;" ::: "memory"); }
__device__ __forceinline__ uint32_t gtime32() { uint64_t t; asm volatile("mov.u64 %0, %%globaltimer;" : "=l"(t) :: "memory"); return (uint32_t)t; }
__device__ __forceinline__ uint32_t clk32() { uint64_t t; asm volatile("mov.u64 %0, %%clock64;" : "=l"(t) :: "memory"); return (uint32_t)t; }
__device__ __forceinline__ void spin_until(uint32_t t) { while ((int)(clk32() - t) < 0) {} }
#define SLEEPNS 20
__device__ __forceinline__ void sleep_until(uint32_t t) { while ((int)(clk32() - t) < 0) { if (SLEEPNS) __nanosleep(SLEEPNS); } }
__device__ __forceinline__ void st_flag(uint32_t* p, uint32_t v) {
    const uint64_t w = ((uint64_t)gtime32() << 32) | v;
    asm volatile("st.relaxed.gpu.global.u64 [%0], %1;" :: "l"(p), "l"(w) : "memory");
}
__device__ __forceinline__ void ld_flag_if(uint64_t& v, const uint32_t* p, bool pred) {
    asm volatile("{ .reg .pred p; setp.ne.u32 p, %2, 0; @p ld.relaxed.gpu.global.u64 %0, [%1]; }" : "+l"(v) : "l"(p), "r"((uint32_t)pred) : "memory");
}
__device__ __forceinline__ uint32_t ld_acq(const uint32_t* p) { uint32_t v; asm volatile("ld.acquire.gpu.global.u32 %0, [%1];" : "=r"(v) : "l"(p) : "memory"); return v; }
__device__ __forceinline__ uint32_t ld_rlx(const uint32_t* p) { uint32_t v; asm volatile("ld.relaxed.gpu.global.u32 %0, [%1];" : "=r"(v) : "l"(p) : "memory"); return v; }
template <class T> __device__ __forceinline__ T* opaque_ptr(T* p) { asm volatile("" : "+l"(p)); return p; }
__device__ __forceinline__ uint4 ld_rlx4(const uint4* p) {
    uint4 v; asm volatile("ld.relaxed.gpu.global.v4.u32 {%0,%1,%2,%3}, [%4];" : "=r"(v.x), "=r"(v.y), "=r"(v.z), "=r"(v.w) : "l"(p) : "memory"); return v;
}
__device__ __forceinline__ void st_ll(uint4* p, uint32_t a, uint32_t b, uint32_t tag) {
    uint64_t lo = ((uint64_t)tag << 32) | a, hi = ((uint64_t)tag << 32) | b;
    asm volatile("st.relaxed.gpu.global.v2.u64 [%0], {%1,%2};" :: "l"(p), "l"(lo), "l"(hi) : "memory");
}
__device__ __forceinline__ bool ld_ll(const uint4* p, uint32_t& a, uint32_t& b, uint32_t tag) {
    uint64_t lo, hi;
    asm volatile("ld.relaxed.gpu.global.v2.u64 {%0,%1}, [%2];" : "=l"(lo), "=l"(hi) : "l"(p) : "memory");
    a = (uint32_t)lo; b = (uint32_t)hi;
    return (uint32_t)(lo >> 32) == tag && (uint32_t)(hi >> 32) == tag;
}
__device__ __forceinline__ uint2 ld_acq2(const uint2* p) {
    uint2 v; asm volatile("ld.acquire.gpu.global.v2.u32 {%0,%1}, [%2];" : "=r"(v.x), "=r"(v.y) : "l"(p) : "memory"); return v;
}
__device__ __forceinline__ uint2 ld_rlx2(const uint2* p) {
    uint2 v; asm volatile("ld.relaxed.gpu.global.v2.u32 {%0,%1}, [%2];" : "=r"(v.x), "=r"(v.y) : "l"(p) : "memory"); return v;
}
__device__ __forceinline__ void stg1(uint32_t* p, uint32_t v) { asm volatile("st.global.u32 [%0], %1;" :: "l"(p), "r"(v) : "memory"); }
__device__ __forceinline__ void stg2(void* p, uint32_t x, uint32_t y) { asm volatile("st.global.v2.u32 [%0], {%1,%2};" :: "l"(p), "r"(x), "r"(y) : "memory"); }
__device__ __forceinline__ void stg4(void* p, uint32_t x, uint32_t y, uint32_t z, uint32_t w) { asm volatile("st.global.v4.u32 [%0], {%1,%2,%3,%4};" :: "l"(p), "r"(x), "r"(y), "r"(z), "r"(w) : "memory"); }
__device__ __forceinline__ uint32_t lds1(uint32_t a) { uint32_t v; asm volatile("ld.shared.u32 %0, [%1];" : "=r"(v) : "r"(a) : "memory"); return v; }
__device__ __forceinline__ uint2 lds2(uint32_t a) { uint2 v; asm volatile("ld.shared.v2.u32 {%0,%1}, [%2];" : "=r"(v.x), "=r"(v.y) : "r"(a) : "memory"); return v; }
__device__ __forceinline__ uint32_t set_par(uint32_t v, uint32_t mask, uint32_t par) { return (v & ~mask) | (par & mask); }
__device__ __forceinline__ float tanh_hw(float x) { float r; asm("tanh.approx.f32 %0, %1;" : "=f"(r) : "f"(x)); return r; }
__device__ __forceinline__ bool bar_any(int id, int n, bool v) {
    uint32_t r;
    asm volatile("{ .reg .pred p, q; setp.ne.u32 p, %3, 0; bar.red.or.pred q, %1, %2, p; selp.u32 %0, 1, 0, q; }" : "=r"(r) : "r"(id), "r"(n), "r"((uint32_t)v) : "memory");
    return r;
}
__device__ __forceinline__ void sts4(uint32_t a, uint32_t x, uint32_t y, uint32_t z, uint32_t w) { asm volatile("st.shared.v4.u32 [%0], {%1,%2,%3,%4};" :: "r"(a), "r"(x), "r"(y), "r"(z), "r"(w) : "memory"); }
__device__ __forceinline__ uint4 lds4(uint32_t a) { uint4 v; asm volatile("ld.shared.v4.u32 {%0,%1,%2,%3}, [%4];" : "=r"(v.x), "=r"(v.y), "=r"(v.z), "=r"(v.w) : "r"(a) : "memory"); return v; }
__device__ __forceinline__ uint32_t pack_bf16(float lo, float hi) { uint32_t r; asm("cvt.rn.bf16x2.f32 %0, %1, %2;" : "=r"(r) : "f"(hi), "f"(lo)); return r; }
__device__ __forceinline__ float bf_lo(uint32_t v) { return __uint_as_float(v << 16); }
__device__ __forceinline__ float bf_hi(uint32_t v) { return __uint_as_float(v & 0xffff0000u); }
__device__ __forceinline__ uint32_t sub_bf16x2(uint32_t a, uint32_t b) { uint32_t r; asm("sub.rn.bf16x2 %0, %1, %2;" : "=r"(r) : "r"(a), "r"(b)); return r; }
__device__ __forceinline__ uint32_t movm(uint32_t a) { uint32_t r; asm volatile("movmatrix.sync.aligned.m8n8.trans.b16 %0, %1;" : "=r"(r) : "r"(a)); return r; }
__device__ __forceinline__ float ex2(float x) { float r; asm("ex2.approx.ftz.f32 %0, %1;" : "=f"(r) : "f"(x)); return r; }
__device__ __forceinline__ float rsq(float x) { float r; asm("rsqrt.approx.ftz.f32 %0, %1;" : "=f"(r) : "f"(x)); return r; }
__device__ __forceinline__ float rcp(float x) { float r; asm("rcp.approx.ftz.f32 %0, %1;" : "=f"(r) : "f"(x)); return r; }
__device__ __forceinline__ void mma16816(float (&c)[4], uint32_t a0, uint32_t a1, uint32_t a2, uint32_t a3, uint32_t b0, uint32_t b1) {
    asm("mma.sync.aligned.m16n8k16.row.col.f32.bf16.bf16.f32 {%0,%1,%2,%3}, {%4,%5,%6,%7}, {%8,%9}, {%0,%1,%2,%3};"
        : "+f"(c[0]), "+f"(c[1]), "+f"(c[2]), "+f"(c[3]) : "r"(a0), "r"(a1), "r"(a2), "r"(a3), "r"(b0), "r"(b1));
}
__device__ __forceinline__ void mma1688(float (&c)[4], uint32_t a0, uint32_t a1, uint32_t b0) {
    asm("mma.sync.aligned.m16n8k8.row.col.f32.bf16.bf16.f32 {%0,%1,%2,%3}, {%4,%5}, {%6}, {%0,%1,%2,%3};"
        : "+f"(c[0]), "+f"(c[1]), "+f"(c[2]), "+f"(c[3]) : "r"(a0), "r"(a1), "r"(b0));
}
__device__ __forceinline__ float quad_sum(float v) { v += __shfl_xor_sync(~0u, v, 1); v += __shfl_xor_sync(~0u, v, 2); return v; }
__device__ __forceinline__ float quad_max(float v) { v = fmaxf(v, __shfl_xor_sync(~0u, v, 1)); v = fmaxf(v, __shfl_xor_sync(~0u, v, 2)); return v; }
__device__ __forceinline__ uint64_t make_desc(uint32_t addr, uint32_t lbo, bool swz) {
    const uint32_t lo = __shfl_sync(~0u, ((addr & 0x3FFFF) >> 4) | ((lbo >> 4) << 16), 0);
    const uint32_t hi = __shfl_sync(~0u, (swz ? 0x40000040u : 0x40u) + (threadIdx.x & 31), 0);
    return ((uint64_t)hi << 32) | lo;
}
template <int I, int N, class F> __device__ __forceinline__ void static_for(F&& f) {
    if constexpr (I < N) { f(std::integral_constant<int, I>{}); static_for<I + 1, N>(f); }
}
__device__ __forceinline__ uint32_t opaque(uint32_t v) { asm volatile("" : "+r"(v)); return v; }
template <int BOFF, int SCALE_D>
__device__ __forceinline__ void wgmma_rs_n56(float (&d)[28], uint32_t a0, uint32_t a1, uint32_t a2, uint32_t a3, uint64_t db) {
    asm volatile("{ .reg .b64 db; add.s64 db, %32, %33;\n"
        "wgmma.mma_async.sync.aligned.m64n56k16.f32.bf16.bf16 "
        "{%0, %1, %2, %3, %4, %5, %6, %7, %8, %9, %10, %11, %12, %13, %14, %15, %16, %17, %18, %19, %20, %21, %22, %23, %24, %25, %26, %27}, "
        "{%28, %29, %30, %31}, db, %34, 1, 1, 1; }"
        : "+f"(d[0]), "+f"(d[1]), "+f"(d[2]), "+f"(d[3]), "+f"(d[4]), "+f"(d[5]), "+f"(d[6]), "+f"(d[7]),
        "+f"(d[8]), "+f"(d[9]), "+f"(d[10]), "+f"(d[11]), "+f"(d[12]), "+f"(d[13]), "+f"(d[14]), "+f"(d[15]),
        "+f"(d[16]), "+f"(d[17]), "+f"(d[18]), "+f"(d[19]), "+f"(d[20]), "+f"(d[21]), "+f"(d[22]), "+f"(d[23]),
        "+f"(d[24]), "+f"(d[25]), "+f"(d[26]), "+f"(d[27])
        : "r"(a0), "r"(a1), "r"(a2), "r"(a3), "l"(db), "n"(BOFF >> 4), "n"(SCALE_D));
}
template <int BOFF, int SCALE_D>
__device__ __forceinline__ void wgmma_rs_n128(float (&d)[64], uint32_t a0, uint32_t a1, uint32_t a2, uint32_t a3, uint64_t db) {
    asm volatile("{ .reg .b64 db; add.s64 db, %68, %69;\n"
        "wgmma.mma_async.sync.aligned.m64n128k16.f32.bf16.bf16 "
        "{%0, %1, %2, %3, %4, %5, %6, %7, %8, %9, %10, %11, %12, %13, %14, %15, %16, %17, %18, %19, %20, %21, %22, %23, %24, %25, %26, %27, %28, %29, %30, %31, %32, %33, %34, %35, %36, %37, %38, %39, %40, %41, %42, %43, %44, %45, %46, %47, %48, %49, %50, %51, %52, %53, %54, %55, %56, %57, %58, %59, %60, %61, %62, %63}, "
        "{%64, %65, %66, %67}, db, %70, 1, 1, 1; }"
        : "+f"(d[0]), "+f"(d[1]), "+f"(d[2]), "+f"(d[3]), "+f"(d[4]), "+f"(d[5]), "+f"(d[6]), "+f"(d[7]),
        "+f"(d[8]), "+f"(d[9]), "+f"(d[10]), "+f"(d[11]), "+f"(d[12]), "+f"(d[13]), "+f"(d[14]), "+f"(d[15]),
        "+f"(d[16]), "+f"(d[17]), "+f"(d[18]), "+f"(d[19]), "+f"(d[20]), "+f"(d[21]), "+f"(d[22]), "+f"(d[23]),
        "+f"(d[24]), "+f"(d[25]), "+f"(d[26]), "+f"(d[27]), "+f"(d[28]), "+f"(d[29]), "+f"(d[30]), "+f"(d[31]),
        "+f"(d[32]), "+f"(d[33]), "+f"(d[34]), "+f"(d[35]), "+f"(d[36]), "+f"(d[37]), "+f"(d[38]), "+f"(d[39]),
        "+f"(d[40]), "+f"(d[41]), "+f"(d[42]), "+f"(d[43]), "+f"(d[44]), "+f"(d[45]), "+f"(d[46]), "+f"(d[47]),
        "+f"(d[48]), "+f"(d[49]), "+f"(d[50]), "+f"(d[51]), "+f"(d[52]), "+f"(d[53]), "+f"(d[54]), "+f"(d[55]),
        "+f"(d[56]), "+f"(d[57]), "+f"(d[58]), "+f"(d[59]), "+f"(d[60]), "+f"(d[61]), "+f"(d[62]), "+f"(d[63])
        : "r"(a0), "r"(a1), "r"(a2), "r"(a3), "l"(db), "n"(BOFF >> 4), "n"(SCALE_D));
}
template <int AOFF, int BOFF>
__device__ __forceinline__ void wgmma_ss_n112(float (&d)[56], uint64_t da, uint64_t db) {
    asm volatile("{ .reg .b64 da, db; add.s64 da, %56, %58; add.s64 db, %57, %59;\n"
        "wgmma.mma_async.sync.aligned.m64n112k16.f32.bf16.bf16 "
        "{%0, %1, %2, %3, %4, %5, %6, %7, %8, %9, %10, %11, %12, %13, %14, %15, %16, %17, %18, %19, %20, %21, %22, %23, %24, %25, %26, %27, %28, %29, %30, %31, %32, %33, %34, %35, %36, %37, %38, %39, %40, %41, %42, %43, %44, %45, %46, %47, %48, %49, %50, %51, %52, %53, %54, %55}, "
        "da, db, 1, 1, 1, 1, 1; }"
        : "+f"(d[0]), "+f"(d[1]), "+f"(d[2]), "+f"(d[3]), "+f"(d[4]), "+f"(d[5]), "+f"(d[6]), "+f"(d[7]),
        "+f"(d[8]), "+f"(d[9]), "+f"(d[10]), "+f"(d[11]), "+f"(d[12]), "+f"(d[13]), "+f"(d[14]), "+f"(d[15]),
        "+f"(d[16]), "+f"(d[17]), "+f"(d[18]), "+f"(d[19]), "+f"(d[20]), "+f"(d[21]), "+f"(d[22]), "+f"(d[23]),
        "+f"(d[24]), "+f"(d[25]), "+f"(d[26]), "+f"(d[27]), "+f"(d[28]), "+f"(d[29]), "+f"(d[30]), "+f"(d[31]),
        "+f"(d[32]), "+f"(d[33]), "+f"(d[34]), "+f"(d[35]), "+f"(d[36]), "+f"(d[37]), "+f"(d[38]), "+f"(d[39]),
        "+f"(d[40]), "+f"(d[41]), "+f"(d[42]), "+f"(d[43]), "+f"(d[44]), "+f"(d[45]), "+f"(d[46]), "+f"(d[47]),
        "+f"(d[48]), "+f"(d[49]), "+f"(d[50]), "+f"(d[51]), "+f"(d[52]), "+f"(d[53]), "+f"(d[54]), "+f"(d[55])
        : "l"(da), "l"(db), "n"(AOFF >> 4), "n"(BOFF >> 4));
}

struct Params {
    const __nv_bfloat16 *x, *wqkv, *wo, *w1, *w2, *b1, *b2;
    __nv_bfloat16* out;
};

__global__ void __cluster_dims__(2, 1, 1) __launch_bounds__(384, 1)
fused_kernel(const __grid_constant__ CUtensorMap mX, const __grid_constant__ CUtensorMap mWqkv,
             const __grid_constant__ CUtensorMap mWo, const __grid_constant__ CUtensorMap mW1,
             const __grid_constant__ CUtensorMap mW2, const Params prm)
{
    extern __shared__ __align__(1024) unsigned char smem_raw[];
    uint32_t sb = (uint32_t)__cvta_generic_to_shared(smem_raw);
    asm volatile("mov.u32 %0, %0;" : "+r"(sb));
    const uint32_t bar0 = sb + SM_BAR;
    auto BAR = [&](int i) { return bar0 + 8u * i; };

    const int tid = threadIdx.x, lane = tid & 31;
    const int warp = __shfl_sync(~0u, tid >> 5, 0);
    const int b = __shfl_sync(~0u, (int)blockIdx.x, 0);
    const int rank = b & 1;
    const int cl = (b >> 1) - 4, cq = ((cl - 32) * 37) >> 8;
    const int res = cl < 0 ? 0 : cl < 32 ? cl & 7 : cl - 31 - 7 * cq;
    const int rnd = cl < 0 ? cl + 8 : cl < 32 ? cl >> 3 : 4 + cq;
    const int hg = (res & 1) * 4 + (rnd & 3);
    const int ti = (res >> 1) * 4 + (rnd >> 2) * 2 + rank;
    const int a2p = res & 1, a2j = rnd & 3;
    const int a2s = ti * 2 + a2p;
    const bool g1_on = rnd != 7;
    const int g1j = (rnd < 6 ? rnd : res) & 1, g1f = rnd < 6 ? res * 3 + (rnd >> 1) : 24 + (res >> 1);
    const int g2j = rnd & 1, g2s = res * 4 + (rnd >> 1);
    uint32_t pbar0;
    asm volatile("mapa.shared::cluster.u32 %0, %1, %2;" : "=r"(pbar0) : "r"(bar0), "r"(rank ^ 1));
    auto pair_arrive = [&](int i) { __syncwarp(); const bool l = elect_one(); mbar_arrive_if(BAR(i), l); mbar_arrive_remote_if(pbar0 + 8u * i, l); };
    const int wcol = hg * 56 - (hg & 1) * 8;

    if (tid == 32) { TRG(60); TRW(59); }
    if (warp == 8) {
        if (elect_one()) {
            #pragma unroll
            for (int i = 0; i < B_WQF; i++) mbar_init(BAR(i), 1);
            asm volatile("fence.mbarrier_init.release.cluster;" ::: "memory");
            fence_async_smem();
            TRW(56);
            #pragma unroll 1
            for (int kb = 0; kb < 7; kb++) {
                mbar_expect(BAR(B_XF + kb), 16384);
                tma2d(sb + SM_X + kb * 8192, &mX, kb * 64, ti * 64, BAR(B_XF + kb));
                tma2d(sb + SM_X + 57344 + kb * 8192, &mX, kD + kb * 64, ti * 64, BAR(B_XF + kb));
                if (TMPF == 2 && kb == 0) asm volatile("prefetch.tensormap [%0];" :: "l"(&mWqkv) : "memory");
            }
        }
    } else if (warp > 8) {
        if (elect_one()) {
            if (warp == 9) {
                if (TMPF == 1) asm volatile("prefetch.tensormap [%0];" :: "l"(&mWqkv) : "memory");
                #pragma unroll
                for (int i = B_WQF; i < B_AF; i++) mbar_init(BAR(i), i < B_XC ? 1 : i < B_A1D ? 16 : i < B_BE ? 8 : i < B_AE ? 4 : 1);
            } else if (warp == 10) {
                #pragma unroll
                for (int i = B_AF; i < B_BL; i++) mbar_init(BAR(i), 1);
            } else {
                #pragma unroll
                for (int i = B_BL; i < B_COUNT; i++) mbar_init(BAR(i), 1);
            }
            asm volatile("fence.mbarrier_init.release.cluster;" ::: "memory");
            fence_async_smem();
        }
    } else {
        const char* p = tid < 112 ? (const char*)prm.x + (size_t)(ti * 8 + hg) * 14336 + tid * 128
                                  : (const char*)prm.wqkv + b * 2688 + 896 + (tid - 112) * 128;
        if (tid < PF0) asm volatile("prefetch.global.L2 [%0];" :: "l"(p));
    }
    __syncwarp();
    __syncthreads();
    asm volatile("barrier.cluster.arrive.relaxed.aligned;" ::: "memory");
    if (tid < 256) TR(0);
    if (tid == 0) TRG(61);

    if (warp >= 8) {
        asm volatile("setmaxnreg.dec.sync.aligned.u32 40;");
        asm volatile("barrier.cluster.wait.aligned;" ::: "memory");
        if (warp == 8) {
            if (elect_one()) {
                #pragma unroll 1
                for (int s = 0; s < 7; s++) {
                    mbar_expect(BAR(B_WKVF + s), 16384);
                    tma2d_mc(sb + SM_WKV + s * 16384 + rank * 8192, &mWqkv, (1 + rank) * kD + wcol, s * 64, BAR(B_WKVF + s));
                }
            }
            __syncwarp();
            mbar_wait(BAR(B_XC), 0);
            if (elect_one()) {
                asm volatile("prefetch.tensormap [%0];" :: "l"(&mWo) : "memory");
                asm volatile("prefetch.tensormap [%0];" :: "l"(&mW1) : "memory");
                asm volatile("prefetch.tensormap [%0];" :: "l"(&mW2) : "memory");
                mbar_expect(BAR(B_WQF), 57344);
                #pragma unroll 1
                for (int s = rank; s < 7; s += 2) tma2d_mc(sb + SM_X + s * 8192, &mWqkv, wcol, s * 64, BAR(B_WQF));
                mbar_expect(BAR(B_XRF), a2j == 3 ? 8192 : 16384);
                tma2d(sb + SM_X + 8 * 8192, &mX, a2p * kD + a2j * 128, ti * 64, BAR(B_XRF));
                if (a2j != 3) tma2d(sb + SM_X + 9 * 8192, &mX, a2p * kD + a2j * 128 + 64, ti * 64, BAR(B_XRF));
            }
            __syncwarp();
            #pragma unroll 1
            for (int h = 0; h < 2; h++) {
                mbar_wait(BAR(B_KV3 + h), 0);
                if (elect_one()) {
                    mbar_expect(BAR(B_WOF + h), a2j == 3 ? 28672 : 57344);
                    const int atom = rank ^ h;
                    if (a2j != 3 || atom == 0) tma2d_mc(sb + SM_WKV + h * 57344 + atom * 28672, &mWo, a2j * 128 + atom * 64, h * 224, BAR(B_WOF + h));
                }
                __syncwarp();
            }
            auto load_slab = [&](int s, bool second) {
                if (elect_one()) {
                    mbar_expect(BAR(B_AF + s), 8192);
                    const uint32_t dst = sb + s * 8192;
                    if (!second) tma2d(dst, &mW1, (s & 1) * kF + g1f * 64, (rank * 8 + (s >> 1)) * 64, BAR(B_AF + s));
                    else         tma2d(dst, &mW2, g2s * 64, (rank * 14 + s) * 64, BAR(B_AF + s));
                }
                __syncwarp();
            };
            if (g1_on) {
                mbar_wait(BAR(B_A1D), 0);
                #pragma unroll 1
                for (int s = 0; s < 8; s++) {
                    if (s == AEARLY) mbar_wait(BAR(B_OL), 0);
                    load_slab(s, false);
                }
            }
            mbar_wait(BAR(B_GO), 0);
            const uint32_t t0 = lds1(sb + SM_TG + 4);
            if (g1_on) {
                #pragma unroll 1
                for (int s = 8; s < 16; s++) {
                    sleep_until(t0 + W1OFF + (s - 8) * W1PACE);
                    load_slab(s, false);
                    TR2(128 + s);
                }
            }
            #pragma unroll 1
            for (int s = 0; s < 14; s++) {
                if (g1_on) mbar_wait(BAR(B_AE + s), 0);
                sleep_until(t0 + W2OFF + s * W2PACE);
                load_slab(s, true);
                TR2(144 + s);
            }
        } else if (warp == 9) {
            if (elect_one()) {
                const char* src1 = (const char*)&g_hn[rank * 16 * 3584 + g1j * 896];
                const char* src2 = (const char*)&g_g[rank * 14 * 3584 + g2j * 896];
                const long long jump = src2 - src1 - (16 * 57344 + 2 * 14336);
                const char* src = g1_on ? src1 - 2 * 57344 : src2;
                uint32_t pair = g1_on ? 2 : 0, ph = g1_on ? 0 : 1, gate = g1_on ? 0 : 2;
                CAP_DECL(ti_, 0);
                #pragma unroll 1
                for (int q = g1_on ? 0 : 17; q < 31; q++) {
                    const uint32_t dst = sb + SM_B + pair * 28672, eb = q ? BAR(B_BE) + pair * 16 : BAR(B_XF), f = BAR(B_BL) + pair * 16;
                    if ((0x1020003u >> q) & 1) {
                        mbar_wait(BAR(B_HD + gate), 0);
                        spin_until(lds1(sb + SM_TG + gate * 4));
                        gate++;
                    }
                    #pragma unroll
                    for (int h = 0; h < 2; h++) {
                        if (!mbar_try(eb + h * 8, ph)) mbar_wait(eb + h * 8, ph);
                        if (q) {
                            bulk_g2s(dst + h * 14336, src + h * 57344, 14336, f + h * 8);
                            mbar_expect(f + h * 8, 14336);
                            mbar_arrive_if(BAR(B_AE - 24 + h) + q * 16, (0x7F000u >> q) & 1);
                            CAP(ti_);
                        }
                    }
                    src += 2 * 57344 + (q == 8 ? 2 * 14336 - 16 * 57344 : q == 16 ? jump : q == 23 ? 2 * 14336 - 14 * 57344 : 0);
                    if (++pair == NB / 2) { pair = 0; ph ^= 1; }
                }
            }
        } else {
          uint32_t tag;
          if (warp == 10) {
            mbar_wait(BAR(PFBAR), 0);
            const char* p1 = (const char*)prm.w1 + (size_t)b * 57344 + lane * 128;
            const char* p2 = (const char*)prm.w2 + (size_t)b * 57344 + lane * 128;
            if (lane < 25) asm volatile("prefetch.global.L2 [%0];" :: "l"((const char*)prm.wo + min(b * 25 + lane, 3135) * 128));
            uint32_t tnext = (uint32_t)clock();
            #pragma unroll 1
            for (int i = 0; i < 28; i++) {
                asm volatile("prefetch.global.L2 [%0];" :: "l"(i < 14 ? p1 + i * 4096 : p2 + (i - 14) * 4096));
                tnext += PFPACE;
                while ((int)((uint32_t)clock() - tnext) < 0) __nanosleep(40);
            }
            mbar_wait(BAR(B_EP), 0);
            tag = lds1(sb + SM_EPOCH);
          } else {
            tag = *(volatile uint32_t*)&g_epoch + 1;
            const uint4 z4 = make_uint4(0u, 0u, 0u, 0u);
            #pragma unroll 1
            for (int i = 0; i < 14; i++) g_halo[(ti * 8 + hg) * 448 + i * 32 + lane] = z4;
            g_stats[(a2s * 4 + a2j) * 64 + lane] = z4; g_stats[(a2s * 4 + a2j) * 64 + 32 + lane] = z4;
            g_flag_h[(a2s * 4 + a2j) * FS + lane] = 0;
            #pragma unroll 1
            for (int i = 0; i < 2; i++) ((uint4*)g_flag_o)[((ti * 8 + i * 4 + (lane >> 3)) * 8 + hg) * 8 + (lane & 7)] = z4;
            __syncwarp();
            if (lane == 0) {
                asm volatile("st.shared.u32 [%0], %1;" :: "r"(sb + SM_EPOCH), "r"(tag) : "memory");
                mbar_arrive(BAR(B_EP));
            }
            if (lane < 4) mbar_expect(BAR(B_RF + lane), 7168);
            __syncwarp();
            TRW(44);
            const uint32_t* fp = &g_flag_h[(rank * 64 + lane) * FS];
            mbar_wait(BAR(B_HD), 0);
            uint64_t v0 = 0, v1 = 0;
            int it = 0;
            do {
                ld_flag_if(v0, fp, (uint32_t)v0 != tag); ld_flag_if(v1, fp + 32 * FS, (uint32_t)v1 != tag);
                if (++it > kSpinLimit) { TIMEOUT(108); break; }
            } while (__any_sync(~0u, (uint32_t)v0 != tag || (uint32_t)v1 != tag));
            const uint32_t gbase = __shfl_sync(~0u, (uint32_t)(v0 >> 32), 0);
            const uint32_t tg = gbase + DELTA + __reduce_max_sync(~0u, max((int)((uint32_t)(v0 >> 32) - gbase), (int)((uint32_t)(v1 >> 32) - gbase)));
            TRW(57);
            uint32_t late;
            it = 0;
            while ((int)(late = gtime32() - tg) < 0 && ++it < 64) {}
            const uint32_t t0 = clk32() - (it ? 0u : min(late + 16u, 4096u) * 7u / 4u);
            if (lane < (g1_on ? 1 : 3)) {
                asm volatile("st.shared.u32 [%0], %1;" :: "r"(sb + SM_TG + 4 + lane * 4), "r"(t0 + (lane == 0 ? 0 : lane == 1 ? CN2 : CN3)) : "memory");
                mbar_arrive(BAR(B_GO + lane));
            }
            __syncwarp();
            TRW(40);
          }
          const int h = warp & 1;
          const bool lead = elect_one();
          const uint32_t w2o = lane * 128 + ((lane + 16 * g2j) & 31) * 4, l3 = lane < 16 ? 12288 : 0;
          uint32_t wo = g1_on ? w2o ^ ((g1j ^ g2j) << 6) : w2o, pair = 0, ph = 0, rph = 0, af = BAR(B_AF + h), aph = 0;
          CAP_DECL(ta_, 1); CAP_DECL(tc_, 2);
          #pragma unroll 1
          for (int q = g1_on ? 1 : 17; q < 31; q++) {
              const uint32_t rb = bar0 + pair * 16 + h * 8, dst = sb + SM_B + pair * 28672 + h * 14336;
              auto stale = [&]() {
                  uint32_t d;
                  asm volatile("{ .reg .b32 x, y, z, u;\n"
                               "ld.shared.u32 x, [%1]; ld.shared.u32 y, [%1 + 4096]; ld.shared.u32 z, [%1 + 8192]; ld.shared.u32 u, [%2];\n"
                               "lop3.b32 x, x, y, %3, 0x7e; lop3.b32 z, z, u, %3, 0x7e; lop3.b32 %0, x, z, 1, 0xa8; }"
                               : "=r"(d) : "r"(dst + wo), "r"(dst + wo + l3), "r"(tag) : "memory");
                  return __any_sync(~0u, d);
              };
              mbar_wait(rb + B_BL * 8, ph);
              const bool aok = mbar_test(af, aph);
              bool bad = stale();
              if (!aok) mbar_wait(af, aph);
              mbar_arrive_if(rb + B_BF * 8, lead && !bad);
              if (bad) {
                  RETRY_COUNT(2);
                  const int e = (q > 8) + (q > 16) + (q > 23), s = (q - (e < 3 ? 1 + 8 * e : 24)) * 2 + h;
                  const char* src = (const char*)(e < 2 ? &g_hn[(rank * 16 + s) * 3584 + (g1j + 2 * e) * 896] : &g_g[(rank * 14 + s) * 3584 + (g2j + 2 * e - 4) * 896]);
                  int it = 0;
                  do {
                      if (++it > kSpinLimit) { TIMEOUT(111); break; }
                      const uint32_t* p = (const uint32_t*)(src + wo);
                      if (__any_sync(~0u, ((ld_rlx(p) ^ tag) | (ld_rlx(p + 1024) ^ tag) | (ld_rlx(p + 2048) ^ tag) | (ld_rlx(p + l3 / 4) ^ tag)) & 1)) continue;
                      if (lead) {
                          mbar_expect(BAR(B_RT + h), 14336);
                          bulk_g2s(dst, src, 14336, BAR(B_RT + h));
                      }
                      __syncwarp();
                      mbar_wait(BAR(B_RT + h), rph);
                      rph ^= 1;
                      bad = stale();
                  } while (bad);
                  mbar_arrive_if(rb + B_BF * 8, lead);
              }
              if (q == 16) { wo = w2o; aph = 1; }
              af = (0x810100u >> q) & 1 ? BAR(B_AF + h) : af + 16;
              if (++pair == NB / 2) { pair = 0; ph ^= 1; }
          }
        }
    } else {
        asm volatile("setmaxnreg.inc.sync.aligned.u32 232;");
        asm volatile("barrier.cluster.wait.aligned;" ::: "memory");
        const int wg = warp >> 2, w = warp & 3;
        const int g = lane >> 2, t = lane & 3;
        uint32_t tag;
        __nv_bfloat16 bias1;
        {
            uint32_t a[28][4];
            float sm0[4] = {0.f, 0.f, 0.f, 0.f}, sm1[4] = {0.f, 0.f, 0.f, 0.f};
            {
                const int r = w * 16 + (lane & 15);
                const uint32_t rowa = sb + SM_X + wg * 57344 + r * 128;
                #pragma unroll
                for (int kb = 0; kb < 7; kb++) {
                    mbar_wait(BAR(B_XF + kb), 0);
                    #pragma unroll
                    for (int q = 0; q < 4; q++) {
                        const uint32_t addr = rowa + kb * 8192 + (((q * 2 + (lane >> 4)) ^ (r & 7)) << 4);
                        uint32_t (&f)[4] = a[kb * 4 + q];
                        asm volatile("ldmatrix.sync.aligned.m8n8.x4.shared.b16 {%0,%1,%2,%3}, [%4];"
                                     : "=r"(f[0]), "=r"(f[1]), "=r"(f[2]), "=r"(f[3]) : "r"(addr) : "memory");
                        if (q & 1) mma16816(sm1, f[0], f[1], f[2], f[3], 0x3F803F80u, 0x3F803F80u);
                        else       mma16816(sm0, f[0], f[1], f[2], f[3], 0x3F803F80u, 0x3F803F80u);
                    }
                }
            }
            const float mean0 = (sm0[0] + sm1[0]) * (1.f / kD), mean1 = (sm0[2] + sm1[2]) * (1.f / kD);
            const uint32_t mb0 = pack_bf16(mean0, mean0), mb1 = pack_bf16(mean1, mean1);
            pair_arrive(B_XC);
            TR(1);
            float ak[28], av[28], aq[28];
            float ss0 = 0.f, ss1 = 0.f, ss2 = 0.f, ss3 = 0.f;
            const uint64_t dw = make_desc(sb + (hg & 1) * 16, 0, true);
            static_for<0, 7>([&](auto S_) {
                constexpr int s = decltype(S_)::value;
                #pragma unroll
                for (int q = 0; q < 4; q++) {
                    uint32_t (&f)[4] = a[s * 4 + q];
                    f[0] = sub_bf16x2(f[0], mb0); f[1] = sub_bf16x2(f[1], mb1);
                    f[2] = sub_bf16x2(f[2], mb0); f[3] = sub_bf16x2(f[3], mb1);
                    ss0 = fmaf(bf_lo(f[0]), bf_lo(f[0]), ss0); ss2 = fmaf(bf_hi(f[0]), bf_hi(f[0]), ss2);
                    ss1 = fmaf(bf_lo(f[1]), bf_lo(f[1]), ss1); ss3 = fmaf(bf_hi(f[1]), bf_hi(f[1]), ss3);
                    ss0 = fmaf(bf_lo(f[2]), bf_lo(f[2]), ss0); ss2 = fmaf(bf_hi(f[2]), bf_hi(f[2]), ss2);
                    ss1 = fmaf(bf_lo(f[3]), bf_lo(f[3]), ss1); ss3 = fmaf(bf_hi(f[3]), bf_hi(f[3]), ss3);
                }
                mbar_wait(BAR(B_WKVF + s), 0);
                wg_fence();
                static_for<0, 4>([&](auto Q_) {
                    constexpr int q = decltype(Q_)::value;
                    uint32_t (&f)[4] = a[s * 4 + q];
                    wgmma_rs_n56<SM_WKV + s * 16384 + q * 2048, (s | q) != 0>(ak, f[0], f[1], f[2], f[3], dw);
                    wgmma_rs_n56<SM_WKV + s * 16384 + q * 2048 + 8192, (s | q) != 0>(av, f[0], f[1], f[2], f[3], dw);
                });
                wg_commit();
                if (s == 4) { wg_wait<1>(); pair_arrive(B_KV3); }
            });
            auto q_chunk = [&](auto C_) {
                wg_fence();
                static_for<0, 7>([&](auto K_) {
                    constexpr int k = decltype(C_)::value * 7 + decltype(K_)::value;
                    wgmma_rs_n56<SM_X + k * 2048, k != 0>(aq, a[k][0], a[k][1], a[k][2], a[k][3], dw);
                });
                wg_commit();
            };
            const float dl0 = mean0 - bf_lo(mb0), dl1 = mean1 - bf_lo(mb1);
            const float rs0 = rsq(fmaxf(quad_sum(ss0 + ss2) * (1.f / kD) - dl0 * dl0, 0.f) + kEps);
            const float rs1 = rsq(fmaxf(quad_sum(ss1 + ss3) * (1.f / kD) - dl1 * dl1, 0.f) + kEps);
            mbar_wait2(BAR(B_EP), 0, BAR(B_WQF), 0);
            asm volatile("ld.shared.u32 %0, [%1];" : "=r"(tag) : "r"(sb + SM_EPOCH) : "memory");
            q_chunk(std::integral_constant<int, 0>{});
            wg_wait<1>();
            reg_fence(ak); reg_fence(av);
            TR(2);
            uint32_t kf[3][7], vf[3][7];
            #pragma unroll
            for (int c = 0; c < 7; c++) {
                kf[2][c] = pack_bf16(ak[4 * c + 2] * rs1, ak[4 * c + 3] * rs1);
                vf[2][c] = movm(pack_bf16(av[4 * c + 2] * rs1, av[4 * c + 3] * rs1));
            }
            const uint32_t stg = sb + SM_RED + (1 - wg) * 16384 + lane * 16;
            if (w == 3) {
                uint4* hp = &g_halo[((ti * 8 + hg) * 2 + wg) * 7 * 32 + lane];
                #pragma unroll
                for (int c = 0; c < 7; c++) st_ll(hp + c * 32, kf[2][c], vf[2][c], tag);
            } else {
                sts4(stg + w * 2048 + 0,    kf[2][0], kf[2][1], kf[2][2], kf[2][3]);
                sts4(stg + w * 2048 + 512,  kf[2][4], kf[2][5], kf[2][6], vf[2][0]);
                sts4(stg + w * 2048 + 1024, vf[2][1], vf[2][2], vf[2][3], vf[2][4]);
                sts4(stg + w * 2048 + 1536, vf[2][5], vf[2][6], 0u, 0u);
            }
            pair_arrive(B_KVC);
            q_chunk(std::integral_constant<int, 1>{});
            #pragma unroll
            for (int c = 0; c < 7; c++) {
                kf[1][c] = pack_bf16(ak[4 * c] * rs0, ak[4 * c + 1] * rs0);
                vf[1][c] = movm(pack_bf16(av[4 * c] * rs0, av[4 * c + 1] * rs0));
            }
            named_bar(1 + wg, 128);
            q_chunk(std::integral_constant<int, 2>{});
            q_chunk(std::integral_constant<int, 3>{});
            if (w == 0) {
                if (ti > 0) {
                    const uint4* hp = &g_halo[(((ti - 1) * 8 + hg) * 2 + wg) * 7 * 32 + lane];
                    int it = 0; bool ok;
                    do {
                        ok = true;
                        #pragma unroll
                        for (int c = 0; c < 7; c++) ok &= ld_ll(hp + c * 32, kf[0][c], vf[0][c], tag);
                        if (++it > kSpinLimit) { TIMEOUT(101); break; }
                    } while (!__all_sync(~0u, ok));
                } else {
                    #pragma unroll
                    for (int c = 0; c < 7; c++) { kf[0][c] = 0u; vf[0][c] = 0u; }
                }
            } else {
                const uint4 u0 = lds4(stg + (w - 1) * 2048), u1 = lds4(stg + (w - 1) * 2048 + 512),
                            u2 = lds4(stg + (w - 1) * 2048 + 1024), u3 = lds4(stg + (w - 1) * 2048 + 1536);
                kf[0][0] = u0.x; kf[0][1] = u0.y; kf[0][2] = u0.z; kf[0][3] = u0.w;
                kf[0][4] = u1.x; kf[0][5] = u1.y; kf[0][6] = u1.z; vf[0][0] = u1.w;
                vf[0][1] = u2.x; vf[0][2] = u2.y; vf[0][3] = u2.z; vf[0][4] = u2.w;
                vf[0][5] = u3.x; vf[0][6] = u3.y;
            }
            uint4* op = opaque_ptr(&g_o[(((ti * 2 + wg) * 4 + w) * 28 + ((7 * hg) >> 1)) * 32 + lane]);
            uint32_t* ofl = opaque_ptr(&g_flag_o[(((ti * 2 + wg) * 4 + w) * 8 + hg) * FS]);
            TR(3);
            wg_wait<0>();
            reg_fence(aq);
            warp_arrive(BAR(B_A1D));
            TR(4);
            uint32_t qf[7][2];
            #pragma unroll
            for (int c = 0; c < 7; c++) {
                qf[c][0] = pack_bf16(aq[4 * c], aq[4 * c + 1]);
                qf[c][1] = pack_bf16(aq[4 * c + 2], aq[4 * c + 3]);
            }
            const bool has_prev = (ti > 0) || (w > 0);
            const float sc0 = rs0 * (0.18898223650461362f * 1.4426950408889634f);
            const float sc1 = rs1 * (0.18898223650461362f * 1.4426950408889634f);
            const float NEG = -__int_as_float(0x7f800000);
            uint32_t ow[7][2];
            #pragma unroll
            for (int hd = 0; hd < 2; hd++) {
                const int c0 = hd * 3;
                const bool keep = hd == 0 ? (t < 2) : (t >= 2);
                const uint32_t q3a = keep ? qf[3][0] : 0u, q3b = keep ? qf[3][1] : 0u;
                float sc_[3][4];
                #pragma unroll
                for (int n = 0; n < 3; n++) {
                    sc_[n][0] = sc_[n][1] = sc_[n][2] = sc_[n][3] = 0.f;
                    if (hd == 0) {
                        mma16816(sc_[n], qf[0][0], qf[0][1], qf[1][0], qf[1][1], kf[n][0], kf[n][1]);
                        mma16816(sc_[n], qf[2][0], qf[2][1], q3a, q3b, kf[n][2], kf[n][3]);
                    } else {
                        mma16816(sc_[n], q3a, q3b, qf[4][0], qf[4][1], kf[n][3], kf[n][4]);
                        mma16816(sc_[n], qf[5][0], qf[5][1], qf[6][0], qf[6][1], kf[n][5], kf[n][6]);
                    }
                }
                const bool gt0 = 2 * t > g, gt1 = 2 * t + 1 > g;
                const float e0 = gt0 ? (has_prev ? sc_[0][0] : NEG) : sc_[1][0], e1 = gt1 ? (has_prev ? sc_[0][1] : NEG) : sc_[1][1];
                const float f0 = gt0 ? sc_[1][2] : sc_[2][2], f1 = gt1 ? sc_[1][3] : sc_[2][3];
                const float me = quad_max(fmaxf(e0, e1)) * sc0, mf = quad_max(fmaxf(f0, f1)) * sc1;
                float p0 = ex2(fmaf(e0, sc0, -me)), p1 = ex2(fmaf(e1, sc0, -me));
                float r0 = ex2(fmaf(f0, sc1, -mf)), r1 = ex2(fmaf(f1, sc1, -mf));
                const float ie = rcp(quad_sum(p0 + p1)), jf = rcp(quad_sum(r0 + r1));
                const uint32_t pp = pack_bf16(p0 * ie, p1 * ie), rp = pack_bf16(r0 * jf, r1 * jf);
                const uint32_t mk = (gt0 ? 0x0000ffffu : 0u) | (gt1 ? 0xffff0000u : 0u);
                const uint32_t sw = hg >= 4 ? ~0u : 0u;
                const uint32_t pa0 = pp & mk & ~sw, pa1 = pp & mk & sw, pb0 = rp & ~mk & sw, pb1 = rp & ~mk & ~sw;
                const uint32_t pa2 = sw ? rp & mk : pp & ~mk, pa3 = sw ? pp & ~mk : rp & mk;
                #pragma unroll
                for (int c = 0; c < 4; c++) {
                    float o[4] = {0.f, 0.f, 0.f, 0.f};
                    mma16816(o, pa0, pa1, pa2, pa3, vf[0][c0 + c], vf[1][c0 + c]);
                    mma1688(o, pb0, pb1, vf[2][c0 + c]);
                    const uint32_t lo = pack_bf16(o[0], o[1]), hi = pack_bf16(o[2], o[3]);
                    if (hd == 1 && c == 0) { if (t >= 2) { ow[3][0] = lo; ow[3][1] = hi; } }
                    else { ow[c0 + c][0] = lo; ow[c0 + c][1] = hi; }
                }
            }
            const uint32_t om = ~lane & 1;
            if (hg & 1) {
                stg2((uint2*)(op - lane) + 32 + lane, set_par(ow[0][0], om, tag), ow[0][1]);
                stg4(op + 32, set_par(ow[1][0], om, tag), ow[1][1], ow[2][0], ow[2][1]);
                stg4(op + 64, set_par(ow[3][0], om, tag), ow[3][1], ow[4][0], ow[4][1]);
                stg4(op + 96, set_par(ow[5][0], om, tag), ow[5][1], ow[6][0], ow[6][1]);
            } else {
                stg4(op,      set_par(ow[0][0], om, tag), ow[0][1], ow[1][0], ow[1][1]);
                stg4(op + 32, set_par(ow[2][0], om, tag), ow[2][1], ow[3][0], ow[3][1]);
                stg4(op + 64, set_par(ow[4][0], om, tag), ow[4][1], ow[5][0], ow[5][1]);
                stg2((uint2*)(op + 96 - lane) + lane, set_par(ow[6][0], om, tag), ow[6][1]);
            }
            if (lane == 0) asm volatile("st.relaxed.gpu.global.u32 [%0], %1;" :: "l"(ofl), "r"(tag) : "memory");
            TR(5);
        }
        {
            float acc2[64];
            const bool wide = a2j != 3;
            mbar_wait(BAR(B_XRF), 0);
            {
                const uint32_t xa = sb + SM_X + 8 * 8192 + (w * 16 + wg * 8 + (lane & 7)) * 128;
                #pragma unroll
                for (int c = 0; c < 4; c++) {
                    uint32_t xr[4];
                    asm volatile("ldmatrix.sync.aligned.m8n8.x4.shared.b16 {%0,%1,%2,%3}, [%4];"
                                 : "=r"(xr[0]), "=r"(xr[1]), "=r"(xr[2]), "=r"(xr[3])
                                 : "r"(xa + (c >> 1) * 8192 + ((((c & 1) * 4 + (lane >> 3)) ^ (lane & 7)) << 4)) : "memory");
                    #pragma unroll
                    for (int e = 0; e < 4; e++) {
                        acc2[16 * c + 4 * e] = bf_lo(xr[e]); acc2[16 * c + 4 * e + 1] = bf_hi(xr[e]);
                        acc2[16 * c + 4 * e + 2] = 0.f;      acc2[16 * c + 4 * e + 3] = 0.f;
                    }
                }
            }
            const uint4* op = &g_o[((a2s * 4 + w) * 28 + wg * 14) * 32];
            const uint32_t rsend = opaque(sb + SM_RED + (1 - wg) * 16384 + w * 4096 + lane * 16);
            const uint32_t rrecv = opaque(sb + SM_RED + wg * 16384 + w * 4096 + lane * 16);
            uint4* spw = opaque_ptr(&g_stats[(a2s * 4 + a2j) * 64 + (w * 2 + wg) * 8 + g]);
            const uint4* spr = opaque_ptr(&g_stats[(a2s * 4 + t) * 64 + (w * 2 + wg) * 8 + g]);
            uint2* hp = opaque_ptr((uint2*)g_h + ((a2s * 8 + w * 2 + wg) * 28 + a2j * 8) * 32 + lane);
            uint32_t* np = opaque_ptr((uint32_t*)&g_hn[(a2s * 56 + a2j * 16) * 64] + (w * 2 + wg) * 32 + lane);
            uint32_t* nfl = opaque_ptr(&g_flag_h[(a2s * 4 + a2j) * FS]);
            const uint64_t dwo = make_desc(sb + SM_WKV + wg * 57344, 28672, true);
            bias1 = prm.b1[g1f * 64 + w * 16 + rank * 8 + g];
            const __nv_bfloat16 bias2 = prm.b2[ti * 128 + (w * 16 + wg * 8 + g) * 2 + a2p];
            reg_fence(acc2);
            mbar_wait(BAR(B_WOF + wg), 0);
            {
                const uint32_t* pp = &g_flag_o[((a2s * 4 + w) * 8 + wg * 4 + t) * FS];
                int it = 0;
                while (__any_sync(~0u, ld_rlx(pp) != tag)) { if (++it > kSpinLimit) { TIMEOUT(102); break; } }
            }
            TR(6);
            uint4 of[14];
            auto load_o = [&](int k) {
                if (k % 7 == 3) {
                    const uint2 lo = ld_rlx2((const uint2*)(op + k * 32) + lane), hi = ld_rlx2((const uint2*)(op + k * 32) + 32 + lane);
                    of[k] = make_uint4(lo.x, lo.y, hi.x, hi.y);
                } else of[k] = ld_rlx4(op + k * 32 + lane);
            };
            #pragma unroll
            for (int k = 0; k < 14; k++) load_o(k);
            static_for<0, 4>([&](auto G_) {
                constexpr int k0 = (decltype(G_)::value * 7) / 2, k1 = (decltype(G_)::value * 7 + 7) / 2;
                int it = 0;
                while (true) {
                    uint32_t bad = 0;
                    #pragma unroll
                    for (int k = k0; k < k1; k++) bad |= (of[k].x ^ tag) | (k % 7 == 3 ? of[k].z ^ tag : 0u);
                    if (!__any_sync(~0u, bad & ~lane & 1)) break;
                    if (++it > kSpinLimit) { TIMEOUT(109); break; }
                    RETRY_COUNT(1);
                    #pragma unroll
                    for (int k = k0; k < k1; k++) load_o(k);
                }
                if (k1 == 14) warp_arrive(BAR(B_OL));
                wg_fence();
                static_for<k0, k1>([&](auto K_) { constexpr int k = decltype(K_)::value;
                    wgmma_rs_n128<k * 2048, 1>(acc2, of[k].x, of[k].y, of[k].z, of[k].w, dwo); });
            });
            wg_commit();
            wg_wait<0>();
            reg_fence(acc2);
            TR(7);
            #pragma unroll
            for (int c = 0; c < 8; c++)
                sts4(rsend + c * 512, __float_as_uint(acc2[8 * c + 2]), __float_as_uint(acc2[8 * c + 3]), __float_as_uint(acc2[8 * c + 6]), __float_as_uint(acc2[8 * c + 7]));
            named_bar(3, 256);
            float hv[32];
            float s0 = 0.f, s1 = 0.f, q0 = 0.f, q1 = 0.f;
            #pragma unroll
            for (int c = 0; c < 8; c++) {
                const uint4 u = lds4(rrecv + c * 512);
                hv[4 * c]     = acc2[8 * c] + __uint_as_float(u.x);     hv[4 * c + 1] = acc2[8 * c + 1] + __uint_as_float(u.y);
                hv[4 * c + 2] = acc2[8 * c + 4] + __uint_as_float(u.z); hv[4 * c + 3] = acc2[8 * c + 5] + __uint_as_float(u.w);
            }
            #pragma unroll
            for (int c = 0; c < 16; c += 2) { s0 += hv[c]; s1 += hv[c + 1]; q0 = fmaf(hv[c], hv[c], q0); q1 = fmaf(hv[c + 1], hv[c + 1], q1); }
            if (wide) {
                #pragma unroll
                for (int c = 16; c < 32; c += 2) { s0 += hv[c]; s1 += hv[c + 1]; q0 = fmaf(hv[c], hv[c], q0); q1 = fmaf(hv[c + 1], hv[c + 1], q1); }
            }
            s0 = quad_sum(s0 + s1); q0 = quad_sum(q0 + q1);
            if (t == 0) st_ll(spw, __float_as_uint(s0), __float_as_uint(q0), tag);
            TR(8);
            fence_async_smem();
            const float b2v = __bfloat162float(bias2);
            #pragma unroll
            for (int c = 0; c < 8; c++)
                if (c < 4 || wide) stg2(hp + c * 32, set_par(pack_bf16(hv[4 * c] + b2v, hv[4 * c + 1] + b2v), t == 0, tag), pack_bf16(hv[4 * c + 2] + b2v, hv[4 * c + 3] + b2v));
            const uint32_t nm = opaque((lane & 7) == w * 2 + wg ? 1u << (lane >> 3) : 0u);
            uint32_t um, uv;
            {
                int it = 0;
                while (!__all_sync(~0u, ld_ll(spr, um, uv, tag))) { if (++it > kSpinLimit) { TIMEOUT(103); break; } }
            }
            TR(9);
            const float mean = quad_sum(__uint_as_float(um)) * (1.f / kD);
            const float var = fmaxf(fmaf(quad_sum(__uint_as_float(uv)), 1.f / kD, -mean * mean), 0.f);
            const float r1 = rsq(var + kEps);
            const float rr = 0.5f * r1 * rsq(fmaf(var * r1, r1, kEps));
            const float mr = -mean * rr;
            #pragma unroll
            for (int c = 0; c < 16; c++)
                if (c < 8 || wide) stg1(np + c * 256, set_par(pack_bf16(fmaf(hv[2 * c], rr, mr), fmaf(hv[2 * c + 1], rr, mr)), (nm >> (c & 3)) & 1, tag));
            named_bar(3, 256);
            mbar_arrive_remote_if(pbar0 + 8u * B_PD, tid == 0);
            if (tid == 128) {
                st_flag(nfl, tag);
                asm volatile("st.shared.u32 [%0], %1;" :: "r"(sb + SM_TG), "r"(clk32()) : "memory");
                mbar_arrive(BAR(B_HD));
            }
            __syncwarp();
            TR(10);
        }
        float acc[56];
        const uint32_t xch = opaque(sb + SM_XCH + w * 1920 + lane * 16);
        uint32_t peer_xch; const uint32_t peer_bar = pbar0;
        asm volatile("mapa.shared::cluster.u32 %0, %1, %2;" : "=r"(peer_xch) : "r"(xch), "r"(rank ^ 1));
        uint2 hr[7];
        const int tok = g2s * 64 + w * 16 + rank * 8 + g, pr = (tok & 127) >> 1;
        const uint2* hp = (const uint2*)g_h + ((((tok >> 7) * 2 + (tok & 1)) * 8 + (pr >> 3)) * 28 + (g2j + 2 * wg) * 7) * 32 + (pr & 7) * 4 + t;
        auto load_h = [&]() {
            #pragma unroll
            for (int c = 0; c < 7; c++) hr[c] = ld_rlx2(hp + c * 32);
        };
        const uint32_t b1h = pack_bf16(0.5f * __bfloat162float(bias1), 0.5f * __bfloat162float(bias1));
        #pragma unroll
        for (int c = 0; c < 7; c++) hr[c] = make_uint2(b1h, b1h);
        if (!g1_on) { mbar_wait(BAR(B_GO), 0); load_h(); }
        uint32_t* const gp1 = (uint32_t*)&g_g[(g1f * 56 + (g1j + 2 * wg) * 14) * 64] + (w * 2 + rank) * 32 + lane;
        uint32_t* const gp2 = (uint32_t*)(prm.out + (size_t)(g2s * 64 + w * 16 + rank * 8 + (lane >> 4)) * kD + (g2j + 2 * wg) * 112) + (lane & 15) * 4;
        uint32_t gm[4];
        #pragma unroll
        for (int i = 0; i < 4; i++) gm[i] = lane == ((g1j * 2 + i) & 3) * 8 + w * 2 + rank;
        const bool lead = elect_one();
        const uint64_t da0 = make_desc(sb, 0, true), db0 = make_desc(sb + SM_B, 128, false);
        #pragma unroll 1
        for (int ge = g1_on ? 0 : 1; ge < 2; ge++) {
            if (ge) {
                int it = 0;
                while (true) {
                    uint32_t bad = 0;
                    #pragma unroll
                    for (int c = 0; c < 7; c++) bad |= hr[c].x ^ tag;
                    if (!__any_sync(~0u, t == 0 && (bad & 1))) break;
                    if (++it > kSpinLimit) { TIMEOUT(110); break; }
                    load_h();
                }
            }
            auto init_acc = [&](auto R_) {
                constexpr int o = decltype(R_)::value * 2;
                #pragma unroll
                for (int c = 0; c < 14; c++) {
                    const uint32_t hw = c & 1 ? hr[c >> 1].y : hr[c >> 1].x;
                    acc[4 * c + o] = bf_lo(hw); acc[4 * c + 1 + o] = bf_hi(hw);
                    acc[4 * c + 2 - o] = 0.f;   acc[4 * c + 3 - o] = 0.f;
                }
                reg_fence(acc);
            };
            if (rank) init_acc(std::integral_constant<int, 1>{}); else init_acc(std::integral_constant<int, 0>{});
            uint32_t pair = g1_on ? (wg ? 2 : ge) : wg, ph = g1_on ? ge : 0;
            uint64_t da = da0;
            uint32_t prev = BAR(B_WKVF);
            mbar_wait(BAR(B_EP), 0);
            if (wg == 1 || (ge && g1_on)) named_bar(5 - wg, 256);
            mbar_wait(BAR(B_BF) + pair * 16, ph);
            TR(11 + ge * 4);
            wg_fence();
            #pragma unroll 1
            for (int n = ge ? 7 : 8;;) {
                const uint64_t db = db0 + pair * 1792;
                const uint32_t rb = bar0 + pair * 16;
                wgmma_ss_n112<0,    0>(acc, da, db);
                wgmma_ss_n112<2048, 256>(acc, da, db);
                wgmma_ss_n112<4096, 512>(acc, da, db);
                wgmma_ss_n112<6144, 768>(acc, da, db);
                wg_commit();
                wg_wait<1>();
                mbar_arrive_if(prev, lead);
                if (!mbar_try(rb + B_BF * 8 + 8, ph)) mbar_wait(rb + B_BF * 8 + 8, ph);
                wgmma_ss_n112<8192,        14336>(acc, da, db);
                wgmma_ss_n112<8192 + 2048, 14336 + 256>(acc, da, db);
                wgmma_ss_n112<8192 + 4096, 14336 + 512>(acc, da, db);
                wgmma_ss_n112<8192 + 6144, 14336 + 768>(acc, da, db);
                wg_commit();
                if (--n == 0 && ge + wg < 2) named_arrive(4 + wg, 256);
                da += 1024; prev = rb + B_BE * 8 + 8;
                if (++pair == NB / 2) { pair = 0; ph ^= 1; }
                wg_wait<1>();
                mbar_arrive_if(rb + B_BE * 8, lead);
                if (n == 0) break;
                if (!mbar_try(BAR(B_BF) + pair * 16, ph)) mbar_wait(BAR(B_BF) + pair * 16, ph);
            }
            const int use = ge * 2 + wg;
            mbar_wait(BAR(use > (g1_on ? 0 : 2) ? B_RE + use - 1 : B_PD), 0);
            wg_wait<0>();
            reg_fence(acc);
            TR(12 + ge * 4);
            mbar_arrive_if(prev, lead);
            float v[28];
            auto reduce = [&](auto R_) {
                constexpr int o = decltype(R_)::value * 2;
                const uint32_t rf = peer_bar + (B_RF + use) * 8;
                float dly = __uint_as_float(0x3f800000u | lane); uint32_t pa = peer_xch;
                #pragma unroll
                for (int c = 0; c < 4; c++) {
                    const uint32_t p0 = pack_bf16(acc[16 * c + 2 - o], acc[16 * c + 3 - o]), p1 = pack_bf16(acc[16 * c + 6 - o], acc[16 * c + 7 - o]);
                    if (c < 3) {
                        const uint32_t p2 = pack_bf16(acc[16 * c + 10 - o], acc[16 * c + 11 - o]), p3 = pack_bf16(acc[16 * c + 14 - o], acc[16 * c + 15 - o]);
                        asm volatile("st.async.shared::cluster.mbarrier::complete_tx::bytes.v4.b32 [%0], {%1,%2,%3,%4}, [%5];"
                                     :: "r"(pa + c * 512), "r"(p0), "r"(p1), "r"(p2), "r"(p3), "r"(rf) : "memory");
                        if (use != 3) {
                            #pragma unroll
                            for (int i = 0; i < XPACE; i++) asm volatile("tanh.approx.f32 %0, %0;" : "+f"(dly) :: "memory");
                            pa += __float_as_uint(dly) >> 30;
                        }
                    } else {
                        asm volatile("st.async.shared::cluster.mbarrier::complete_tx::bytes.v2.b32 [%0], {%1,%2}, [%3];"
                                     :: "r"(pa + 1536 - lane * 8), "r"(p0), "r"(p1), "r"(rf) : "memory");
                    }
                }
                if (!ge) load_h();
                mbar_wait(BAR(B_RF + use), 0);
                #pragma unroll
                for (int c = 0; c < 4; c++) {
                    uint4 u;
                    if (c < 3) u = lds4(xch + c * 512); else { const uint2 u2 = lds2(xch + 1536 - lane * 8); u.x = u2.x; u.y = u2.y; }
                    v[8 * c]     = acc[16 * c + o] + bf_lo(u.x);     v[8 * c + 1] = acc[16 * c + 1 + o] + bf_hi(u.x);
                    v[8 * c + 2] = acc[16 * c + 4 + o] + bf_lo(u.y); v[8 * c + 3] = acc[16 * c + 5 + o] + bf_hi(u.y);
                    if (c < 3) {
                        v[8 * c + 4] = acc[16 * c + 8 + o] + bf_lo(u.z);  v[8 * c + 5] = acc[16 * c + 9 + o] + bf_hi(u.z);
                        v[8 * c + 6] = acc[16 * c + 12 + o] + bf_lo(u.w); v[8 * c + 7] = acc[16 * c + 13 + o] + bf_hi(u.w);
                    }
                }
            };
            if (rank) reduce(std::integral_constant<int, 1>{}); else reduce(std::integral_constant<int, 0>{});
            TR(13 + ge * 4);
            if (!ge) {
                #pragma unroll
                for (int c = 0; c < 14; c++) {
                    float r[2];
                    #pragma unroll
                    for (int e = 0; e < 2; e++) {
                        const float u = v[2 * c + e];
                        r[e] = fmaf(u, tanh_hw(u * fmaf(u * u, 8.f * 0.7978845608f * 0.044715f, 2.f * 0.7978845608f)), u);
                    }
                    stg1(gp1 + c * 256, set_par(pack_bf16(r[0], r[1]), gm[c & 3], tag));
                }
                named_bar(1 + wg, 128);
                if (w == 0 && lane == 0) {
                    asm volatile("st.shared.u32 [%0], %1;" :: "r"(sb + SM_TG + 8 + wg * 4), "r"(clk32() + XSPEC) : "memory");
                    mbar_arrive(BAR(B_GD + wg));
                }
                mbar_arrive_remote_if(peer_bar + (B_RE + use) * 8, lead);
            } else {
                const uint32_t stw = xch - lane * 16;
                uint32_t pk[14];
                #pragma unroll
                for (int c = 0; c < 14; c++) pk[c] = pack_bf16(v[2 * c], v[2 * c + 1]);
                __syncwarp();
                const uint32_t sa = stw + (lane & 7) * 240 + (lane >> 3) * 16;
                #pragma unroll
                for (int m = 0; m < 3; m++)
                    asm volatile("stmatrix.sync.aligned.m8n8.x4.shared.b16 [%0], {%1,%2,%3,%4};"
                                 :: "r"(sa + m * 64), "r"(pk[4 * m]), "r"(pk[4 * m + 1]), "r"(pk[4 * m + 2]), "r"(pk[4 * m + 3]) : "memory");
                asm volatile("stmatrix.sync.aligned.m8n8.x2.shared.b16 [%0], {%1,%2};" :: "r"(sa + 192), "r"(pk[12]), "r"(pk[13]) : "memory");
                __syncwarp();
                #pragma unroll
                for (int i = 0; i < 4; i++) {
                    const int r = 2 * i + (lane >> 4), ch = lane & 15;
                    if (ch < 14) { const uint4 u = lds4(stw + r * 240 + ch * 16); stg4(gp2 + i * 448, u.x, u.y, u.z, u.w); }
                }
                __syncwarp();
                mbar_arrive_remote_if(peer_bar + (B_RE + 2) * 8, lead && wg == 0);
            }
            TR(14 + ge * 4);
        }
        if (tid == 128) TRG(62);
        if (b == 0 && tid == 128) g_epoch = tag;
    }
}

typedef CUresult (*EncodeFn)(CUtensorMap*, CUtensorMapDataType, cuuint32_t, void*, const cuuint64_t*, const cuuint64_t*,
                             const cuuint32_t*, const cuuint32_t*, CUtensorMapInterleave, CUtensorMapSwizzle,
                             CUtensorMapL2promotion, CUtensorMapFloatOOBfill);

void make_map(EncodeFn enc, CUtensorMap* m, const void* base, uint64_t cols, uint64_t rows, uint32_t box_rows) {
    cuuint64_t dims[2] = {cols, rows};
    cuuint64_t strides[1] = {cols * 2};
    cuuint32_t box[2] = {64, box_rows};
    cuuint32_t es[2] = {1, 1};
    enc(m, CU_TENSOR_MAP_DATA_TYPE_BFLOAT16, 2, const_cast<void*>(base), dims, strides, box, es, CU_TENSOR_MAP_INTERLEAVE_NONE,
        CU_TENSOR_MAP_SWIZZLE_128B, CU_TENSOR_MAP_L2_PROMOTION_L2_128B, CU_TENSOR_MAP_FLOAT_OOB_FILL_NONE);
}

}

extern "C" void kernel_launch(void* const* d_in, const int* in_sizes, int n_in, void* d_out, int out_size) {
    (void)in_sizes; (void)n_in; (void)out_size;
    void* fn = nullptr;
    cudaDriverEntryPointQueryResult qr;
    cudaGetDriverEntryPoint("cuTensorMapEncodeTiled", &fn, cudaEnableDefault, &qr);
    EncodeFn enc = (EncodeFn)fn;
    CUtensorMap mX, mWqkv, mWo, mW1, mW2;
    make_map(enc, &mX, d_in[0], 2 * kD, kS / 2, 64);
    make_map(enc, &mWqkv, d_in[1], 3 * kD, kD, 64);
    make_map(enc, &mWo, d_in[2], kD, kD, 224);
    make_map(enc, &mW1, d_in[4], 2 * kF, kS / 2, 64);
    make_map(enc, &mW2, d_in[6], kS, kF, 64);
    Params prm;
    prm.x = (const __nv_bfloat16*)d_in[0];
    prm.wqkv = (const __nv_bfloat16*)d_in[1];
    prm.wo = (const __nv_bfloat16*)d_in[2];
    prm.w1 = (const __nv_bfloat16*)d_in[4];
    prm.b1 = (const __nv_bfloat16*)d_in[5];
    prm.w2 = (const __nv_bfloat16*)d_in[6];
    prm.b2 = (const __nv_bfloat16*)d_in[7];
    prm.out = (__nv_bfloat16*)d_out;
    cudaFuncSetAttribute(fused_kernel, cudaFuncAttributeMaxDynamicSharedMemorySize, SM_TOTAL);
    fused_kernel<<<128, 384, SM_TOTAL, cudaStreamPerThread>>>(mX, mWqkv, mWo, mW1, mW2, prm);
}
```

```cpp
#include <cuda_runtime.h>
#include <cuda.h>
#include <cuda_bf16.h>
#include <stdint.h>
#include <type_traits>

namespace {

constexpr int kS = 2048, kD = 448, kF = 1792;
constexpr float kEps = 1e-5f;

#define FS 32
__device__ __align__(1024) uint4    g_o[32 * 4 * 28 * 32];
__device__ __align__(1024) uint4    g_h[kS * kD * 2 / 16];
__device__ __align__(1024) uint4    g_hn[32 * 56 * 64];
__device__ __align__(1024) uint4    g_g[28 * 56 * 64];
__device__ __align__(1024) uint4    g_halo[16 * 8 * 2 * 7 * 32];
__device__ __align__(1024) uint4    g_stats[32 * 4 * 64];
__device__ __align__(1024) uint32_t g_flag_o[32 * 4 * 8 * FS];
__device__ __align__(1024) uint32_t g_flag_h[32 * 4 * FS];
__device__ uint32_t g_epoch;
#define TIMEOUT(code)
#define RETRY_COUNT(i)
#define CAP_DECL(n, k)
#define CAP(n)
#define CAP_SKIP(n)
#define TR2(idx)
#define TR(idx)
#define TRW(idx)
#define TRG(idx)

constexpr uint32_t SM_X    = 0;
constexpr uint32_t SM_WKV  = 114688;
constexpr uint32_t SM_RED  = 81920;
constexpr uint32_t SM_XCH  = 0;
constexpr uint32_t SM_B    = 131072;
constexpr uint32_t SM_BAR  = 231424;
constexpr uint32_t SM_TOTAL = SM_BAR + 1024;
constexpr int NB = 7;
#define SH1 0
#define SH2 0
#define SH2N 5
#define SH3 0
#define NSPEC 4
#define XSPEC 700
#define C2 0
#define C3 0
#define CN2 8000
#define CN3 12000
constexpr int B_XF = 0, B_WKVF = 7, B_WQF = 14, B_XRF = 15, B_WOF = 16,
              B_XC = 18, B_KV3 = 19, B_KVC = 20,
              B_A1D = 21, B_OL = 22,
              B_BE = 23, B_RE = B_BE + NB,
              B_AE = B_RE + 3, B_AF = B_AE + 14, B_BL = B_AF + 16  , B_BF = B_BL + NB  , B_RF = B_BF + NB,
              B_EP = B_RF + 4, B_PD = B_EP + 1, B_RT = B_PD + 1,
              B_HD = B_RT + 2, B_GO = B_HD + 1, B_GD = B_GO + 1, B_COUNT = B_GD + 2;
#define WEARLY 6
#define PF0 126
#define TMPF 2
#define RSTE 2
#define POLLP 1
#define PROBEP 1
#define LOADP 1
#define LOADW 64
#define NOB 0
#define AEARLY 5
#define W1PACE 400
#define W2PACE 390
#define PFPACE 330
#define PFBAR (B_XF + 6)
#define DELTA 640
#define DELTA2 DELTA
#define BPACE 230
#define BURST 2
#define W1OFF 350
#define W2OFF 5500
#define XPACE 0
#define PSTAG 200
constexpr uint32_t SM_EPOCH = SM_BAR + B_COUNT * 8, SM_TG = SM_EPOCH + 4  , SM_TR = SM_BAR + 768;

constexpr int kSpinLimit = 1 << 15;
__device__ __forceinline__ bool elect_one() {
    uint32_t p;
    asm volatile("{ .reg .pred P; elect.sync _|P, 0xffffffff; selp.u32 %0, 1, 0, P; }" : "=r"(p));
    return p;
}
__device__ __forceinline__ void mbar_init(uint32_t bar, uint32_t cnt) { asm volatile("mbarrier.init.shared::cta.b64 [%0], %1;" :: "r"(bar), "r"(cnt)); }
__device__ __forceinline__ void mbar_expect(uint32_t bar, uint32_t bytes) { asm volatile("mbarrier.arrive.expect_tx.shared::cta.b64 _, [%0], %1;" :: "r"(bar), "r"(bytes) : "memory"); }
__device__ __forceinline__ void mbar_arrive(uint32_t bar) { asm volatile("mbarrier.arrive.shared::cta.b64 _, [%0];" :: "r"(bar) : "memory"); }
__device__ __forceinline__ void mbar_wait(uint32_t bar, uint32_t parity) {
    uint32_t ok; int it = 0;
    do {
        asm volatile("{ .reg .pred p; mbarrier.try_wait.parity.shared::cta.b64 p, [%1], %2; selp.u32 %0, 1, 0, p; }"
                     : "=r"(ok) : "r"(bar), "r"(parity) : "memory");
        if (++it > kSpinLimit) { TIMEOUT((bar & 1023) >> 3); break; }
    } while (!ok);
}
__device__ __forceinline__ bool mbar_try(uint32_t bar, uint32_t parity) {
    uint32_t ok;
    asm volatile("{ .reg .pred p; mbarrier.try_wait.parity.shared::cta.b64 p, [%1], %2; selp.u32 %0, 1, 0, p; }" : "=r"(ok) : "r"(bar), "r"(parity) : "memory");
    return ok;
}
__device__ __forceinline__ bool mbar_test(uint32_t bar, uint32_t parity) {
    uint32_t ok;
    asm volatile("{ .reg .pred p; mbarrier.test_wait.parity.shared::cta.b64 p, [%1], %2; selp.u32 %0, 1, 0, p; }" : "=r"(ok) : "r"(bar), "r"(parity) : "memory");
    return ok;
}
__device__ __forceinline__ void mbar_wait2(uint32_t bar0, uint32_t par0, uint32_t bar1, uint32_t par1) {
    uint32_t ok; int it = 0;
    do {
        asm volatile("{ .reg .pred p, q; mbarrier.try_wait.parity.shared::cta.b64 p, [%1], %2;\n"
                     "mbarrier.try_wait.parity.shared::cta.b64 q, [%3], %4; and.pred p, p, q; selp.u32 %0, 1, 0, p; }"
                     : "=r"(ok) : "r"(bar0), "r"(par0), "r"(bar1), "r"(par1) : "memory");
        if (++it > kSpinLimit) { TIMEOUT((bar0 & 1023) >> 3); break; }
    } while (!ok);
}
template <int N> __device__ __forceinline__ void reg_fence(float (&d)[N]) {
    #pragma unroll
    for (int i = 0; i < N; i++) asm volatile("" : "+f"(d[i]) :: "memory");
}
__device__ __forceinline__ void mbar_wait_cluster(uint32_t bar, uint32_t parity) {
    uint32_t ok; int it = 0;
    do {
        asm volatile("{ .reg .pred p; mbarrier.try_wait.parity.acquire.cluster.shared::cta.b64 p, [%1], %2; selp.u32 %0, 1, 0, p; }"
                     : "=r"(ok) : "r"(bar), "r"(parity) : "memory");
        if (++it > kSpinLimit) { TIMEOUT((bar & 1023) >> 3); break; }
    } while (!ok);
}
__device__ __forceinline__ void mbar_arrive_if(uint32_t bar, bool pred) {
    asm volatile("{ .reg .pred p; setp.ne.u32 p, %1, 0; @p mbarrier.arrive.shared::cta.b64 _, [%0]; }" :: "r"(bar), "r"((uint32_t)pred) : "memory");
}
template <int P> __device__ __forceinline__ void tick() {
    if (P > 1) { const uint32_t t = ((uint32_t)clock() | (P - 1)) + 1; while ((int)((uint32_t)clock() - t) < 0) {} }
}
__device__ __forceinline__ void warp_arrive(uint32_t bar) { __syncwarp(); if (elect_one()) mbar_arrive(bar); }
__device__ __forceinline__ void tma2d(uint32_t dst, const CUtensorMap* m, int c0, int c1, uint32_t bar) {
    asm volatile("cp.async.bulk.tensor.2d.shared::cluster.global.mbarrier::complete_tx::bytes [%0], [%1, {%3, %4}], [%2];"
                 :: "r"(dst), "l"(m), "r"(bar), "r"(c0), "r"(c1) : "memory");
}
__device__ __forceinline__ void tma2d_mc(uint32_t dst, const CUtensorMap* m, int c0, int c1, uint32_t bar) {
    asm volatile("cp.async.bulk.tensor.2d.shared::cluster.global.mbarrier::complete_tx::bytes.multicast::cluster [%0], [%1, {%3, %4}], [%2], %5;"
                 :: "r"(dst), "l"(m), "r"(bar), "r"(c0), "r"(c1), "h"((uint16_t)3) : "memory");
}
__device__ __forceinline__ void bulk_g2s_mc(uint32_t dst, const void* src, uint32_t bytes, uint32_t bar) {
    asm volatile("cp.async.bulk.shared::cluster.global.mbarrier::complete_tx::bytes.multicast::cluster [%0], [%1], %2, [%3], %4;"
                 :: "r"(dst), "l"(src), "r"(bytes), "r"(bar), "h"((uint16_t)3) : "memory");
}
__device__ __forceinline__ void mbar_arrive_remote_if(uint32_t cluster_bar, bool pred) {
    asm volatile("{ .reg .pred p; setp.ne.u32 p, %1, 0; @p mbarrier.arrive.shared::cluster.b64 _, [%0]; }" :: "r"(cluster_bar), "r"((uint32_t)pred) : "memory");
}
__device__ __forceinline__ void bulk_g2s(uint32_t dst, const void* src, uint32_t bytes, uint32_t bar) {
    asm volatile("cp.async.bulk.shared::cluster.global.mbarrier::complete_tx::bytes [%0], [%1], %2, [%3];"
                 :: "r"(dst), "l"(src), "r"(bytes), "r"(bar) : "memory");
}
__device__ __forceinline__ void wg_fence()  { asm volatile("wgmma.fence.sync.aligned;" ::: "memory"); }
__device__ __forceinline__ void wg_commit() { asm volatile("wgmma.commit_group.sync.aligned;" ::: "memory"); }
template <int N> __device__ __forceinline__ void wg_wait() { asm volatile("wgmma.wait_group.sync.aligned %0;" :: "n"(N) : "memory"); }
__device__ __forceinline__ void named_bar(int id, int n) { asm volatile("bar.sync %0, %1;" :: "r"(id), "r"(n) : "memory"); }
__device__ __forceinline__ void named_arrive(int id, int n) { asm volatile("bar.arrive %0, %1;" :: "r"(id), "r"(n) : "memory"); }
__device__ __forceinline__ bool mbar_try2(uint32_t bar0, uint32_t par0, uint32_t bar1, uint32_t par1) {
    uint32_t ok;
    asm volatile("{ .reg .pred p, q; mbarrier.test_wait.parity.shared::cta.b64 p, [%1], %2;\n"
                 "mbarrier.test_wait.parity.shared::cta.b64 q, [%3], %4; and.pred p, p, q; selp.u32 %0, 1, 0, p; }"
                 : "=r"(ok) : "r"(bar0), "r"(par0), "r"(bar1), "r"(par1) : "memory");
    return ok;
}
__device__ __forceinline__ void fence_gpu() { asm volatile("fence.release.gpu;" ::: "memory"); }
__device__ __forceinline__ void fence_async_global() { asm volatile("fence.proxy.async.global;" ::: "memory"); }
__device__ __forceinline__ void fence_async_smem() { asm volatile("fence.proxy.async.shared::cta;" ::: "memory"); }
__device__ __forceinline__ uint32_t gtime32() { uint64_t t; asm volatile("mov.u64 %0, %%globaltimer;" : "=l"(t) :: "memory"); return (uint32_t)t; }
__device__ __forceinline__ uint32_t clk32() { uint64_t t; asm volatile("mov.u64 %0, %%clock64;" : "=l"(t) :: "memory"); return (uint32_t)t; }
__device__ __forceinline__ void spin_until(uint32_t t) { while ((int)(clk32() - t) < 0) {} }
#define SLEEPNS 20
__device__ __forceinline__ void sleep_until(uint32_t t) { while ((int)(clk32() - t) < 0) { if (SLEEPNS) __nanosleep(SLEEPNS); } }
__device__ __forceinline__ void st_flag(uint32_t* p, uint32_t v) {
    const uint64_t w = ((uint64_t)gtime32() << 32) | v;
    asm volatile("st.relaxed.gpu.global.u64 [%0], %1;" :: "l"(p), "l"(w) : "memory");
}
__device__ __forceinline__ void ld_flag_if(uint64_t& v, const uint32_t* p, bool pred) {
    asm volatile("{ .reg .pred p; setp.ne.u32 p, %2, 0; @p ld.relaxed.gpu.global.u64 %0, [%1]; }" : "+l"(v) : "l"(p), "r"((uint32_t)pred) : "memory");
}
__device__ __forceinline__ uint32_t ld_acq(const uint32_t* p) { uint32_t v; asm volatile("ld.acquire.gpu.global.u32 %0, [%1];" : "=r"(v) : "l"(p) : "memory"); return v; }
__device__ __forceinline__ uint32_t ld_rlx(const uint32_t* p) { uint32_t v; asm volatile("ld.relaxed.gpu.global.u32 %0, [%1];" : "=r"(v) : "l"(p) : "memory"); return v; }
template <class T> __device__ __forceinline__ T* opaque_ptr(T* p) { asm volatile("" : "+l"(p)); return p; }
__device__ __forceinline__ uint4 ld_rlx4(const uint4* p) {
    uint4 v; asm volatile("ld.relaxed.gpu.global.v4.u32 {%0,%1,%2,%3}, [%4];" : "=r"(v.x), "=r"(v.y), "=r"(v.z), "=r"(v.w) : "l"(p) : "memory"); return v;
}
__device__ __forceinline__ void st_ll(uint4* p, uint32_t a, uint32_t b, uint32_t tag) {
    uint64_t lo = ((uint64_t)tag << 32) | a, hi = ((uint64_t)tag << 32) | b;
    asm volatile("st.relaxed.gpu.global.v2.u64 [%0], {%1,%2};" :: "l"(p), "l"(lo), "l"(hi) : "memory");
}
__device__ __forceinline__ bool ld_ll(const uint4* p, uint32_t& a, uint32_t& b, uint32_t tag) {
    uint64_t lo, hi;
    asm volatile("ld.relaxed.gpu.global.v2.u64 {%0,%1}, [%2];" : "=l"(lo), "=l"(hi) : "l"(p) : "memory");
    a = (uint32_t)lo; b = (uint32_t)hi;
    return (uint32_t)(lo >> 32) == tag && (uint32_t)(hi >> 32) == tag;
}
__device__ __forceinline__ uint2 ld_acq2(const uint2* p) {
    uint2 v; asm volatile("ld.acquire.gpu.global.v2.u32 {%0,%1}, [%2];" : "=r"(v.x), "=r"(v.y) : "l"(p) : "memory"); return v;
}
__device__ __forceinline__ uint2 ld_rlx2(const uint2* p) {
    uint2 v; asm volatile("ld.relaxed.gpu.global.v2.u32 {%0,%1}, [%2];" : "=r"(v.x), "=r"(v.y) : "l"(p) : "memory"); return v;
}
__device__ __forceinline__ void stg1(uint32_t* p, uint32_t v) { asm volatile("st.global.u32 [%0], %1;" :: "l"(p), "r"(v) : "memory"); }
__device__ __forceinline__ void stg2(void* p, uint32_t x, uint32_t y) { asm volatile("st.global.v2.u32 [%0], {%1,%2};" :: "l"(p), "r"(x), "r"(y) : "memory"); }
__device__ __forceinline__ void stg4(void* p, uint32_t x, uint32_t y, uint32_t z, uint32_t w) { asm volatile("st.global.v4.u32 [%0], {%1,%2,%3,%4};" :: "l"(p), "r"(x), "r"(y), "r"(z), "r"(w) : "memory"); }
__device__ __forceinline__ uint32_t lds1(uint32_t a) { uint32_t v; asm volatile("ld.shared.u32 %0, [%1];" : "=r"(v) : "r"(a) : "memory"); return v; }
__device__ __forceinline__ uint2 lds2(uint32_t a) { uint2 v; asm volatile("ld.shared.v2.u32 {%0,%1}, [%2];" : "=r"(v.x), "=r"(v.y) : "r"(a) : "memory"); return v; }
__device__ __forceinline__ uint32_t set_par(uint32_t v, uint32_t mask, uint32_t par) { return (v & ~mask) | (par & mask); }
__device__ __forceinline__ float tanh_hw(float x) { float r; asm("tanh.approx.f32 %0, %1;" : "=f"(r) : "f"(x)); return r; }
__device__ __forceinline__ bool bar_any(int id, int n, bool v) {
    uint32_t r;
    asm volatile("{ .reg .pred p, q; setp.ne.u32 p, %3, 0; bar.red.or.pred q, %1, %2, p; selp.u32 %0, 1, 0, q; }" : "=r"(r) : "r"(id), "r"(n), "r"((uint32_t)v) : "memory");
    return r;
}
__device__ __forceinline__ void sts4(uint32_t a, uint32_t x, uint32_t y, uint32_t z, uint32_t w) { asm volatile("st.shared.v4.u32 [%0], {%1,%2,%3,%4};" :: "r"(a), "r"(x), "r"(y), "r"(z), "r"(w) : "memory"); }
__device__ __forceinline__ uint4 lds4(uint32_t a) { uint4 v; asm volatile("ld.shared.v4.u32 {%0,%1,%2,%3}, [%4];" : "=r"(v.x), "=r"(v.y), "=r"(v.z), "=r"(v.w) : "r"(a) : "memory"); return v; }
__device__ __forceinline__ uint32_t pack_bf16(float lo, float hi) { uint32_t r; asm("cvt.rn.bf16x2.f32 %0, %1, %2;" : "=r"(r) : "f"(hi), "f"(lo)); return r; }
__device__ __forceinline__ float bf_lo(uint32_t v) { return __uint_as_float(v << 16); }
__device__ __forceinline__ float bf_hi(uint32_t v) { return __uint_as_float(v & 0xffff0000u); }
__device__ __forceinline__ uint32_t sub_bf16x2(uint32_t a, uint32_t b) { uint32_t r; asm("sub.rn.bf16x2 %0, %1, %2;" : "=r"(r) : "r"(a), "r"(b)); return r; }
__device__ __forceinline__ uint32_t movm(uint32_t a) { uint32_t r; asm volatile("movmatrix.sync.aligned.m8n8.trans.b16 %0, %1;" : "=r"(r) : "r"(a)); return r; }
__device__ __forceinline__ float ex2(float x) { float r; asm("ex2.approx.ftz.f32 %0, %1;" : "=f"(r) : "f"(x)); return r; }
__device__ __forceinline__ float rsq(float x) { float r; asm("rsqrt.approx.ftz.f32 %0, %1;" : "=f"(r) : "f"(x)); return r; }
__device__ __forceinline__ float rcp(float x) { float r; asm("rcp.approx.ftz.f32 %0, %1;" : "=f"(r) : "f"(x)); return r; }
__device__ __forceinline__ void mma16816(float (&c)[4], uint32_t a0, uint32_t a1, uint32_t a2, uint32_t a3, uint32_t b0, uint32_t b1) {
    asm("mma.sync.aligned.m16n8k16.row.col.f32.bf16.bf16.f32 {%0,%1,%2,%3}, {%4,%5,%6,%7}, {%8,%9}, {%0,%1,%2,%3};"
        : "+f"(c[0]), "+f"(c[1]), "+f"(c[2]), "+f"(c[3]) : "r"(a0), "r"(a1), "r"(a2), "r"(a3), "r"(b0), "r"(b1));
}
__device__ __forceinline__ void mma1688(float (&c)[4], uint32_t a0, uint32_t a1, uint32_t b0) {
    asm("mma.sync.aligned.m16n8k8.row.col.f32.bf16.bf16.f32 {%0,%1,%2,%3}, {%4,%5}, {%6}, {%0,%1,%2,%3};"
        : "+f"(c[0]), "+f"(c[1]), "+f"(c[2]), "+f"(c[3]) : "r"(a0), "r"(a1), "r"(b0));
}
__device__ __forceinline__ float quad_sum(float v) { v += __shfl_xor_sync(~0u, v, 1); v += __shfl_xor_sync(~0u, v, 2); return v; }
__device__ __forceinline__ float quad_max(float v) { v = fmaxf(v, __shfl_xor_sync(~0u, v, 1)); v = fmaxf(v, __shfl_xor_sync(~0u, v, 2)); return v; }
__device__ __forceinline__ uint64_t make_desc(uint32_t addr, uint32_t lbo, bool swz) {
    const uint32_t lo = __shfl_sync(~0u, ((addr & 0x3FFFF) >> 4) | ((lbo >> 4) << 16), 0);
    const uint32_t hi = __shfl_sync(~0u, (swz ? 0x40000040u : 0x40u) + (threadIdx.x & 31), 0);
    return ((uint64_t)hi << 32) | lo;
}
template <int I, int N, class F> __device__ __forceinline__ void static_for(F&& f) {
    if constexpr (I < N) { f(std::integral_constant<int, I>{}); static_for<I + 1, N>(f); }
}
__device__ __forceinline__ uint32_t opaque(uint32_t v) { asm volatile("" : "+r"(v)); return v; }
template <int BOFF, int SCALE_D>
__device__ __forceinline__ void wgmma_rs_n56(float (&d)[28], uint32_t a0, uint32_t a1, uint32_t a2, uint32_t a3, uint64_t db) {
    asm volatile("{ .reg .b64 db; add.s64 db, %32, %33;\n"
        "wgmma.mma_async.sync.aligned.m64n56k16.f32.bf16.bf16 "
        "{%0, %1, %2, %3, %4, %5, %6, %7, %8, %9, %10, %11, %12, %13, %14, %15, %16, %17, %18, %19, %20, %21, %22, %23, %24, %25, %26, %27}, "
        "{%28, %29, %30, %31}, db, %34, 1, 1, 1; }"
        : "+f"(d[0]), "+f"(d[1]), "+f"(d[2]), "+f"(d[3]), "+f"(d[4]), "+f"(d[5]), "+f"(d[6]), "+f"(d[7]),
        "+f"(d[8]), "+f"(d[9]), "+f"(d[10]), "+f"(d[11]), "+f"(d[12]), "+f"(d[13]), "+f"(d[14]), "+f"(d[15]),
        "+f"(d[16]), "+f"(d[17]), "+f"(d[18]), "+f"(d[19]), "+f"(d[20]), "+f"(d[21]), "+f"(d[22]), "+f"(d[23]),
        "+f"(d[24]), "+f"(d[25]), "+f"(d[26]), "+f"(d[27])
        : "r"(a0), "r"(a1), "r"(a2), "r"(a3), "l"(db), "n"(BOFF >> 4), "n"(SCALE_D));
}
template <int BOFF, int SCALE_D>
__device__ __forceinline__ void wgmma_rs_n128(float (&d)[64], uint32_t a0, uint32_t a1, uint32_t a2, uint32_t a3, uint64_t db) {
    asm volatile("{ .reg .b64 db; add.s64 db, %68, %69;\n"
        "wgmma.mma_async.sync.aligned.m64n128k16.f32.bf16.bf16 "
        "{%0, %1, %2, %3, %4, %5, %6, %7, %8, %9, %10, %11, %12, %13, %14, %15, %16, %17, %18, %19, %20, %21, %22, %23, %24, %25, %26, %27, %28, %29, %30, %31, %32, %33, %34, %35, %36, %37, %38, %39, %40, %41, %42, %43, %44, %45, %46, %47, %48, %49, %50, %51, %52, %53, %54, %55, %56, %57, %58, %59, %60, %61, %62, %63}, "
        "{%64, %65, %66, %67}, db, %70, 1, 1, 1; }"
        : "+f"(d[0]), "+f"(d[1]), "+f"(d[2]), "+f"(d[3]), "+f"(d[4]), "+f"(d[5]), "+f"(d[6]), "+f"(d[7]),
        "+f"(d[8]), "+f"(d[9]), "+f"(d[10]), "+f"(d[11]), "+f"(d[12]), "+f"(d[13]), "+f"(d[14]), "+f"(d[15]),
        "+f"(d[16]), "+f"(d[17]), "+f"(d[18]), "+f"(d[19]), "+f"(d[20]), "+f"(d[21]), "+f"(d[22]), "+f"(d[23]),
        "+f"(d[24]), "+f"(d[25]), "+f"(d[26]), "+f"(d[27]), "+f"(d[28]), "+f"(d[29]), "+f"(d[30]), "+f"(d[31]),
        "+f"(d[32]), "+f"(d[33]), "+f"(d[34]), "+f"(d[35]), "+f"(d[36]), "+f"(d[37]), "+f"(d[38]), "+f"(d[39]),
        "+f"(d[40]), "+f"(d[41]), "+f"(d[42]), "+f"(d[43]), "+f"(d[44]), "+f"(d[45]), "+f"(d[46]), "+f"(d[47]),
        "+f"(d[48]), "+f"(d[49]), "+f"(d[50]), "+f"(d[51]), "+f"(d[52]), "+f"(d[53]), "+f"(d[54]), "+f"(d[55]),
        "+f"(d[56]), "+f"(d[57]), "+f"(d[58]), "+f"(d[59]), "+f"(d[60]), "+f"(d[61]), "+f"(d[62]), "+f"(d[63])
        : "r"(a0), "r"(a1), "r"(a2), "r"(a3), "l"(db), "n"(BOFF >> 4), "n"(SCALE_D));
}
template <int AOFF, int BOFF>
__device__ __forceinline__ void wgmma_ss_n112(float (&d)[56], uint64_t da, uint64_t db) {
    asm volatile("{ .reg .b64 da, db; add.s64 da, %56, %58; add.s64 db, %57, %59;\n"
        "wgmma.mma_async.sync.aligned.m64n112k16.f32.bf16.bf16 "
        "{%0, %1, %2, %3, %4, %5, %6, %7, %8, %9, %10, %11, %12, %13, %14, %15, %16, %17, %18, %19, %20, %21, %22, %23, %24, %25, %26, %27, %28, %29, %30, %31, %32, %33, %34, %35, %36, %37, %38, %39, %40, %41, %42, %43, %44, %45, %46, %47, %48, %49, %50, %51, %52, %53, %54, %55}, "
        "da, db, 1, 1, 1, 1, 1; }"
        : "+f"(d[0]), "+f"(d[1]), "+f"(d[2]), "+f"(d[3]), "+f"(d[4]), "+f"(d[5]), "+f"(d[6]), "+f"(d[7]),
        "+f"(d[8]), "+f"(d[9]), "+f"(d[10]), "+f"(d[11]), "+f"(d[12]), "+f"(d[13]), "+f"(d[14]), "+f"(d[15]),
        "+f"(d[16]), "+f"(d[17]), "+f"(d[18]), "+f"(d[19]), "+f"(d[20]), "+f"(d[21]), "+f"(d[22]), "+f"(d[23]),
        "+f"(d[24]), "+f"(d[25]), "+f"(d[26]), "+f"(d[27]), "+f"(d[28]), "+f"(d[29]), "+f"(d[30]), "+f"(d[31]),
        "+f"(d[32]), "+f"(d[33]), "+f"(d[34]), "+f"(d[35]), "+f"(d[36]), "+f"(d[37]), "+f"(d[38]), "+f"(d[39]),
        "+f"(d[40]), "+f"(d[41]), "+f"(d[42]), "+f"(d[43]), "+f"(d[44]), "+f"(d[45]), "+f"(d[46]), "+f"(d[47]),
        "+f"(d[48]), "+f"(d[49]), "+f"(d[50]), "+f"(d[51]), "+f"(d[52]), "+f"(d[53]), "+f"(d[54]), "+f"(d[55])
        : "l"(da), "l"(db), "n"(AOFF >> 4), "n"(BOFF >> 4));
}

struct Params {
    const __nv_bfloat16 *x, *wqkv, *wo, *w1, *w2, *b1, *b2;
    __nv_bfloat16* out;
};

__global__ void __cluster_dims__(2, 1, 1) __launch_bounds__(384, 1)
fused_kernel(const __grid_constant__ CUtensorMap mX, const __grid_constant__ CUtensorMap mWqkv,
             const __grid_constant__ CUtensorMap mWo, const __grid_constant__ CUtensorMap mW1,
             const __grid_constant__ CUtensorMap mW2, const Params prm)
{
    extern __shared__ __align__(1024) unsigned char smem_raw[];
    uint32_t sb = (uint32_t)__cvta_generic_to_shared(smem_raw);
    asm volatile("mov.u32 %0, %0;" : "+r"(sb));
    const uint32_t bar0 = sb + SM_BAR;
    auto BAR = [&](int i) { return bar0 + 8u * i; };

    const int tid = threadIdx.x, lane = tid & 31;
    const int warp = __shfl_sync(~0u, tid >> 5, 0);
    const int b = __shfl_sync(~0u, (int)blockIdx.x, 0);
    const int rank = b & 1;
    const int cl = (b >> 1) - 4, cq = ((cl - 32) * 37) >> 8;
    const int res = cl < 0 ? 0 : cl < 32 ? cl & 7 : cl - 31 - 7 * cq;
    const int rnd = cl < 0 ? cl + 8 : cl < 32 ? cl >> 3 : 4 + cq;
    const int hg = (res & 1) * 4 + (rnd & 3);
    const int ti = (res >> 1) * 4 + (rnd >> 2) * 2 + rank;
    const int a2p = res & 1, a2j = rnd & 3;
    const int a2s = ti * 2 + a2p;
    const bool g1_on = rnd != 7;
    const int g1j = (rnd < 6 ? rnd : res) & 1, g1f = rnd < 6 ? res * 3 + (rnd >> 1) : 24 + (res >> 1);
    const int g2j = rnd & 1, g2s = res * 4 + (rnd >> 1);
    uint32_t pbar0;
    asm volatile("mapa.shared::cluster.u32 %0, %1, %2;" : "=r"(pbar0) : "r"(bar0), "r"(rank ^ 1));
    auto pair_arrive = [&](int i) { __syncwarp(); const bool l = elect_one(); mbar_arrive_if(BAR(i), l); mbar_arrive_remote_if(pbar0 + 8u * i, l); };
    const int wcol = hg * 56 - (hg & 1) * 8;

    if (tid == 32) { TRG(60); TRW(59); }
    if (warp == 8) {
        if (elect_one()) {
            #pragma unroll
            for (int i = 0; i < B_WQF; i++) mbar_init(BAR(i), 1);
            asm volatile("fence.mbarrier_init.release.cluster;" ::: "memory");
            fence_async_smem();
            TRW(56);
            #pragma unroll 1
            for (int kb = 0; kb < 7; kb++) {
                mbar_expect(BAR(B_XF + kb), 16384);
                tma2d(sb + SM_X + kb * 8192, &mX, kb * 64, ti * 64, BAR(B_XF + kb));
                tma2d(sb + SM_X + 57344 + kb * 8192, &mX, kD + kb * 64, ti * 64, BAR(B_XF + kb));
                if (TMPF == 2 && kb == 0) asm volatile("prefetch.tensormap [%0];" :: "l"(&mWqkv) : "memory");
            }
        }
    } else if (warp > 8) {
        if (elect_one()) {
            if (warp == 9) {
                if (TMPF == 1) asm volatile("prefetch.tensormap [%0];" :: "l"(&mWqkv) : "memory");
                #pragma unroll
                for (int i = B_WQF; i < B_AF; i++) mbar_init(BAR(i), i < B_XC ? 1 : i < B_A1D ? 16 : i < B_BE ? 8 : i < B_AE ? 4 : 1);
            } else if (warp == 10) {
                #pragma unroll
                for (int i = B_AF; i < B_BL; i++) mbar_init(BAR(i), 1);
            } else {
                #pragma unroll
                for (int i = B_BL; i < B_COUNT; i++) mbar_init(BAR(i), 1);
            }
            asm volatile("fence.mbarrier_init.release.cluster;" ::: "memory");
            fence_async_smem();
        }
    } else {
        const char* p = tid < 112 ? (const char*)prm.x + (size_t)(ti * 8 + hg) * 14336 + tid * 128
                                  : (const char*)prm.wqkv + b * 2688 + 896 + (tid - 112) * 128;
        if (tid < PF0) asm volatile("prefetch.global.L2 [%0];" :: "l"(p));
    }
    __syncwarp();
    __syncthreads();
    asm volatile("barrier.cluster.arrive.relaxed.aligned;" ::: "memory");
    if (tid < 256) TR(0);
    if (tid == 0) TRG(61);

    if (warp >= 8) {
        asm volatile("setmaxnreg.dec.sync.aligned.u32 40;");
        asm volatile("barrier.cluster.wait.aligned;" ::: "memory");
        if (warp == 8) {
            if (elect_one()) {
                #pragma unroll 1
                for (int s = 0; s < 7; s++) {
                    mbar_expect(BAR(B_WKVF + s), 16384);
                    tma2d_mc(sb + SM_WKV + s * 16384 + rank * 8192, &mWqkv, (1 + rank) * kD + wcol, s * 64, BAR(B_WKVF + s));
                }
            }
            __syncwarp();
            mbar_wait(BAR(B_XC), 0);
            if (elect_one()) {
                asm volatile("prefetch.tensormap [%0];" :: "l"(&mWo) : "memory");
                asm volatile("prefetch.tensormap [%0];" :: "l"(&mW1) : "memory");
                asm volatile("prefetch.tensormap [%0];" :: "l"(&mW2) : "memory");
                mbar_expect(BAR(B_WQF), 57344);
                #pragma unroll 1
                for (int s = rank; s < 7; s += 2) tma2d_mc(sb + SM_X + s * 8192, &mWqkv, wcol, s * 64, BAR(B_WQF));
                mbar_expect(BAR(B_XRF), a2j == 3 ? 8192 : 16384);
                tma2d(sb + SM_X + 8 * 8192, &mX, a2p * kD + a2j * 128, ti * 64, BAR(B_XRF));
                if (a2j != 3) tma2d(sb + SM_X + 9 * 8192, &mX, a2p * kD + a2j * 128 + 64, ti * 64, BAR(B_XRF));
            }
            __syncwarp();
            #pragma unroll 1
            for (int h = 0; h < 2; h++) {
                mbar_wait(BAR(B_KV3 + h), 0);
                if (elect_one()) {
                    mbar_expect(BAR(B_WOF + h), a2j == 3 ? 28672 : 57344);
                    const int atom = rank ^ h;
                    if (a2j != 3 || atom == 0) tma2d_mc(sb + SM_WKV + h * 57344 + atom * 28672, &mWo, a2j * 128 + atom * 64, h * 224, BAR(B_WOF + h));
                }
                __syncwarp();
            }
            auto load_slab = [&](int s, bool second) {
                if (elect_one()) {
                    mbar_expect(BAR(B_AF + s), 8192);
                    if (!second) tma2d(sb + s * 8192, &mW1, (s & 1) * kF + g1f * 64, (rank * 8 + (s >> 1)) * 64, BAR(B_AF + s));
                    else         tma2d(sb + s * 8192, &mW2, g2s * 64, (rank * 14 + s - 2) * 64, BAR(B_AF + s));
                }
                __syncwarp();
            };
            if (g1_on) {
                mbar_wait(BAR(B_A1D), 0);
                #pragma unroll 1
                for (int s = 0; s < 8; s++) {
                    if (s == AEARLY) mbar_wait(BAR(B_OL), 0);
                    load_slab(s, false);
                }
            }
            mbar_wait(BAR(B_GO), 0);
            const uint32_t tg = lds1(sb + SM_TG + 4);
            uint32_t late; int it = 0;
            while ((int)(late = gtime32() - tg) < 0 && ++it < 64) {}
            const uint32_t t0 = clk32() - (it ? 0u : min(late + 16u, 4096u) * 7u / 4u);
            if (!g1_on && lane < 2) {
                asm volatile("st.shared.u32 [%0], %1;" :: "r"(sb + SM_TG + 8 + lane * 4), "r"(t0 + (lane ? CN3 : CN2)) : "memory");
                mbar_arrive(BAR(B_GD + lane));
            }
            __syncwarp();
            if (g1_on) {
                #pragma unroll 1
                for (int s = 8; s < 16; s++) {
                    sleep_until(t0 + W1OFF + (s - 8) * W1PACE);
                    load_slab(s, false);
                    TR2(128 + s);
                }
            }
            #pragma unroll 1
            for (int s = 0; s < 14; s++) {
                if (g1_on) mbar_wait(BAR(B_AE + s), 0);
                sleep_until(t0 + W2OFF + s * W2PACE);
                load_slab(s + 2, true);
                TR2(144 + s);
            }
        } else if (warp == 9) {
            if (elect_one()) {
                const char* src1 = (const char*)&g_hn[rank * 16 * 3584 + g1j * 896];
                const char* src2 = (const char*)&g_g[rank * 14 * 3584 + g2j * 896];
                const long long jump = src2 - src1 - (16 * 57344 + 2 * 14336);
                const char* src = g1_on ? src1 - 2 * 57344 : src2;
                uint32_t slot = g1_on ? NB - 2 : 0, ph = g1_on ? 0 : 1, gate = g1_on ? 0 : 2;
                CAP_DECL(ti_, 0);
                #pragma unroll 1
                for (int q = g1_on ? 0 : 17; q < 31; q++) {
                    if ((0x1020003u >> q) & 1) {
                        mbar_wait(BAR(B_HD + gate), 0);
                        const uint32_t tg = lds1(sb + SM_TG + gate * 4);
                        int it = 0;
                        if (gate < 2) while ((int)(gtime32() - tg) < 0 && ++it < 64) {}
                        else spin_until(tg);
                        gate++;
                    }
                    #pragma unroll
                    for (int h = 0; h < 2; h++) {
                        const uint32_t eb = q ? BAR(B_BE) + slot * 8 : BAR(B_XF);
                        if (!mbar_try(eb, ph)) mbar_wait(eb, ph);
                        if (q) {
                            bulk_g2s(sb + SM_B + slot * 14336, src + h * 57344, 14336, eb + (B_BL - B_BE) * 8);
                            mbar_expect(eb + (B_BL - B_BE) * 8, 14336);
                            mbar_arrive_if(BAR(B_AE - 27 + h) + q * 16, ((h ? 0xFE000u : 0x1FC000u) >> q) & 1);
                            if (h) mbar_arrive_remote_if(pbar0 + 8u * B_PD, q == 12);
                            CAP(ti_);
                        }
                        if (++slot == NB) { slot = 0; ph ^= 1; }
                    }
                    src += 2 * 57344 + (q == 8 ? 2 * 14336 - 16 * 57344 : q == 16 ? jump : q == 23 ? 2 * 14336 - 14 * 57344 : 0);
                }
            }
        } else {
          uint32_t tag;
          if (warp == 10) {
            mbar_wait(BAR(PFBAR), 0);
            const char* p1 = (const char*)prm.w1 + (size_t)b * 57344 + lane * 128;
            const char* p2 = (const char*)prm.w2 + (size_t)b * 57344 + lane * 128;
            if (lane < 25) asm volatile("prefetch.global.L2 [%0];" :: "l"((const char*)prm.wo + min(b * 25 + lane, 3135) * 128));
            uint32_t tnext = (uint32_t)clock();
            #pragma unroll 1
            for (int i = 0; i < 28; i++) {
                asm volatile("prefetch.global.L2 [%0];" :: "l"(i < 14 ? p1 + i * 4096 : p2 + (i - 14) * 4096));
                tnext += PFPACE;
                while ((int)((uint32_t)clock() - tnext) < 0) __nanosleep(40);
            }
            mbar_wait(BAR(B_EP), 0);
            tag = lds1(sb + SM_EPOCH);
          } else {
            tag = *(volatile uint32_t*)&g_epoch + 1;
            const uint4 z4 = make_uint4(0u, 0u, 0u, 0u);
            #pragma unroll 1
            for (int i = 0; i < 14; i++) g_halo[(ti * 8 + hg) * 448 + i * 32 + lane] = z4;
            g_stats[(a2s * 4 + a2j) * 64 + lane] = z4; g_stats[(a2s * 4 + a2j) * 64 + 32 + lane] = z4;
            g_flag_h[(a2s * 4 + a2j) * FS + lane] = 0;
            #pragma unroll 1
            for (int i = 0; i < 2; i++) ((uint4*)g_flag_o)[((ti * 8 + i * 4 + (lane >> 3)) * 8 + hg) * 8 + (lane & 7)] = z4;
            __syncwarp();
            if (lane == 0) {
                asm volatile("st.shared.u32 [%0], %1;" :: "r"(sb + SM_EPOCH), "r"(tag) : "memory");
                mbar_arrive(BAR(B_EP));
            }
            if (lane < 4) mbar_expect(BAR(B_RF + lane), 7168);
            __syncwarp();
            TRW(44);
            const uint32_t* fp = &g_flag_h[(rank * 64 + lane) * FS];
            mbar_wait(BAR(B_HD), 0);
            uint64_t v0 = 0, v1 = 0;
            int it = 0;
            do {
                ld_flag_if(v0, fp, (uint32_t)v0 != tag); ld_flag_if(v1, fp + 32 * FS, (uint32_t)v1 != tag);
                if (++it > kSpinLimit) { TIMEOUT(108); break; }
            } while (__any_sync(~0u, (uint32_t)v0 != tag || (uint32_t)v1 != tag));
            const uint32_t gbase = __shfl_sync(~0u, (uint32_t)(v0 >> 32), 0);
            const uint32_t tg = gbase + DELTA + __reduce_max_sync(~0u, max((int)((uint32_t)(v0 >> 32) - gbase), (int)((uint32_t)(v1 >> 32) - gbase)));
            if (lane == 0) {
                asm volatile("st.shared.u32 [%0], %1;" :: "r"(sb + SM_TG + 4), "r"(tg) : "memory");
                mbar_arrive(BAR(B_GO));
            }
            __syncwarp();
            TRW(40);
          }
          const int h = warp & 1;
          const bool lead = elect_one();
          const uint32_t w2o = lane * 128 + ((lane + 16 * g2j) & 31) * 4, l3 = lane < 16 ? 12288 : 0;
          uint32_t wo = g1_on ? w2o ^ ((g1j ^ g2j) << 6) : w2o, slot = h, ph = 0, rph = 0, af = BAR(B_AF + h + (g1_on ? 0 : 2)), aph = 0;
          #pragma unroll 1
          for (int q = g1_on ? 1 : 17; q < 31; q++) {
              const uint32_t rb = bar0 + slot * 8, dst = sb + SM_B + slot * 14336;
              auto stale = [&]() {
                  uint32_t d;
                  asm volatile("{ .reg .b32 x, y, z, u;\n"
                               "ld.shared.u32 x, [%1]; ld.shared.u32 y, [%1 + 4096]; ld.shared.u32 z, [%1 + 8192]; ld.shared.u32 u, [%2];\n"
                               "lop3.b32 x, x, y, %3, 0x7e; lop3.b32 z, z, u, %3, 0x7e; lop3.b32 %0, x, z, 1, 0xa8; }"
                               : "=r"(d) : "r"(dst + wo), "r"(dst + wo + l3), "r"(tag) : "memory");
                  return __any_sync(~0u, d);
              };
              mbar_wait(rb + B_BL * 8, ph);
              const bool aok = mbar_test(af, aph);
              bool bad = stale();
              if (!aok) mbar_wait(af, aph);
              mbar_arrive_if(rb + B_BF * 8, lead && !bad);
              if (bad) {
                  RETRY_COUNT(2);
                  const int e = (q > 8) + (q > 16) + (q > 23), s = (q - (e < 3 ? 1 + 8 * e : 24)) * 2 + h;
                  const char* src = (const char*)(e < 2 ? &g_hn[(rank * 16 + s) * 3584 + (g1j + 2 * e) * 896] : &g_g[(rank * 14 + s) * 3584 + (g2j + 2 * e - 4) * 896]);
                  int it = 0;
                  do {
                      if (++it > kSpinLimit) { TIMEOUT(111); break; }
                      const uint32_t* p = (const uint32_t*)(src + wo);
                      if (__any_sync(~0u, ((ld_rlx(p) ^ tag) | (ld_rlx(p + 1024) ^ tag) | (ld_rlx(p + 2048) ^ tag) | (ld_rlx(p + l3 / 4) ^ tag)) & 1)) continue;
                      if (lead) {
                          mbar_expect(BAR(B_RT + h), 14336);
                          bulk_g2s(dst, src, 14336, BAR(B_RT + h));
                      }
                      __syncwarp();
                      mbar_wait(BAR(B_RT + h), rph);
                      rph ^= 1;
                      bad = stale();
                  } while (bad);
                  mbar_arrive_if(rb + B_BF * 8, lead);
              }
              if (q == 16) { wo = w2o; aph = 1; }
              af += q == 8 ? -112 : (0x810000u >> q) & 1 ? -96 : 16;
              slot += 2;
              if (slot >= NB) { slot -= NB; ph ^= 1; }
          }
        }
    } else {
        asm volatile("setmaxnreg.inc.sync.aligned.u32 232;");
        asm volatile("barrier.cluster.wait.aligned;" ::: "memory");
        const int wg = warp >> 2, w = warp & 3;
        const int g = lane >> 2, t = lane & 3;
        uint32_t tag;
        __nv_bfloat16 bias1;
        {
            uint32_t a[28][4];
            float sm0[4] = {0.f, 0.f, 0.f, 0.f}, sm1[4] = {0.f, 0.f, 0.f, 0.f};
            {
                const int r = w * 16 + (lane & 15);
                const uint32_t rowa = sb + SM_X + wg * 57344 + r * 128;
                #pragma unroll
                for (int kb = 0; kb < 7; kb++) {
                    mbar_wait(BAR(B_XF + kb), 0);
                    #pragma unroll
                    for (int q = 0; q < 4; q++) {
                        const uint32_t addr = rowa + kb * 8192 + (((q * 2 + (lane >> 4)) ^ (r & 7)) << 4);
                        uint32_t (&f)[4] = a[kb * 4 + q];
                        asm volatile("ldmatrix.sync.aligned.m8n8.x4.shared.b16 {%0,%1,%2,%3}, [%4];"
                                     : "=r"(f[0]), "=r"(f[1]), "=r"(f[2]), "=r"(f[3]) : "r"(addr) : "memory");
                        if (q & 1) mma16816(sm1, f[0], f[1], f[2], f[3], 0x3F803F80u, 0x3F803F80u);
                        else       mma16816(sm0, f[0], f[1], f[2], f[3], 0x3F803F80u, 0x3F803F80u);
                    }
                }
            }
            const float mean0 = (sm0[0] + sm1[0]) * (1.f / kD), mean1 = (sm0[2] + sm1[2]) * (1.f / kD);
            const uint32_t mb0 = pack_bf16(mean0, mean0), mb1 = pack_bf16(mean1, mean1);
            pair_arrive(B_XC);
            TR(1);
            float ak[28], av[28], aq[28];
            float ss0 = 0.f, ss1 = 0.f, ss2 = 0.f, ss3 = 0.f;
            const uint64_t dw = make_desc(sb + (hg & 1) * 16, 0, true);
            static_for<0, 7>([&](auto S_) {
                constexpr int s = decltype(S_)::value;
                #pragma unroll
                for (int q = 0; q < 4; q++) {
                    uint32_t (&f)[4] = a[s * 4 + q];
                    f[0] = sub_bf16x2(f[0], mb0); f[1] = sub_bf16x2(f[1], mb1);
                    f[2] = sub_bf16x2(f[2], mb0); f[3] = sub_bf16x2(f[3], mb1);
                    ss0 = fmaf(bf_lo(f[0]), bf_lo(f[0]), ss0); ss2 = fmaf(bf_hi(f[0]), bf_hi(f[0]), ss2);
                    ss1 = fmaf(bf_lo(f[1]), bf_lo(f[1]), ss1); ss3 = fmaf(bf_hi(f[1]), bf_hi(f[1]), ss3);
                    ss0 = fmaf(bf_lo(f[2]), bf_lo(f[2]), ss0); ss2 = fmaf(bf_hi(f[2]), bf_hi(f[2]), ss2);
                    ss1 = fmaf(bf_lo(f[3]), bf_lo(f[3]), ss1); ss3 = fmaf(bf_hi(f[3]), bf_hi(f[3]), ss3);
                }
                mbar_wait(BAR(B_WKVF + s), 0);
                wg_fence();
                static_for<0, 4>([&](auto Q_) {
                    constexpr int q = decltype(Q_)::value;
                    uint32_t (&f)[4] = a[s * 4 + q];
                    wgmma_rs_n56<SM_WKV + s * 16384 + q * 2048, (s | q) != 0>(ak, f[0], f[1], f[2], f[3], dw);
                    wgmma_rs_n56<SM_WKV + s * 16384 + q * 2048 + 8192, (s | q) != 0>(av, f[0], f[1], f[2], f[3], dw);
                });
                wg_commit();
                if (s == 4) { wg_wait<1>(); pair_arrive(B_KV3); }
            });
            auto q_chunk = [&](auto C_) {
                wg_fence();
                static_for<0, 7>([&](auto K_) {
                    constexpr int k = decltype(C_)::value * 7 + decltype(K_)::value;
                    wgmma_rs_n56<SM_X + k * 2048, k != 0>(aq, a[k][0], a[k][1], a[k][2], a[k][3], dw);
                });
                wg_commit();
            };
            const float dl0 = mean0 - bf_lo(mb0), dl1 = mean1 - bf_lo(mb1);
            const float rs0 = rsq(fmaxf(quad_sum(ss0 + ss2) * (1.f / kD) - dl0 * dl0, 0.f) + kEps);
            const float rs1 = rsq(fmaxf(quad_sum(ss1 + ss3) * (1.f / kD) - dl1 * dl1, 0.f) + kEps);
            mbar_wait2(BAR(B_EP), 0, BAR(B_WQF), 0);
            asm volatile("ld.shared.u32 %0, [%1];" : "=r"(tag) : "r"(sb + SM_EPOCH) : "memory");
            q_chunk(std::integral_constant<int, 0>{});
            wg_wait<1>();
            reg_fence(ak); reg_fence(av);
            TR(2);
            uint32_t kf[3][7], vf[3][7];
            #pragma unroll
            for (int c = 0; c < 7; c++) {
                kf[2][c] = pack_bf16(ak[4 * c + 2] * rs1, ak[4 * c + 3] * rs1);
                vf[2][c] = movm(pack_bf16(av[4 * c + 2] * rs1, av[4 * c + 3] * rs1));
            }
            const uint32_t stg = sb + SM_RED + (1 - wg) * 16384 + lane * 16;
            if (w == 3) {
                uint4* hp = &g_halo[((ti * 8 + hg) * 2 + wg) * 7 * 32 + lane];
                #pragma unroll
                for (int c = 0; c < 7; c++) st_ll(hp + c * 32, kf[2][c], vf[2][c], tag);
            } else {
                sts4(stg + w * 2048 + 0,    kf[2][0], kf[2][1], kf[2][2], kf[2][3]);
                sts4(stg + w * 2048 + 512,  kf[2][4], kf[2][5], kf[2][6], vf[2][0]);
                sts4(stg + w * 2048 + 1024, vf[2][1], vf[2][2], vf[2][3], vf[2][4]);
                sts4(stg + w * 2048 + 1536, vf[2][5], vf[2][6], 0u, 0u);
            }
            pair_arrive(B_KVC);
            q_chunk(std::integral_constant<int, 1>{});
            #pragma unroll
            for (int c = 0; c < 7; c++) {
                kf[1][c] = pack_bf16(ak[4 * c] * rs0, ak[4 * c + 1] * rs0);
                vf[1][c] = movm(pack_bf16(av[4 * c] * rs0, av[4 * c + 1] * rs0));
            }
            named_bar(1 + wg, 128);
            q_chunk(std::integral_constant<int, 2>{});
            q_chunk(std::integral_constant<int, 3>{});
            if (w == 0) {
                if (ti > 0) {
                    const uint4* hp = &g_halo[(((ti - 1) * 8 + hg) * 2 + wg) * 7 * 32 + lane];
                    int it = 0; bool ok;
                    do {
                        ok = true;
                        #pragma unroll
                        for (int c = 0; c < 7; c++) ok &= ld_ll(hp + c * 32, kf[0][c], vf[0][c], tag);
                        if (++it > kSpinLimit) { TIMEOUT(101); break; }
                    } while (!__all_sync(~0u, ok));
                } else {
                    #pragma unroll
                    for (int c = 0; c < 7; c++) { kf[0][c] = 0u; vf[0][c] = 0u; }
                }
            } else {
                const uint4 u0 = lds4(stg + (w - 1) * 2048), u1 = lds4(stg + (w - 1) * 2048 + 512),
                            u2 = lds4(stg + (w - 1) * 2048 + 1024), u3 = lds4(stg + (w - 1) * 2048 + 1536);
                kf[0][0] = u0.x; kf[0][1] = u0.y; kf[0][2] = u0.z; kf[0][3] = u0.w;
                kf[0][4] = u1.x; kf[0][5] = u1.y; kf[0][6] = u1.z; vf[0][0] = u1.w;
                vf[0][1] = u2.x; vf[0][2] = u2.y; vf[0][3] = u2.z; vf[0][4] = u2.w;
                vf[0][5] = u3.x; vf[0][6] = u3.y;
            }
            uint4* op = opaque_ptr(&g_o[(((ti * 2 + wg) * 4 + w) * 28 + ((7 * hg) >> 1)) * 32 + lane]);
            uint32_t* ofl = opaque_ptr(&g_flag_o[(((ti * 2 + wg) * 4 + w) * 8 + hg) * FS]);
            TR(3);
            wg_wait<0>();
            reg_fence(aq);
            warp_arrive(BAR(B_A1D));
            TR(4);
            uint32_t qf[7][2];
            #pragma unroll
            for (int c = 0; c < 7; c++) {
                qf[c][0] = pack_bf16(aq[4 * c], aq[4 * c + 1]);
                qf[c][1] = pack_bf16(aq[4 * c + 2], aq[4 * c + 3]);
            }
            const bool has_prev = (ti > 0) || (w > 0);
            const float sc0 = rs0 * (0.18898223650461362f * 1.4426950408889634f);
            const float sc1 = rs1 * (0.18898223650461362f * 1.4426950408889634f);
            const float NEG = -__int_as_float(0x7f800000);
            uint32_t ow[7][2];
            #pragma unroll
            for (int hd = 0; hd < 2; hd++) {
                const int c0 = hd * 3;
                const bool keep = hd == 0 ? (t < 2) : (t >= 2);
                const uint32_t q3a = keep ? qf[3][0] : 0u, q3b = keep ? qf[3][1] : 0u;
                float sc_[3][4];
                #pragma unroll
                for (int n = 0; n < 3; n++) {
                    sc_[n][0] = sc_[n][1] = sc_[n][2] = sc_[n][3] = 0.f;
                    if (hd == 0) {
                        mma16816(sc_[n], qf[0][0], qf[0][1], qf[1][0], qf[1][1], kf[n][0], kf[n][1]);
                        mma16816(sc_[n], qf[2][0], qf[2][1], q3a, q3b, kf[n][2], kf[n][3]);
                    } else {
                        mma16816(sc_[n], q3a, q3b, qf[4][0], qf[4][1], kf[n][3], kf[n][4]);
                        mma16816(sc_[n], qf[5][0], qf[5][1], qf[6][0], qf[6][1], kf[n][5], kf[n][6]);
                    }
                }
                const bool gt0 = 2 * t > g, gt1 = 2 * t + 1 > g;
                const float e0 = gt0 ? (has_prev ? sc_[0][0] : NEG) : sc_[1][0], e1 = gt1 ? (has_prev ? sc_[0][1] : NEG) : sc_[1][1];
                const float f0 = gt0 ? sc_[1][2] : sc_[2][2], f1 = gt1 ? sc_[1][3] : sc_[2][3];
                const float me = quad_max(fmaxf(e0, e1)) * sc0, mf = quad_max(fmaxf(f0, f1)) * sc1;
                float p0 = ex2(fmaf(e0, sc0, -me)), p1 = ex2(fmaf(e1, sc0, -me));
                float r0 = ex2(fmaf(f0, sc1, -mf)), r1 = ex2(fmaf(f1, sc1, -mf));
                const float ie = rcp(quad_sum(p0 + p1)), jf = rcp(quad_sum(r0 + r1));
                const uint32_t pp = pack_bf16(p0 * ie, p1 * ie), rp = pack_bf16(r0 * jf, r1 * jf);
                const uint32_t mk = (gt0 ? 0x0000ffffu : 0u) | (gt1 ? 0xffff0000u : 0u);
                const uint32_t sw = hg >= 4 ? ~0u : 0u;
                const uint32_t pa0 = pp & mk & ~sw, pa1 = pp & mk & sw, pb0 = rp & ~mk & sw, pb1 = rp & ~mk & ~sw;
                const uint32_t pa2 = sw ? rp & mk : pp & ~mk, pa3 = sw ? pp & ~mk : rp & mk;
                #pragma unroll
                for (int c = 0; c < 4; c++) {
                    float o[4] = {0.f, 0.f, 0.f, 0.f};
                    mma16816(o, pa0, pa1, pa2, pa3, vf[0][c0 + c], vf[1][c0 + c]);
                    mma1688(o, pb0, pb1, vf[2][c0 + c]);
                    const uint32_t lo = pack_bf16(o[0], o[1]), hi = pack_bf16(o[2], o[3]);
                    if (hd == 1 && c == 0) { if (t >= 2) { ow[3][0] = lo; ow[3][1] = hi; } }
                    else { ow[c0 + c][0] = lo; ow[c0 + c][1] = hi; }
                }
            }
            const uint32_t om = ~lane & 1;
            if (hg & 1) {
                stg2((uint2*)(op - lane) + 32 + lane, set_par(ow[0][0], om, tag), ow[0][1]);
                stg4(op + 32, set_par(ow[1][0], om, tag), ow[1][1], ow[2][0], ow[2][1]);
                stg4(op + 64, set_par(ow[3][0], om, tag), ow[3][1], ow[4][0], ow[4][1]);
                stg4(op + 96, set_par(ow[5][0], om, tag), ow[5][1], ow[6][0], ow[6][1]);
            } else {
                stg4(op,      set_par(ow[0][0], om, tag), ow[0][1], ow[1][0], ow[1][1]);
                stg4(op + 32, set_par(ow[2][0], om, tag), ow[2][1], ow[3][0], ow[3][1]);
                stg4(op + 64, set_par(ow[4][0], om, tag), ow[4][1], ow[5][0], ow[5][1]);
                stg2((uint2*)(op + 96 - lane) + lane, set_par(ow[6][0], om, tag), ow[6][1]);
            }
            if (lane == 0) asm volatile("st.relaxed.gpu.global.u32 [%0], %1;" :: "l"(ofl), "r"(tag) : "memory");
            TR(5);
        }
        {
            float acc2[64];
            const bool wide = a2j != 3;
            mbar_wait(BAR(B_XRF), 0);
            {
                const uint32_t xa = sb + SM_X + 8 * 8192 + (w * 16 + wg * 8 + (lane & 7)) * 128;
                #pragma unroll
                for (int c = 0; c < 4; c++) {
                    uint32_t xr[4];
                    asm volatile("ldmatrix.sync.aligned.m8n8.x4.shared.b16 {%0,%1,%2,%3}, [%4];"
                                 : "=r"(xr[0]), "=r"(xr[1]), "=r"(xr[2]), "=r"(xr[3])
                                 : "r"(xa + (c >> 1) * 8192 + ((((c & 1) * 4 + (lane >> 3)) ^ (lane & 7)) << 4)) : "memory");
                    #pragma unroll
                    for (int e = 0; e < 4; e++) {
                        acc2[16 * c + 4 * e] = bf_lo(xr[e]); acc2[16 * c + 4 * e + 1] = bf_hi(xr[e]);
                        acc2[16 * c + 4 * e + 2] = 0.f;      acc2[16 * c + 4 * e + 3] = 0.f;
                    }
                }
            }
            const uint4* op = &g_o[((a2s * 4 + w) * 28 + wg * 14) * 32];
            const uint32_t rsend = opaque(sb + SM_RED + (1 - wg) * 16384 + w * 4096 + lane * 16);
            const uint32_t rrecv = opaque(sb + SM_RED + wg * 16384 + w * 4096 + lane * 16);
            uint4* spw = opaque_ptr(&g_stats[(a2s * 4 + a2j) * 64 + (w * 2 + wg) * 8 + g]);
            const uint4* spr = opaque_ptr(&g_stats[(a2s * 4 + t) * 64 + (w * 2 + wg) * 8 + g]);
            uint2* hp = opaque_ptr((uint2*)g_h + ((a2s * 8 + w * 2 + wg) * 28 + a2j * 8) * 32 + lane);
            uint32_t* np = opaque_ptr((uint32_t*)&g_hn[(a2s * 56 + a2j * 16) * 64] + (w * 2 + wg) * 32 + lane);
            uint32_t* nfl = opaque_ptr(&g_flag_h[(a2s * 4 + a2j) * FS]);
            const uint64_t dwo = make_desc(sb + SM_WKV + wg * 57344, 28672, true);
            bias1 = prm.b1[g1f * 64 + w * 16 + rank * 8 + g];
            const __nv_bfloat16 bias2 = prm.b2[ti * 128 + (w * 16 + wg * 8 + g) * 2 + a2p];
            reg_fence(acc2);
            mbar_wait(BAR(B_WOF + wg), 0);
            {
                const uint32_t* pp = &g_flag_o[((a2s * 4 + w) * 8 + wg * 4 + t) * FS];
                int it = 0;
                while (__any_sync(~0u, ld_rlx(pp) != tag)) { if (++it > kSpinLimit) { TIMEOUT(102); break; } }
            }
            TR(6);
            uint4 of[14];
            auto load_o = [&](int k) {
                if (k % 7 == 3) {
                    const uint2 lo = ld_rlx2((const uint2*)(op + k * 32) + lane), hi = ld_rlx2((const uint2*)(op + k * 32) + 32 + lane);
                    of[k] = make_uint4(lo.x, lo.y, hi.x, hi.y);
                } else of[k] = ld_rlx4(op + k * 32 + lane);
            };
            #pragma unroll
            for (int k = 0; k < 14; k++) load_o(k);
            static_for<0, 4>([&](auto G_) {
                constexpr int k0 = (decltype(G_)::value * 7) / 2, k1 = (decltype(G_)::value * 7 + 7) / 2;
                int it = 0;
                while (true) {
                    uint32_t bad = 0;
                    #pragma unroll
                    for (int k = k0; k < k1; k++) bad |= (of[k].x ^ tag) | (k % 7 == 3 ? of[k].z ^ tag : 0u);
                    if (!__any_sync(~0u, bad & ~lane & 1)) break;
                    if (++it > kSpinLimit) { TIMEOUT(109); break; }
                    RETRY_COUNT(1);
                    #pragma unroll
                    for (int k = k0; k < k1; k++) load_o(k);
                }
                if (k1 == 14) warp_arrive(BAR(B_OL));
                wg_fence();
                static_for<k0, k1>([&](auto K_) { constexpr int k = decltype(K_)::value;
                    wgmma_rs_n128<k * 2048, 1>(acc2, of[k].x, of[k].y, of[k].z, of[k].w, dwo); });
            });
            wg_commit();
            wg_wait<0>();
            reg_fence(acc2);
            TR(7);
            #pragma unroll
            for (int c = 0; c < 8; c++)
                sts4(rsend + c * 512, __float_as_uint(acc2[8 * c + 2]), __float_as_uint(acc2[8 * c + 3]), __float_as_uint(acc2[8 * c + 6]), __float_as_uint(acc2[8 * c + 7]));
            named_bar(3, 256);
            float hv[32];
            float s0 = 0.f, s1 = 0.f, q0 = 0.f, q1 = 0.f;
            #pragma unroll
            for (int c = 0; c < 8; c++) {
                const uint4 u = lds4(rrecv + c * 512);
                hv[4 * c]     = acc2[8 * c] + __uint_as_float(u.x);     hv[4 * c + 1] = acc2[8 * c + 1] + __uint_as_float(u.y);
                hv[4 * c + 2] = acc2[8 * c + 4] + __uint_as_float(u.z); hv[4 * c + 3] = acc2[8 * c + 5] + __uint_as_float(u.w);
            }
            #pragma unroll
            for (int c = 0; c < 16; c += 2) { s0 += hv[c]; s1 += hv[c + 1]; q0 = fmaf(hv[c], hv[c], q0); q1 = fmaf(hv[c + 1], hv[c + 1], q1); }
            if (wide) {
                #pragma unroll
                for (int c = 16; c < 32; c += 2) { s0 += hv[c]; s1 += hv[c + 1]; q0 = fmaf(hv[c], hv[c], q0); q1 = fmaf(hv[c + 1], hv[c + 1], q1); }
            }
            s0 = quad_sum(s0 + s1); q0 = quad_sum(q0 + q1);
            if (t == 0) st_ll(spw, __float_as_uint(s0), __float_as_uint(q0), tag);
            TR(8);
            fence_async_smem();
            const float b2v = __bfloat162float(bias2);
            #pragma unroll
            for (int c = 0; c < 8; c++)
                if (c < 4 || wide) stg2(hp + c * 32, set_par(pack_bf16(hv[4 * c] + b2v, hv[4 * c + 1] + b2v), t == 0, tag), pack_bf16(hv[4 * c + 2] + b2v, hv[4 * c + 3] + b2v));
            const uint32_t nm = opaque((lane & 7) == w * 2 + wg ? 1u << (lane >> 3) : 0u);
            uint32_t um, uv;
            {
                int it = 0;
                while (!__all_sync(~0u, ld_ll(spr, um, uv, tag))) { if (++it > kSpinLimit) { TIMEOUT(103); break; } }
            }
            TR(9);
            const float mean = quad_sum(__uint_as_float(um)) * (1.f / kD);
            const float var = fmaxf(fmaf(quad_sum(__uint_as_float(uv)), 1.f / kD, -mean * mean), 0.f);
            const float r1 = rsq(var + kEps);
            const float rr = 0.5f * r1 * rsq(fmaf(var * r1, r1, kEps));
            const float mr = -mean * rr;
            #pragma unroll
            for (int c = 0; c < 16; c++)
                if (c < 8 || wide) stg1(np + c * 256, set_par(pack_bf16(fmaf(hv[2 * c], rr, mr), fmaf(hv[2 * c + 1], rr, mr)), (nm >> (c & 3)) & 1, tag));
            named_bar(3, 256);
            mbar_arrive_remote_if(pbar0 + 8u * B_PD, tid == 0 && !g1_on);
            if (tid == 128) {
                st_flag(nfl, tag);
                asm volatile("st.shared.u32 [%0], %1;" :: "r"(sb + SM_TG), "r"(gtime32()) : "memory");
                mbar_arrive(BAR(B_HD));
            }
            __syncwarp();
            TR(10);
        }
        float acc[56];
        const uint32_t xch = opaque(sb + SM_XCH + w * 1920 + lane * 16);
        uint32_t peer_xch; const uint32_t peer_bar = pbar0;
        asm volatile("mapa.shared::cluster.u32 %0, %1, %2;" : "=r"(peer_xch) : "r"(xch), "r"(rank ^ 1));
        uint2 hr[7];
        const int tok = g2s * 64 + w * 16 + rank * 8 + g, pr = (tok & 127) >> 1;
        const uint2* hp = (const uint2*)g_h + ((((tok >> 7) * 2 + (tok & 1)) * 8 + (pr >> 3)) * 28 + (g2j + 2 * wg) * 7) * 32 + (pr & 7) * 4 + t;
        auto load_h = [&]() {
            #pragma unroll
            for (int c = 0; c < 7; c++) hr[c] = ld_rlx2(hp + c * 32);
        };
        const uint32_t b1h = pack_bf16(0.5f * __bfloat162float(bias1), 0.5f * __bfloat162float(bias1));
        #pragma unroll
        for (int c = 0; c < 7; c++) hr[c] = make_uint2(b1h, b1h);
        if (!g1_on) { mbar_wait(BAR(B_GO), 0); load_h(); }
        uint32_t* const gp1 = (uint32_t*)&g_g[(g1f * 56 + (g1j + 2 * wg) * 14) * 64] + (w * 2 + rank) * 32 + lane;
        uint32_t* const gp2 = (uint32_t*)(prm.out + (size_t)(g2s * 64 + w * 16 + rank * 8 + (lane >> 4)) * kD + (g2j + 2 * wg) * 112) + (lane & 15) * 4;
        uint32_t gm[4];
        #pragma unroll
        for (int i = 0; i < 4; i++) gm[i] = lane == ((g1j * 2 + i) & 3) * 8 + w * 2 + rank;
        const bool lead = elect_one();
        const uint64_t da0 = make_desc(sb, 0, true), db0 = make_desc(sb + SM_B, 128, false);
        #pragma unroll 1
        for (int ge = g1_on ? 0 : 1; ge < 2; ge++) {
            if (ge) {
                int it = 0;
                while (true) {
                    uint32_t bad = 0;
                    #pragma unroll
                    for (int c = 0; c < 7; c++) bad |= hr[c].x ^ tag;
                    if (!__any_sync(~0u, t == 0 && (bad & 1))) break;
                    if (++it > kSpinLimit) { TIMEOUT(110); break; }
                    load_h();
                }
            }
            auto init_acc = [&](auto R_) {
                constexpr int o = decltype(R_)::value * 2;
                #pragma unroll
                for (int c = 0; c < 14; c++) {
                    const uint32_t hw = c & 1 ? hr[c >> 1].y : hr[c >> 1].x;
                    acc[4 * c + o] = bf_lo(hw); acc[4 * c + 1 + o] = bf_hi(hw);
                    acc[4 * c + 2 - o] = 0.f;   acc[4 * c + 3 - o] = 0.f;
                }
                reg_fence(acc);
            };
            if (rank) init_acc(std::integral_constant<int, 1>{}); else init_acc(std::integral_constant<int, 0>{});
            const uint32_t slot0 = g1_on ? (ge ? 4 : 2 * wg) : 0;
            uint32_t ph = 0, rb = bar0 + slot0 * 8;
            uint64_t da = da0 + ge * 1024, db = db0 + slot0 * 896;
            uint32_t prev = BAR(B_WKVF);
            mbar_wait(BAR(B_EP), 0);
            if (wg == 1 || (ge && g1_on)) named_bar(5 - wg, 256);
            mbar_wait(rb + B_BF * 8, ph);
            TR(11 + ge * 4);
            #pragma unroll 1
            for (int n = ge ? 14 : 16;;) {
                wg_fence();
                wgmma_ss_n112<0,    0>(acc, da, db);
                wgmma_ss_n112<2048, 256>(acc, da, db);
                wgmma_ss_n112<4096, 512>(acc, da, db);
                wgmma_ss_n112<6144, 768>(acc, da, db);
                wg_commit();
                if (--n == 0 && ge + wg < 2) named_arrive(4 + wg, 256);
                const uint32_t cur = rb + B_BE * 8;
                da += 512; db += 896; rb += 8;
                if (rb == bar0 + NB * 8) { rb = bar0; db = db0; ph ^= 1; }
                wg_wait<1>();
                mbar_arrive_if(prev, lead);
                prev = cur;
                if (n == 0) break;
                if (!mbar_try(rb + B_BF * 8, ph)) mbar_wait(rb + B_BF * 8, ph);
            }
            const int use = ge * 2 + wg;
            const uint32_t xfree = BAR(use > (g1_on ? 0 : 2) ? B_RE + use - 1 : B_PD);
            const bool xok = mbar_test(xfree, 0);
            wg_wait<0>();
            reg_fence(acc);
            mbar_arrive_if(prev, lead);
            TR(12 + ge * 4);
            if (!xok) mbar_wait(xfree, 0);
            float v[28];
            auto reduce = [&](auto R_) {
                constexpr int o = decltype(R_)::value * 2;
                const uint32_t rf = peer_bar + (B_RF + use) * 8;
                float dly = __uint_as_float(0x3f800000u | lane); uint32_t pa = peer_xch;
                #pragma unroll
                for (int c = 0; c < 4; c++) {
                    const uint32_t p0 = pack_bf16(acc[16 * c + 2 - o], acc[16 * c + 3 - o]), p1 = pack_bf16(acc[16 * c + 6 - o], acc[16 * c + 7 - o]);
                    if (c < 3) {
                        const uint32_t p2 = pack_bf16(acc[16 * c + 10 - o], acc[16 * c + 11 - o]), p3 = pack_bf16(acc[16 * c + 14 - o], acc[16 * c + 15 - o]);
                        asm volatile("st.async.shared::cluster.mbarrier::complete_tx::bytes.v4.b32 [%0], {%1,%2,%3,%4}, [%5];"
                                     :: "r"(pa + c * 512), "r"(p0), "r"(p1), "r"(p2), "r"(p3), "r"(rf) : "memory");
                        if (use != 3) {
                            #pragma unroll
                            for (int i = 0; i < XPACE; i++) asm volatile("tanh.approx.f32 %0, %0;" : "+f"(dly) :: "memory");
                            pa += __float_as_uint(dly) >> 30;
                        }
                    } else {
                        asm volatile("st.async.shared::cluster.mbarrier::complete_tx::bytes.v2.b32 [%0], {%1,%2}, [%3];"
                                     :: "r"(pa + 1536 - lane * 8), "r"(p0), "r"(p1), "r"(rf) : "memory");
                    }
                }
                if (!ge) load_h();
                mbar_wait(BAR(B_RF + use), 0);
                #pragma unroll
                for (int c = 0; c < 4; c++) {
                    uint4 u;
                    if (c < 3) u = lds4(xch + c * 512); else { const uint2 u2 = lds2(xch + 1536 - lane * 8); u.x = u2.x; u.y = u2.y; }
                    v[8 * c]     = acc[16 * c + o] + bf_lo(u.x);     v[8 * c + 1] = acc[16 * c + 1 + o] + bf_hi(u.x);
                    v[8 * c + 2] = acc[16 * c + 4 + o] + bf_lo(u.y); v[8 * c + 3] = acc[16 * c + 5 + o] + bf_hi(u.y);
                    if (c < 3) {
                        v[8 * c + 4] = acc[16 * c + 8 + o] + bf_lo(u.z);  v[8 * c + 5] = acc[16 * c + 9 + o] + bf_hi(u.z);
                        v[8 * c + 6] = acc[16 * c + 12 + o] + bf_lo(u.w); v[8 * c + 7] = acc[16 * c + 13 + o] + bf_hi(u.w);
                    }
                }
            };
            if (rank) reduce(std::integral_constant<int, 1>{}); else reduce(std::integral_constant<int, 0>{});
            TR(13 + ge * 4);
            if (!ge) {
                #pragma unroll
                for (int c = 0; c < 14; c++) {
                    float r[2];
                    #pragma unroll
                    for (int e = 0; e < 2; e++) {
                        const float u = v[2 * c + e];
                        r[e] = fmaf(u, tanh_hw(u * fmaf(u * u, 8.f * 0.7978845608f * 0.044715f, 2.f * 0.7978845608f)), u);
                    }
                    stg1(gp1 + c * 256, set_par(pack_bf16(r[0], r[1]), gm[c & 3], tag));
                }
                named_bar(1 + wg, 128);
                if (w == 0 && lane == 0) {
                    asm volatile("st.shared.u32 [%0], %1;" :: "r"(sb + SM_TG + 8 + wg * 4), "r"(clk32() + XSPEC) : "memory");
                    mbar_arrive(BAR(B_GD + wg));
                }
                mbar_arrive_remote_if(peer_bar + (B_RE + use) * 8, lead);
            } else {
                const uint32_t stw = xch - lane * 16;
                uint32_t pk[14];
                #pragma unroll
                for (int c = 0; c < 14; c++) pk[c] = pack_bf16(v[2 * c], v[2 * c + 1]);
                __syncwarp();
                const uint32_t sa = stw + (lane & 7) * 240 + (lane >> 3) * 16;
                #pragma unroll
                for (int m = 0; m < 3; m++)
                    asm volatile("stmatrix.sync.aligned.m8n8.x4.shared.b16 [%0], {%1,%2,%3,%4};"
                                 :: "r"(sa + m * 64), "r"(pk[4 * m]), "r"(pk[4 * m + 1]), "r"(pk[4 * m + 2]), "r"(pk[4 * m + 3]) : "memory");
                asm volatile("stmatrix.sync.aligned.m8n8.x2.shared.b16 [%0], {%1,%2};" :: "r"(sa + 192), "r"(pk[12]), "r"(pk[13]) : "memory");
                __syncwarp();
                #pragma unroll
                for (int i = 0; i < 4; i++) {
                    const int r = 2 * i + (lane >> 4), ch = lane & 15;
                    if (ch < 14) { const uint4 u = lds4(stw + r * 240 + ch * 16); stg4(gp2 + i * 448, u.x, u.y, u.z, u.w); }
                }
                __syncwarp();
                mbar_arrive_remote_if(peer_bar + (B_RE + 2) * 8, lead && wg == 0);
            }
            TR(14 + ge * 4);
        }
        if (tid == 128) TRG(62);
        if (b == 0 && tid == 128) g_epoch = tag;
    }
}

typedef CUresult (*EncodeFn)(CUtensorMap*, CUtensorMapDataType, cuuint32_t, void*, const cuuint64_t*, const cuuint64_t*,
                             const cuuint32_t*, const cuuint32_t*, CUtensorMapInterleave, CUtensorMapSwizzle,
                             CUtensorMapL2promotion, CUtensorMapFloatOOBfill);

void make_map(EncodeFn enc, CUtensorMap* m, const void* base, uint64_t cols, uint64_t rows, uint32_t box_rows) {
    cuuint64_t dims[2] = {cols, rows};
    cuuint64_t strides[1] = {cols * 2};
    cuuint32_t box[2] = {64, box_rows};
    cuuint32_t es[2] = {1, 1};
    enc(m, CU_TENSOR_MAP_DATA_TYPE_BFLOAT16, 2, const_cast<void*>(base), dims, strides, box, es, CU_TENSOR_MAP_INTERLEAVE_NONE,
        CU_TENSOR_MAP_SWIZZLE_128B, CU_TENSOR_MAP_L2_PROMOTION_L2_128B, CU_TENSOR_MAP_FLOAT_OOB_FILL_NONE);
}

}

extern "C" void kernel_launch(void* const* d_in, const int* in_sizes, int n_in, void* d_out, int out_size) {
    (void)in_sizes; (void)n_in; (void)out_size;
    void* fn = nullptr;
    cudaDriverEntryPointQueryResult qr;
    cudaGetDriverEntryPoint("cuTensorMapEncodeTiled", &fn, cudaEnableDefault, &qr);
    EncodeFn enc = (EncodeFn)fn;
    CUtensorMap mX, mWqkv, mWo, mW1, mW2;
    make_map(enc, &mX, d_in[0], 2 * kD, kS / 2, 64);
    make_map(enc, &mWqkv, d_in[1], 3 * kD, kD, 64);
    make_map(enc, &mWo, d_in[2], kD, kD, 224);
    make_map(enc, &mW1, d_in[4], 2 * kF, kS / 2, 64);
    make_map(enc, &mW2, d_in[6], kS, kF, 64);
    Params prm;
    prm.x = (const __nv_bfloat16*)d_in[0];
    prm.wqkv = (const __nv_bfloat16*)d_in[1];
    prm.wo = (const __nv_bfloat16*)d_in[2];
    prm.w1 = (const __nv_bfloat16*)d_in[4];
    prm.b1 = (const __nv_bfloat16*)d_in[5];
    prm.w2 = (const __nv_bfloat16*)d_in[6];
    prm.b2 = (const __nv_bfloat16*)d_in[7];
    prm.out = (__nv_bfloat16*)d_out;
    cudaFuncSetAttribute(fused_kernel, cudaFuncAttributeMaxDynamicSharedMemorySize, SM_TOTAL);
    fused_kernel<<<128, 384, SM_TOTAL, cudaStreamPerThread>>>(mX, mWqkv, mWo, mW1, mW2, prm);
}
```

```cpp
#include <cuda_runtime.h>
#include <cuda.h>
#include <cuda_bf16.h>
#include <stdint.h>
#include <type_traits>

namespace {

constexpr int kS = 2048, kD = 448, kF = 1792;
constexpr float kEps = 1e-5f;

#define FS 32
__device__ __align__(1024) uint4    g_o[32 * 4 * 28 * 32];
__device__ __align__(1024) uint4    g_h[kS * kD * 2 / 16];
__device__ __align__(1024) uint4    g_hn[32 * 56 * 64];
__device__ __align__(1024) uint4    g_g[28 * 56 * 64];
__device__ __align__(1024) uint4    g_halo[16 * 8 * 2 * 7 * 32];
__device__ __align__(1024) uint4    g_stats[32 * 4 * 64];
__device__ __align__(1024) uint32_t g_flag_o[32 * 4 * 8 * FS];
__device__ __align__(1024) uint32_t g_flag_h[32 * 4 * FS];
__device__ uint32_t g_epoch;
#define TIMEOUT(code)
#define RETRY_COUNT(i)
#define CAP_DECL(n, k)
#define CAP(n)
#define CAP_SKIP(n)
#define TR2(idx)
#define TR(idx)
#define TRW(idx)
#define TRG(idx)

constexpr uint32_t SM_X    = 0;
constexpr uint32_t SM_WKV  = 114688;
constexpr uint32_t SM_RED  = 81920;
constexpr uint32_t SM_XCH  = 0;
constexpr uint32_t SM_B    = 131072;
constexpr uint32_t SM_BAR  = 231424;
constexpr uint32_t SM_TOTAL = SM_BAR + 1024;
constexpr int NB = 7;
#define SH1 0
#define SH2 0
#define SH2N 5
#define SH3 0
#define NSPEC 4
#define XSPEC 700
#define C2 0
#define C3 0
#define CN2 8000
#define CN3 12000
constexpr int B_XF = 0, B_WKVF = 7, B_WQF = 14, B_XRF = 15, B_WOF = 16,
              B_XC = 18, B_KV3 = 19, B_KVC = 20,
              B_A1D = 21, B_OL = 22,
              B_BE = 23, B_RE = B_BE + NB,
              B_AF = B_RE + 3, B_BL = B_AF + 16  , B_BF = B_BL + NB  , B_RF = B_BF + NB,
              B_EP = B_RF + 4, B_PD = B_EP + 1, B_RT = B_PD + 1,
              B_HD = B_RT + 2, B_GO = B_HD + 1, B_GD = B_GO + 1, B_COUNT = B_GD + 2;
#define WEARLY 6
#define PF0 126
#define TMPF 2
#define RSTE 2
#define POLLP 1
#define PROBEP 1
#define LOADP 1
#define LOADW 64
#define NOB 0
#define AEARLY 5
#define W1PACE 400
#define W2PACE 200
#define PFPACE 330
#define PFBAR (B_XF + 6)
#define DELTA 640
#define DELTA2 DELTA
#define BPACE 230
#define BURST 2
#define W1OFF 350
#define W2OFF 2900
#define XPACE 0
#define PSTAG 200
constexpr uint32_t SM_EPOCH = SM_BAR + B_COUNT * 8, SM_TG = SM_EPOCH + 4  , SM_TR = SM_BAR + 768;

#define W1Q 1
constexpr uint32_t w2_rounds(int h) { uint32_t m = 0; for (int i = 0; i < 14; i++) { const int p = 25 + i * 20 / 13; if ((p & 1) == h) m |= 1u << (p / 2 + 1); } return m; }
constexpr uint32_t kAMask0 = w2_rounds(0), kAMask1 = w2_rounds(1) | 0xFFu << W1Q;

constexpr int kSpinLimit = 1 << 15;
__device__ __forceinline__ bool elect_one() {
    uint32_t p;
    asm volatile("{ .reg .pred P; elect.sync _|P, 0xffffffff; selp.u32 %0, 1, 0, P; }" : "=r"(p));
    return p;
}
__device__ __forceinline__ void mbar_init(uint32_t bar, uint32_t cnt) { asm volatile("mbarrier.init.shared::cta.b64 [%0], %1;" :: "r"(bar), "r"(cnt)); }
__device__ __forceinline__ void mbar_expect(uint32_t bar, uint32_t bytes) { asm volatile("mbarrier.arrive.expect_tx.shared::cta.b64 _, [%0], %1;" :: "r"(bar), "r"(bytes) : "memory"); }
__device__ __forceinline__ void mbar_arrive(uint32_t bar) { asm volatile("mbarrier.arrive.shared::cta.b64 _, [%0];" :: "r"(bar) : "memory"); }
__device__ __forceinline__ void mbar_wait(uint32_t bar, uint32_t parity) {
    uint32_t ok; int it = 0;
    do {
        asm volatile("{ .reg .pred p; mbarrier.try_wait.parity.shared::cta.b64 p, [%1], %2; selp.u32 %0, 1, 0, p; }"
                     : "=r"(ok) : "r"(bar), "r"(parity) : "memory");
        if (++it > kSpinLimit) { TIMEOUT((bar & 1023) >> 3); break; }
    } while (!ok);
}
__device__ __forceinline__ bool mbar_try(uint32_t bar, uint32_t parity) {
    uint32_t ok;
    asm volatile("{ .reg .pred p; mbarrier.try_wait.parity.shared::cta.b64 p, [%1], %2; selp.u32 %0, 1, 0, p; }" : "=r"(ok) : "r"(bar), "r"(parity) : "memory");
    return ok;
}
__device__ __forceinline__ bool mbar_test(uint32_t bar, uint32_t parity) {
    uint32_t ok;
    asm volatile("{ .reg .pred p; mbarrier.test_wait.parity.shared::cta.b64 p, [%1], %2; selp.u32 %0, 1, 0, p; }" : "=r"(ok) : "r"(bar), "r"(parity) : "memory");
    return ok;
}
__device__ __forceinline__ void mbar_wait2(uint32_t bar0, uint32_t par0, uint32_t bar1, uint32_t par1) {
    uint32_t ok; int it = 0;
    do {
        asm volatile("{ .reg .pred p, q; mbarrier.try_wait.parity.shared::cta.b64 p, [%1], %2;\n"
                     "mbarrier.try_wait.parity.shared::cta.b64 q, [%3], %4; and.pred p, p, q; selp.u32 %0, 1, 0, p; }"
                     : "=r"(ok) : "r"(bar0), "r"(par0), "r"(bar1), "r"(par1) : "memory");
        if (++it > kSpinLimit) { TIMEOUT((bar0 & 1023) >> 3); break; }
    } while (!ok);
}
template <int N> __device__ __forceinline__ void reg_fence(float (&d)[N]) {
    #pragma unroll
    for (int i = 0; i < N; i++) asm volatile("" : "+f"(d[i]) :: "memory");
}
__device__ __forceinline__ void mbar_wait_cluster(uint32_t bar, uint32_t parity) {
    uint32_t ok; int it = 0;
    do {
        asm volatile("{ .reg .pred p; mbarrier.try_wait.parity.acquire.cluster.shared::cta.b64 p, [%1], %2; selp.u32 %0, 1, 0, p; }"
                     : "=r"(ok) : "r"(bar), "r"(parity) : "memory");
        if (++it > kSpinLimit) { TIMEOUT((bar & 1023) >> 3); break; }
    } while (!ok);
}
__device__ __forceinline__ void mbar_arrive_if(uint32_t bar, bool pred) {
    asm volatile("{ .reg .pred p; setp.ne.u32 p, %1, 0; @p mbarrier.arrive.shared::cta.b64 _, [%0]; }" :: "r"(bar), "r"((uint32_t)pred) : "memory");
}
template <int P> __device__ __forceinline__ void tick() {
    if (P > 1) { const uint32_t t = ((uint32_t)clock() | (P - 1)) + 1; while ((int)((uint32_t)clock() - t) < 0) {} }
}
__device__ __forceinline__ void warp_arrive(uint32_t bar) { __syncwarp(); if (elect_one()) mbar_arrive(bar); }
__device__ __forceinline__ void tma2d(uint32_t dst, const CUtensorMap* m, int c0, int c1, uint32_t bar) {
    asm volatile("cp.async.bulk.tensor.2d.shared::cluster.global.mbarrier::complete_tx::bytes [%0], [%1, {%3, %4}], [%2];"
                 :: "r"(dst), "l"(m), "r"(bar), "r"(c0), "r"(c1) : "memory");
}
__device__ __forceinline__ void tma2d_mc(uint32_t dst, const CUtensorMap* m, int c0, int c1, uint32_t bar) {
    asm volatile("cp.async.bulk.tensor.2d.shared::cluster.global.mbarrier::complete_tx::bytes.multicast::cluster [%0], [%1, {%3, %4}], [%2], %5;"
                 :: "r"(dst), "l"(m), "r"(bar), "r"(c0), "r"(c1), "h"((uint16_t)3) : "memory");
}
__device__ __forceinline__ void bulk_g2s_mc(uint32_t dst, const void* src, uint32_t bytes, uint32_t bar) {
    asm volatile("cp.async.bulk.shared::cluster.global.mbarrier::complete_tx::bytes.multicast::cluster [%0], [%1], %2, [%3], %4;"
                 :: "r"(dst), "l"(src), "r"(bytes), "r"(bar), "h"((uint16_t)3) : "memory");
}
__device__ __forceinline__ void mbar_arrive_remote_if(uint32_t cluster_bar, bool pred) {
    asm volatile("{ .reg .pred p; setp.ne.u32 p, %1, 0; @p mbarrier.arrive.shared::cluster.b64 _, [%0]; }" :: "r"(cluster_bar), "r"((uint32_t)pred) : "memory");
}
__device__ __forceinline__ void bulk_g2s(uint32_t dst, const void* src, uint32_t bytes, uint32_t bar) {
    asm volatile("cp.async.bulk.shared::cluster.global.mbarrier::complete_tx::bytes [%0], [%1], %2, [%3];"
                 :: "r"(dst), "l"(src), "r"(bytes), "r"(bar) : "memory");
}
__device__ __forceinline__ void wg_fence()  { asm volatile("wgmma.fence.sync.aligned;" ::: "memory"); }
__device__ __forceinline__ void wg_commit() { asm volatile("wgmma.commit_group.sync.aligned;" ::: "memory"); }
template <int N> __device__ __forceinline__ void wg_wait() { asm volatile("wgmma.wait_group.sync.aligned %0;" :: "n"(N) : "memory"); }
__device__ __forceinline__ void named_bar(int id, int n) { asm volatile("bar.sync %0, %1;" :: "r"(id), "r"(n) : "memory"); }
__device__ __forceinline__ void named_arrive(int id, int n) { asm volatile("bar.arrive %0, %1;" :: "r"(id), "r"(n) : "memory"); }
__device__ __forceinline__ bool mbar_try2(uint32_t bar0, uint32_t par0, uint32_t bar1, uint32_t par1) {
    uint32_t ok;
    asm volatile("{ .reg .pred p, q; mbarrier.test_wait.parity.shared::cta.b64 p, [%1], %2;\n"
                 "mbarrier.test_wait.parity.shared::cta.b64 q, [%3], %4; and.pred p, p, q; selp.u32 %0, 1, 0, p; }"
                 : "=r"(ok) : "r"(bar0), "r"(par0), "r"(bar1), "r"(par1) : "memory");
    return ok;
}
__device__ __forceinline__ void fence_gpu() { asm volatile("fence.release.gpu;" ::: "memory"); }
__device__ __forceinline__ void fence_async_global() { asm volatile("fence.proxy.async.global;" ::: "memory"); }
__device__ __forceinline__ void fence_async_smem() { asm volatile("fence.proxy.async.shared::cta;" ::: "memory"); }
__device__ __forceinline__ uint32_t gtime32() { uint64_t t; asm volatile("mov.u64 %0, %%globaltimer;" : "=l"(t) :: "memory"); return (uint32_t)t; }
__device__ __forceinline__ uint32_t clk32() { uint64_t t; asm volatile("mov.u64 %0, %%clock64;" : "=l"(t) :: "memory"); return (uint32_t)t; }
__device__ __forceinline__ void spin_until(uint32_t t) { while ((int)(clk32() - t) < 0) {} }
#define SLEEPNS 20
__device__ __forceinline__ void sleep_until(uint32_t t) { while ((int)(clk32() - t) < 0) { if (SLEEPNS) __nanosleep(SLEEPNS); } }
__device__ __forceinline__ void st_flag(uint32_t* p, uint32_t v) {
    const uint64_t w = ((uint64_t)gtime32() << 32) | v;
    asm volatile("st.relaxed.gpu.global.u64 [%0], %1;" :: "l"(p), "l"(w) : "memory");
}
__device__ __forceinline__ void ld_flag_if(uint64_t& v, const uint32_t* p, bool pred) {
    asm volatile("{ .reg .pred p; setp.ne.u32 p, %2, 0; @p ld.relaxed.gpu.global.u64 %0, [%1]; }" : "+l"(v) : "l"(p), "r"((uint32_t)pred) : "memory");
}
__device__ __forceinline__ uint32_t ld_acq(const uint32_t* p) { uint32_t v; asm volatile("ld.acquire.gpu.global.u32 %0, [%1];" : "=r"(v) : "l"(p) : "memory"); return v; }
__device__ __forceinline__ uint32_t ld_rlx(const uint32_t* p) { uint32_t v; asm volatile("ld.relaxed.gpu.global.u32 %0, [%1];" : "=r"(v) : "l"(p) : "memory"); return v; }
template <class T> __device__ __forceinline__ T* opaque_ptr(T* p) { asm volatile("" : "+l"(p)); return p; }
__device__ __forceinline__ uint4 ld_rlx4(const uint4* p) {
    uint4 v; asm volatile("ld.relaxed.gpu.global.v4.u32 {%0,%1,%2,%3}, [%4];" : "=r"(v.x), "=r"(v.y), "=r"(v.z), "=r"(v.w) : "l"(p) : "memory"); return v;
}
__device__ __forceinline__ void st_ll(uint4* p, uint32_t a, uint32_t b, uint32_t tag) {
    uint64_t lo = ((uint64_t)tag << 32) | a, hi = ((uint64_t)tag << 32) | b;
    asm volatile("st.relaxed.gpu.global.v2.u64 [%0], {%1,%2};" :: "l"(p), "l"(lo), "l"(hi) : "memory");
}
__device__ __forceinline__ bool ld_ll(const uint4* p, uint32_t& a, uint32_t& b, uint32_t tag) {
    uint64_t lo, hi;
    asm volatile("ld.relaxed.gpu.global.v2.u64 {%0,%1}, [%2];" : "=l"(lo), "=l"(hi) : "l"(p) : "memory");
    a = (uint32_t)lo; b = (uint32_t)hi;
    return (uint32_t)(lo >> 32) == tag && (uint32_t)(hi >> 32) == tag;
}
__device__ __forceinline__ uint2 ld_acq2(const uint2* p) {
    uint2 v; asm volatile("ld.acquire.gpu.global.v2.u32 {%0,%1}, [%2];" : "=r"(v.x), "=r"(v.y) : "l"(p) : "memory"); return v;
}
__device__ __forceinline__ uint2 ld_rlx2(const uint2* p) {
    uint2 v; asm volatile("ld.relaxed.gpu.global.v2.u32 {%0,%1}, [%2];" : "=r"(v.x), "=r"(v.y) : "l"(p) : "memory"); return v;
}
__device__ __forceinline__ void stg1(uint32_t* p, uint32_t v) { asm volatile("st.global.u32 [%0], %1;" :: "l"(p), "r"(v) : "memory"); }
__device__ __forceinline__ void stg2(void* p, uint32_t x, uint32_t y) { asm volatile("st.global.v2.u32 [%0], {%1,%2};" :: "l"(p), "r"(x), "r"(y) : "memory"); }
__device__ __forceinline__ void stg4(void* p, uint32_t x, uint32_t y, uint32_t z, uint32_t w) { asm volatile("st.global.v4.u32 [%0], {%1,%2,%3,%4};" :: "l"(p), "r"(x), "r"(y), "r"(z), "r"(w) : "memory"); }
__device__ __forceinline__ uint32_t lds1(uint32_t a) { uint32_t v; asm volatile("ld.shared.u32 %0, [%1];" : "=r"(v) : "r"(a) : "memory"); return v; }
__device__ __forceinline__ uint2 lds2(uint32_t a) { uint2 v; asm volatile("ld.shared.v2.u32 {%0,%1}, [%2];" : "=r"(v.x), "=r"(v.y) : "r"(a) : "memory"); return v; }
__device__ __forceinline__ uint32_t set_par(uint32_t v, uint32_t mask, uint32_t par) { return (v & ~mask) | (par & mask); }
__device__ __forceinline__ float tanh_hw(float x) { float r; asm("tanh.approx.f32 %0, %1;" : "=f"(r) : "f"(x)); return r; }
__device__ __forceinline__ bool bar_any(int id, int n, bool v) {
    uint32_t r;
    asm volatile("{ .reg .pred p, q; setp.ne.u32 p, %3, 0; bar.red.or.pred q, %1, %2, p; selp.u32 %0, 1, 0, q; }" : "=r"(r) : "r"(id), "r"(n), "r"((uint32_t)v) : "memory");
    return r;
}
__device__ __forceinline__ void sts4(uint32_t a, uint32_t x, uint32_t y, uint32_t z, uint32_t w) { asm volatile("st.shared.v4.u32 [%0], {%1,%2,%3,%4};" :: "r"(a), "r"(x), "r"(y), "r"(z), "r"(w) : "memory"); }
__device__ __forceinline__ uint4 lds4(uint32_t a) { uint4 v; asm volatile("ld.shared.v4.u32 {%0,%1,%2,%3}, [%4];" : "=r"(v.x), "=r"(v.y), "=r"(v.z), "=r"(v.w) : "r"(a) : "memory"); return v; }
__device__ __forceinline__ uint32_t pack_bf16(float lo, float hi) { uint32_t r; asm("cvt.rn.bf16x2.f32 %0, %1, %2;" : "=r"(r) : "f"(hi), "f"(lo)); return r; }
__device__ __forceinline__ float bf_lo(uint32_t v) { return __uint_as_float(v << 16); }
__device__ __forceinline__ float bf_hi(uint32_t v) { return __uint_as_float(v & 0xffff0000u); }
__device__ __forceinline__ uint32_t sub_bf16x2(uint32_t a, uint32_t b) { uint32_t r; asm("sub.rn.bf16x2 %0, %1, %2;" : "=r"(r) : "r"(a), "r"(b)); return r; }
__device__ __forceinline__ uint32_t movm(uint32_t a) { uint32_t r; asm volatile("movmatrix.sync.aligned.m8n8.trans.b16 %0, %1;" : "=r"(r) : "r"(a)); return r; }
__device__ __forceinline__ float ex2(float x) { float r; asm("ex2.approx.ftz.f32 %0, %1;" : "=f"(r) : "f"(x)); return r; }
__device__ __forceinline__ float rsq(float x) { float r; asm("rsqrt.approx.ftz.f32 %0, %1;" : "=f"(r) : "f"(x)); return r; }
__device__ __forceinline__ float rcp(float x) { float r; asm("rcp.approx.ftz.f32 %0, %1;" : "=f"(r) : "f"(x)); return r; }
__device__ __forceinline__ void mma16816(float (&c)[4], uint32_t a0, uint32_t a1, uint32_t a2, uint32_t a3, uint32_t b0, uint32_t b1) {
    asm("mma.sync.aligned.m16n8k16.row.col.f32.bf16.bf16.f32 {%0,%1,%2,%3}, {%4,%5,%6,%7}, {%8,%9}, {%0,%1,%2,%3};"
        : "+f"(c[0]), "+f"(c[1]), "+f"(c[2]), "+f"(c[3]) : "r"(a0), "r"(a1), "r"(a2), "r"(a3), "r"(b0), "r"(b1));
}
__device__ __forceinline__ void mma1688(float (&c)[4], uint32_t a0, uint32_t a1, uint32_t b0) {
    asm("mma.sync.aligned.m16n8k8.row.col.f32.bf16.bf16.f32 {%0,%1,%2,%3}, {%4,%5}, {%6}, {%0,%1,%2,%3};"
        : "+f"(c[0]), "+f"(c[1]), "+f"(c[2]), "+f"(c[3]) : "r"(a0), "r"(a1), "r"(b0));
}
__device__ __forceinline__ float quad_sum(float v) { v += __shfl_xor_sync(~0u, v, 1); v += __shfl_xor_sync(~0u, v, 2); return v; }
__device__ __forceinline__ float quad_max(float v) { v = fmaxf(v, __shfl_xor_sync(~0u, v, 1)); v = fmaxf(v, __shfl_xor_sync(~0u, v, 2)); return v; }
__device__ __forceinline__ uint64_t make_desc(uint32_t addr, uint32_t lbo, bool swz) {
    const uint32_t lo = __shfl_sync(~0u, ((addr & 0x3FFFF) >> 4) | ((lbo >> 4) << 16), 0);
    const uint32_t hi = __shfl_sync(~0u, (swz ? 0x40000040u : 0x40u) + (threadIdx.x & 31), 0);
    return ((uint64_t)hi << 32) | lo;
}
template <int I, int N, class F> __device__ __forceinline__ void static_for(F&& f) {
    if constexpr (I < N) { f(std::integral_constant<int, I>{}); static_for<I + 1, N>(f); }
}
__device__ __forceinline__ uint32_t opaque(uint32_t v) { asm volatile("" : "+r"(v)); return v; }
template <int BOFF, int SCALE_D>
__device__ __forceinline__ void wgmma_rs_n56(float (&d)[28], uint32_t a0, uint32_t a1, uint32_t a2, uint32_t a3, uint64_t db) {
    asm volatile("{ .reg .b64 db; add.s64 db, %32, %33;\n"
        "wgmma.mma_async.sync.aligned.m64n56k16.f32.bf16.bf16 "
        "{%0, %1, %2, %3, %4, %5, %6, %7, %8, %9, %10, %11, %12, %13, %14, %15, %16, %17, %18, %19, %20, %21, %22, %23, %24, %25, %26, %27}, "
        "{%28, %29, %30, %31}, db, %34, 1, 1, 1; }"
        : "+f"(d[0]), "+f"(d[1]), "+f"(d[2]), "+f"(d[3]), "+f"(d[4]), "+f"(d[5]), "+f"(d[6]), "+f"(d[7]),
        "+f"(d[8]), "+f"(d[9]), "+f"(d[10]), "+f"(d[11]), "+f"(d[12]), "+f"(d[13]), "+f"(d[14]), "+f"(d[15]),
        "+f"(d[16]), "+f"(d[17]), "+f"(d[18]), "+f"(d[19]), "+f"(d[20]), "+f"(d[21]), "+f"(d[22]), "+f"(d[23]),
        "+f"(d[24]), "+f"(d[25]), "+f"(d[26]), "+f"(d[27])
        : "r"(a0), "r"(a1), "r"(a2), "r"(a3), "l"(db), "n"(BOFF >> 4), "n"(SCALE_D));
}
template <int BOFF, int SCALE_D>
__device__ __forceinline__ void wgmma_rs_n128(float (&d)[64], uint32_t a0, uint32_t a1, uint32_t a2, uint32_t a3, uint64_t db) {
    asm volatile("{ .reg .b64 db; add.s64 db, %68, %69;\n"
        "wgmma.mma_async.sync.aligned.m64n128k16.f32.bf16.bf16 "
        "{%0, %1, %2, %3, %4, %5, %6, %7, %8, %9, %10, %11, %12, %13, %14, %15, %16, %17, %18, %19, %20, %21, %22, %23, %24, %25, %26, %27, %28, %29, %30, %31, %32, %33, %34, %35, %36, %37, %38, %39, %40, %41, %42, %43, %44, %45, %46, %47, %48, %49, %50, %51, %52, %53, %54, %55, %56, %57, %58, %59, %60, %61, %62, %63}, "
        "{%64, %65, %66, %67}, db, %70, 1, 1, 1; }"
        : "+f"(d[0]), "+f"(d[1]), "+f"(d[2]), "+f"(d[3]), "+f"(d[4]), "+f"(d[5]), "+f"(d[6]), "+f"(d[7]),
        "+f"(d[8]), "+f"(d[9]), "+f"(d[10]), "+f"(d[11]), "+f"(d[12]), "+f"(d[13]), "+f"(d[14]), "+f"(d[15]),
        "+f"(d[16]), "+f"(d[17]), "+f"(d[18]), "+f"(d[19]), "+f"(d[20]), "+f"(d[21]), "+f"(d[22]), "+f"(d[23]),
        "+f"(d[24]), "+f"(d[25]), "+f"(d[26]), "+f"(d[27]), "+f"(d[28]), "+f"(d[29]), "+f"(d[30]), "+f"(d[31]),
        "+f"(d[32]), "+f"(d[33]), "+f"(d[34]), "+f"(d[35]), "+f"(d[36]), "+f"(d[37]), "+f"(d[38]), "+f"(d[39]),
        "+f"(d[40]), "+f"(d[41]), "+f"(d[42]), "+f"(d[43]), "+f"(d[44]), "+f"(d[45]), "+f"(d[46]), "+f"(d[47]),
        "+f"(d[48]), "+f"(d[49]), "+f"(d[50]), "+f"(d[51]), "+f"(d[52]), "+f"(d[53]), "+f"(d[54]), "+f"(d[55]),
        "+f"(d[56]), "+f"(d[57]), "+f"(d[58]), "+f"(d[59]), "+f"(d[60]), "+f"(d[61]), "+f"(d[62]), "+f"(d[63])
        : "r"(a0), "r"(a1), "r"(a2), "r"(a3), "l"(db), "n"(BOFF >> 4), "n"(SCALE_D));
}
template <int AOFF, int BOFF>
__device__ __forceinline__ void wgmma_ss_n112(float (&d)[56], uint64_t da, uint64_t db) {
    asm volatile("{ .reg .b64 da, db; add.s64 da, %56, %58; add.s64 db, %57, %59;\n"
        "wgmma.mma_async.sync.aligned.m64n112k16.f32.bf16.bf16 "
        "{%0, %1, %2, %3, %4, %5, %6, %7, %8, %9, %10, %11, %12, %13, %14, %15, %16, %17, %18, %19, %20, %21, %22, %23, %24, %25, %26, %27, %28, %29, %30, %31, %32, %33, %34, %35, %36, %37, %38, %39, %40, %41, %42, %43, %44, %45, %46, %47, %48, %49, %50, %51, %52, %53, %54, %55}, "
        "da, db, 1, 1, 1, 1, 1; }"
        : "+f"(d[0]), "+f"(d[1]), "+f"(d[2]), "+f"(d[3]), "+f"(d[4]), "+f"(d[5]), "+f"(d[6]), "+f"(d[7]),
        "+f"(d[8]), "+f"(d[9]), "+f"(d[10]), "+f"(d[11]), "+f"(d[12]), "+f"(d[13]), "+f"(d[14]), "+f"(d[15]),
        "+f"(d[16]), "+f"(d[17]), "+f"(d[18]), "+f"(d[19]), "+f"(d[20]), "+f"(d[21]), "+f"(d[22]), "+f"(d[23]),
        "+f"(d[24]), "+f"(d[25]), "+f"(d[26]), "+f"(d[27]), "+f"(d[28]), "+f"(d[29]), "+f"(d[30]), "+f"(d[31]),
        "+f"(d[32]), "+f"(d[33]), "+f"(d[34]), "+f"(d[35]), "+f"(d[36]), "+f"(d[37]), "+f"(d[38]), "+f"(d[39]),
        "+f"(d[40]), "+f"(d[41]), "+f"(d[42]), "+f"(d[43]), "+f"(d[44]), "+f"(d[45]), "+f"(d[46]), "+f"(d[47]),
        "+f"(d[48]), "+f"(d[49]), "+f"(d[50]), "+f"(d[51]), "+f"(d[52]), "+f"(d[53]), "+f"(d[54]), "+f"(d[55])
        : "l"(da), "l"(db), "n"(AOFF >> 4), "n"(BOFF >> 4));
}

struct Params {
    const __nv_bfloat16 *x, *wqkv, *wo, *w1, *w2, *b1, *b2;
    __nv_bfloat16* out;
};

__global__ void __cluster_dims__(2, 1, 1) __launch_bounds__(384, 1)
fused_kernel(const __grid_constant__ CUtensorMap mX, const __grid_constant__ CUtensorMap mWqkv,
             const __grid_constant__ CUtensorMap mWo, const __grid_constant__ CUtensorMap mW1,
             const __grid_constant__ CUtensorMap mW2, const Params prm)
{
    extern __shared__ __align__(1024) unsigned char smem_raw[];
    uint32_t sb = (uint32_t)__cvta_generic_to_shared(smem_raw);
    asm volatile("mov.u32 %0, %0;" : "+r"(sb));
    const uint32_t bar0 = sb + SM_BAR;
    auto BAR = [&](int i) { return bar0 + 8u * i; };

    const int tid = threadIdx.x, lane = tid & 31;
    const int warp = __shfl_sync(~0u, tid >> 5, 0);
    const int b = __shfl_sync(~0u, (int)blockIdx.x, 0);
    const int rank = b & 1;
    const int cl = (b >> 1) - 4, cq = ((cl - 32) * 37) >> 8;
    const int res = cl < 0 ? 0 : cl < 32 ? cl & 7 : cl - 31 - 7 * cq;
    const int rnd = cl < 0 ? cl + 8 : cl < 32 ? cl >> 3 : 4 + cq;
    const int hg = (res & 1) * 4 + (rnd & 3);
    const int ti = (res >> 1) * 4 + (rnd >> 2) * 2 + rank;
    const int a2p = res & 1, a2j = rnd & 3;
    const int a2s = ti * 2 + a2p;
    const bool g1_on = rnd != 7;
    const int g1j = (rnd < 6 ? rnd : res) & 1, g1f = rnd < 6 ? res * 3 + (rnd >> 1) : 24 + (res >> 1);
    const int g2j = rnd & 1, g2s = res * 4 + (rnd >> 1);
    uint32_t pbar0;
    asm volatile("mapa.shared::cluster.u32 %0, %1, %2;" : "=r"(pbar0) : "r"(bar0), "r"(rank ^ 1));
    auto pair_arrive = [&](int i) { __syncwarp(); const bool l = elect_one(); mbar_arrive_if(BAR(i), l); mbar_arrive_remote_if(pbar0 + 8u * i, l); };
    const int wcol = hg * 56 - (hg & 1) * 8;

    if (tid == 32) { TRG(60); TRW(59); }
    if (warp == 8) {
        if (elect_one()) {
            #pragma unroll
            for (int i = 0; i < B_WQF; i++) mbar_init(BAR(i), 1);
            asm volatile("fence.mbarrier_init.release.cluster;" ::: "memory");
            fence_async_smem();
            TRW(56);
            #pragma unroll 1
            for (int kb = 0; kb < 7; kb++) {
                mbar_expect(BAR(B_XF + kb), 16384);
                tma2d(sb + SM_X + kb * 8192, &mX, kb * 64, ti * 64, BAR(B_XF + kb));
                tma2d(sb + SM_X + 57344 + kb * 8192, &mX, kD + kb * 64, ti * 64, BAR(B_XF + kb));
                if (TMPF == 2 && kb == 0) asm volatile("prefetch.tensormap [%0];" :: "l"(&mWqkv) : "memory");
            }
        }
    } else if (warp > 8) {
        if (elect_one()) {
            if (warp == 9) {
                if (TMPF == 1) asm volatile("prefetch.tensormap [%0];" :: "l"(&mWqkv) : "memory");
                #pragma unroll
                for (int i = B_WQF; i < B_AF; i++) mbar_init(BAR(i), i < B_XC ? 1 : i < B_A1D ? 16 : i < B_BE ? 8 : 4);
            } else if (warp == 10) {
                #pragma unroll
                for (int i = B_AF; i < B_BL; i++) mbar_init(BAR(i), 1);
            } else {
                #pragma unroll
                for (int i = B_BL; i < B_COUNT; i++) mbar_init(BAR(i), 1);
            }
            asm volatile("fence.mbarrier_init.release.cluster;" ::: "memory");
            fence_async_smem();
        }
    } else {
        const char* p = tid < 112 ? (const char*)prm.x + (size_t)(ti * 8 + hg) * 14336 + tid * 128
                                  : (const char*)prm.wqkv + b * 2688 + 896 + (tid - 112) * 128;
        if (tid < PF0) asm volatile("prefetch.global.L2 [%0];" :: "l"(p));
    }
    __syncwarp();
    __syncthreads();
    asm volatile("barrier.cluster.arrive.relaxed.aligned;" ::: "memory");
    if (tid < 256) TR(0);
    if (tid == 0) TRG(61);

    if (warp >= 8) {
        asm volatile("setmaxnreg.dec.sync.aligned.u32 40;");
        asm volatile("barrier.cluster.wait.aligned;" ::: "memory");
        if (warp < 10) {
          auto load_slab = [&](int s, bool second) {
              mbar_expect(BAR(B_AF + s), 8192);
              if (!second) tma2d(sb + s * 8192, &mW1, (s & 1) * kF + g1f * 64, (rank * 8 + (s >> 1)) * 64, BAR(B_AF + s));
              else         tma2d(sb + s * 8192, &mW2, g2s * 64, (rank * 14 + s - 2) * 64, BAR(B_AF + s));
          };
          if (warp == 8) {
            if (elect_one()) {
                #pragma unroll 1
                for (int s = 0; s < 7; s++) {
                    mbar_expect(BAR(B_WKVF + s), 16384);
                    tma2d_mc(sb + SM_WKV + s * 16384 + rank * 8192, &mWqkv, (1 + rank) * kD + wcol, s * 64, BAR(B_WKVF + s));
                }
            }
            __syncwarp();
            mbar_wait(BAR(B_XC), 0);
            if (elect_one()) {
                asm volatile("prefetch.tensormap [%0];" :: "l"(&mWo) : "memory");
                asm volatile("prefetch.tensormap [%0];" :: "l"(&mW1) : "memory");
                asm volatile("prefetch.tensormap [%0];" :: "l"(&mW2) : "memory");
                mbar_expect(BAR(B_WQF), 57344);
                #pragma unroll 1
                for (int s = rank; s < 7; s += 2) tma2d_mc(sb + SM_X + s * 8192, &mWqkv, wcol, s * 64, BAR(B_WQF));
                mbar_expect(BAR(B_XRF), a2j == 3 ? 8192 : 16384);
                tma2d(sb + SM_X + 8 * 8192, &mX, a2p * kD + a2j * 128, ti * 64, BAR(B_XRF));
                if (a2j != 3) tma2d(sb + SM_X + 9 * 8192, &mX, a2p * kD + a2j * 128 + 64, ti * 64, BAR(B_XRF));
            }
            __syncwarp();
            #pragma unroll 1
            for (int h = 0; h < 2; h++) {
                mbar_wait(BAR(B_KV3 + h), 0);
                if (elect_one()) {
                    mbar_expect(BAR(B_WOF + h), a2j == 3 ? 28672 : 57344);
                    const int atom = rank ^ h;
                    if (a2j != 3 || atom == 0) tma2d_mc(sb + SM_WKV + h * 57344 + atom * 28672, &mWo, a2j * 128 + atom * 64, h * 224, BAR(B_WOF + h));
                }
                __syncwarp();
            }
            if (g1_on) {
                mbar_wait(BAR(B_A1D), 0);
                #pragma unroll 1
                for (int s = 0; s < 8; s++) {
                    if (s == AEARLY) mbar_wait(BAR(B_OL), 0);
                    if (elect_one()) load_slab(s, false);
                    __syncwarp();
                }
            } else {
                mbar_wait(BAR(B_GO), 0);
                const uint32_t tg = lds1(sb + SM_TG + 4);
                int it = 0;
                while ((int)(gtime32() - tg) < 0 && ++it < 64) {}
                const uint32_t t0 = clk32();
                if (lane < 2) {
                    asm volatile("st.shared.u32 [%0], %1;" :: "r"(sb + SM_TG + 8 + lane * 4), "r"(t0 + (lane ? CN3 : CN2)) : "memory");
                    mbar_arrive(BAR(B_GD + lane));
                }
                __syncwarp();
                #pragma unroll 1
                for (int s = 2; s < 16; s++) {
                    sleep_until(t0 + W2OFF + s * W2PACE);
                    if (elect_one()) load_slab(s, true);
                    __syncwarp();
                }
            }
          } else {
          }
          if (elect_one()) {
              const int h = ~warp & 1;
              const char* src1 = (const char*)&g_hn[(rank * 16 + h) * 3584 + g1j * 896];
              const char* src2 = (const char*)&g_g[(rank * 14 + h) * 3584 + g2j * 896];
              const long long jump = src2 - src1 - (16 * 57344 + 2 * 14336);
              const char* src = g1_on ? src1 - 2 * 57344 : src2;
              const uint32_t amask = g1_on ? (h ? kAMask1 : kAMask0) : 0u;
              uint32_t slot = g1_on ? NB - 2 + h : h, ph = g1_on ? 0 : 1, gate = g1_on ? 0 : 2;
              CAP_DECL(ti_, 0);
              #pragma unroll 1
              for (int q = g1_on ? 0 : 17; q < 31; q++) {
                  const uint32_t eb = q ? BAR(B_BE) + slot * 8 : BAR(B_XF), dst = sb + SM_B + slot * 14336;
                  if ((0x1020003u >> q) & 1) {
                      mbar_wait(BAR(B_HD + gate), 0);
                      const uint32_t tg = lds1(sb + SM_TG + gate * 4) + h * 64;
                      int it = 0;
                      if (gate < 2) while ((int)(gtime32() - tg) < 0 && ++it < 64) {}
                      else spin_until(tg);
                      gate++;
                  }
                  if (!mbar_try(eb, ph)) mbar_wait(eb, ph);
                  if (q) {
                      bulk_g2s(dst, src, 14336, eb + (B_BL - B_BE) * 8);
                      mbar_expect(eb + (B_BL - B_BE) * 8, 14336);
                      CAP(ti_);
                  }
                  mbar_arrive_remote_if(pbar0 + 8u * B_PD, h && q == 12);
                  if ((amask >> q) & 1) {
                      if (q < 12) load_slab(8 + __popc(amask & ((1u << q) - 1)), false);
                      else load_slab(2 + ((2 * q + h - 27) * 13 + 19) / 20, true);
                  }
                  src += 2 * 57344 + (q == 8 ? 2 * 14336 - 16 * 57344 : q == 16 ? jump : q == 23 ? 2 * 14336 - 14 * 57344 : 0);
                  slot += 2;
                  if (slot >= NB) { slot -= NB; ph ^= 1; }
              }
          }
        } else {
          uint32_t tag;
          if (warp == 10) {
            mbar_wait(BAR(PFBAR), 0);
            const char* p1 = (const char*)prm.w1 + (size_t)b * 57344 + lane * 128;
            const char* p2 = (const char*)prm.w2 + (size_t)b * 57344 + lane * 128;
            if (lane < 25) asm volatile("prefetch.global.L2 [%0];" :: "l"((const char*)prm.wo + min(b * 25 + lane, 3135) * 128));
            uint32_t tnext = (uint32_t)clock();
            #pragma unroll 1
            for (int i = 0; i < 28; i++) {
                asm volatile("prefetch.global.L2 [%0];" :: "l"(i < 14 ? p1 + i * 4096 : p2 + (i - 14) * 4096));
                tnext += PFPACE;
                while ((int)((uint32_t)clock() - tnext) < 0) __nanosleep(40);
            }
            mbar_wait(BAR(B_EP), 0);
            tag = lds1(sb + SM_EPOCH);
          } else {
            tag = *(volatile uint32_t*)&g_epoch + 1;
            const uint4 z4 = make_uint4(0u, 0u, 0u, 0u);
            #pragma unroll 1
            for (int i = 0; i < 14; i++) g_halo[(ti * 8 + hg) * 448 + i * 32 + lane] = z4;
            g_stats[(a2s * 4 + a2j) * 64 + lane] = z4; g_stats[(a2s * 4 + a2j) * 64 + 32 + lane] = z4;
            g_flag_h[(a2s * 4 + a2j) * FS + lane] = 0;
            #pragma unroll 1
            for (int i = 0; i < 2; i++) ((uint4*)g_flag_o)[((ti * 8 + i * 4 + (lane >> 3)) * 8 + hg) * 8 + (lane & 7)] = z4;
            __syncwarp();
            if (lane == 0) {
                asm volatile("st.shared.u32 [%0], %1;" :: "r"(sb + SM_EPOCH), "r"(tag) : "memory");
                mbar_arrive(BAR(B_EP));
            }
            if (lane < 4) mbar_expect(BAR(B_RF + lane), 7168);
            __syncwarp();
            TRW(44);
            const uint32_t* fp = &g_flag_h[(rank * 64 + lane) * FS];
            mbar_wait(BAR(B_HD), 0);
            uint64_t v0 = 0, v1 = 0;
            int it = 0;
            do {
                ld_flag_if(v0, fp, (uint32_t)v0 != tag); ld_flag_if(v1, fp + 32 * FS, (uint32_t)v1 != tag);
                if (++it > kSpinLimit) { TIMEOUT(108); break; }
            } while (__any_sync(~0u, (uint32_t)v0 != tag || (uint32_t)v1 != tag));
            const uint32_t gbase = __shfl_sync(~0u, (uint32_t)(v0 >> 32), 0);
            const uint32_t tg = gbase + DELTA + __reduce_max_sync(~0u, max((int)((uint32_t)(v0 >> 32) - gbase), (int)((uint32_t)(v1 >> 32) - gbase)));
            if (lane == 0) {
                asm volatile("st.shared.u32 [%0], %1;" :: "r"(sb + SM_TG + 4), "r"(tg) : "memory");
                mbar_arrive(BAR(B_GO));
            }
            __syncwarp();
            TRW(40);
          }
          const int h = warp & 1;
          const bool lead = elect_one();
          const uint32_t w2o = lane * 128 + ((lane + 16 * g2j) & 31) * 4, l3 = lane < 16 ? 12288 : 0;
          uint32_t wo = g1_on ? w2o ^ ((g1j ^ g2j) << 6) : w2o, slot = h, ph = 0, rph = 0, af = BAR(B_AF + h + (g1_on ? 0 : 2)), aph = 0;
          #pragma unroll 1
          for (int q = g1_on ? 1 : 17; q < 31; q++) {
              const uint32_t rb = bar0 + slot * 8, dst = sb + SM_B + slot * 14336;
              auto stale = [&]() {
                  uint32_t d;
                  asm volatile("{ .reg .b32 x, y, z, u;\n"
                               "ld.shared.u32 x, [%1]; ld.shared.u32 y, [%1 + 4096]; ld.shared.u32 z, [%1 + 8192]; ld.shared.u32 u, [%2];\n"
                               "lop3.b32 x, x, y, %3, 0x7e; lop3.b32 z, z, u, %3, 0x7e; lop3.b32 %0, x, z, 1, 0xa8; }"
                               : "=r"(d) : "r"(dst + wo), "r"(dst + wo + l3), "r"(tag) : "memory");
                  return __any_sync(~0u, d);
              };
              mbar_wait(rb + B_BF * 8, ph ^ 1);
              mbar_wait(rb + B_BL * 8, ph);
              const bool aok = mbar_test(af, aph);
              bool bad = stale();
              if (!aok) mbar_wait(af, aph);
              mbar_arrive_if(rb + B_BF * 8, lead && !bad);
              if (bad) {
                  RETRY_COUNT(2);
                  const int e = (q > 8) + (q > 16) + (q > 23), s = (q - (e < 3 ? 1 + 8 * e : 24)) * 2 + h;
                  const char* src = (const char*)(e < 2 ? &g_hn[(rank * 16 + s) * 3584 + (g1j + 2 * e) * 896] : &g_g[(rank * 14 + s) * 3584 + (g2j + 2 * e - 4) * 896]);
                  int it = 0;
                  do {
                      if (++it > kSpinLimit) { TIMEOUT(111); break; }
                      const uint32_t* p = (const uint32_t*)(src + wo);
                      if (__any_sync(~0u, ((ld_rlx(p) ^ tag) | (ld_rlx(p + 1024) ^ tag) | (ld_rlx(p + 2048) ^ tag) | (ld_rlx(p + l3 / 4) ^ tag)) & 1)) continue;
                      if (lead) {
                          mbar_expect(BAR(B_RT + h), 14336);
                          bulk_g2s(dst, src, 14336, BAR(B_RT + h));
                      }
                      __syncwarp();
                      mbar_wait(BAR(B_RT + h), rph);
                      rph ^= 1;
                      bad = stale();
                  } while (bad);
                  mbar_arrive_if(rb + B_BF * 8, lead);
              }
              if (q == 16) { wo = w2o; aph = 1; }
              af += q == 8 ? -112 : (0x810000u >> q) & 1 ? -96 : 16;
              slot += 2;
              if (slot >= NB) { slot -= NB; ph ^= 1; }
          }
        }
    } else {
        asm volatile("setmaxnreg.inc.sync.aligned.u32 232;");
        asm volatile("barrier.cluster.wait.aligned;" ::: "memory");
        const int wg = warp >> 2, w = warp & 3;
        const int g = lane >> 2, t = lane & 3;
        uint32_t tag;
        __nv_bfloat16 bias1;
        {
            uint32_t a[28][4];
            float sm0[4] = {0.f, 0.f, 0.f, 0.f}, sm1[4] = {0.f, 0.f, 0.f, 0.f};
            {
                const int r = w * 16 + (lane & 15);
                const uint32_t rowa = sb + SM_X + wg * 57344 + r * 128;
                #pragma unroll
                for (int kb = 0; kb < 7; kb++) {
                    mbar_wait(BAR(B_XF + kb), 0);
                    #pragma unroll
                    for (int q = 0; q < 4; q++) {
                        const uint32_t addr = rowa + kb * 8192 + (((q * 2 + (lane >> 4)) ^ (r & 7)) << 4);
                        uint32_t (&f)[4] = a[kb * 4 + q];
                        asm volatile("ldmatrix.sync.aligned.m8n8.x4.shared.b16 {%0,%1,%2,%3}, [%4];"
                                     : "=r"(f[0]), "=r"(f[1]), "=r"(f[2]), "=r"(f[3]) : "r"(addr) : "memory");
                        if (q & 1) mma16816(sm1, f[0], f[1], f[2], f[3], 0x3F803F80u, 0x3F803F80u);
                        else       mma16816(sm0, f[0], f[1], f[2], f[3], 0x3F803F80u, 0x3F803F80u);
                    }
                }
            }
            const float mean0 = (sm0[0] + sm1[0]) * (1.f / kD), mean1 = (sm0[2] + sm1[2]) * (1.f / kD);
            const uint32_t mb0 = pack_bf16(mean0, mean0), mb1 = pack_bf16(mean1, mean1);
            pair_arrive(B_XC);
            TR(1);
            float ak[28], av[28], aq[28];
            float ss0 = 0.f, ss1 = 0.f, ss2 = 0.f, ss3 = 0.f;
            const uint64_t dw = make_desc(sb + (hg & 1) * 16, 0, true);
            static_for<0, 7>([&](auto S_) {
                constexpr int s = decltype(S_)::value;
                #pragma unroll
                for (int q = 0; q < 4; q++) {
                    uint32_t (&f)[4] = a[s * 4 + q];
                    f[0] = sub_bf16x2(f[0], mb0); f[1] = sub_bf16x2(f[1], mb1);
                    f[2] = sub_bf16x2(f[2], mb0); f[3] = sub_bf16x2(f[3], mb1);
                    ss0 = fmaf(bf_lo(f[0]), bf_lo(f[0]), ss0); ss2 = fmaf(bf_hi(f[0]), bf_hi(f[0]), ss2);
                    ss1 = fmaf(bf_lo(f[1]), bf_lo(f[1]), ss1); ss3 = fmaf(bf_hi(f[1]), bf_hi(f[1]), ss3);
                    ss0 = fmaf(bf_lo(f[2]), bf_lo(f[2]), ss0); ss2 = fmaf(bf_hi(f[2]), bf_hi(f[2]), ss2);
                    ss1 = fmaf(bf_lo(f[3]), bf_lo(f[3]), ss1); ss3 = fmaf(bf_hi(f[3]), bf_hi(f[3]), ss3);
                }
                mbar_wait(BAR(B_WKVF + s), 0);
                wg_fence();
                static_for<0, 4>([&](auto Q_) {
                    constexpr int q = decltype(Q_)::value;
                    uint32_t (&f)[4] = a[s * 4 + q];
                    wgmma_rs_n56<SM_WKV + s * 16384 + q * 2048, (s | q) != 0>(ak, f[0], f[1], f[2], f[3], dw);
                    wgmma_rs_n56<SM_WKV + s * 16384 + q * 2048 + 8192, (s | q) != 0>(av, f[0], f[1], f[2], f[3], dw);
                });
                wg_commit();
                if (s == 4) { wg_wait<1>(); pair_arrive(B_KV3); }
            });
            auto q_chunk = [&](auto C_) {
                wg_fence();
                static_for<0, 7>([&](auto K_) {
                    constexpr int k = decltype(C_)::value * 7 + decltype(K_)::value;
                    wgmma_rs_n56<SM_X + k * 2048, k != 0>(aq, a[k][0], a[k][1], a[k][2], a[k][3], dw);
                });
                wg_commit();
            };
            const float dl0 = mean0 - bf_lo(mb0), dl1 = mean1 - bf_lo(mb1);
            const float rs0 = rsq(fmaxf(quad_sum(ss0 + ss2) * (1.f / kD) - dl0 * dl0, 0.f) + kEps);
            const float rs1 = rsq(fmaxf(quad_sum(ss1 + ss3) * (1.f / kD) - dl1 * dl1, 0.f) + kEps);
            mbar_wait2(BAR(B_EP), 0, BAR(B_WQF), 0);
            asm volatile("ld.shared.u32 %0, [%1];" : "=r"(tag) : "r"(sb + SM_EPOCH) : "memory");
            q_chunk(std::integral_constant<int, 0>{});
            wg_wait<1>();
            reg_fence(ak); reg_fence(av);
            TR(2);
            uint32_t kf[3][7], vf[3][7];
            #pragma unroll
            for (int c = 0; c < 7; c++) {
                kf[2][c] = pack_bf16(ak[4 * c + 2] * rs1, ak[4 * c + 3] * rs1);
                vf[2][c] = movm(pack_bf16(av[4 * c + 2] * rs1, av[4 * c + 3] * rs1));
            }
            const uint32_t stg = sb + SM_RED + (1 - wg) * 16384 + lane * 16;
            if (w == 3) {
                uint4* hp = &g_halo[((ti * 8 + hg) * 2 + wg) * 7 * 32 + lane];
                #pragma unroll
                for (int c = 0; c < 7; c++) st_ll(hp + c * 32, kf[2][c], vf[2][c], tag);
            } else {
                sts4(stg + w * 2048 + 0,    kf[2][0], kf[2][1], kf[2][2], kf[2][3]);
                sts4(stg + w * 2048 + 512,  kf[2][4], kf[2][5], kf[2][6], vf[2][0]);
                sts4(stg + w * 2048 + 1024, vf[2][1], vf[2][2], vf[2][3], vf[2][4]);
                sts4(stg + w * 2048 + 1536, vf[2][5], vf[2][6], 0u, 0u);
            }
            pair_arrive(B_KVC);
            q_chunk(std::integral_constant<int, 1>{});
            #pragma unroll
            for (int c = 0; c < 7; c++) {
                kf[1][c] = pack_bf16(ak[4 * c] * rs0, ak[4 * c + 1] * rs0);
                vf[1][c] = movm(pack_bf16(av[4 * c] * rs0, av[4 * c + 1] * rs0));
            }
            named_bar(1 + wg, 128);
            q_chunk(std::integral_constant<int, 2>{});
            q_chunk(std::integral_constant<int, 3>{});
            if (w == 0) {
                if (ti > 0) {
                    const uint4* hp = &g_halo[(((ti - 1) * 8 + hg) * 2 + wg) * 7 * 32 + lane];
                    int it = 0; bool ok;
                    do {
                        ok = true;
                        #pragma unroll
                        for (int c = 0; c < 7; c++) ok &= ld_ll(hp + c * 32, kf[0][c], vf[0][c], tag);
                        if (++it > kSpinLimit) { TIMEOUT(101); break; }
                    } while (!__all_sync(~0u, ok));
                } else {
                    #pragma unroll
                    for (int c = 0; c < 7; c++) { kf[0][c] = 0u; vf[0][c] = 0u; }
                }
            } else {
                const uint4 u0 = lds4(stg + (w - 1) * 2048), u1 = lds4(stg + (w - 1) * 2048 + 512),
                            u2 = lds4(stg + (w - 1) * 2048 + 1024), u3 = lds4(stg + (w - 1) * 2048 + 1536);
                kf[0][0] = u0.x; kf[0][1] = u0.y; kf[0][2] = u0.z; kf[0][3] = u0.w;
                kf[0][4] = u1.x; kf[0][5] = u1.y; kf[0][6] = u1.z; vf[0][0] = u1.w;
                vf[0][1] = u2.x; vf[0][2] = u2.y; vf[0][3] = u2.z; vf[0][4] = u2.w;
                vf[0][5] = u3.x; vf[0][6] = u3.y;
            }
            uint4* op = opaque_ptr(&g_o[(((ti * 2 + wg) * 4 + w) * 28 + ((7 * hg) >> 1)) * 32 + lane]);
            uint32_t* ofl = opaque_ptr(&g_flag_o[(((ti * 2 + wg) * 4 + w) * 8 + hg) * FS]);
            TR(3);
            wg_wait<0>();
            reg_fence(aq);
            warp_arrive(BAR(B_A1D));
            TR(4);
            uint32_t qf[7][2];
            #pragma unroll
            for (int c = 0; c < 7; c++) {
                qf[c][0] = pack_bf16(aq[4 * c], aq[4 * c + 1]);
                qf[c][1] = pack_bf16(aq[4 * c + 2], aq[4 * c + 3]);
            }
            const bool has_prev = (ti > 0) || (w > 0);
            const float sc0 = rs0 * (0.18898223650461362f * 1.4426950408889634f);
            const float sc1 = rs1 * (0.18898223650461362f * 1.4426950408889634f);
            const float NEG = -__int_as_float(0x7f800000);
            uint32_t ow[7][2];
            #pragma unroll
            for (int hd = 0; hd < 2; hd++) {
                const int c0 = hd * 3;
                const bool keep = hd == 0 ? (t < 2) : (t >= 2);
                const uint32_t q3a = keep ? qf[3][0] : 0u, q3b = keep ? qf[3][1] : 0u;
                float sc_[3][4];
                #pragma unroll
                for (int n = 0; n < 3; n++) {
                    sc_[n][0] = sc_[n][1] = sc_[n][2] = sc_[n][3] = 0.f;
                    if (hd == 0) {
                        mma16816(sc_[n], qf[0][0], qf[0][1], qf[1][0], qf[1][1], kf[n][0], kf[n][1]);
                        mma16816(sc_[n], qf[2][0], qf[2][1], q3a, q3b, kf[n][2], kf[n][3]);
                    } else {
                        mma16816(sc_[n], q3a, q3b, qf[4][0], qf[4][1], kf[n][3], kf[n][4]);
                        mma16816(sc_[n], qf[5][0], qf[5][1], qf[6][0], qf[6][1], kf[n][5], kf[n][6]);
                    }
                }
                const bool gt0 = 2 * t > g, gt1 = 2 * t + 1 > g;
                const float e0 = gt0 ? (has_prev ? sc_[0][0] : NEG) : sc_[1][0], e1 = gt1 ? (has_prev ? sc_[0][1] : NEG) : sc_[1][1];
                const float f0 = gt0 ? sc_[1][2] : sc_[2][2], f1 = gt1 ? sc_[1][3] : sc_[2][3];
                const float me = quad_max(fmaxf(e0, e1)) * sc0, mf = quad_max(fmaxf(f0, f1)) * sc1;
                float p0 = ex2(fmaf(e0, sc0, -me)), p1 = ex2(fmaf(e1, sc0, -me));
                float r0 = ex2(fmaf(f0, sc1, -mf)), r1 = ex2(fmaf(f1, sc1, -mf));
                const float ie = rcp(quad_sum(p0 + p1)), jf = rcp(quad_sum(r0 + r1));
                const uint32_t pp = pack_bf16(p0 * ie, p1 * ie), rp = pack_bf16(r0 * jf, r1 * jf);
                const uint32_t mk = (gt0 ? 0x0000ffffu : 0u) | (gt1 ? 0xffff0000u : 0u);
                const uint32_t sw = hg >= 4 ? ~0u : 0u;
                const uint32_t pa0 = pp & mk & ~sw, pa1 = pp & mk & sw, pb0 = rp & ~mk & sw, pb1 = rp & ~mk & ~sw;
                const uint32_t pa2 = sw ? rp & mk : pp & ~mk, pa3 = sw ? pp & ~mk : rp & mk;
                #pragma unroll
                for (int c = 0; c < 4; c++) {
                    float o[4] = {0.f, 0.f, 0.f, 0.f};
                    mma16816(o, pa0, pa1, pa2, pa3, vf[0][c0 + c], vf[1][c0 + c]);
                    mma1688(o, pb0, pb1, vf[2][c0 + c]);
                    const uint32_t lo = pack_bf16(o[0], o[1]), hi = pack_bf16(o[2], o[3]);
                    if (hd == 1 && c == 0) { if (t >= 2) { ow[3][0] = lo; ow[3][1] = hi; } }
                    else { ow[c0 + c][0] = lo; ow[c0 + c][1] = hi; }
                }
            }
            const uint32_t om = ~lane & 1;
            if (hg & 1) {
                stg2((uint2*)(op - lane) + 32 + lane, set_par(ow[0][0], om, tag), ow[0][1]);
                stg4(op + 32, set_par(ow[1][0], om, tag), ow[1][1], ow[2][0], ow[2][1]);
                stg4(op + 64, set_par(ow[3][0], om, tag), ow[3][1], ow[4][0], ow[4][1]);
                stg4(op + 96, set_par(ow[5][0], om, tag), ow[5][1], ow[6][0], ow[6][1]);
            } else {
                stg4(op,      set_par(ow[0][0], om, tag), ow[0][1], ow[1][0], ow[1][1]);
                stg4(op + 32, set_par(ow[2][0], om, tag), ow[2][1], ow[3][0], ow[3][1]);
                stg4(op + 64, set_par(ow[4][0], om, tag), ow[4][1], ow[5][0], ow[5][1]);
                stg2((uint2*)(op + 96 - lane) + lane, set_par(ow[6][0], om, tag), ow[6][1]);
            }
            if (lane == 0) asm volatile("st.relaxed.gpu.global.u32 [%0], %1;" :: "l"(ofl), "r"(tag) : "memory");
            TR(5);
        }
        {
            float acc2[64];
            const bool wide = a2j != 3;
            mbar_wait(BAR(B_XRF), 0);
            {
                const uint32_t xa = sb + SM_X + 8 * 8192 + (w * 16 + wg * 8 + (lane & 7)) * 128;
                #pragma unroll
                for (int c = 0; c < 4; c++) {
                    uint32_t xr[4];
                    asm volatile("ldmatrix.sync.aligned.m8n8.x4.shared.b16 {%0,%1,%2,%3}, [%4];"
                                 : "=r"(xr[0]), "=r"(xr[1]), "=r"(xr[2]), "=r"(xr[3])
                                 : "r"(xa + (c >> 1) * 8192 + ((((c & 1) * 4 + (lane >> 3)) ^ (lane & 7)) << 4)) : "memory");
                    #pragma unroll
                    for (int e = 0; e < 4; e++) {
                        acc2[16 * c + 4 * e] = bf_lo(xr[e]); acc2[16 * c + 4 * e + 1] = bf_hi(xr[e]);
                        acc2[16 * c + 4 * e + 2] = 0.f;      acc2[16 * c + 4 * e + 3] = 0.f;
                    }
                }
            }
            const uint4* op = &g_o[((a2s * 4 + w) * 28 + wg * 14) * 32];
            const uint32_t rsend = opaque(sb + SM_RED + (1 - wg) * 16384 + w * 4096 + lane * 16);
            const uint32_t rrecv = opaque(sb + SM_RED + wg * 16384 + w * 4096 + lane * 16);
            uint4* spw = opaque_ptr(&g_stats[(a2s * 4 + a2j) * 64 + (w * 2 + wg) * 8 + g]);
            const uint4* spr = opaque_ptr(&g_stats[(a2s * 4 + t) * 64 + (w * 2 + wg) * 8 + g]);
            uint2* hp = opaque_ptr((uint2*)g_h + ((a2s * 8 + w * 2 + wg) * 28 + a2j * 8) * 32 + lane);
            uint32_t* np = opaque_ptr((uint32_t*)&g_hn[(a2s * 56 + a2j * 16) * 64] + (w * 2 + wg) * 32 + lane);
            uint32_t* nfl = opaque_ptr(&g_flag_h[(a2s * 4 + a2j) * FS]);
            const uint64_t dwo = make_desc(sb + SM_WKV + wg * 57344, 28672, true);
            bias1 = prm.b1[g1f * 64 + w * 16 + rank * 8 + g];
            const __nv_bfloat16 bias2 = prm.b2[ti * 128 + (w * 16 + wg * 8 + g) * 2 + a2p];
            reg_fence(acc2);
            mbar_wait(BAR(B_WOF + wg), 0);
            {
                const uint32_t* pp = &g_flag_o[((a2s * 4 + w) * 8 + wg * 4 + t) * FS];
                int it = 0;
                while (__any_sync(~0u, ld_rlx(pp) != tag)) { if (++it > kSpinLimit) { TIMEOUT(102); break; } }
            }
            TR(6);
            uint4 of[14];
            auto load_o = [&](int k) {
                if (k % 7 == 3) {
                    const uint2 lo = ld_rlx2((const uint2*)(op + k * 32) + lane), hi = ld_rlx2((const uint2*)(op + k * 32) + 32 + lane);
                    of[k] = make_uint4(lo.x, lo.y, hi.x, hi.y);
                } else of[k] = ld_rlx4(op + k * 32 + lane);
            };
            #pragma unroll
            for (int k = 0; k < 14; k++) load_o(k);
            static_for<0, 4>([&](auto G_) {
                constexpr int k0 = (decltype(G_)::value * 7) / 2, k1 = (decltype(G_)::value * 7 + 7) / 2;
                int it = 0;
                while (true) {
                    uint32_t bad = 0;
                    #pragma unroll
                    for (int k = k0; k < k1; k++) bad |= (of[k].x ^ tag) | (k % 7 == 3 ? of[k].z ^ tag : 0u);
                    if (!__any_sync(~0u, bad & ~lane & 1)) break;
                    if (++it > kSpinLimit) { TIMEOUT(109); break; }
                    RETRY_COUNT(1);
                    #pragma unroll
                    for (int k = k0; k < k1; k++) load_o(k);
                }
                if (k1 == 14) warp_arrive(BAR(B_OL));
                wg_fence();
                static_for<k0, k1>([&](auto K_) { constexpr int k = decltype(K_)::value;
                    wgmma_rs_n128<k * 2048, 1>(acc2, of[k].x, of[k].y, of[k].z, of[k].w, dwo); });
            });
            wg_commit();
            wg_wait<0>();
            reg_fence(acc2);
            TR(7);
            #pragma unroll
            for (int c = 0; c < 8; c++)
                sts4(rsend + c * 512, __float_as_uint(acc2[8 * c + 2]), __float_as_uint(acc2[8 * c + 3]), __float_as_uint(acc2[8 * c + 6]), __float_as_uint(acc2[8 * c + 7]));
            named_bar(3, 256);
            float hv[32];
            float s0 = 0.f, s1 = 0.f, q0 = 0.f, q1 = 0.f;
            #pragma unroll
            for (int c = 0; c < 8; c++) {
                const uint4 u = lds4(rrecv + c * 512);
                hv[4 * c]     = acc2[8 * c] + __uint_as_float(u.x);     hv[4 * c + 1] = acc2[8 * c + 1] + __uint_as_float(u.y);
                hv[4 * c + 2] = acc2[8 * c + 4] + __uint_as_float(u.z); hv[4 * c + 3] = acc2[8 * c + 5] + __uint_as_float(u.w);
            }
            #pragma unroll
            for (int c = 0; c < 16; c += 2) { s0 += hv[c]; s1 += hv[c + 1]; q0 = fmaf(hv[c], hv[c], q0); q1 = fmaf(hv[c + 1], hv[c + 1], q1); }
            if (wide) {
                #pragma unroll
                for (int c = 16; c < 32; c += 2) { s0 += hv[c]; s1 += hv[c + 1]; q0 = fmaf(hv[c], hv[c], q0); q1 = fmaf(hv[c + 1], hv[c + 1], q1); }
            }
            s0 = quad_sum(s0 + s1); q0 = quad_sum(q0 + q1);
            if (t == 0) st_ll(spw, __float_as_uint(s0), __float_as_uint(q0), tag);
            TR(8);
            fence_async_smem();
            const float b2v = __bfloat162float(bias2);
            #pragma unroll
            for (int c = 0; c < 8; c++)
                if (c < 4 || wide) stg2(hp + c * 32, set_par(pack_bf16(hv[4 * c] + b2v, hv[4 * c + 1] + b2v), t == 0, tag), pack_bf16(hv[4 * c + 2] + b2v, hv[4 * c + 3] + b2v));
            const uint32_t nm = opaque((lane & 7) == w * 2 + wg ? 1u << (lane >> 3) : 0u);
            uint32_t um, uv;
            {
                int it = 0;
                while (!__all_sync(~0u, ld_ll(spr, um, uv, tag))) { if (++it > kSpinLimit) { TIMEOUT(103); break; } }
            }
            TR(9);
            const float mean = quad_sum(__uint_as_float(um)) * (1.f / kD);
            const float var = fmaxf(fmaf(quad_sum(__uint_as_float(uv)), 1.f / kD, -mean * mean), 0.f);
            const float r1 = rsq(var + kEps);
            const float rr = 0.5f * r1 * rsq(fmaf(var * r1, r1, kEps));
            const float mr = -mean * rr;
            #pragma unroll
            for (int c = 0; c < 16; c++)
                if (c < 8 || wide) stg1(np + c * 256, set_par(pack_bf16(fmaf(hv[2 * c], rr, mr), fmaf(hv[2 * c + 1], rr, mr)), (nm >> (c & 3)) & 1, tag));
            named_bar(3, 256);
            mbar_arrive_remote_if(pbar0 + 8u * B_PD, tid == 0 && !g1_on);
            if (tid == 128) {
                st_flag(nfl, tag);
                asm volatile("st.shared.u32 [%0], %1;" :: "r"(sb + SM_TG), "r"(gtime32()) : "memory");
                mbar_arrive(BAR(B_HD));
            }
            __syncwarp();
            TR(10);
        }
        float acc[56];
        const uint32_t xch = opaque(sb + SM_XCH + w * 1920 + lane * 16);
        uint32_t peer_xch; const uint32_t peer_bar = pbar0;
        asm volatile("mapa.shared::cluster.u32 %0, %1, %2;" : "=r"(peer_xch) : "r"(xch), "r"(rank ^ 1));
        uint2 hr[7];
        const int tok = g2s * 64 + w * 16 + rank * 8 + g, pr = (tok & 127) >> 1;
        const uint2* hp = (const uint2*)g_h + ((((tok >> 7) * 2 + (tok & 1)) * 8 + (pr >> 3)) * 28 + (g2j + 2 * wg) * 7) * 32 + (pr & 7) * 4 + t;
        auto load_h = [&]() {
            #pragma unroll
            for (int c = 0; c < 7; c++) hr[c] = ld_rlx2(hp + c * 32);
        };
        const uint32_t b1h = pack_bf16(0.5f * __bfloat162float(bias1), 0.5f * __bfloat162float(bias1));
        #pragma unroll
        for (int c = 0; c < 7; c++) hr[c] = make_uint2(b1h, b1h);
        if (!g1_on) { mbar_wait(BAR(B_GO), 0); load_h(); }
        uint32_t* const gp1 = (uint32_t*)&g_g[(g1f * 56 + (g1j + 2 * wg) * 14) * 64] + (w * 2 + rank) * 32 + lane;
        uint32_t* const gp2 = (uint32_t*)(prm.out + (size_t)(g2s * 64 + w * 16 + rank * 8 + (lane >> 4)) * kD + (g2j + 2 * wg) * 112) + (lane & 15) * 4;
        uint32_t gm[4];
        #pragma unroll
        for (int i = 0; i < 4; i++) gm[i] = lane == ((g1j * 2 + i) & 3) * 8 + w * 2 + rank;
        const bool lead = elect_one();
        const uint64_t da0 = make_desc(sb, 0, true), db0 = make_desc(sb + SM_B, 128, false);
        #pragma unroll 1
        for (int ge = g1_on ? 0 : 1; ge < 2; ge++) {
            if (ge) {
                int it = 0;
                while (true) {
                    uint32_t bad = 0;
                    #pragma unroll
                    for (int c = 0; c < 7; c++) bad |= hr[c].x ^ tag;
                    if (!__any_sync(~0u, t == 0 && (bad & 1))) break;
                    if (++it > kSpinLimit) { TIMEOUT(110); break; }
                    load_h();
                }
            }
            auto init_acc = [&](auto R_) {
                constexpr int o = decltype(R_)::value * 2;
                #pragma unroll
                for (int c = 0; c < 14; c++) {
                    const uint32_t hw = c & 1 ? hr[c >> 1].y : hr[c >> 1].x;
                    acc[4 * c + o] = bf_lo(hw); acc[4 * c + 1 + o] = bf_hi(hw);
                    acc[4 * c + 2 - o] = 0.f;   acc[4 * c + 3 - o] = 0.f;
                }
                reg_fence(acc);
            };
            if (rank) init_acc(std::integral_constant<int, 1>{}); else init_acc(std::integral_constant<int, 0>{});
            const uint32_t slot0 = g1_on ? (ge ? 4 : 2 * wg) : 0;
            uint32_t ph = 0, rb = bar0 + slot0 * 8;
            uint64_t da = da0 + ge * 1024, db = db0 + slot0 * 896;
            uint32_t prev = BAR(B_WKVF);
            mbar_wait(BAR(B_EP), 0);
            if (wg == 1 || (ge && g1_on)) named_bar(5 - wg, 256);
            mbar_wait(rb + B_BF * 8, ph);
            TR(11 + ge * 4);
            #pragma unroll 1
            for (int n = ge ? 14 : 16;;) {
                wg_fence();
                wgmma_ss_n112<0,    0>(acc, da, db);
                wgmma_ss_n112<2048, 256>(acc, da, db);
                wgmma_ss_n112<4096, 512>(acc, da, db);
                wgmma_ss_n112<6144, 768>(acc, da, db);
                wg_commit();
                if (--n == 0 && ge + wg < 2) named_arrive(4 + wg, 256);
                const uint32_t cur = rb + B_BE * 8;
                da += 512; db += 896; rb += 8;
                if (rb == bar0 + NB * 8) { rb = bar0; db = db0; ph ^= 1; }
                wg_wait<1>();
                mbar_arrive_if(prev, lead);
                prev = cur;
                if (n == 0) break;
                if (!mbar_try(rb + B_BF * 8, ph)) mbar_wait(rb + B_BF * 8, ph);
            }
            const int use = ge * 2 + wg;
            const uint32_t xfree = BAR(use > (g1_on ? 0 : 2) ? B_RE + use - 1 : B_PD);
            const bool xok = mbar_test(xfree, 0);
            wg_wait<0>();
            reg_fence(acc);
            mbar_arrive_if(prev, lead);
            TR(12 + ge * 4);
            if (!xok) mbar_wait(xfree, 0);
            float v[28];
            auto reduce = [&](auto R_) {
                constexpr int o = decltype(R_)::value * 2;
                const uint32_t rf = peer_bar + (B_RF + use) * 8;
                float dly = __uint_as_float(0x3f800000u | lane); uint32_t pa = peer_xch;
                #pragma unroll
                for (int c = 0; c < 4; c++) {
                    const uint32_t p0 = pack_bf16(acc[16 * c + 2 - o], acc[16 * c + 3 - o]), p1 = pack_bf16(acc[16 * c + 6 - o], acc[16 * c + 7 - o]);
                    if (c < 3) {
                        const uint32_t p2 = pack_bf16(acc[16 * c + 10 - o], acc[16 * c + 11 - o]), p3 = pack_bf16(acc[16 * c + 14 - o], acc[16 * c + 15 - o]);
                        asm volatile("st.async.shared::cluster.mbarrier::complete_tx::bytes.v4.b32 [%0], {%1,%2,%3,%4}, [%5];"
                                     :: "r"(pa + c * 512), "r"(p0), "r"(p1), "r"(p2), "r"(p3), "r"(rf) : "memory");
                        if (use != 3) {
                            #pragma unroll
                            for (int i = 0; i < XPACE; i++) asm volatile("tanh.approx.f32 %0, %0;" : "+f"(dly) :: "memory");
                            pa += __float_as_uint(dly) >> 30;
                        }
                    } else {
                        asm volatile("st.async.shared::cluster.mbarrier::complete_tx::bytes.v2.b32 [%0], {%1,%2}, [%3];"
                                     :: "r"(pa + 1536 - lane * 8), "r"(p0), "r"(p1), "r"(rf) : "memory");
                    }
                }
                if (!ge) load_h();
                mbar_wait(BAR(B_RF + use), 0);
                #pragma unroll
                for (int c = 0; c < 4; c++) {
                    uint4 u;
                    if (c < 3) u = lds4(xch + c * 512); else { const uint2 u2 = lds2(xch + 1536 - lane * 8); u.x = u2.x; u.y = u2.y; }
                    v[8 * c]     = acc[16 * c + o] + bf_lo(u.x);     v[8 * c + 1] = acc[16 * c + 1 + o] + bf_hi(u.x);
                    v[8 * c + 2] = acc[16 * c + 4 + o] + bf_lo(u.y); v[8 * c + 3] = acc[16 * c + 5 + o] + bf_hi(u.y);
                    if (c < 3) {
                        v[8 * c + 4] = acc[16 * c + 8 + o] + bf_lo(u.z);  v[8 * c + 5] = acc[16 * c + 9 + o] + bf_hi(u.z);
                        v[8 * c + 6] = acc[16 * c + 12 + o] + bf_lo(u.w); v[8 * c + 7] = acc[16 * c + 13 + o] + bf_hi(u.w);
                    }
                }
            };
            if (rank) reduce(std::integral_constant<int, 1>{}); else reduce(std::integral_constant<int, 0>{});
            TR(13 + ge * 4);
            if (!ge) {
                #pragma unroll
                for (int c = 0; c < 14; c++) {
                    float r[2];
                    #pragma unroll
                    for (int e = 0; e < 2; e++) {
                        const float u = v[2 * c + e];
                        r[e] = fmaf(u, tanh_hw(u * fmaf(u * u, 8.f * 0.7978845608f * 0.044715f, 2.f * 0.7978845608f)), u);
                    }
                    stg1(gp1 + c * 256, set_par(pack_bf16(r[0], r[1]), gm[c & 3], tag));
                }
                named_bar(1 + wg, 128);
                if (w == 0 && lane == 0) {
                    asm volatile("st.shared.u32 [%0], %1;" :: "r"(sb + SM_TG + 8 + wg * 4), "r"(clk32() + XSPEC) : "memory");
                    mbar_arrive(BAR(B_GD + wg));
                }
                mbar_arrive_remote_if(peer_bar + (B_RE + use) * 8, lead);
            } else {
                const uint32_t stw = xch - lane * 16;
                uint32_t pk[14];
                #pragma unroll
                for (int c = 0; c < 14; c++) pk[c] = pack_bf16(v[2 * c], v[2 * c + 1]);
                __syncwarp();
                const uint32_t sa = stw + (lane & 7) * 240 + (lane >> 3) * 16;
                #pragma unroll
                for (int m = 0; m < 3; m++)
                    asm volatile("stmatrix.sync.aligned.m8n8.x4.shared.b16 [%0], {%1,%2,%3,%4};"
                                 :: "r"(sa + m * 64), "r"(pk[4 * m]), "r"(pk[4 * m + 1]), "r"(pk[4 * m + 2]), "r"(pk[4 * m + 3]) : "memory");
                asm volatile("stmatrix.sync.aligned.m8n8.x2.shared.b16 [%0], {%1,%2};" :: "r"(sa + 192), "r"(pk[12]), "r"(pk[13]) : "memory");
                __syncwarp();
                #pragma unroll
                for (int i = 0; i < 4; i++) {
                    const int r = 2 * i + (lane >> 4), ch = lane & 15;
                    if (ch < 14) { const uint4 u = lds4(stw + r * 240 + ch * 16); stg4(gp2 + i * 448, u.x, u.y, u.z, u.w); }
                }
                __syncwarp();
                mbar_arrive_remote_if(peer_bar + (B_RE + 2) * 8, lead && wg == 0);
            }
            TR(14 + ge * 4);
        }
        if (tid == 128) TRG(62);
        if (b == 0 && tid == 128) g_epoch = tag;
    }
}

typedef CUresult (*EncodeFn)(CUtensorMap*, CUtensorMapDataType, cuuint32_t, void*, const cuuint64_t*, const cuuint64_t*,
                             const cuuint32_t*, const cuuint32_t*, CUtensorMapInterleave, CUtensorMapSwizzle,
                             CUtensorMapL2promotion, CUtensorMapFloatOOBfill);

void make_map(EncodeFn enc, CUtensorMap* m, const void* base, uint64_t cols, uint64_t rows, uint32_t box_rows) {
    cuuint64_t dims[2] = {cols, rows};
    cuuint64_t strides[1] = {cols * 2};
    cuuint32_t box[2] = {64, box_rows};
    cuuint32_t es[2] = {1, 1};
    enc(m, CU_TENSOR_MAP_DATA_TYPE_BFLOAT16, 2, const_cast<void*>(base), dims, strides, box, es, CU_TENSOR_MAP_INTERLEAVE_NONE,
        CU_TENSOR_MAP_SWIZZLE_128B, CU_TENSOR_MAP_L2_PROMOTION_L2_128B, CU_TENSOR_MAP_FLOAT_OOB_FILL_NONE);
}

}

extern "C" void kernel_launch(void* const* d_in, const int* in_sizes, int n_in, void* d_out, int out_size) {
    (void)in_sizes; (void)n_in; (void)out_size;
    void* fn = nullptr;
    cudaDriverEntryPointQueryResult qr;
    cudaGetDriverEntryPoint("cuTensorMapEncodeTiled", &fn, cudaEnableDefault, &qr);
    EncodeFn enc = (EncodeFn)fn;
    CUtensorMap mX, mWqkv, mWo, mW1, mW2;
    make_map(enc, &mX, d_in[0], 2 * kD, kS / 2, 64);
    make_map(enc, &mWqkv, d_in[1], 3 * kD, kD, 64);
    make_map(enc, &mWo, d_in[2], kD, kD, 224);
    make_map(enc, &mW1, d_in[4], 2 * kF, kS / 2, 64);
    make_map(enc, &mW2, d_in[6], kS, kF, 64);
    Params prm;
    prm.x = (const __nv_bfloat16*)d_in[0];
    prm.wqkv = (const __nv_bfloat16*)d_in[1];
    prm.wo = (const __nv_bfloat16*)d_in[2];
    prm.w1 = (const __nv_bfloat16*)d_in[4];
    prm.b1 = (const __nv_bfloat16*)d_in[5];
    prm.w2 = (const __nv_bfloat16*)d_in[6];
    prm.b2 = (const __nv_bfloat16*)d_in[7];
    prm.out = (__nv_bfloat16*)d_out;
    cudaFuncSetAttribute(fused_kernel, cudaFuncAttributeMaxDynamicSharedMemorySize, SM_TOTAL);
    fused_kernel<<<128, 384, SM_TOTAL, cudaStreamPerThread>>>(mX, mWqkv, mWo, mW1, mW2, prm);
}
```

```cpp
#include <cuda_runtime.h>
#include <cuda.h>
#include <cuda_bf16.h>
#include <stdint.h>
#include <type_traits>

namespace {

constexpr int kS = 2048, kD = 448, kF = 1792;
constexpr float kEps = 1e-5f;

#define FS 32
__device__ __align__(1024) uint4    g_o[32 * 4 * 28 * 32];
__device__ __align__(1024) uint4    g_h[kS * kD * 2 / 16];
__device__ __align__(1024) uint4    g_hn[32 * 56 * 64];
__device__ __align__(1024) uint4    g_g[28 * 56 * 64];
__device__ __align__(1024) uint4    g_halo[16 * 8 * 2 * 4 * 32];
__device__ __align__(1024) uint4    g_stats[32 * 4 * 64];
__device__ __align__(1024) uint32_t g_flag_o[32 * 4 * 8 * FS];
__device__ __align__(1024) uint32_t g_flag_h[32 * 4 * FS];
__device__ uint32_t g_epoch;
#define TIMEOUT(code)
#define RETRY_COUNT(i)
#define CAP_DECL(n, k)
#define CAP(n)
#define CAP_SKIP(n)
#define TR2(idx)
#define TR(idx)
#define TRW(idx)
#define TRG(idx)

constexpr uint32_t SM_X    = 0;
constexpr uint32_t SM_WKV  = 114688;
constexpr uint32_t SM_RED  = 81920;
constexpr uint32_t SM_XCH  = 0;
constexpr uint32_t SM_B    = 131072;
constexpr uint32_t SM_BAR  = 231424;
constexpr uint32_t SM_TOTAL = SM_BAR + 1024;
constexpr int NB = 7;
#define SH1 0
#define SH2 0
#define SH2N 5
#define SH3 0
#define NSPEC 4
#define XSPEC 700
#define C2 0
#define C3 0
#define CN2 8000
#define CN3 12000
constexpr int B_XF = 0, B_WKVF = 7, B_WQF = 14, B_XRF = 15, B_WOF = 16,
              B_XC = 18, B_KV3 = 19, B_KVC = 20,
              B_A1D = 21, B_OL = 22,
              B_BE = 23, B_RE = B_BE + NB,
              B_AF = B_RE + 3, B_BL = B_AF + 16  , B_BF = B_BL + NB  , B_RF = B_BF + NB,
              B_EP = B_RF + 4, B_PD = B_EP + 1, B_RT = B_PD + 1, B_HL = B_RT + 2,
              B_HD = B_HL + 2, B_GO = B_HD + 1, B_GD = B_GO + 1, B_COUNT = B_GD + 2;
#define WEARLY 6
#define PF0 126
#define TMPF 2
#define RSTE 2
#define POLLP 1
#define PROBEP 1
#define LOADP 1
#define LOADW 64
#define NOB 0
#define AEARLY 5
#define W1PACE 400
#define W2PACE 200
#define PFPACE 330
#define PFBAR (B_XF + 6)
#define DELTA 640
#define DELTA2 DELTA
#define BPACE 230
#define BURST 2
#define W1OFF 350
#define W2OFF 2900
#define XPACE 0
#define PSTAG 200
constexpr uint32_t SM_EPOCH = SM_BAR + B_COUNT * 8, SM_TG = SM_EPOCH + 4  , SM_TR = SM_BAR + 768;

#define HDELAY 200
#define QC0 4
#define QC1 10
#define QC2 16
#define W1Q 1
constexpr uint32_t w2_rounds(int h) { uint32_t m = 0; for (int i = 0; i < 14; i++) { const int p = 25 + i * 20 / 13; if ((p & 1) == h) m |= 1u << (p / 2 + 1); } return m; }
constexpr uint32_t kAMask0 = w2_rounds(0), kAMask1 = w2_rounds(1) | 0xFFu << W1Q;

constexpr int kSpinLimit = 1 << 15;
__device__ __forceinline__ bool elect_one() {
    uint32_t p;
    asm volatile("{ .reg .pred P; elect.sync _|P, 0xffffffff; selp.u32 %0, 1, 0, P; }" : "=r"(p));
    return p;
}
__device__ __forceinline__ void mbar_init(uint32_t bar, uint32_t cnt) { asm volatile("mbarrier.init.shared::cta.b64 [%0], %1;" :: "r"(bar), "r"(cnt)); }
__device__ __forceinline__ void mbar_expect(uint32_t bar, uint32_t bytes) { asm volatile("mbarrier.arrive.expect_tx.shared::cta.b64 _, [%0], %1;" :: "r"(bar), "r"(bytes) : "memory"); }
__device__ __forceinline__ void mbar_arrive(uint32_t bar) { asm volatile("mbarrier.arrive.shared::cta.b64 _, [%0];" :: "r"(bar) : "memory"); }
__device__ __forceinline__ void mbar_wait(uint32_t bar, uint32_t parity) {
    uint32_t ok; int it = 0;
    do {
        asm volatile("{ .reg .pred p; mbarrier.try_wait.parity.shared::cta.b64 p, [%1], %2; selp.u32 %0, 1, 0, p; }"
                     : "=r"(ok) : "r"(bar), "r"(parity) : "memory");
        if (++it > kSpinLimit) { TIMEOUT((bar & 1023) >> 3); break; }
    } while (!ok);
}
__device__ __forceinline__ bool mbar_try(uint32_t bar, uint32_t parity) {
    uint32_t ok;
    asm volatile("{ .reg .pred p; mbarrier.try_wait.parity.shared::cta.b64 p, [%1], %2; selp.u32 %0, 1, 0, p; }" : "=r"(ok) : "r"(bar), "r"(parity) : "memory");
    return ok;
}
__device__ __forceinline__ bool mbar_test(uint32_t bar, uint32_t parity) {
    uint32_t ok;
    asm volatile("{ .reg .pred p; mbarrier.test_wait.parity.shared::cta.b64 p, [%1], %2; selp.u32 %0, 1, 0, p; }" : "=r"(ok) : "r"(bar), "r"(parity) : "memory");
    return ok;
}
__device__ __forceinline__ void mbar_wait2(uint32_t bar0, uint32_t par0, uint32_t bar1, uint32_t par1) {
    uint32_t ok; int it = 0;
    do {
        asm volatile("{ .reg .pred p, q; mbarrier.try_wait.parity.shared::cta.b64 p, [%1], %2;\n"
                     "mbarrier.try_wait.parity.shared::cta.b64 q, [%3], %4; and.pred p, p, q; selp.u32 %0, 1, 0, p; }"
                     : "=r"(ok) : "r"(bar0), "r"(par0), "r"(bar1), "r"(par1) : "memory");
        if (++it > kSpinLimit) { TIMEOUT((bar0 & 1023) >> 3); break; }
    } while (!ok);
}
template <int N> __device__ __forceinline__ void reg_fence(float (&d)[N]) {
    #pragma unroll
    for (int i = 0; i < N; i++) asm volatile("" : "+f"(d[i]) :: "memory");
}
__device__ __forceinline__ void mbar_wait_cluster(uint32_t bar, uint32_t parity) {
    uint32_t ok; int it = 0;
    do {
        asm volatile("{ .reg .pred p; mbarrier.try_wait.parity.acquire.cluster.shared::cta.b64 p, [%1], %2; selp.u32 %0, 1, 0, p; }"
                     : "=r"(ok) : "r"(bar), "r"(parity) : "memory");
        if (++it > kSpinLimit) { TIMEOUT((bar & 1023) >> 3); break; }
    } while (!ok);
}
__device__ __forceinline__ void mbar_arrive_if(uint32_t bar, bool pred) {
    asm volatile("{ .reg .pred p; setp.ne.u32 p, %1, 0; @p mbarrier.arrive.shared::cta.b64 _, [%0]; }" :: "r"(bar), "r"((uint32_t)pred) : "memory");
}
template <int P> __device__ __forceinline__ void tick() {
    if (P > 1) { const uint32_t t = ((uint32_t)clock() | (P - 1)) + 1; while ((int)((uint32_t)clock() - t) < 0) {} }
}
__device__ __forceinline__ void warp_arrive(uint32_t bar) { __syncwarp(); if (elect_one()) mbar_arrive(bar); }
__device__ __forceinline__ void tma2d(uint32_t dst, const CUtensorMap* m, int c0, int c1, uint32_t bar) {
    asm volatile("cp.async.bulk.tensor.2d.shared::cluster.global.mbarrier::complete_tx::bytes [%0], [%1, {%3, %4}], [%2];"
                 :: "r"(dst), "l"(m), "r"(bar), "r"(c0), "r"(c1) : "memory");
}
__device__ __forceinline__ void tma2d_mc(uint32_t dst, const CUtensorMap* m, int c0, int c1, uint32_t bar) {
    asm volatile("cp.async.bulk.tensor.2d.shared::cluster.global.mbarrier::complete_tx::bytes.multicast::cluster [%0], [%1, {%3, %4}], [%2], %5;"
                 :: "r"(dst), "l"(m), "r"(bar), "r"(c0), "r"(c1), "h"((uint16_t)3) : "memory");
}
__device__ __forceinline__ void bulk_g2s_mc(uint32_t dst, const void* src, uint32_t bytes, uint32_t bar) {
    asm volatile("cp.async.bulk.shared::cluster.global.mbarrier::complete_tx::bytes.multicast::cluster [%0], [%1], %2, [%3], %4;"
                 :: "r"(dst), "l"(src), "r"(bytes), "r"(bar), "h"((uint16_t)3) : "memory");
}
__device__ __forceinline__ void mbar_arrive_remote_if(uint32_t cluster_bar, bool pred) {
    asm volatile("{ .reg .pred p; setp.ne.u32 p, %1, 0; @p mbarrier.arrive.shared::cluster.b64 _, [%0]; }" :: "r"(cluster_bar), "r"((uint32_t)pred) : "memory");
}
__device__ __forceinline__ void bulk_g2s(uint32_t dst, const void* src, uint32_t bytes, uint32_t bar) {
    asm volatile("cp.async.bulk.shared::cluster.global.mbarrier::complete_tx::bytes [%0], [%1], %2, [%3];"
                 :: "r"(dst), "l"(src), "r"(bytes), "r"(bar) : "memory");
}
__device__ __forceinline__ void wg_fence()  { asm volatile("wgmma.fence.sync.aligned;" ::: "memory"); }
__device__ __forceinline__ void wg_commit() { asm volatile("wgmma.commit_group.sync.aligned;" ::: "memory"); }
template <int N> __device__ __forceinline__ void wg_wait() { asm volatile("wgmma.wait_group.sync.aligned %0;" :: "n"(N) : "memory"); }
__device__ __forceinline__ void named_bar(int id, int n) { asm volatile("bar.sync %0, %1;" :: "r"(id), "r"(n) : "memory"); }
__device__ __forceinline__ void named_arrive(int id, int n) { asm volatile("bar.arrive %0, %1;" :: "r"(id), "r"(n) : "memory"); }
__device__ __forceinline__ bool mbar_try2(uint32_t bar0, uint32_t par0, uint32_t bar1, uint32_t par1) {
    uint32_t ok;
    asm volatile("{ .reg .pred p, q; mbarrier.test_wait.parity.shared::cta.b64 p, [%1], %2;\n"
                 "mbarrier.test_wait.parity.shared::cta.b64 q, [%3], %4; and.pred p, p, q; selp.u32 %0, 1, 0, p; }"
                 : "=r"(ok) : "r"(bar0), "r"(par0), "r"(bar1), "r"(par1) : "memory");
    return ok;
}
__device__ __forceinline__ void fence_gpu() { asm volatile("fence.release.gpu;" ::: "memory"); }
__device__ __forceinline__ void fence_async_global() { asm volatile("fence.proxy.async.global;" ::: "memory"); }
__device__ __forceinline__ void fence_async_smem() { asm volatile("fence.proxy.async.shared::cta;" ::: "memory"); }
__device__ __forceinline__ uint32_t gtime32() { uint64_t t; asm volatile("mov.u64 %0, %%globaltimer;" : "=l"(t) :: "memory"); return (uint32_t)t; }
__device__ __forceinline__ uint32_t clk32() { uint64_t t; asm volatile("mov.u64 %0, %%clock64;" : "=l"(t) :: "memory"); return (uint32_t)t; }
__device__ __forceinline__ void spin_until(uint32_t t) { while ((int)(clk32() - t) < 0) {} }
#define SLEEPNS 20
__device__ __forceinline__ void sleep_until(uint32_t t) { while ((int)(clk32() - t) < 0) { if (SLEEPNS) __nanosleep(SLEEPNS); } }
__device__ __forceinline__ void st_flag(uint32_t* p, uint32_t v) {
    const uint64_t w = ((uint64_t)gtime32() << 32) | v;
    asm volatile("st.relaxed.gpu.global.u64 [%0], %1;" :: "l"(p), "l"(w) : "memory");
}
__device__ __forceinline__ void ld_flag_if(uint64_t& v, const uint32_t* p, bool pred) {
    asm volatile("{ .reg .pred p; setp.ne.u32 p, %2, 0; @p ld.relaxed.gpu.global.u64 %0, [%1]; }" : "+l"(v) : "l"(p), "r"((uint32_t)pred) : "memory");
}
__device__ __forceinline__ uint32_t ld_acq(const uint32_t* p) { uint32_t v; asm volatile("ld.acquire.gpu.global.u32 %0, [%1];" : "=r"(v) : "l"(p) : "memory"); return v; }
__device__ __forceinline__ uint32_t ld_rlx(const uint32_t* p) { uint32_t v; asm volatile("ld.relaxed.gpu.global.u32 %0, [%1];" : "=r"(v) : "l"(p) : "memory"); return v; }
template <class T> __device__ __forceinline__ T* opaque_ptr(T* p) { asm volatile("" : "+l"(p)); return p; }
__device__ __forceinline__ uint4 ld_rlx4(const uint4* p) {
    uint4 v; asm volatile("ld.relaxed.gpu.global.v4.u32 {%0,%1,%2,%3}, [%4];" : "=r"(v.x), "=r"(v.y), "=r"(v.z), "=r"(v.w) : "l"(p) : "memory"); return v;
}
__device__ __forceinline__ void st_ll(uint4* p, uint32_t a, uint32_t b, uint32_t tag) {
    uint64_t lo = ((uint64_t)tag << 32) | a, hi = ((uint64_t)tag << 32) | b;
    asm volatile("st.relaxed.gpu.global.v2.u64 [%0], {%1,%2};" :: "l"(p), "l"(lo), "l"(hi) : "memory");
}
__device__ __forceinline__ bool ld_ll(const uint4* p, uint32_t& a, uint32_t& b, uint32_t tag) {
    uint64_t lo, hi;
    asm volatile("ld.relaxed.gpu.global.v2.u64 {%0,%1}, [%2];" : "=l"(lo), "=l"(hi) : "l"(p) : "memory");
    a = (uint32_t)lo; b = (uint32_t)hi;
    return (uint32_t)(lo >> 32) == tag && (uint32_t)(hi >> 32) == tag;
}
__device__ __forceinline__ uint2 ld_acq2(const uint2* p) {
    uint2 v; asm volatile("ld.acquire.gpu.global.v2.u32 {%0,%1}, [%2];" : "=r"(v.x), "=r"(v.y) : "l"(p) : "memory"); return v;
}
__device__ __forceinline__ uint2 ld_rlx2(const uint2* p) {
    uint2 v; asm volatile("ld.relaxed.gpu.global.v2.u32 {%0,%1}, [%2];" : "=r"(v.x), "=r"(v.y) : "l"(p) : "memory"); return v;
}
__device__ __forceinline__ void stg1(uint32_t* p, uint32_t v) { asm volatile("st.global.u32 [%0], %1;" :: "l"(p), "r"(v) : "memory"); }
__device__ __forceinline__ void stg2(void* p, uint32_t x, uint32_t y) { asm volatile("st.global.v2.u32 [%0], {%1,%2};" :: "l"(p), "r"(x), "r"(y) : "memory"); }
__device__ __forceinline__ void stg4(void* p, uint32_t x, uint32_t y, uint32_t z, uint32_t w) { asm volatile("st.global.v4.u32 [%0], {%1,%2,%3,%4};" :: "l"(p), "r"(x), "r"(y), "r"(z), "r"(w) : "memory"); }
__device__ __forceinline__ uint32_t lds1(uint32_t a) { uint32_t v; asm volatile("ld.shared.u32 %0, [%1];" : "=r"(v) : "r"(a) : "memory"); return v; }
__device__ __forceinline__ uint2 lds2(uint32_t a) { uint2 v; asm volatile("ld.shared.v2.u32 {%0,%1}, [%2];" : "=r"(v.x), "=r"(v.y) : "r"(a) : "memory"); return v; }
__device__ __forceinline__ uint32_t set_par(uint32_t v, uint32_t mask, uint32_t par) { return (v & ~mask) | (par & mask); }
__device__ __forceinline__ float tanh_hw(float x) { float r; asm("tanh.approx.f32 %0, %1;" : "=f"(r) : "f"(x)); return r; }
__device__ __forceinline__ bool bar_any(int id, int n, bool v) {
    uint32_t r;
    asm volatile("{ .reg .pred p, q; setp.ne.u32 p, %3, 0; bar.red.or.pred q, %1, %2, p; selp.u32 %0, 1, 0, q; }" : "=r"(r) : "r"(id), "r"(n), "r"((uint32_t)v) : "memory");
    return r;
}
__device__ __forceinline__ void sts4(uint32_t a, uint32_t x, uint32_t y, uint32_t z, uint32_t w) { asm volatile("st.shared.v4.u32 [%0], {%1,%2,%3,%4};" :: "r"(a), "r"(x), "r"(y), "r"(z), "r"(w) : "memory"); }
__device__ __forceinline__ uint4 lds4(uint32_t a) { uint4 v; asm volatile("ld.shared.v4.u32 {%0,%1,%2,%3}, [%4];" : "=r"(v.x), "=r"(v.y), "=r"(v.z), "=r"(v.w) : "r"(a) : "memory"); return v; }
__device__ __forceinline__ uint32_t pack_bf16(float lo, float hi) { uint32_t r; asm("cvt.rn.bf16x2.f32 %0, %1, %2;" : "=r"(r) : "f"(hi), "f"(lo)); return r; }
__device__ __forceinline__ float bf_lo(uint32_t v) { return __uint_as_float(v << 16); }
__device__ __forceinline__ float bf_hi(uint32_t v) { return __uint_as_float(v & 0xffff0000u); }
__device__ __forceinline__ uint32_t sub_bf16x2(uint32_t a, uint32_t b) { uint32_t r; asm("sub.rn.bf16x2 %0, %1, %2;" : "=r"(r) : "r"(a), "r"(b)); return r; }
__device__ __forceinline__ uint32_t add_bf16x2(uint32_t a, uint32_t b) { uint32_t r; asm("add.rn.bf16x2 %0, %1, %2;" : "=r"(r) : "r"(a), "r"(b)); return r; }
__device__ __forceinline__ uint32_t sqr_bf16x2(uint32_t a) { uint32_t r; asm("mul.rn.bf16x2 %0, %1, %1;" : "=r"(r) : "r"(a)); return r; }
__device__ __forceinline__ uint32_t sqa_bf16x2(uint32_t a, uint32_t c) { uint32_t r; asm("fma.rn.bf16x2 %0, %1, %1, %2;" : "=r"(r) : "r"(a), "r"(c)); return r; }
__device__ __forceinline__ uint32_t movm(uint32_t a) { uint32_t r; asm volatile("movmatrix.sync.aligned.m8n8.trans.b16 %0, %1;" : "=r"(r) : "r"(a)); return r; }
__device__ __forceinline__ float ex2(float x) { float r; asm("ex2.approx.ftz.f32 %0, %1;" : "=f"(r) : "f"(x)); return r; }
__device__ __forceinline__ float rsq(float x) { float r; asm("rsqrt.approx.ftz.f32 %0, %1;" : "=f"(r) : "f"(x)); return r; }
__device__ __forceinline__ float rcp(float x) { float r; asm("rcp.approx.ftz.f32 %0, %1;" : "=f"(r) : "f"(x)); return r; }
__device__ __forceinline__ void mma16816(float (&c)[4], uint32_t a0, uint32_t a1, uint32_t a2, uint32_t a3, uint32_t b0, uint32_t b1) {
    asm("mma.sync.aligned.m16n8k16.row.col.f32.bf16.bf16.f32 {%0,%1,%2,%3}, {%4,%5,%6,%7}, {%8,%9}, {%0,%1,%2,%3};"
        : "+f"(c[0]), "+f"(c[1]), "+f"(c[2]), "+f"(c[3]) : "r"(a0), "r"(a1), "r"(a2), "r"(a3), "r"(b0), "r"(b1));
}
__device__ __forceinline__ void mma1688(float (&c)[4], uint32_t a0, uint32_t a1, uint32_t b0) {
    asm("mma.sync.aligned.m16n8k8.row.col.f32.bf16.bf16.f32 {%0,%1,%2,%3}, {%4,%5}, {%6}, {%0,%1,%2,%3};"
        : "+f"(c[0]), "+f"(c[1]), "+f"(c[2]), "+f"(c[3]) : "r"(a0), "r"(a1), "r"(b0));
}
__device__ __forceinline__ float quad_sum(float v) { v += __shfl_xor_sync(~0u, v, 1); v += __shfl_xor_sync(~0u, v, 2); return v; }
__device__ __forceinline__ float quad_max(float v) { v = fmaxf(v, __shfl_xor_sync(~0u, v, 1)); v = fmaxf(v, __shfl_xor_sync(~0u, v, 2)); return v; }
__device__ __forceinline__ uint64_t make_desc(uint32_t addr, uint32_t lbo, bool swz) {
    const uint32_t lo = __shfl_sync(~0u, ((addr & 0x3FFFF) >> 4) | ((lbo >> 4) << 16), 0);
    const uint32_t hi = __shfl_sync(~0u, (swz ? 0x40000040u : 0x40u) + (threadIdx.x & 31), 0);
    return ((uint64_t)hi << 32) | lo;
}
template <int I, int N, class F> __device__ __forceinline__ void static_for(F&& f) {
    if constexpr (I < N) { f(std::integral_constant<int, I>{}); static_for<I + 1, N>(f); }
}
__device__ __forceinline__ uint32_t opaque(uint32_t v) { asm volatile("" : "+r"(v)); return v; }
template <int BOFF, int SCALE_D>
__device__ __forceinline__ void wgmma_rs_n56(float (&d)[28], uint32_t a0, uint32_t a1, uint32_t a2, uint32_t a3, uint64_t db) {
    asm volatile("{ .reg .b64 db; add.s64 db, %32, %33;\n"
        "wgmma.mma_async.sync.aligned.m64n56k16.f32.bf16.bf16 "
        "{%0, %1, %2, %3, %4, %5, %6, %7, %8, %9, %10, %11, %12, %13, %14, %15, %16, %17, %18, %19, %20, %21, %22, %23, %24, %25, %26, %27}, "
        "{%28, %29, %30, %31}, db, %34, 1, 1, 1; }"
        : "+f"(d[0]), "+f"(d[1]), "+f"(d[2]), "+f"(d[3]), "+f"(d[4]), "+f"(d[5]), "+f"(d[6]), "+f"(d[7]),
        "+f"(d[8]), "+f"(d[9]), "+f"(d[10]), "+f"(d[11]), "+f"(d[12]), "+f"(d[13]), "+f"(d[14]), "+f"(d[15]),
        "+f"(d[16]), "+f"(d[17]), "+f"(d[18]), "+f"(d[19]), "+f"(d[20]), "+f"(d[21]), "+f"(d[22]), "+f"(d[23]),
        "+f"(d[24]), "+f"(d[25]), "+f"(d[26]), "+f"(d[27])
        : "r"(a0), "r"(a1), "r"(a2), "r"(a3), "l"(db), "n"(BOFF >> 4), "n"(SCALE_D));
}
template <int BOFF, int SCALE_D>
__device__ __forceinline__ void wgmma_rs_n128(float (&d)[64], uint32_t a0, uint32_t a1, uint32_t a2, uint32_t a3, uint64_t db) {
    asm volatile("{ .reg .b64 db; add.s64 db, %68, %69;\n"
        "wgmma.mma_async.sync.aligned.m64n128k16.f32.bf16.bf16 "
        "{%0, %1, %2, %3, %4, %5, %6, %7, %8, %9, %10, %11, %12, %13, %14, %15, %16, %17, %18, %19, %20, %21, %22, %23, %24, %25, %26, %27, %28, %29, %30, %31, %32, %33, %34, %35, %36, %37, %38, %39, %40, %41, %42, %43, %44, %45, %46, %47, %48, %49, %50, %51, %52, %53, %54, %55, %56, %57, %58, %59, %60, %61, %62, %63}, "
        "{%64, %65, %66, %67}, db, %70, 1, 1, 1; }"
        : "+f"(d[0]), "+f"(d[1]), "+f"(d[2]), "+f"(d[3]), "+f"(d[4]), "+f"(d[5]), "+f"(d[6]), "+f"(d[7]),
        "+f"(d[8]), "+f"(d[9]), "+f"(d[10]), "+f"(d[11]), "+f"(d[12]), "+f"(d[13]), "+f"(d[14]), "+f"(d[15]),
        "+f"(d[16]), "+f"(d[17]), "+f"(d[18]), "+f"(d[19]), "+f"(d[20]), "+f"(d[21]), "+f"(d[22]), "+f"(d[23]),
        "+f"(d[24]), "+f"(d[25]), "+f"(d[26]), "+f"(d[27]), "+f"(d[28]), "+f"(d[29]), "+f"(d[30]), "+f"(d[31]),
        "+f"(d[32]), "+f"(d[33]), "+f"(d[34]), "+f"(d[35]), "+f"(d[36]), "+f"(d[37]), "+f"(d[38]), "+f"(d[39]),
        "+f"(d[40]), "+f"(d[41]), "+f"(d[42]), "+f"(d[43]), "+f"(d[44]), "+f"(d[45]), "+f"(d[46]), "+f"(d[47]),
        "+f"(d[48]), "+f"(d[49]), "+f"(d[50]), "+f"(d[51]), "+f"(d[52]), "+f"(d[53]), "+f"(d[54]), "+f"(d[55]),
        "+f"(d[56]), "+f"(d[57]), "+f"(d[58]), "+f"(d[59]), "+f"(d[60]), "+f"(d[61]), "+f"(d[62]), "+f"(d[63])
        : "r"(a0), "r"(a1), "r"(a2), "r"(a3), "l"(db), "n"(BOFF >> 4), "n"(SCALE_D));
}
template <int AOFF, int BOFF>
__device__ __forceinline__ void wgmma_ss_n112(float (&d)[56], uint64_t da, uint64_t db) {
    asm volatile("{ .reg .b64 da, db; add.s64 da, %56, %58; add.s64 db, %57, %59;\n"
        "wgmma.mma_async.sync.aligned.m64n112k16.f32.bf16.bf16 "
        "{%0, %1, %2, %3, %4, %5, %6, %7, %8, %9, %10, %11, %12, %13, %14, %15, %16, %17, %18, %19, %20, %21, %22, %23, %24, %25, %26, %27, %28, %29, %30, %31, %32, %33, %34, %35, %36, %37, %38, %39, %40, %41, %42, %43, %44, %45, %46, %47, %48, %49, %50, %51, %52, %53, %54, %55}, "
        "da, db, 1, 1, 1, 1, 1; }"
        : "+f"(d[0]), "+f"(d[1]), "+f"(d[2]), "+f"(d[3]), "+f"(d[4]), "+f"(d[5]), "+f"(d[6]), "+f"(d[7]),
        "+f"(d[8]), "+f"(d[9]), "+f"(d[10]), "+f"(d[11]), "+f"(d[12]), "+f"(d[13]), "+f"(d[14]), "+f"(d[15]),
        "+f"(d[16]), "+f"(d[17]), "+f"(d[18]), "+f"(d[19]), "+f"(d[20]), "+f"(d[21]), "+f"(d[22]), "+f"(d[23]),
        "+f"(d[24]), "+f"(d[25]), "+f"(d[26]), "+f"(d[27]), "+f"(d[28]), "+f"(d[29]), "+f"(d[30]), "+f"(d[31]),
        "+f"(d[32]), "+f"(d[33]), "+f"(d[34]), "+f"(d[35]), "+f"(d[36]), "+f"(d[37]), "+f"(d[38]), "+f"(d[39]),
        "+f"(d[40]), "+f"(d[41]), "+f"(d[42]), "+f"(d[43]), "+f"(d[44]), "+f"(d[45]), "+f"(d[46]), "+f"(d[47]),
        "+f"(d[48]), "+f"(d[49]), "+f"(d[50]), "+f"(d[51]), "+f"(d[52]), "+f"(d[53]), "+f"(d[54]), "+f"(d[55])
        : "l"(da), "l"(db), "n"(AOFF >> 4), "n"(BOFF >> 4));
}

struct Params {
    const __nv_bfloat16 *x, *wqkv, *wo, *w1, *w2, *b1, *b2;
    __nv_bfloat16* out;
};

__global__ void __cluster_dims__(2, 1, 1) __launch_bounds__(384, 1)
fused_kernel(const __grid_constant__ CUtensorMap mX, const __grid_constant__ CUtensorMap mWqkv,
             const __grid_constant__ CUtensorMap mWo, const __grid_constant__ CUtensorMap mW1,
             const __grid_constant__ CUtensorMap mW2, const Params prm)
{
    extern __shared__ __align__(1024) unsigned char smem_raw[];
    uint32_t sb = (uint32_t)__cvta_generic_to_shared(smem_raw);
    asm volatile("mov.u32 %0, %0;" : "+r"(sb));
    const uint32_t bar0 = sb + SM_BAR;
    auto BAR = [&](int i) { return bar0 + 8u * i; };

    const int tid = threadIdx.x, lane = tid & 31;
    const int warp = __shfl_sync(~0u, tid >> 5, 0);
    const int b = __shfl_sync(~0u, (int)blockIdx.x, 0);
    const int rank = b & 1;
    const int cl = (b >> 1) - 4, cq = ((cl - 32) * 37) >> 8;
    const int res = cl < 0 ? 0 : cl < 32 ? cl & 7 : cl - 31 - 7 * cq;
    const int rnd = cl < 0 ? cl + 8 : cl < 32 ? cl >> 3 : 4 + cq;
    const int hg = (res & 1) * 4 + (rnd & 3);
    const int ti = (res >> 1) * 4 + (rnd >> 2) * 2 + rank;
    const int a2p = res & 1, a2j = rnd & 3;
    const int a2s = ti * 2 + a2p;
    const bool g1_on = rnd != 7;
    const int g1j = (rnd < 6 ? rnd : res) & 1, g1f = rnd < 6 ? res * 3 + (rnd >> 1) : 24 + (res >> 1);
    const int g2j = rnd & 1, g2s = res * 4 + (rnd >> 1);
    uint32_t pbar0;
    asm volatile("mapa.shared::cluster.u32 %0, %1, %2;" : "=r"(pbar0) : "r"(bar0), "r"(rank ^ 1));
    auto pair_arrive = [&](int i) { __syncwarp(); const bool l = elect_one(); mbar_arrive_if(BAR(i), l); mbar_arrive_remote_if(pbar0 + 8u * i, l); };
    const int wcol = hg * 56 - (hg & 1) * 8;

    if (tid == 32) { TRG(60); TRW(59); }
    if (warp == 8) {
        if (elect_one()) {
            #pragma unroll
            for (int i = 0; i < B_WQF; i++) mbar_init(BAR(i), 1);
            asm volatile("fence.mbarrier_init.release.cluster;" ::: "memory");
            fence_async_smem();
            TRW(56);
            #pragma unroll 1
            for (int kb = 0; kb < 7; kb++) {
                mbar_expect(BAR(B_XF + kb), 16384);
                tma2d(sb + SM_X + kb * 8192, &mX, kb * 64, ti * 64, BAR(B_XF + kb));
                tma2d(sb + SM_X + 57344 + kb * 8192, &mX, kD + kb * 64, ti * 64, BAR(B_XF + kb));
                if (TMPF == 2 && kb == 0) asm volatile("prefetch.tensormap [%0];" :: "l"(&mWqkv) : "memory");
            }
        }
    } else if (warp > 8) {
        if (elect_one()) {
            if (warp == 9) {
                if (TMPF == 1) asm volatile("prefetch.tensormap [%0];" :: "l"(&mWqkv) : "memory");
                #pragma unroll
                for (int i = B_WQF; i < B_AF; i++) mbar_init(BAR(i), i < B_XC ? 1 : i < B_A1D ? 16 : i < B_BE ? 8 : 4);
            } else if (warp == 10) {
                #pragma unroll
                for (int i = B_AF; i < B_BL; i++) mbar_init(BAR(i), 1);
            } else {
                #pragma unroll
                for (int i = B_BL; i < B_COUNT; i++) mbar_init(BAR(i), 1);
            }
            asm volatile("fence.mbarrier_init.release.cluster;" ::: "memory");
            fence_async_smem();
        }
    } else {
        const char* p = tid < 112 ? (const char*)prm.x + (size_t)(ti * 8 + hg) * 14336 + tid * 128
                                  : (const char*)prm.wqkv + b * 2688 + 896 + (tid - 112) * 128;
        if (tid < PF0) asm volatile("prefetch.global.L2 [%0];" :: "l"(p));
    }
    __syncwarp();
    __syncthreads();
    asm volatile("barrier.cluster.arrive.relaxed.aligned;" ::: "memory");
    if (tid < 256) TR(0);
    if (tid == 0) TRG(61);

    if (warp >= 8) {
        asm volatile("setmaxnreg.dec.sync.aligned.u32 40;");
        asm volatile("barrier.cluster.wait.aligned;" ::: "memory");
        auto fetch_halo = [&](int p, uint32_t tag) {
            uint4 u[4];
            #pragma unroll
            for (int c = 0; c < 4; c++) u[c] = make_uint4(0u, 0u, 0u, 0u);
            const uint4* hp = opaque_ptr(&g_halo[(((ti - 1) * 8 + hg) * 2 + p) * 128 + lane]);
            mbar_wait(BAR(B_KVC), 0);
            if (p == 0) TRW(51);
            sleep_until(clk32() + HDELAY);
            if (ti > 0) {
                int it = 0;
                do {
                    #pragma unroll
                    for (int c = 0; c < 4; c++) u[c] = ld_rlx4(hp + c * 32);
                    if (++it > kSpinLimit) { TIMEOUT(101); break; }
                } while (__any_sync(~0u, ((u[0].x ^ tag) | (u[1].x ^ tag) | (u[2].x ^ tag) | (u[3].x ^ tag)) & ~lane & 1));
            }
            #pragma unroll
            for (int c = 0; c < 4; c++) sts4(sb + SM_RED + (1 - p) * 16384 + 3 * 2048 + lane * 16 + c * 512, u[c].x, u[c].y, u[c].z, u[c].w);
            warp_arrive(BAR(B_HL + p));
        };
        if (warp & 1) {
            uint32_t tag;
            if (warp == 11) {
                tag = *(volatile uint32_t*)&g_epoch + 1;
            const uint4 z4 = make_uint4(0u, 0u, 0u, 0u);
            #pragma unroll 1
            for (int i = 0; i < 8; i++) g_halo[(ti * 8 + hg) * 256 + i * 32 + lane] = make_uint4(~tag, 0u, 0u, 0u);
            g_stats[(a2s * 4 + a2j) * 64 + lane] = z4; g_stats[(a2s * 4 + a2j) * 64 + 32 + lane] = z4;
            g_flag_h[(a2s * 4 + a2j) * FS + lane] = 0;
            #pragma unroll 1
            for (int i = 0; i < 2; i++) ((uint4*)g_flag_o)[((ti * 8 + i * 4 + (lane >> 3)) * 8 + hg) * 8 + (lane & 7)] = z4;
            __syncwarp();
            if (lane == 0) {
                asm volatile("st.shared.u32 [%0], %1;" :: "r"(sb + SM_EPOCH), "r"(tag) : "memory");
                mbar_arrive(BAR(B_EP));
            }
            if (lane < 4) mbar_expect(BAR(B_RF + lane), 7168);
            __syncwarp();
            TRW(44);
            } else {
                mbar_wait(BAR(B_EP), 0);
                tag = lds1(sb + SM_EPOCH);
            }
            fetch_halo((warp >> 1) & 1, tag);
        }
        if (warp < 10) {
          auto load_slab = [&](int s, bool second) {
              mbar_expect(BAR(B_AF + s), 8192);
              if (!second) tma2d(sb + s * 8192, &mW1, (s & 1) * kF + g1f * 64, (rank * 8 + (s >> 1)) * 64, BAR(B_AF + s));
              else         tma2d(sb + s * 8192, &mW2, g2s * 64, (rank * 14 + s - 2) * 64, BAR(B_AF + s));
          };
          if (warp == 8) {
            if (elect_one()) {
                #pragma unroll 1
                for (int s = 0; s < 7; s++) {
                    mbar_expect(BAR(B_WKVF + s), 16384);
                    tma2d_mc(sb + SM_WKV + s * 16384 + rank * 8192, &mWqkv, (1 + rank) * kD + wcol, s * 64, BAR(B_WKVF + s));
                }
            }
            __syncwarp();
            mbar_wait(BAR(B_XC), 0);
            if (elect_one()) {
                asm volatile("prefetch.tensormap [%0];" :: "l"(&mWo) : "memory");
                asm volatile("prefetch.tensormap [%0];" :: "l"(&mW1) : "memory");
                asm volatile("prefetch.tensormap [%0];" :: "l"(&mW2) : "memory");
                mbar_expect(BAR(B_WQF), 57344);
                #pragma unroll 1
                for (int s = rank; s < 7; s += 2) tma2d_mc(sb + SM_X + s * 8192, &mWqkv, wcol, s * 64, BAR(B_WQF));
                mbar_expect(BAR(B_XRF), a2j == 3 ? 8192 : 16384);
                tma2d(sb + SM_X + 8 * 8192, &mX, a2p * kD + a2j * 128, ti * 64, BAR(B_XRF));
                if (a2j != 3) tma2d(sb + SM_X + 9 * 8192, &mX, a2p * kD + a2j * 128 + 64, ti * 64, BAR(B_XRF));
            }
            __syncwarp();
            #pragma unroll 1
            for (int h = 0; h < 2; h++) {
                mbar_wait(BAR(B_KV3 + h), 0);
                if (h) mbar_wait2(BAR(B_HL), 0, BAR(B_HL + 1), 0);
                if (elect_one()) {
                    mbar_expect(BAR(B_WOF + h), a2j == 3 ? 28672 : 57344);
                    const int atom = rank ^ h;
                    if (a2j != 3 || atom == 0) tma2d_mc(sb + SM_WKV + h * 57344 + atom * 28672, &mWo, a2j * 128 + atom * 64, h * 224, BAR(B_WOF + h));
                }
                __syncwarp();
            }
            if (g1_on) {
                mbar_wait(BAR(B_A1D), 0);
                #pragma unroll 1
                for (int s = 0; s < 8; s++) {
                    if (s == AEARLY) mbar_wait(BAR(B_OL), 0);
                    if (elect_one()) load_slab(s, false);
                    __syncwarp();
                }
            } else {
                mbar_wait(BAR(B_GO), 0);
                const uint32_t tg = lds1(sb + SM_TG + 4);
                int it = 0;
                while ((int)(gtime32() - tg) < 0 && ++it < 64) {}
                const uint32_t t0 = clk32();
                if (lane < 2) {
                    asm volatile("st.shared.u32 [%0], %1;" :: "r"(sb + SM_TG + 8 + lane * 4), "r"(t0 + (lane ? CN3 : CN2)) : "memory");
                    mbar_arrive(BAR(B_GD + lane));
                }
                __syncwarp();
                #pragma unroll 1
                for (int s = 2; s < 16; s++) {
                    sleep_until(t0 + W2OFF + s * W2PACE);
                    if (elect_one()) load_slab(s, true);
                    __syncwarp();
                }
            }
          } else {
          }
          if (elect_one()) {
              const int h = ~warp & 1;
              const char* src1 = (const char*)&g_hn[(rank * 16 + h) * 3584 + g1j * 896];
              const char* src2 = (const char*)&g_g[(rank * 14 + h) * 3584 + g2j * 896];
              const long long jump = src2 - src1 - (16 * 57344 + 2 * 14336);
              const char* src = g1_on ? src1 - 2 * 57344 : src2;
              const uint32_t amask = g1_on ? (h ? kAMask1 : kAMask0) : 0u;
              uint32_t slot = g1_on ? NB - 2 + h : h, ph = g1_on ? 0 : 1, gate = g1_on ? 0 : 2;
              CAP_DECL(ti_, 0);
              #pragma unroll 1
              for (int q = g1_on ? 0 : 17; q < 31; q++) {
                  const uint32_t eb = q ? BAR(B_BE) + slot * 8 : BAR(B_XF), dst = sb + SM_B + slot * 14336;
                  if ((0x1020003u >> q) & 1) {
                      mbar_wait(BAR(B_HD + gate), 0);
                      const uint32_t tg = lds1(sb + SM_TG + gate * 4) + h * 64;
                      int it = 0;
                      if (gate < 2) while ((int)(gtime32() - tg) < 0 && ++it < 64) {}
                      else spin_until(tg);
                      gate++;
                  }
                  if (!mbar_try(eb, ph)) mbar_wait(eb, ph);
                  if (q) {
                      bulk_g2s(dst, src, 14336, eb + (B_BL - B_BE) * 8);
                      mbar_expect(eb + (B_BL - B_BE) * 8, 14336);
                      CAP(ti_);
                  }
                  mbar_arrive_remote_if(pbar0 + 8u * B_PD, h && q == 12);
                  if ((amask >> q) & 1) {
                      if (q < 12) load_slab(8 + __popc(amask & ((1u << q) - 1)), false);
                      else load_slab(2 + ((2 * q + h - 27) * 13 + 19) / 20, true);
                  }
                  src += 2 * 57344 + (q == 8 ? 2 * 14336 - 16 * 57344 : q == 16 ? jump : q == 23 ? 2 * 14336 - 14 * 57344 : 0);
                  slot += 2;
                  if (slot >= NB) { slot -= NB; ph ^= 1; }
              }
          }
        } else {
          uint32_t tag;
          if (warp == 10) {
            mbar_wait(BAR(PFBAR), 0);
            const char* p1 = (const char*)prm.w1 + (size_t)b * 57344 + lane * 128;
            const char* p2 = (const char*)prm.w2 + (size_t)b * 57344 + lane * 128;
            if (lane < 27) asm volatile("prefetch.global.L2 [%0];" :: "l"(lane < 25 ? (const char*)prm.wo + min(b * 25 + lane, 3135) * 128
                                                                          : lane == 25 ? (const char*)prm.b1 + (b % 28) * 128 : (const char*)prm.b2 + (b & 31) * 128));
            uint32_t tnext = (uint32_t)clock();
            #pragma unroll 1
            for (int i = 0; i < 28; i++) {
                asm volatile("prefetch.global.L2 [%0];" :: "l"(i < 14 ? p1 + i * 4096 : p2 + (i - 14) * 4096));
                tnext += PFPACE;
                while ((int)((uint32_t)clock() - tnext) < 0) __nanosleep(40);
            }
            mbar_wait(BAR(B_EP), 0);
            tag = lds1(sb + SM_EPOCH);
          } else {
            tag = lds1(sb + SM_EPOCH);
            const uint32_t* fp = &g_flag_h[(rank * 64 + lane) * FS];
            mbar_wait(BAR(B_HD), 0);
            uint64_t v0 = 0, v1 = 0;
            int it = 0;
            do {
                ld_flag_if(v0, fp, (uint32_t)v0 != tag); ld_flag_if(v1, fp + 32 * FS, (uint32_t)v1 != tag);
                if (++it > kSpinLimit) { TIMEOUT(108); break; }
            } while (__any_sync(~0u, (uint32_t)v0 != tag || (uint32_t)v1 != tag));
            const uint32_t gbase = __shfl_sync(~0u, (uint32_t)(v0 >> 32), 0);
            const uint32_t tg = gbase + DELTA + __reduce_max_sync(~0u, max((int)((uint32_t)(v0 >> 32) - gbase), (int)((uint32_t)(v1 >> 32) - gbase)));
            if (lane == 0) {
                asm volatile("st.shared.u32 [%0], %1;" :: "r"(sb + SM_TG + 4), "r"(tg) : "memory");
                mbar_arrive(BAR(B_GO));
            }
            __syncwarp();
            TRW(40);
          }
          const int h = warp & 1;
          const bool lead = elect_one();
          const uint32_t w2o = lane * 128 + ((lane + 16 * g2j) & 31) * 4, l3 = lane < 16 ? 12288 : 0;
          uint32_t wo = g1_on ? w2o ^ ((g1j ^ g2j) << 6) : w2o, slot = h, ph = 0, rph = 0, af = BAR(B_AF + h + (g1_on ? 0 : 2)), aph = 0;
          #pragma unroll 1
          for (int q = g1_on ? 1 : 17; q < 31; q++) {
              const uint32_t rb = bar0 + slot * 8, dst = sb + SM_B + slot * 14336;
              auto stale = [&]() {
                  uint32_t d;
                  asm volatile("{ .reg .b32 x, y, z, u;\n"
                               "ld.shared.u32 x, [%1]; ld.shared.u32 y, [%1 + 4096]; ld.shared.u32 z, [%1 + 8192]; ld.shared.u32 u, [%2];\n"
                               "lop3.b32 x, x, y, %3, 0x7e; lop3.b32 z, z, u, %3, 0x7e; lop3.b32 %0, x, z, 1, 0xa8; }"
                               : "=r"(d) : "r"(dst + wo), "r"(dst + wo + l3), "r"(tag) : "memory");
                  return __any_sync(~0u, d);
              };
              mbar_wait(rb + B_BF * 8, ph ^ 1);
              mbar_wait(rb + B_BL * 8, ph);
              const bool aok = mbar_test(af, aph);
              bool bad = stale();
              if (!aok) mbar_wait(af, aph);
              mbar_arrive_if(rb + B_BF * 8, lead && !bad);
              if (bad) {
                  RETRY_COUNT(2);
                  const int e = (q > 8) + (q > 16) + (q > 23), s = (q - (e < 3 ? 1 + 8 * e : 24)) * 2 + h;
                  const char* src = (const char*)(e < 2 ? &g_hn[(rank * 16 + s) * 3584 + (g1j + 2 * e) * 896] : &g_g[(rank * 14 + s) * 3584 + (g2j + 2 * e - 4) * 896]);
                  int it = 0;
                  do {
                      if (++it > kSpinLimit) { TIMEOUT(111); break; }
                      const uint32_t* p = (const uint32_t*)(src + wo);
                      if (__any_sync(~0u, ((ld_rlx(p) ^ tag) | (ld_rlx(p + 1024) ^ tag) | (ld_rlx(p + 2048) ^ tag) | (ld_rlx(p + l3 / 4) ^ tag)) & 1)) continue;
                      if (lead) {
                          mbar_expect(BAR(B_RT + h), 14336);
                          bulk_g2s(dst, src, 14336, BAR(B_RT + h));
                      }
                      __syncwarp();
                      mbar_wait(BAR(B_RT + h), rph);
                      rph ^= 1;
                      bad = stale();
                  } while (bad);
                  mbar_arrive_if(rb + B_BF * 8, lead);
              }
              if (q == 16) { wo = w2o; aph = 1; }
              af += q == 8 ? -112 : (0x810000u >> q) & 1 ? -96 : 16;
              slot += 2;
              if (slot >= NB) { slot -= NB; ph ^= 1; }
          }
        }
    } else {
        asm volatile("setmaxnreg.inc.sync.aligned.u32 232;");
        asm volatile("barrier.cluster.wait.aligned;" ::: "memory");
        const int wg = warp >> 2, w = warp & 3;
        const int g = lane >> 2, t = lane & 3;
        uint32_t tag;
        __nv_bfloat16 bias1;
        {
            const uint64_t dw = make_desc(sb + (hg & 1) * 16, 0, true);
            uint32_t a[28][4];
            float sm0[4] = {0.f, 0.f, 0.f, 0.f}, sm1[4] = {0.f, 0.f, 0.f, 0.f};
            {
                const int r = w * 16 + (lane & 15);
                const uint32_t rowa = sb + SM_X + wg * 57344 + r * 128;
                #pragma unroll
                for (int kb = 0; kb < 7; kb++) {
                    mbar_wait(BAR(B_XF + kb), 0);
                    #pragma unroll
                    for (int q = 0; q < 4; q++) {
                        const uint32_t addr = rowa + kb * 8192 + (((q * 2 + (lane >> 4)) ^ (r & 7)) << 4);
                        uint32_t (&f)[4] = a[kb * 4 + q];
                        asm volatile("ldmatrix.sync.aligned.m8n8.x4.shared.b16 {%0,%1,%2,%3}, [%4];"
                                     : "=r"(f[0]), "=r"(f[1]), "=r"(f[2]), "=r"(f[3]) : "r"(addr) : "memory");
                        if (q & 1) mma16816(sm1, f[0], f[1], f[2], f[3], 0x3F803F80u, 0x3F803F80u);
                        else       mma16816(sm0, f[0], f[1], f[2], f[3], 0x3F803F80u, 0x3F803F80u);
                    }
                }
            }
            const float mean0 = (sm0[0] + sm1[0]) * (1.f / kD), mean1 = (sm0[2] + sm1[2]) * (1.f / kD);
            const uint32_t mb0 = pack_bf16(mean0, mean0), mb1 = pack_bf16(mean1, mean1);
            pair_arrive(B_XC);
            TR(1);
            float ak[28], av[28], aq[28];
            float ss0 = 0.f, ss1 = 0.f, ss2 = 0.f, ss3 = 0.f;
            static_for<0, 7>([&](auto S_) {
                constexpr int s = decltype(S_)::value;
                #pragma unroll
                for (int q = 0; q < 4; q++) {
                    uint32_t (&f)[4] = a[s * 4 + q];
                    f[0] = sub_bf16x2(f[0], mb0); f[1] = sub_bf16x2(f[1], mb1);
                    f[2] = sub_bf16x2(f[2], mb0); f[3] = sub_bf16x2(f[3], mb1);
                }
                mbar_wait(BAR(B_WKVF + s), 0);
                wg_fence();
                static_for<0, 4>([&](auto Q_) {
                    constexpr int q = decltype(Q_)::value;
                    uint32_t (&f)[4] = a[s * 4 + q];
                    wgmma_rs_n56<SM_WKV + s * 16384 + q * 2048, (s | q) != 0>(ak, f[0], f[1], f[2], f[3], dw);
                    wgmma_rs_n56<SM_WKV + s * 16384 + q * 2048 + 8192, (s | q) != 0>(av, f[0], f[1], f[2], f[3], dw);
                });
                wg_commit();
                uint32_t p0 = sqr_bf16x2(a[s * 4][0]), p1 = sqr_bf16x2(a[s * 4][1]), p2 = sqr_bf16x2(a[s * 4][2]), p3 = sqr_bf16x2(a[s * 4][3]);
                #pragma unroll
                for (int q = 1; q < 4; q++) {
                    p0 = sqa_bf16x2(a[s * 4 + q][0], p0); p1 = sqa_bf16x2(a[s * 4 + q][1], p1);
                    p2 = sqa_bf16x2(a[s * 4 + q][2], p2); p3 = sqa_bf16x2(a[s * 4 + q][3], p3);
                }
                p0 = add_bf16x2(p0, p2); p1 = add_bf16x2(p1, p3);
                ss0 += bf_lo(p0); ss2 += bf_hi(p0); ss1 += bf_lo(p1); ss3 += bf_hi(p1);
                if (s == 4) { wg_wait<1>(); pair_arrive(B_KV3); }
            });
            auto q_chunk = [&](auto K0_, auto K1_) {
                wg_fence();
                static_for<decltype(K0_)::value, decltype(K1_)::value>([&](auto K_) {
                    constexpr int k = decltype(K_)::value;
                    wgmma_rs_n56<SM_X + k * 2048, k != 0>(aq, a[k][0], a[k][1], a[k][2], a[k][3], dw);
                });
                wg_commit();
            };
            #define QCHUNK(k0, k1) q_chunk(std::integral_constant<int, k0>{}, std::integral_constant<int, k1>{})
            const float dl0 = mean0 - bf_lo(mb0), dl1 = mean1 - bf_lo(mb1);
            const float rs0 = rsq(fmaxf(quad_sum(ss0 + ss2) * (1.f / kD) - dl0 * dl0, 0.f) + kEps);
            const float rs1 = rsq(fmaxf(quad_sum(ss1 + ss3) * (1.f / kD) - dl1 * dl1, 0.f) + kEps);
            float rk[3][2];
            rk[1][0] = __shfl_sync(~0u, rs0, t * 8); rk[1][1] = __shfl_sync(~0u, rs0, t * 8 + 4);
            rk[2][0] = __shfl_sync(~0u, rs1, t * 8); rk[2][1] = __shfl_sync(~0u, rs1, t * 8 + 4);
            const uint32_t stg = sb + SM_RED + (1 - wg) * 16384 + lane * 16;
            uint4* hp = opaque_ptr(&g_halo[((ti * 8 + hg) * 2 + wg) * 128 + lane]);
            mbar_wait2(BAR(B_EP), 0, BAR(B_WQF), 0);
            tag = lds1(sb + SM_EPOCH);
            QCHUNK(0, QC0);
            wg_wait<1>();
            reg_fence(ak); reg_fence(av);
            TR(2);
            uint32_t kf[3][7], vf[3][7];
            #pragma unroll
            for (int c = 0; c < 7; c++) {
                kf[2][c] = pack_bf16(ak[4 * c + 2], ak[4 * c + 3]);
                vf[2][c] = movm(pack_bf16(av[4 * c + 2], av[4 * c + 3]));
            }
            const uint32_t om = ~lane & 1;
            if (w == 3) {
                stg4(hp,      set_par(kf[2][0], om, tag), kf[2][1], kf[2][2], kf[2][3]);
                stg4(hp + 32, set_par(kf[2][4], om, tag), kf[2][5], kf[2][6], vf[2][0]);
                stg4(hp + 64, set_par(vf[2][1], om, tag), vf[2][2], vf[2][3], vf[2][4]);
                stg4(hp + 96, set_par(vf[2][5], om, tag), vf[2][6], __float_as_uint(rk[2][0]), __float_as_uint(rk[2][1]));
            } else {
                sts4(stg + w * 2048 + 0,    kf[2][0], kf[2][1], kf[2][2], kf[2][3]);
                sts4(stg + w * 2048 + 512,  kf[2][4], kf[2][5], kf[2][6], vf[2][0]);
                sts4(stg + w * 2048 + 1024, vf[2][1], vf[2][2], vf[2][3], vf[2][4]);
                sts4(stg + w * 2048 + 1536, vf[2][5], vf[2][6], __float_as_uint(rk[2][0]), __float_as_uint(rk[2][1]));
            }
            pair_arrive(B_KVC);
            QCHUNK(QC0, QC1);
            #pragma unroll
            for (int c = 0; c < 7; c++) {
                kf[1][c] = pack_bf16(ak[4 * c], ak[4 * c + 1]);
                vf[1][c] = movm(pack_bf16(av[4 * c], av[4 * c + 1]));
            }
            QCHUNK(QC1, QC2);
            named_bar(1 + wg, 128);
            uint4* op = opaque_ptr(&g_o[(((ti * 2 + wg) * 4 + w) * 28 + ((7 * hg) >> 1)) * 32 + lane]);
            uint32_t* ofl = opaque_ptr(&g_flag_o[(((ti * 2 + wg) * 4 + w) * 8 + hg) * FS]);
            QCHUNK(QC2, 28);
            #undef QCHUNK
            mbar_wait(BAR(w == 0 ? B_HL + wg : B_EP), 0);
            {
                const uint32_t sr = stg + ((w + 3) & 3) * 2048;
                const uint4 u0 = lds4(sr), u1 = lds4(sr + 512), u2 = lds4(sr + 1024), u3 = lds4(sr + 1536);
                kf[0][0] = u0.x; kf[0][1] = u0.y; kf[0][2] = u0.z; kf[0][3] = u0.w;
                kf[0][4] = u1.x; kf[0][5] = u1.y; kf[0][6] = u1.z; vf[0][0] = u1.w;
                vf[0][1] = u2.x; vf[0][2] = u2.y; vf[0][3] = u2.z; vf[0][4] = u2.w;
                vf[0][5] = u3.x; vf[0][6] = u3.y; rk[0][0] = __uint_as_float(u3.z); rk[0][1] = __uint_as_float(u3.w);
            }
            const bool gt0 = 2 * t > g, gt1 = 2 * t + 1 > g, no_prev = ti == 0 && w == 0;
            const float ke0 = gt0 ? rk[0][0] : rk[1][0], ke1 = gt1 ? rk[0][1] : rk[1][1];
            const float kf0 = gt0 ? rk[1][0] : rk[2][0], kf1 = gt1 ? rk[1][1] : rk[2][1];
            constexpr float kScale = 0.18898223650461362f * 1.4426950408889634f;
            const float se0 = ke0 * (rs0 * kScale), se1 = ke1 * (rs0 * kScale), sf0 = kf0 * (rs1 * kScale), sf1 = kf1 * (rs1 * kScale);
            const float NEG = -__int_as_float(0x7f800000);
            const float nb0 = gt0 && no_prev ? NEG : 0.f, nb1 = gt1 && no_prev ? NEG : 0.f;
            TR(3);
            wg_wait<0>();
            reg_fence(aq);
            warp_arrive(BAR(B_A1D));
            TR(4);
            uint32_t qf[7][2];
            #pragma unroll
            for (int c = 0; c < 7; c++) {
                qf[c][0] = pack_bf16(aq[4 * c], aq[4 * c + 1]);
                qf[c][1] = pack_bf16(aq[4 * c + 2], aq[4 * c + 3]);
            }
            uint32_t ow[7][2];
            #pragma unroll
            for (int hd = 0; hd < 2; hd++) {
                const int c0 = hd * 3;
                const bool keep = hd == 0 ? (t < 2) : (t >= 2);
                const uint32_t q3a = keep ? qf[3][0] : 0u, q3b = keep ? qf[3][1] : 0u;
                float sc_[3][4];
                #pragma unroll
                for (int n = 0; n < 3; n++) {
                    sc_[n][0] = sc_[n][1] = sc_[n][2] = sc_[n][3] = 0.f;
                    if (hd == 0) {
                        mma16816(sc_[n], qf[0][0], qf[0][1], qf[1][0], qf[1][1], kf[n][0], kf[n][1]);
                        mma16816(sc_[n], qf[2][0], qf[2][1], q3a, q3b, kf[n][2], kf[n][3]);
                    } else {
                        mma16816(sc_[n], q3a, q3b, qf[4][0], qf[4][1], kf[n][3], kf[n][4]);
                        mma16816(sc_[n], qf[5][0], qf[5][1], qf[6][0], qf[6][1], kf[n][5], kf[n][6]);
                    }
                }
                const float e0 = fmaf(gt0 ? sc_[0][0] : sc_[1][0], se0, nb0), e1 = fmaf(gt1 ? sc_[0][1] : sc_[1][1], se1, nb1);
                const float f0 = (gt0 ? sc_[1][2] : sc_[2][2]) * sf0, f1 = (gt1 ? sc_[1][3] : sc_[2][3]) * sf1;
                const float me = quad_max(fmaxf(e0, e1)), mf = quad_max(fmaxf(f0, f1));
                const float p0 = ex2(e0 - me), p1 = ex2(e1 - me), r0 = ex2(f0 - mf), r1 = ex2(f1 - mf);
                const float ie = rcp(quad_sum(p0 + p1)), jf = rcp(quad_sum(r0 + r1));
                const uint32_t pp = pack_bf16(p0 * ke0 * ie, p1 * ke1 * ie), rp = pack_bf16(r0 * kf0 * jf, r1 * kf1 * jf);
                const uint32_t mk = (gt0 ? 0x0000ffffu : 0u) | (gt1 ? 0xffff0000u : 0u);
                const uint32_t sw = hg >= 4 ? ~0u : 0u;
                const uint32_t pa0 = pp & mk & ~sw, pa1 = pp & mk & sw, pb0 = rp & ~mk & sw, pb1 = rp & ~mk & ~sw;
                const uint32_t pa2 = sw ? rp & mk : pp & ~mk, pa3 = sw ? pp & ~mk : rp & mk;
                #pragma unroll
                for (int c = 0; c < 4; c++) {
                    float o[4] = {0.f, 0.f, 0.f, 0.f};
                    mma16816(o, pa0, pa1, pa2, pa3, vf[0][c0 + c], vf[1][c0 + c]);
                    mma1688(o, pb0, pb1, vf[2][c0 + c]);
                    const uint32_t lo = pack_bf16(o[0], o[1]), hi = pack_bf16(o[2], o[3]);
                    if (hd == 1 && c == 0) { if (t >= 2) { ow[3][0] = lo; ow[3][1] = hi; } }
                    else { ow[c0 + c][0] = lo; ow[c0 + c][1] = hi; }
                }
            }
            if (hg & 1) {
                stg2((uint2*)(op - lane) + 32 + lane, set_par(ow[0][0], om, tag), ow[0][1]);
                stg4(op + 32, set_par(ow[1][0], om, tag), ow[1][1], ow[2][0], ow[2][1]);
                stg4(op + 64, set_par(ow[3][0], om, tag), ow[3][1], ow[4][0], ow[4][1]);
                stg4(op + 96, set_par(ow[5][0], om, tag), ow[5][1], ow[6][0], ow[6][1]);
            } else {
                stg4(op,      set_par(ow[0][0], om, tag), ow[0][1], ow[1][0], ow[1][1]);
                stg4(op + 32, set_par(ow[2][0], om, tag), ow[2][1], ow[3][0], ow[3][1]);
                stg4(op + 64, set_par(ow[4][0], om, tag), ow[4][1], ow[5][0], ow[5][1]);
                stg2((uint2*)(op + 96 - lane) + lane, set_par(ow[6][0], om, tag), ow[6][1]);
            }
            if (lane == 0) asm volatile("st.relaxed.gpu.global.u32 [%0], %1;" :: "l"(ofl), "r"(tag) : "memory");
            TR(5);
        }
        {
            float acc2[64];
            const bool wide = a2j != 3;
            mbar_wait(BAR(B_XRF), 0);
            {
                const uint32_t xa = sb + SM_X + 8 * 8192 + (w * 16 + wg * 8 + (lane & 7)) * 128;
                #pragma unroll
                for (int c = 0; c < 4; c++) {
                    uint32_t xr[4];
                    asm volatile("ldmatrix.sync.aligned.m8n8.x4.shared.b16 {%0,%1,%2,%3}, [%4];"
                                 : "=r"(xr[0]), "=r"(xr[1]), "=r"(xr[2]), "=r"(xr[3])
                                 : "r"(xa + (c >> 1) * 8192 + ((((c & 1) * 4 + (lane >> 3)) ^ (lane & 7)) << 4)) : "memory");
                    #pragma unroll
                    for (int e = 0; e < 4; e++) {
                        acc2[16 * c + 4 * e] = bf_lo(xr[e]); acc2[16 * c + 4 * e + 1] = bf_hi(xr[e]);
                        acc2[16 * c + 4 * e + 2] = 0.f;      acc2[16 * c + 4 * e + 3] = 0.f;
                    }
                }
            }
            const uint4* op = &g_o[((a2s * 4 + w) * 28 + wg * 14) * 32];
            const uint32_t rsend = opaque(sb + SM_RED + (1 - wg) * 16384 + w * 4096 + lane * 16);
            const uint32_t rrecv = opaque(sb + SM_RED + wg * 16384 + w * 4096 + lane * 16);
            uint4* spw = opaque_ptr(&g_stats[(a2s * 4 + a2j) * 64 + (w * 2 + wg) * 8 + g]);
            const uint4* spr = opaque_ptr(&g_stats[(a2s * 4 + t) * 64 + (w * 2 + wg) * 8 + g]);
            uint2* hp = opaque_ptr((uint2*)g_h + ((a2s * 8 + w * 2 + wg) * 28 + a2j * 8) * 32 + lane);
            uint32_t* np = opaque_ptr((uint32_t*)&g_hn[(a2s * 56 + a2j * 16) * 64] + (w * 2 + wg) * 32 + lane);
            uint32_t* nfl = opaque_ptr(&g_flag_h[(a2s * 4 + a2j) * FS]);
            const uint64_t dwo = make_desc(sb + SM_WKV + wg * 57344, 28672, true);
            bias1 = prm.b1[g1f * 64 + w * 16 + rank * 8 + g];
            const __nv_bfloat16 bias2 = prm.b2[ti * 128 + (w * 16 + wg * 8 + g) * 2 + a2p];
            reg_fence(acc2);
            mbar_wait(BAR(B_WOF + wg), 0);
            {
                const uint32_t* pp = &g_flag_o[((a2s * 4 + w) * 8 + wg * 4 + t) * FS];
                int it = 0;
                while (__any_sync(~0u, ld_rlx(pp) != tag)) { if (++it > kSpinLimit) { TIMEOUT(102); break; } }
            }
            TR(6);
            uint4 of[14];
            auto load_o = [&](int k) {
                if (k % 7 == 3) {
                    const uint2 lo = ld_rlx2((const uint2*)(op + k * 32) + lane), hi = ld_rlx2((const uint2*)(op + k * 32) + 32 + lane);
                    of[k] = make_uint4(lo.x, lo.y, hi.x, hi.y);
                } else of[k] = ld_rlx4(op + k * 32 + lane);
            };
            #pragma unroll
            for (int k = 0; k < 14; k++) load_o(k);
            static_for<0, 4>([&](auto G_) {
                constexpr int k0 = (decltype(G_)::value * 7) / 2, k1 = (decltype(G_)::value * 7 + 7) / 2;
                int it = 0;
                while (true) {
                    uint32_t bad = 0;
                    #pragma unroll
                    for (int k = k0; k < k1; k++) bad |= (of[k].x ^ tag) | (k % 7 == 3 ? of[k].z ^ tag : 0u);
                    if (!__any_sync(~0u, bad & ~lane & 1)) break;
                    if (++it > kSpinLimit) { TIMEOUT(109); break; }
                    RETRY_COUNT(1);
                    #pragma unroll
                    for (int k = k0; k < k1; k++) load_o(k);
                }
                if (k1 == 14) warp_arrive(BAR(B_OL));
                wg_fence();
                static_for<k0, k1>([&](auto K_) { constexpr int k = decltype(K_)::value;
                    wgmma_rs_n128<k * 2048, 1>(acc2, of[k].x, of[k].y, of[k].z, of[k].w, dwo); });
            });
            wg_commit();
            wg_wait<0>();
            reg_fence(acc2);
            TR(7);
            #pragma unroll
            for (int c = 0; c < 8; c++)
                sts4(rsend + c * 512, __float_as_uint(acc2[8 * c + 2]), __float_as_uint(acc2[8 * c + 3]), __float_as_uint(acc2[8 * c + 6]), __float_as_uint(acc2[8 * c + 7]));
            named_bar(3, 256);
            float hv[32];
            float s0 = 0.f, s1 = 0.f, q0 = 0.f, q1 = 0.f;
            #pragma unroll
            for (int c = 0; c < 8; c++) {
                const uint4 u = lds4(rrecv + c * 512);
                hv[4 * c]     = acc2[8 * c] + __uint_as_float(u.x);     hv[4 * c + 1] = acc2[8 * c + 1] + __uint_as_float(u.y);
                hv[4 * c + 2] = acc2[8 * c + 4] + __uint_as_float(u.z); hv[4 * c + 3] = acc2[8 * c + 5] + __uint_as_float(u.w);
            }
            #pragma unroll
            for (int c = 0; c < 16; c += 2) { s0 += hv[c]; s1 += hv[c + 1]; q0 = fmaf(hv[c], hv[c], q0); q1 = fmaf(hv[c + 1], hv[c + 1], q1); }
            if (wide) {
                #pragma unroll
                for (int c = 16; c < 32; c += 2) { s0 += hv[c]; s1 += hv[c + 1]; q0 = fmaf(hv[c], hv[c], q0); q1 = fmaf(hv[c + 1], hv[c + 1], q1); }
            }
            s0 = quad_sum(s0 + s1); q0 = quad_sum(q0 + q1);
            if (t == 0) st_ll(spw, __float_as_uint(s0), __float_as_uint(q0), tag);
            TR(8);
            fence_async_smem();
            const float b2v = __bfloat162float(bias2);
            #pragma unroll
            for (int c = 0; c < 8; c++)
                if (c < 4 || wide) stg2(hp + c * 32, set_par(pack_bf16(hv[4 * c] + b2v, hv[4 * c + 1] + b2v), t == 0, tag), pack_bf16(hv[4 * c + 2] + b2v, hv[4 * c + 3] + b2v));
            const uint32_t nm = opaque((lane & 7) == w * 2 + wg ? 1u << (lane >> 3) : 0u);
            uint32_t um, uv;
            {
                int it = 0;
                while (!__all_sync(~0u, ld_ll(spr, um, uv, tag))) { if (++it > kSpinLimit) { TIMEOUT(103); break; } }
            }
            TR(9);
            const float mean = quad_sum(__uint_as_float(um)) * (1.f / kD);
            const float var = fmaxf(fmaf(quad_sum(__uint_as_float(uv)), 1.f / kD, -mean * mean), 0.f);
            const float r1 = rsq(var + kEps);
            const float rr = 0.5f * r1 * rsq(fmaf(var * r1, r1, kEps));
            const float mr = -mean * rr;
            #pragma unroll
            for (int c = 0; c < 16; c++)
                if (c < 8 || wide) stg1(np + c * 256, set_par(pack_bf16(fmaf(hv[2 * c], rr, mr), fmaf(hv[2 * c + 1], rr, mr)), (nm >> (c & 3)) & 1, tag));
            named_bar(3, 256);
            mbar_arrive_remote_if(pbar0 + 8u * B_PD, tid == 0 && !g1_on);
            if (tid == 128) {
                st_flag(nfl, tag);
                asm volatile("st.shared.u32 [%0], %1;" :: "r"(sb + SM_TG), "r"(gtime32()) : "memory");
                mbar_arrive(BAR(B_HD));
            }
            __syncwarp();
            TR(10);
        }
        float acc[56];
        const uint32_t xch = opaque(sb + SM_XCH + w * 1920 + lane * 16);
        uint32_t peer_xch; const uint32_t peer_bar = pbar0;
        asm volatile("mapa.shared::cluster.u32 %0, %1, %2;" : "=r"(peer_xch) : "r"(xch), "r"(rank ^ 1));
        uint2 hr[7];
        const int tok = g2s * 64 + w * 16 + rank * 8 + g, pr = (tok & 127) >> 1;
        const uint2* hp = (const uint2*)g_h + ((((tok >> 7) * 2 + (tok & 1)) * 8 + (pr >> 3)) * 28 + (g2j + 2 * wg) * 7) * 32 + (pr & 7) * 4 + t;
        auto load_h = [&]() {
            #pragma unroll
            for (int c = 0; c < 7; c++) hr[c] = ld_rlx2(hp + c * 32);
        };
        const uint32_t b1h = pack_bf16(0.5f * __bfloat162float(bias1), 0.5f * __bfloat162float(bias1));
        #pragma unroll
        for (int c = 0; c < 7; c++) hr[c] = make_uint2(b1h, b1h);
        if (!g1_on) { mbar_wait(BAR(B_GO), 0); load_h(); }
        uint32_t* const gp1 = (uint32_t*)&g_g[(g1f * 56 + (g1j + 2 * wg) * 14) * 64] + (w * 2 + rank) * 32 + lane;
        uint32_t* const gp2 = (uint32_t*)(prm.out + (size_t)(g2s * 64 + w * 16 + rank * 8 + (lane >> 4)) * kD + (g2j + 2 * wg) * 112) + (lane & 15) * 4;
        uint32_t gm[4];
        #pragma unroll
        for (int i = 0; i < 4; i++) gm[i] = lane == ((g1j * 2 + i) & 3) * 8 + w * 2 + rank;
        const bool lead = elect_one();
        const uint64_t da0 = make_desc(sb, 0, true), db0 = make_desc(sb + SM_B, 128, false);
        #pragma unroll 1
        for (int ge = g1_on ? 0 : 1; ge < 2; ge++) {
            if (ge) {
                int it = 0;
                while (true) {
                    uint32_t bad = 0;
                    #pragma unroll
                    for (int c = 0; c < 7; c++) bad |= hr[c].x ^ tag;
                    if (!__any_sync(~0u, t == 0 && (bad & 1))) break;
                    if (++it > kSpinLimit) { TIMEOUT(110); break; }
                    load_h();
                }
            }
            auto init_acc = [&](auto R_) {
                constexpr int o = decltype(R_)::value * 2;
                #pragma unroll
                for (int c = 0; c < 14; c++) {
                    const uint32_t hw = c & 1 ? hr[c >> 1].y : hr[c >> 1].x;
                    acc[4 * c + o] = bf_lo(hw); acc[4 * c + 1 + o] = bf_hi(hw);
                    acc[4 * c + 2 - o] = 0.f;   acc[4 * c + 3 - o] = 0.f;
                }
                reg_fence(acc);
            };
            if (rank) init_acc(std::integral_constant<int, 1>{}); else init_acc(std::integral_constant<int, 0>{});
            const uint32_t slot0 = g1_on ? (ge ? 4 : 2 * wg) : 0;
            uint32_t ph = 0, rb = bar0 + slot0 * 8;
            uint64_t da = da0 + ge * 1024, db = db0 + slot0 * 896;
            uint32_t prev = BAR(B_WKVF);
            mbar_wait(BAR(B_EP), 0);
            if (wg == 1 || (ge && g1_on)) named_bar(5 - wg, 256);
            mbar_wait(rb + B_BF * 8, ph);
            TR(11 + ge * 4);
            #pragma unroll 1
            for (int n = ge ? 14 : 16;;) {
                wg_fence();
                wgmma_ss_n112<0,    0>(acc, da, db);
                wgmma_ss_n112<2048, 256>(acc, da, db);
                wgmma_ss_n112<4096, 512>(acc, da, db);
                wgmma_ss_n112<6144, 768>(acc, da, db);
                wg_commit();
                if (--n == 0 && ge + wg < 2) named_arrive(4 + wg, 256);
                const uint32_t cur = rb + B_BE * 8;
                da += 512; db += 896; rb += 8;
                if (rb == bar0 + NB * 8) { rb = bar0; db = db0; ph ^= 1; }
                wg_wait<1>();
                mbar_arrive_if(prev, lead);
                prev = cur;
                if (n == 0) break;
                if (!mbar_try(rb + B_BF * 8, ph)) mbar_wait(rb + B_BF * 8, ph);
            }
            const int use = ge * 2 + wg;
            const uint32_t xfree = BAR(use > (g1_on ? 0 : 2) ? B_RE + use - 1 : B_PD);
            const bool xok = mbar_test(xfree, 0);
            wg_wait<0>();
            reg_fence(acc);
            mbar_arrive_if(prev, lead);
            TR(12 + ge * 4);
            if (!xok) mbar_wait(xfree, 0);
            float v[28];
            auto reduce = [&](auto R_) {
                constexpr int o = decltype(R_)::value * 2;
                const uint32_t rf = peer_bar + (B_RF + use) * 8;
                float dly = __uint_as_float(0x3f800000u | lane); uint32_t pa = peer_xch;
                #pragma unroll
                for (int c = 0; c < 4; c++) {
                    const uint32_t p0 = pack_bf16(acc[16 * c + 2 - o], acc[16 * c + 3 - o]), p1 = pack_bf16(acc[16 * c + 6 - o], acc[16 * c + 7 - o]);
                    if (c < 3) {
                        const uint32_t p2 = pack_bf16(acc[16 * c + 10 - o], acc[16 * c + 11 - o]), p3 = pack_bf16(acc[16 * c + 14 - o], acc[16 * c + 15 - o]);
                        asm volatile("st.async.shared::cluster.mbarrier::complete_tx::bytes.v4.b32 [%0], {%1,%2,%3,%4}, [%5];"
                                     :: "r"(pa + c * 512), "r"(p0), "r"(p1), "r"(p2), "r"(p3), "r"(rf) : "memory");
                        if (use != 3) {
                            #pragma unroll
                            for (int i = 0; i < XPACE; i++) asm volatile("tanh.approx.f32 %0, %0;" : "+f"(dly) :: "memory");
                            pa += __float_as_uint(dly) >> 30;
                        }
                    } else {
                        asm volatile("st.async.shared::cluster.mbarrier::complete_tx::bytes.v2.b32 [%0], {%1,%2}, [%3];"
                                     :: "r"(pa + 1536 - lane * 8), "r"(p0), "r"(p1), "r"(rf) : "memory");
                    }
                }
                if (!ge) load_h();
                mbar_wait(BAR(B_RF + use), 0);
                #pragma unroll
                for (int c = 0; c < 4; c++) {
                    uint4 u;
                    if (c < 3) u = lds4(xch + c * 512); else { const uint2 u2 = lds2(xch + 1536 - lane * 8); u.x = u2.x; u.y = u2.y; }
                    v[8 * c]     = acc[16 * c + o] + bf_lo(u.x);     v[8 * c + 1] = acc[16 * c + 1 + o] + bf_hi(u.x);
                    v[8 * c + 2] = acc[16 * c + 4 + o] + bf_lo(u.y); v[8 * c + 3] = acc[16 * c + 5 + o] + bf_hi(u.y);
                    if (c < 3) {
                        v[8 * c + 4] = acc[16 * c + 8 + o] + bf_lo(u.z);  v[8 * c + 5] = acc[16 * c + 9 + o] + bf_hi(u.z);
                        v[8 * c + 6] = acc[16 * c + 12 + o] + bf_lo(u.w); v[8 * c + 7] = acc[16 * c + 13 + o] + bf_hi(u.w);
                    }
                }
            };
            if (rank) reduce(std::integral_constant<int, 1>{}); else reduce(std::integral_constant<int, 0>{});
            TR(13 + ge * 4);
            if (!ge) {
                #pragma unroll
                for (int c = 0; c < 14; c++) {
                    float r[2];
                    #pragma unroll
                    for (int e = 0; e < 2; e++) {
                        const float u = v[2 * c + e];
                        r[e] = fmaf(u, tanh_hw(u * fmaf(u * u, 8.f * 0.7978845608f * 0.044715f, 2.f * 0.7978845608f)), u);
                    }
                    stg1(gp1 + c * 256, set_par(pack_bf16(r[0], r[1]), gm[c & 3], tag));
                }
                named_bar(1 + wg, 128);
                if (w == 0 && lane == 0) {
                    asm volatile("st.shared.u32 [%0], %1;" :: "r"(sb + SM_TG + 8 + wg * 4), "r"(clk32() + XSPEC) : "memory");
                    mbar_arrive(BAR(B_GD + wg));
                }
                mbar_arrive_remote_if(peer_bar + (B_RE + use) * 8, lead);
            } else {
                const uint32_t stw = xch - lane * 16;
                uint32_t pk[14];
                #pragma unroll
                for (int c = 0; c < 14; c++) pk[c] = pack_bf16(v[2 * c], v[2 * c + 1]);
                __syncwarp();
                const uint32_t sa = stw + (lane & 7) * 240 + (lane >> 3) * 16;
                #pragma unroll
                for (int m = 0; m < 3; m++)
                    asm volatile("stmatrix.sync.aligned.m8n8.x4.shared.b16 [%0], {%1,%2,%3,%4};"
                                 :: "r"(sa + m * 64), "r"(pk[4 * m]), "r"(pk[4 * m + 1]), "r"(pk[4 * m + 2]), "r"(pk[4 * m + 3]) : "memory");
                asm volatile("stmatrix.sync.aligned.m8n8.x2.shared.b16 [%0], {%1,%2};" :: "r"(sa + 192), "r"(pk[12]), "r"(pk[13]) : "memory");
                __syncwarp();
                #pragma unroll
                for (int i = 0; i < 4; i++) {
                    const int r = 2 * i + (lane >> 4), ch = lane & 15;
                    if (ch < 14) { const uint4 u = lds4(stw + r * 240 + ch * 16); stg4(gp2 + i * 448, u.x, u.y, u.z, u.w); }
                }
                __syncwarp();
                mbar_arrive_remote_if(peer_bar + (B_RE + 2) * 8, lead && wg == 0);
            }
            TR(14 + ge * 4);
        }
        if (tid == 128) TRG(62);
        if (b == 0 && tid == 128) g_epoch = tag;
    }
}

typedef CUresult (*EncodeFn)(CUtensorMap*, CUtensorMapDataType, cuuint32_t, void*, const cuuint64_t*, const cuuint64_t*,
                             const cuuint32_t*, const cuuint32_t*, CUtensorMapInterleave, CUtensorMapSwizzle,
                             CUtensorMapL2promotion, CUtensorMapFloatOOBfill);

void make_map(EncodeFn enc, CUtensorMap* m, const void* base, uint64_t cols, uint64_t rows, uint32_t box_rows) {
    cuuint64_t dims[2] = {cols, rows};
    cuuint64_t strides[1] = {cols * 2};
    cuuint32_t box[2] = {64, box_rows};
    cuuint32_t es[2] = {1, 1};
    enc(m, CU_TENSOR_MAP_DATA_TYPE_BFLOAT16, 2, const_cast<void*>(base), dims, strides, box, es, CU_TENSOR_MAP_INTERLEAVE_NONE,
        CU_TENSOR_MAP_SWIZZLE_128B, CU_TENSOR_MAP_L2_PROMOTION_L2_128B, CU_TENSOR_MAP_FLOAT_OOB_FILL_NONE);
}

}

extern "C" void kernel_launch(void* const* d_in, const int* in_sizes, int n_in, void* d_out, int out_size) {
    (void)in_sizes; (void)n_in; (void)out_size;
    void* fn = nullptr;
    cudaDriverEntryPointQueryResult qr;
    cudaGetDriverEntryPoint("cuTensorMapEncodeTiled", &fn, cudaEnableDefault, &qr);
    EncodeFn enc = (EncodeFn)fn;
    CUtensorMap mX, mWqkv, mWo, mW1, mW2;
    make_map(enc, &mX, d_in[0], 2 * kD, kS / 2, 64);
    make_map(enc, &mWqkv, d_in[1], 3 * kD, kD, 64);
    make_map(enc, &mWo, d_in[2], kD, kD, 224);
    make_map(enc, &mW1, d_in[4], 2 * kF, kS / 2, 64);
    make_map(enc, &mW2, d_in[6], kS, kF, 64);
    Params prm;
    prm.x = (const __nv_bfloat16*)d_in[0];
    prm.wqkv = (const __nv_bfloat16*)d_in[1];
    prm.wo = (const __nv_bfloat16*)d_in[2];
    prm.w1 = (const __nv_bfloat16*)d_in[4];
    prm.b1 = (const __nv_bfloat16*)d_in[5];
    prm.w2 = (const __nv_bfloat16*)d_in[6];
    prm.b2 = (const __nv_bfloat16*)d_in[7];
    prm.out = (__nv_bfloat16*)d_out;
    cudaFuncSetAttribute(fused_kernel, cudaFuncAttributeMaxDynamicSharedMemorySize, SM_TOTAL);
    fused_kernel<<<128, 384, SM_TOTAL, cudaStreamPerThread>>>(mX, mWqkv, mWo, mW1, mW2, prm);
}
```

```cpp
#include <cuda_runtime.h>
#include <cuda.h>
#include <cuda_bf16.h>
#include <stdint.h>
#include <type_traits>

namespace {

constexpr int kS = 2048, kD = 448, kF = 1792;
constexpr float kEps = 1e-5f;

#define FS 32
__device__ __align__(1024) uint4    g_o[32 * 56 * 64];
__device__ __align__(1024) uint4    g_h[32 * 8 * 8 * 64];
__device__ __align__(1024) uint4    g_hn[32 * 56 * 64];
__device__ __align__(1024) uint4    g_g[28 * 56 * 64];
__device__ __align__(1024) uint4    g_halo[16 * 8 * 2 * 4 * 32];
__device__ __align__(1024) uint32_t g_stats[32 * 8 * 4 * 32];
__device__ __align__(1024) uint32_t g_flag_o[32 * 8 * FS];
__device__ __align__(1024) uint32_t g_flag_h[32 * 4 * FS];
__device__ uint32_t g_epoch;
#define TIMEOUT(code)
#define RETRY_COUNT(i)
#define CAP_DECL(n, k)
#define CAP(n)
#define CAP_SKIP(n)
#define TR2(idx)
#define TR(idx)
#define TRW(idx)
#define TRG(idx)

constexpr uint32_t SM_X    = 0;
constexpr uint32_t SM_WKV  = 114688;
constexpr uint32_t SM_XR   = 24576;
constexpr uint32_t SM_STG  = 40960;
constexpr uint32_t SM_WQ   = 57344;
constexpr uint32_t SM_XCH  = 0;
constexpr uint32_t SM_B    = 131072;
constexpr uint32_t SM_BAR  = 231424;
constexpr uint32_t SM_TOTAL = SM_BAR + 1024;
constexpr int NB = 7;
#define SH1 0
#define SH2 0
#define SH2N 5
#define SH3 0
#define NSPEC 4
#define XSPEC 700
#define C2 0
#define C3 0
#define CN2 8000
#define CN3 12000
constexpr int B_XF = 0, B_WKVF = 7, B_WQF = 14, B_XRF = 15, B_WOF = 16,
              B_XC = 18, B_KV3 = 19, B_KVC = 20,
              B_A1D = 21, B_XD = 22, B_OC = 23,
              B_BE = 24, B_RE = B_BE + NB,
              B_AF = B_RE + 3, B_BL = B_AF + 16  , B_BF = B_BL + NB + 4  ,
              B_RF = B_BF + NB + 4, B_EP = B_RF + 4, B_PD = B_EP + 1, B_RT = B_PD + 1, B_HL = B_RT + 2,
              B_HD = B_HL + 2  , B_GO = B_HD + 1, B_GD = B_GO + 1, B_COUNT = B_GD + 2;
#define WEARLY 6
#define PF0 126
#define TMPF 2
#define RSTE 2
#define POLLP 1
#define PROBEP 1
#define LOADP 1
#define LOADW 64
#define NOB 0
#define AEARLY 5
#define W1PACE 400
#define W2PACE 200
#define PFPACE 290
#define PFBAR (B_XF + 6)
#define DELTA 1344
#define DELTA2 DELTA
#define BPACE 230
#define BURST 2
#define W1OFF 350
#define W2OFF 2900
#define XPACE 0
#define PSTAG 200
constexpr uint32_t SM_EPOCH = SM_BAR + B_COUNT * 8, SM_TG = SM_EPOCH + 4  , SM_TG2 = SM_TG + 16  , SM_TR = SM_BAR + 768;

#define HDELAY 200
#define QC0 4
#define QC1 10
#define QC2 16
#define SDELAY 500
#define PDELAY 500
#define NPRE 10
#define PREPACE 0
#define AFIRST 0
#define DELTAO 1024
#define W1Q 3
constexpr uint32_t w2_rounds(int h) { uint32_t m = 0; for (int i = 0; i < 14; i++) { const int p = 25 + i * 20 / 13; if ((p & 1) == h) m |= 1u << (p / 2 + 1); } return m; }
constexpr uint32_t kAMask0 = w2_rounds(0), kAMask1 = w2_rounds(1) | ((1u << (16 - NPRE)) - 1) << W1Q;

constexpr int kSpinLimit = 1 << 15;
__device__ __forceinline__ bool elect_one() {
    uint32_t p;
    asm volatile("{ .reg .pred P; elect.sync _|P, 0xffffffff; selp.u32 %0, 1, 0, P; }" : "=r"(p));
    return p;
}
__device__ __forceinline__ void mbar_init(uint32_t bar, uint32_t cnt) { asm volatile("mbarrier.init.shared::cta.b64 [%0], %1;" :: "r"(bar), "r"(cnt)); }
__device__ __forceinline__ void mbar_expect(uint32_t bar, uint32_t bytes) { asm volatile("mbarrier.arrive.expect_tx.shared::cta.b64 _, [%0], %1;" :: "r"(bar), "r"(bytes) : "memory"); }
__device__ __forceinline__ void mbar_arrive(uint32_t bar) { asm volatile("mbarrier.arrive.shared::cta.b64 _, [%0];" :: "r"(bar) : "memory"); }
__device__ __forceinline__ void mbar_wait(uint32_t bar, uint32_t parity) {
    uint32_t ok; int it = 0;
    do {
        asm volatile("{ .reg .pred p; mbarrier.try_wait.parity.shared::cta.b64 p, [%1], %2; selp.u32 %0, 1, 0, p; }"
                     : "=r"(ok) : "r"(bar), "r"(parity) : "memory");
        if (++it > kSpinLimit) { TIMEOUT((bar & 1023) >> 3); break; }
    } while (!ok);
}
__device__ __forceinline__ bool mbar_try(uint32_t bar, uint32_t parity) {
    uint32_t ok;
    asm volatile("{ .reg .pred p; mbarrier.try_wait.parity.shared::cta.b64 p, [%1], %2; selp.u32 %0, 1, 0, p; }" : "=r"(ok) : "r"(bar), "r"(parity) : "memory");
    return ok;
}
__device__ __forceinline__ bool mbar_test(uint32_t bar, uint32_t parity) {
    uint32_t ok;
    asm volatile("{ .reg .pred p; mbarrier.test_wait.parity.shared::cta.b64 p, [%1], %2; selp.u32 %0, 1, 0, p; }" : "=r"(ok) : "r"(bar), "r"(parity) : "memory");
    return ok;
}
__device__ __forceinline__ void mbar_wait2(uint32_t bar0, uint32_t par0, uint32_t bar1, uint32_t par1) {
    uint32_t ok; int it = 0;
    do {
        asm volatile("{ .reg .pred p, q; mbarrier.try_wait.parity.shared::cta.b64 p, [%1], %2;\n"
                     "mbarrier.try_wait.parity.shared::cta.b64 q, [%3], %4; and.pred p, p, q; selp.u32 %0, 1, 0, p; }"
                     : "=r"(ok) : "r"(bar0), "r"(par0), "r"(bar1), "r"(par1) : "memory");
        if (++it > kSpinLimit) { TIMEOUT((bar0 & 1023) >> 3); break; }
    } while (!ok);
}
template <int N> __device__ __forceinline__ void reg_fence(float (&d)[N]) {
    #pragma unroll
    for (int i = 0; i < N; i++) asm volatile("" : "+f"(d[i]) :: "memory");
}
__device__ __forceinline__ void mbar_wait_cluster(uint32_t bar, uint32_t parity) {
    uint32_t ok; int it = 0;
    do {
        asm volatile("{ .reg .pred p; mbarrier.try_wait.parity.acquire.cluster.shared::cta.b64 p, [%1], %2; selp.u32 %0, 1, 0, p; }"
                     : "=r"(ok) : "r"(bar), "r"(parity) : "memory");
        if (++it > kSpinLimit) { TIMEOUT((bar & 1023) >> 3); break; }
    } while (!ok);
}
__device__ __forceinline__ void mbar_arrive_if(uint32_t bar, bool pred) {
    asm volatile("{ .reg .pred p; setp.ne.u32 p, %1, 0; @p mbarrier.arrive.shared::cta.b64 _, [%0]; }" :: "r"(bar), "r"((uint32_t)pred) : "memory");
}
template <int P> __device__ __forceinline__ void tick() {
    if (P > 1) { const uint32_t t = ((uint32_t)clock() | (P - 1)) + 1; while ((int)((uint32_t)clock() - t) < 0) {} }
}
__device__ __forceinline__ void warp_arrive(uint32_t bar) { __syncwarp(); if (elect_one()) mbar_arrive(bar); }
__device__ __forceinline__ void tma2d(uint32_t dst, const CUtensorMap* m, int c0, int c1, uint32_t bar) {
    asm volatile("cp.async.bulk.tensor.2d.shared::cluster.global.mbarrier::complete_tx::bytes [%0], [%1, {%3, %4}], [%2];"
                 :: "r"(dst), "l"(m), "r"(bar), "r"(c0), "r"(c1) : "memory");
}
__device__ __forceinline__ void tma2d_mc(uint32_t dst, const CUtensorMap* m, int c0, int c1, uint32_t bar) {
    asm volatile("cp.async.bulk.tensor.2d.shared::cluster.global.mbarrier::complete_tx::bytes.multicast::cluster [%0], [%1, {%3, %4}], [%2], %5;"
                 :: "r"(dst), "l"(m), "r"(bar), "r"(c0), "r"(c1), "h"((uint16_t)3) : "memory");
}
__device__ __forceinline__ void bulk_g2s_mc(uint32_t dst, const void* src, uint32_t bytes, uint32_t bar) {
    asm volatile("cp.async.bulk.shared::cluster.global.mbarrier::complete_tx::bytes.multicast::cluster [%0], [%1], %2, [%3], %4;"
                 :: "r"(dst), "l"(src), "r"(bytes), "r"(bar), "h"((uint16_t)3) : "memory");
}
__device__ __forceinline__ void mbar_arrive_remote_if(uint32_t cluster_bar, bool pred) {
    asm volatile("{ .reg .pred p; setp.ne.u32 p, %1, 0; @p mbarrier.arrive.shared::cluster.b64 _, [%0]; }" :: "r"(cluster_bar), "r"((uint32_t)pred) : "memory");
}
__device__ __forceinline__ void bulk_g2s(uint32_t dst, const void* src, uint32_t bytes, uint32_t bar) {
    asm volatile("cp.async.bulk.shared::cluster.global.mbarrier::complete_tx::bytes [%0], [%1], %2, [%3];"
                 :: "r"(dst), "l"(src), "r"(bytes), "r"(bar) : "memory");
}
__device__ __forceinline__ void wg_fence()  { asm volatile("wgmma.fence.sync.aligned;" ::: "memory"); }
__device__ __forceinline__ void wg_commit() { asm volatile("wgmma.commit_group.sync.aligned;" ::: "memory"); }
template <int N> __device__ __forceinline__ void wg_wait() { asm volatile("wgmma.wait_group.sync.aligned %0;" :: "n"(N) : "memory"); }
__device__ __forceinline__ void named_bar(int id, int n) { asm volatile("bar.sync %0, %1;" :: "r"(id), "r"(n) : "memory"); }
__device__ __forceinline__ void named_arrive(int id, int n) { asm volatile("bar.arrive %0, %1;" :: "r"(id), "r"(n) : "memory"); }
__device__ __forceinline__ bool mbar_try2(uint32_t bar0, uint32_t par0, uint32_t bar1, uint32_t par1) {
    uint32_t ok;
    asm volatile("{ .reg .pred p, q; mbarrier.test_wait.parity.shared::cta.b64 p, [%1], %2;\n"
                 "mbarrier.test_wait.parity.shared::cta.b64 q, [%3], %4; and.pred p, p, q; selp.u32 %0, 1, 0, p; }"
                 : "=r"(ok) : "r"(bar0), "r"(par0), "r"(bar1), "r"(par1) : "memory");
    return ok;
}
__device__ __forceinline__ void fence_gpu() { asm volatile("fence.release.gpu;" ::: "memory"); }
__device__ __forceinline__ void fence_async_global() { asm volatile("fence.proxy.async.global;" ::: "memory"); }
__device__ __forceinline__ void fence_async_smem() { asm volatile("fence.proxy.async.shared::cta;" ::: "memory"); }
__device__ __forceinline__ uint32_t gtime32() { uint64_t t; asm volatile("mov.u64 %0, %%globaltimer;" : "=l"(t) :: "memory"); return (uint32_t)t; }
__device__ __forceinline__ uint32_t clk32() { uint64_t t; asm volatile("mov.u64 %0, %%clock64;" : "=l"(t) :: "memory"); return (uint32_t)t; }
__device__ __forceinline__ void spin_until(uint32_t t) { while ((int)(clk32() - t) < 0) {} }
#define SLEEPNS 20
__device__ __forceinline__ void sleep_until(uint32_t t) { while ((int)(clk32() - t) < 0) { if (SLEEPNS) __nanosleep(SLEEPNS); } }
__device__ __forceinline__ void st_flag(uint32_t* p, uint32_t v) {
    const uint64_t w = ((uint64_t)gtime32() << 32) | v;
    asm volatile("st.relaxed.gpu.global.u64 [%0], %1;" :: "l"(p), "l"(w) : "memory");
}
__device__ __forceinline__ void ld_flag_if(uint64_t& v, const uint32_t* p, bool pred) {
    asm volatile("{ .reg .pred p; setp.ne.u32 p, %2, 0; @p ld.relaxed.gpu.global.u64 %0, [%1]; }" : "+l"(v) : "l"(p), "r"((uint32_t)pred) : "memory");
}
__device__ __forceinline__ uint32_t ld_acq(const uint32_t* p) { uint32_t v; asm volatile("ld.acquire.gpu.global.u32 %0, [%1];" : "=r"(v) : "l"(p) : "memory"); return v; }
__device__ __forceinline__ uint32_t ld_rlx(const uint32_t* p) { uint32_t v; asm volatile("ld.relaxed.gpu.global.u32 %0, [%1];" : "=r"(v) : "l"(p) : "memory"); return v; }
template <class T> __device__ __forceinline__ T* opaque_ptr(T* p) { asm volatile("" : "+l"(p)); return p; }
__device__ __forceinline__ uint4 ld_rlx4(const uint4* p) {
    uint4 v; asm volatile("ld.relaxed.gpu.global.v4.u32 {%0,%1,%2,%3}, [%4];" : "=r"(v.x), "=r"(v.y), "=r"(v.z), "=r"(v.w) : "l"(p) : "memory"); return v;
}
__device__ __forceinline__ void st_ll(uint4* p, uint32_t a, uint32_t b, uint32_t tag) {
    uint64_t lo = ((uint64_t)tag << 32) | a, hi = ((uint64_t)tag << 32) | b;
    asm volatile("st.relaxed.gpu.global.v2.u64 [%0], {%1,%2};" :: "l"(p), "l"(lo), "l"(hi) : "memory");
}
__device__ __forceinline__ bool ld_ll(const uint4* p, uint32_t& a, uint32_t& b, uint32_t tag) {
    uint64_t lo, hi;
    asm volatile("ld.relaxed.gpu.global.v2.u64 {%0,%1}, [%2];" : "=l"(lo), "=l"(hi) : "l"(p) : "memory");
    a = (uint32_t)lo; b = (uint32_t)hi;
    return (uint32_t)(lo >> 32) == tag && (uint32_t)(hi >> 32) == tag;
}
__device__ __forceinline__ uint2 ld_acq2(const uint2* p) {
    uint2 v; asm volatile("ld.acquire.gpu.global.v2.u32 {%0,%1}, [%2];" : "=r"(v.x), "=r"(v.y) : "l"(p) : "memory"); return v;
}
__device__ __forceinline__ uint2 ld_rlx2(const uint2* p) {
    uint2 v; asm volatile("ld.relaxed.gpu.global.v2.u32 {%0,%1}, [%2];" : "=r"(v.x), "=r"(v.y) : "l"(p) : "memory"); return v;
}
__device__ __forceinline__ void stg1(uint32_t* p, uint32_t v) { asm volatile("st.global.u32 [%0], %1;" :: "l"(p), "r"(v) : "memory"); }
__device__ __forceinline__ void stg2(void* p, uint32_t x, uint32_t y) { asm volatile("st.global.v2.u32 [%0], {%1,%2};" :: "l"(p), "r"(x), "r"(y) : "memory"); }
__device__ __forceinline__ void stg4(void* p, uint32_t x, uint32_t y, uint32_t z, uint32_t w) { asm volatile("st.global.v4.u32 [%0], {%1,%2,%3,%4};" :: "l"(p), "r"(x), "r"(y), "r"(z), "r"(w) : "memory"); }
__device__ __forceinline__ uint32_t lds1(uint32_t a) { uint32_t v; asm volatile("ld.shared.u32 %0, [%1];" : "=r"(v) : "r"(a) : "memory"); return v; }
__device__ __forceinline__ uint2 lds2(uint32_t a) { uint2 v; asm volatile("ld.shared.v2.u32 {%0,%1}, [%2];" : "=r"(v.x), "=r"(v.y) : "r"(a) : "memory"); return v; }
__device__ __forceinline__ uint32_t set_par(uint32_t v, uint32_t mask, uint32_t par) { return (v & ~mask) | (par & mask); }
__device__ __forceinline__ float tanh_hw(float x) { float r; asm("tanh.approx.f32 %0, %1;" : "=f"(r) : "f"(x)); return r; }
__device__ __forceinline__ bool bar_any(int id, int n, bool v) {
    uint32_t r;
    asm volatile("{ .reg .pred p, q; setp.ne.u32 p, %3, 0; bar.red.or.pred q, %1, %2, p; selp.u32 %0, 1, 0, q; }" : "=r"(r) : "r"(id), "r"(n), "r"((uint32_t)v) : "memory");
    return r;
}
__device__ __forceinline__ void sts4(uint32_t a, uint32_t x, uint32_t y, uint32_t z, uint32_t w) { asm volatile("st.shared.v4.u32 [%0], {%1,%2,%3,%4};" :: "r"(a), "r"(x), "r"(y), "r"(z), "r"(w) : "memory"); }
__device__ __forceinline__ uint4 lds4(uint32_t a) { uint4 v; asm volatile("ld.shared.v4.u32 {%0,%1,%2,%3}, [%4];" : "=r"(v.x), "=r"(v.y), "=r"(v.z), "=r"(v.w) : "r"(a) : "memory"); return v; }
__device__ __forceinline__ uint32_t pack_bf16(float lo, float hi) { uint32_t r; asm("cvt.rn.bf16x2.f32 %0, %1, %2;" : "=r"(r) : "f"(hi), "f"(lo)); return r; }
__device__ __forceinline__ float bf_lo(uint32_t v) { return __uint_as_float(v << 16); }
__device__ __forceinline__ float bf_hi(uint32_t v) { return __uint_as_float(v & 0xffff0000u); }
__device__ __forceinline__ uint32_t sub_bf16x2(uint32_t a, uint32_t b) { uint32_t r; asm("sub.rn.bf16x2 %0, %1, %2;" : "=r"(r) : "r"(a), "r"(b)); return r; }
__device__ __forceinline__ uint32_t add_bf16x2(uint32_t a, uint32_t b) { uint32_t r; asm("add.rn.bf16x2 %0, %1, %2;" : "=r"(r) : "r"(a), "r"(b)); return r; }
__device__ __forceinline__ uint32_t sqr_bf16x2(uint32_t a) { uint32_t r; asm("mul.rn.bf16x2 %0, %1, %1;" : "=r"(r) : "r"(a)); return r; }
__device__ __forceinline__ uint32_t sqa_bf16x2(uint32_t a, uint32_t c) { uint32_t r; asm("fma.rn.bf16x2 %0, %1, %1, %2;" : "=r"(r) : "r"(a), "r"(c)); return r; }
__device__ __forceinline__ uint32_t movm(uint32_t a) { uint32_t r; asm volatile("movmatrix.sync.aligned.m8n8.trans.b16 %0, %1;" : "=r"(r) : "r"(a)); return r; }
__device__ __forceinline__ float ex2(float x) { float r; asm("ex2.approx.ftz.f32 %0, %1;" : "=f"(r) : "f"(x)); return r; }
__device__ __forceinline__ float rsq(float x) { float r; asm("rsqrt.approx.ftz.f32 %0, %1;" : "=f"(r) : "f"(x)); return r; }
__device__ __forceinline__ float rcp(float x) { float r; asm("rcp.approx.ftz.f32 %0, %1;" : "=f"(r) : "f"(x)); return r; }
__device__ __forceinline__ void mma16816(float (&c)[4], uint32_t a0, uint32_t a1, uint32_t a2, uint32_t a3, uint32_t b0, uint32_t b1) {
    asm("mma.sync.aligned.m16n8k16.row.col.f32.bf16.bf16.f32 {%0,%1,%2,%3}, {%4,%5,%6,%7}, {%8,%9}, {%0,%1,%2,%3};"
        : "+f"(c[0]), "+f"(c[1]), "+f"(c[2]), "+f"(c[3]) : "r"(a0), "r"(a1), "r"(a2), "r"(a3), "r"(b0), "r"(b1));
}
__device__ __forceinline__ void mma1688(float (&c)[4], uint32_t a0, uint32_t a1, uint32_t b0) {
    asm("mma.sync.aligned.m16n8k8.row.col.f32.bf16.bf16.f32 {%0,%1,%2,%3}, {%4,%5}, {%6}, {%0,%1,%2,%3};"
        : "+f"(c[0]), "+f"(c[1]), "+f"(c[2]), "+f"(c[3]) : "r"(a0), "r"(a1), "r"(b0));
}
__device__ __forceinline__ float quad_sum(float v) { v += __shfl_xor_sync(~0u, v, 1); v += __shfl_xor_sync(~0u, v, 2); return v; }
__device__ __forceinline__ float quad_max(float v) { v = fmaxf(v, __shfl_xor_sync(~0u, v, 1)); v = fmaxf(v, __shfl_xor_sync(~0u, v, 2)); return v; }
__device__ __forceinline__ uint64_t make_desc(uint32_t addr, uint32_t lbo, bool swz, uint32_t sbo = 1024) {
    const uint32_t lo = __shfl_sync(~0u, ((addr & 0x3FFFF) >> 4) | ((lbo >> 4) << 16), 0);
    const uint32_t hi = __shfl_sync(~0u, (swz ? 0x40000000u : 0u) + (sbo >> 4) + (threadIdx.x & 31), 0);
    return ((uint64_t)hi << 32) | lo;
}
template <int I, int N, class F> __device__ __forceinline__ void static_for(F&& f) {
    if constexpr (I < N) { f(std::integral_constant<int, I>{}); static_for<I + 1, N>(f); }
}
__device__ __forceinline__ uint32_t opaque(uint32_t v) { asm volatile("" : "+r"(v)); return v; }
template <int BOFF, int SCALE_D>
__device__ __forceinline__ void wgmma_rs_n56(float (&d)[28], uint32_t a0, uint32_t a1, uint32_t a2, uint32_t a3, uint64_t db) {
    asm volatile("{ .reg .b64 db; add.s64 db, %32, %33;\n"
        "wgmma.mma_async.sync.aligned.m64n56k16.f32.bf16.bf16 "
        "{%0, %1, %2, %3, %4, %5, %6, %7, %8, %9, %10, %11, %12, %13, %14, %15, %16, %17, %18, %19, %20, %21, %22, %23, %24, %25, %26, %27}, "
        "{%28, %29, %30, %31}, db, %34, 1, 1, 1; }"
        : "+f"(d[0]), "+f"(d[1]), "+f"(d[2]), "+f"(d[3]), "+f"(d[4]), "+f"(d[5]), "+f"(d[6]), "+f"(d[7]),
        "+f"(d[8]), "+f"(d[9]), "+f"(d[10]), "+f"(d[11]), "+f"(d[12]), "+f"(d[13]), "+f"(d[14]), "+f"(d[15]),
        "+f"(d[16]), "+f"(d[17]), "+f"(d[18]), "+f"(d[19]), "+f"(d[20]), "+f"(d[21]), "+f"(d[22]), "+f"(d[23]),
        "+f"(d[24]), "+f"(d[25]), "+f"(d[26]), "+f"(d[27])
        : "r"(a0), "r"(a1), "r"(a2), "r"(a3), "l"(db), "n"(BOFF >> 4), "n"(SCALE_D));
}
template <int AOFF, int BOFF>
__device__ __forceinline__ void wgmma_ss_n56(float (&d)[28], uint64_t da, uint64_t db) {
    asm volatile("{ .reg .b64 da, db; add.s64 da, %28, %30; add.s64 db, %29, %31;\n"
        "wgmma.mma_async.sync.aligned.m64n56k16.f32.bf16.bf16 "
        "{%0, %1, %2, %3, %4, %5, %6, %7, %8, %9, %10, %11, %12, %13, %14, %15, %16, %17, %18, %19, %20, %21, %22, %23, %24, %25, %26, %27}, "
        "da, db, 1, 1, 1, 0, 1; }"
        : "+f"(d[0]), "+f"(d[1]), "+f"(d[2]), "+f"(d[3]), "+f"(d[4]), "+f"(d[5]), "+f"(d[6]), "+f"(d[7]),
        "+f"(d[8]), "+f"(d[9]), "+f"(d[10]), "+f"(d[11]), "+f"(d[12]), "+f"(d[13]), "+f"(d[14]), "+f"(d[15]),
        "+f"(d[16]), "+f"(d[17]), "+f"(d[18]), "+f"(d[19]), "+f"(d[20]), "+f"(d[21]), "+f"(d[22]), "+f"(d[23]),
        "+f"(d[24]), "+f"(d[25]), "+f"(d[26]), "+f"(d[27])
        : "l"(da), "l"(db), "n"(AOFF >> 4), "n"(BOFF >> 4));
}
template <int AOFF, int BOFF>
__device__ __forceinline__ void wgmma_ss_n112(float (&d)[56], uint64_t da, uint64_t db) {
    asm volatile("{ .reg .b64 da, db; add.s64 da, %56, %58; add.s64 db, %57, %59;\n"
        "wgmma.mma_async.sync.aligned.m64n112k16.f32.bf16.bf16 "
        "{%0, %1, %2, %3, %4, %5, %6, %7, %8, %9, %10, %11, %12, %13, %14, %15, %16, %17, %18, %19, %20, %21, %22, %23, %24, %25, %26, %27, %28, %29, %30, %31, %32, %33, %34, %35, %36, %37, %38, %39, %40, %41, %42, %43, %44, %45, %46, %47, %48, %49, %50, %51, %52, %53, %54, %55}, "
        "da, db, 1, 1, 1, 1, 1; }"
        : "+f"(d[0]), "+f"(d[1]), "+f"(d[2]), "+f"(d[3]), "+f"(d[4]), "+f"(d[5]), "+f"(d[6]), "+f"(d[7]),
        "+f"(d[8]), "+f"(d[9]), "+f"(d[10]), "+f"(d[11]), "+f"(d[12]), "+f"(d[13]), "+f"(d[14]), "+f"(d[15]),
        "+f"(d[16]), "+f"(d[17]), "+f"(d[18]), "+f"(d[19]), "+f"(d[20]), "+f"(d[21]), "+f"(d[22]), "+f"(d[23]),
        "+f"(d[24]), "+f"(d[25]), "+f"(d[26]), "+f"(d[27]), "+f"(d[28]), "+f"(d[29]), "+f"(d[30]), "+f"(d[31]),
        "+f"(d[32]), "+f"(d[33]), "+f"(d[34]), "+f"(d[35]), "+f"(d[36]), "+f"(d[37]), "+f"(d[38]), "+f"(d[39]),
        "+f"(d[40]), "+f"(d[41]), "+f"(d[42]), "+f"(d[43]), "+f"(d[44]), "+f"(d[45]), "+f"(d[46]), "+f"(d[47]),
        "+f"(d[48]), "+f"(d[49]), "+f"(d[50]), "+f"(d[51]), "+f"(d[52]), "+f"(d[53]), "+f"(d[54]), "+f"(d[55])
        : "l"(da), "l"(db), "n"(AOFF >> 4), "n"(BOFF >> 4));
}

struct Params {
    const __nv_bfloat16 *x, *wqkv, *wo, *w1, *w2, *b1, *b2;
    __nv_bfloat16* out;
};

__global__ void __cluster_dims__(2, 1, 1) __launch_bounds__(384, 1)
fused_kernel(const __grid_constant__ CUtensorMap mX, const __grid_constant__ CUtensorMap mWqkv,
             const __grid_constant__ CUtensorMap mWo, const __grid_constant__ CUtensorMap mW1,
             const __grid_constant__ CUtensorMap mW2, const Params prm)
{
    extern __shared__ __align__(1024) unsigned char smem_raw[];
    uint32_t sb = (uint32_t)__cvta_generic_to_shared(smem_raw);
    asm volatile("mov.u32 %0, %0;" : "+r"(sb));
    const uint32_t bar0 = sb + SM_BAR;
    auto BAR = [&](int i) { return bar0 + 8u * i; };

    const int tid = threadIdx.x, lane = tid & 31;
    const int warp = __shfl_sync(~0u, tid >> 5, 0);
    const int b = __shfl_sync(~0u, (int)blockIdx.x, 0);
    const int rank = b & 1;
    const int cl = (b >> 1) - 4, cq = ((cl - 32) * 37) >> 8;
    const int res = cl < 0 ? 0 : cl < 32 ? cl & 7 : cl - 31 - 7 * cq;
    const int rnd = cl < 0 ? cl + 8 : cl < 32 ? cl >> 3 : 4 + cq;
    const int hg = (res & 1) * 4 + (rnd & 3);
    const int ti = (res >> 1) * 4 + (rnd >> 2) * 2 + rank;
    const int a2p = res & 1, a2j = rnd & 3;
    const int a2s = ti * 2 + a2p;
    const bool g1_on = rnd != 7;
    const int g1j = (rnd < 6 ? rnd : res) & 1, g1f = rnd < 6 ? res * 3 + (rnd >> 1) : 24 + (res >> 1);
    const int g2j = rnd & 1, g2s = res * 4 + (rnd >> 1);
    uint32_t pbar0;
    asm volatile("mapa.shared::cluster.u32 %0, %1, %2;" : "=r"(pbar0) : "r"(bar0), "r"(rank ^ 1));
    auto pair_arrive = [&](int i) { __syncwarp(); const bool l = elect_one(); mbar_arrive_if(BAR(i), l); mbar_arrive_remote_if(pbar0 + 8u * i, l); };
    const int wcol = hg * 56 - (hg & 1) * 8;

    if (tid == 32) { TRG(60); TRW(59); }
    if (warp == 8) {
        if (elect_one()) {
            #pragma unroll
            for (int i = 0; i < B_WQF; i++) mbar_init(BAR(i), 1);
            asm volatile("fence.mbarrier_init.release.cluster;" ::: "memory");
            fence_async_smem();
            TRW(56);
            #pragma unroll 1
            for (int kb = 0; kb < 7; kb++) {
                mbar_expect(BAR(B_XF + kb), 16384);
                tma2d(sb + SM_X + kb * 8192, &mX, kb * 64, ti * 64, BAR(B_XF + kb));
                tma2d(sb + SM_X + 57344 + kb * 8192, &mX, kD + kb * 64, ti * 64, BAR(B_XF + kb));
                if (TMPF == 2 && kb == 0) asm volatile("prefetch.tensormap [%0];" :: "l"(&mWqkv) : "memory");
            }
        }
    } else if (warp > 8) {
        if (elect_one()) {
            if (warp == 9) {
                if (TMPF == 1) asm volatile("prefetch.tensormap [%0];" :: "l"(&mWqkv) : "memory");
                #pragma unroll
                for (int i = B_WQF; i < B_AF; i++) mbar_init(BAR(i), i < B_XC ? 1 : i < B_A1D ? 16 : i < B_BE ? 8 : 4);
            } else if (warp == 10) {
                #pragma unroll
                for (int i = B_AF; i < B_BL; i++) mbar_init(BAR(i), 1);
            } else {
                #pragma unroll
                for (int i = B_BL; i < B_COUNT; i++) mbar_init(BAR(i), i == B_HD ? 8 : 1);
            }
            asm volatile("fence.mbarrier_init.release.cluster;" ::: "memory");
            fence_async_smem();
        }
    } else {
        const char* p = tid < 112 ? (const char*)prm.x + (size_t)(ti * 8 + hg) * 14336 + tid * 128
                                  : (const char*)prm.wqkv + b * 2688 + 896 + (tid - 112) * 128;
        if (tid < PF0) asm volatile("prefetch.global.L2 [%0];" :: "l"(p));
    }
    __syncwarp();
    __syncthreads();
    asm volatile("barrier.cluster.arrive.relaxed.aligned;" ::: "memory");
    if (tid < 256) TR(0);
    if (tid == 0) TRG(61);

    if (warp >= 8) {
        asm volatile("setmaxnreg.dec.sync.aligned.u32 40;");
        asm volatile("barrier.cluster.wait.aligned;" ::: "memory");
        auto fetch_halo = [&](int p, uint32_t tag) {
            uint4 u[4];
            #pragma unroll
            for (int c = 0; c < 4; c++) u[c] = make_uint4(0u, 0u, 0u, 0u);
            const uint4* hp = opaque_ptr(&g_halo[(((ti - 1) * 8 + hg) * 2 + p) * 128 + lane]);
            mbar_wait(BAR(B_KVC), 0);
            if (p == 0) TRW(51);
            sleep_until(clk32() + HDELAY);
            if (ti > 0) {
                int it = 0;
                do {
                    #pragma unroll
                    for (int c = 0; c < 4; c++) u[c] = ld_rlx4(hp + c * 32);
                    if (it) RETRY_COUNT(4);
                    if (++it > kSpinLimit) { TIMEOUT(101); break; }
                } while (__any_sync(~0u, ((u[0].x ^ tag) | (u[1].x ^ tag) | (u[2].x ^ tag) | (u[3].x ^ tag)) & ~lane & 1));
            }
            #pragma unroll
            for (int c = 0; c < 4; c++) sts4(sb + SM_STG + p * 8192 + 3 * 2048 + lane * 16 + c * 512, u[c].x, u[c].y, u[c].z, u[c].w);
            warp_arrive(BAR(B_HL + p));
        };
        if (warp & 1) {
            uint32_t tag;
            if (warp == 11) {
                tag = *(volatile uint32_t*)&g_epoch + 1;
            #pragma unroll 1
            for (int i = 0; i < 8; i++) g_halo[(ti * 8 + hg) * 256 + i * 32 + lane] = make_uint4(~tag, 0u, 0u, 0u);
            ((uint4*)g_stats)[(a2s * 4 + a2j) * 64 + lane] = ((uint4*)g_stats)[(a2s * 4 + a2j) * 64 + 32 + lane] = make_uint4(~tag, ~tag, ~tag, ~tag);
            g_flag_h[(a2s * 4 + a2j) * FS + lane] = 0;
            g_flag_o[(ti * 16 + hg) * FS + lane] = g_flag_o[(ti * 16 + 8 + hg) * FS + lane] = 0;
            __syncwarp();
            if (lane == 0) {
                asm volatile("st.shared.v2.u32 [%0], {%1, %2};" :: "r"(sb + SM_EPOCH), "r"(tag), "r"(gtime32()) : "memory");
                mbar_arrive(BAR(B_EP));
            }
            if (lane < 4) mbar_expect(BAR(B_RF + lane), 7168);
            __syncwarp();
            TRW(44);
            } else {
                mbar_wait(BAR(B_EP), 0);
                tag = lds1(sb + SM_EPOCH);
            }
            fetch_halo((warp >> 1) & 1, tag);
        }
        if (warp < 10) {
          auto load_slab = [&](int s, bool second) {
              mbar_expect(BAR(B_AF + s), 8192);
              if (!second) tma2d(sb + s * 8192, &mW1, (s & 1) * kF + g1f * 64, (rank * 8 + (s >> 1)) * 64, BAR(B_AF + s));
              else         tma2d(sb + s * 8192, &mW2, g2s * 64, (rank * 14 + s - 2) * 64, BAR(B_AF + s));
          };
          if (warp == 8) {
            if (elect_one()) {
                #pragma unroll 1
                for (int s = 0; s < 7; s++) {
                    mbar_expect(BAR(B_WKVF + s), 16384);
                    tma2d_mc(sb + SM_WKV + s * 16384 + rank * 8192, &mWqkv, (1 + rank) * kD + wcol, s * 64, BAR(B_WKVF + s));
                }
            }
            __syncwarp();
            mbar_wait(BAR(B_XC), 0);
            if (elect_one()) {
                asm volatile("prefetch.tensormap [%0];" :: "l"(&mWo) : "memory");
                asm volatile("prefetch.tensormap [%0];" :: "l"(&mW1) : "memory");
                asm volatile("prefetch.tensormap [%0];" :: "l"(&mW2) : "memory");
                mbar_expect(BAR(B_WQF), 57344);
                #pragma unroll 1
                for (int s = rank; s < 7; s += 2) tma2d_mc(sb + SM_WQ + s * 8192, &mWqkv, wcol, s * 64, BAR(B_WQF));
                mbar_expect(BAR(B_XRF), 16384);
                tma2d(sb + SM_XR, &mX, a2p * kD + a2j * 112, ti * 64, BAR(B_XRF));
                tma2d(sb + SM_XR + 8192, &mX, a2p * kD + a2j * 112 + 48, ti * 64, BAR(B_XRF));
            }
            __syncwarp();
            #pragma unroll 1
            for (int h = 0; h < 2; h++) {
                mbar_wait(BAR(B_KV3 + h), 0);
                if (h) mbar_wait2(BAR(B_HL), 0, BAR(B_HL + 1), 0);
                if (elect_one()) {
                    mbar_expect(BAR(B_WOF + h), 57344);
                    tma2d_mc(sb + SM_WKV + h * 57344 + rank * 28672, &mWo, a2j * 112 + rank * 48, h * 224, BAR(B_WOF + h));
                    if (g1_on && h == AFIRST) { load_slab(0, false); load_slab(1, false); load_slab(2, false); }
                }
                __syncwarp();
            }
            if (g1_on) {
                mbar_wait2(BAR(B_XD), 0, BAR(B_BL + NB + 3), 0);
                #pragma unroll 1
                for (int i = 3; i < NPRE; i++) {
                    if (i == 7) mbar_wait(BAR(B_OC), 0);
                    if (elect_one()) load_slab(i, false);
                    __syncwarp();
                }
            } else {
                mbar_wait(BAR(B_HD), 0);
                mbar_arrive_remote_if(pbar0 + 8u * B_PD, lane == 0);
                mbar_wait(BAR(B_GO), 0);
                uint32_t tg = lds1(sb + SM_TG + 4);
                tg += max((int)(lds1(sb + SM_TG2) - tg), 0);
                int it = 0;
                while ((int)(gtime32() - tg) < 0 && ++it < 128) {}
                const uint32_t t0 = clk32();
                if (lane < 2) {
                    asm volatile("st.shared.u32 [%0], %1;" :: "r"(sb + SM_TG + 8 + lane * 4), "r"(t0 + (lane ? CN3 : CN2)) : "memory");
                    mbar_arrive(BAR(B_GD + lane));
                }
                __syncwarp();
                #pragma unroll 1
                for (int s = 2; s < 16; s++) {
                    sleep_until(t0 + W2OFF + s * W2PACE);
                    if (elect_one()) load_slab(s, true);
                    __syncwarp();
                }
            }
          } else {
            TRW(58);
            const uint32_t tag = lds1(sb + SM_EPOCH);
            if (lane < 4) mbar_expect(BAR(B_BL + NB + lane), 14336);
            #pragma unroll 1
            for (int e = 0; e < 2; e++) {
                const uint32_t* fp = e ? &g_flag_h[(rank * 64 + lane) * FS] : &g_flag_o[(a2s * 8 + (lane & 7)) * FS];
                if (e) { mbar_wait(BAR(B_HD), 0); sleep_until(clk32() + PDELAY); }
                uint64_t v0 = 0, v1 = e ? 0 : tag;
                int it = 0;
                do {
                    ld_flag_if(v0, fp, (uint32_t)v0 != tag); ld_flag_if(v1, fp + 32 * FS, (uint32_t)v1 != tag);
                    if (++it > kSpinLimit) { TIMEOUT(108); break; }
                } while (__any_sync(~0u, (uint32_t)v0 != tag || (uint32_t)v1 != tag));
                const uint32_t gbase = __shfl_sync(~0u, (uint32_t)(v0 >> 32), 0);
                const uint32_t tg = gbase + (e ? DELTA : DELTAO)
                                  + __reduce_max_sync(~0u, max((int)((uint32_t)(v0 >> 32) - gbase), e ? (int)((uint32_t)(v1 >> 32) - gbase) : 0));
                TRW(e ? 40 : 53);
                mbar_wait(BAR(B_A1D), 0);
                if (elect_one()) {
                    if (e) {
                        asm volatile("st.async.shared::cluster.mbarrier::complete_tx::bytes.b32 [%0], %1, [%2];"
                                     :: "r"(pbar0 + (SM_TG2 - SM_BAR)), "r"(tg), "r"(pbar0 + 8u * B_GO) : "memory");
                        asm volatile("st.shared.u32 [%0], %1;" :: "r"(sb + SM_TG + 4), "r"(tg) : "memory");
                        mbar_expect(BAR(B_GO), 4);
                    } else {
                        it = 0;
                        while ((int)(gtime32() - tg) < 0 && ++it < 128) {}
                        #pragma unroll
                        for (int i = 0; i < 4; i++) bulk_g2s(sb + SM_WQ + i * 14336, &g_o[(a2s * 4 + i) * 896], 14336, BAR(B_BL + NB + i));
                    }
                }
                __syncwarp();
            }
          }
          if (elect_one()) {
              const int h = ~warp & 1;
              const char* src1 = (const char*)&g_hn[(rank * 16 + h) * 3584 + g1j * 896];
              const char* src2 = (const char*)&g_g[(rank * 14 + h) * 3584 + g2j * 896];
              const long long jump = src2 - src1 - (16 * 57344 + 2 * 14336);
              const char* src = g1_on ? src1 - 2 * 57344 : src2;
              const uint32_t amask = g1_on ? (h ? kAMask1 : kAMask0) : 0u;
              uint32_t slot = g1_on ? NB - 2 + h : h, ph = g1_on ? 0 : 1, gate = g1_on ? 0 : 2;
              CAP_DECL(ti_, 0);
              #pragma unroll 1
              for (int q = g1_on ? 0 : 17; q < 31; q++) {
                  const uint32_t eb = q ? BAR(B_BE) + slot * 8 : BAR(B_XF), dst = sb + SM_B + slot * 14336;
                  if ((0x1020003u >> q) & 1) {
                      mbar_wait(BAR(B_HD + gate), 0);
                      uint32_t tg = lds1(sb + SM_TG + gate * 4);
                      tg += max((int)(lds1(gate == 1 ? sb + SM_TG2 : sb + SM_TG + gate * 4) - tg), 0) + h * 64;
                      int it = 0;
                      if (gate < 2) while ((int)(gtime32() - tg) < 0 && ++it < 128) {}
                      else spin_until(tg);
                      gate++;
                  }
                  if (!mbar_try(eb, ph)) mbar_wait(eb, ph);
                  if (q) {
                      bulk_g2s(dst, src, 14336, eb + (B_BL - B_BE) * 8);
                      mbar_expect(eb + (B_BL - B_BE) * 8, 14336);
                      CAP(ti_);
                  }
                  mbar_arrive_remote_if(pbar0 + 8u * B_PD, h && q == 12);
                  if ((amask >> q) & 1) {
                      if (q < 12) load_slab(NPRE - W1Q + q, false);
                      else load_slab(2 + ((2 * q + h - 27) * 13 + 19) / 20, true);
                  }
                  src += 2 * 57344 + (q == 8 ? 2 * 14336 - 16 * 57344 : q == 16 ? jump : q == 23 ? 2 * 14336 - 14 * 57344 : 0);
                  slot += 2;
                  if (slot >= NB) { slot -= NB; ph ^= 1; }
              }
          }
        } else {
          if (warp == 10) {
            mbar_wait(BAR(PFBAR), 0);
            const char* p1 = (const char*)prm.w1 + (size_t)b * 57344 + lane * 128;
            const char* p2 = (const char*)prm.w2 + (size_t)b * 57344 + lane * 128;
            if (lane < 27) asm volatile("prefetch.global.L2 [%0];" :: "l"(lane < 25 ? (const char*)prm.wo + min(b * 25 + lane, 3135) * 128
                                                                          : lane == 25 ? (const char*)prm.b1 + (b % 28) * 128 : (const char*)prm.b2 + (b & 31) * 128));
            uint32_t tnext = (uint32_t)clock();
            #pragma unroll 1
            for (int i = 0; i < 28; i++) {
                asm volatile("prefetch.global.L2 [%0];" :: "l"(i < 14 ? p1 + i * 4096 : p2 + (i - 14) * 4096));
                tnext += PFPACE;
                while ((int)((uint32_t)clock() - tnext) < 0) __nanosleep(40);
            }
            mbar_wait(BAR(B_EP), 0);
          }
          const uint32_t tag = lds1(sb + SM_EPOCH);
          const int h = warp & 1;
          const bool lead = elect_one();
          const uint32_t w0o = lane * 132, l3 = lane < 16 ? 12288 : 0;
          uint32_t wo = w0o ^ (h << 6), slot = NB + h, dst = sb + SM_WQ + h * 14336, ph = 0, rph = 0, af = BAR(B_WOF), aph = 0;
          #pragma unroll 1
          for (int q = -1; q < 31; q++) {
              const uint32_t rb = bar0 + slot * 8;
              auto stale = [&]() {
                  uint32_t d;
                  asm volatile("{ .reg .b32 x, y, z, u;\n"
                               "ld.shared.u32 x, [%1]; ld.shared.u32 y, [%1 + 4096]; ld.shared.u32 z, [%1 + 8192]; ld.shared.u32 u, [%2];\n"
                               "lop3.b32 x, x, y, %3, 0x7e; lop3.b32 z, z, u, %3, 0x7e; lop3.b32 %0, x, z, 1, 0xa8; }"
                               : "=r"(d) : "r"(dst + wo), "r"(dst + wo + l3), "r"(tag) : "memory");
                  return __any_sync(~0u, d);
              };
              mbar_wait(rb + B_BF * 8, ph ^ 1);
              mbar_wait(rb + B_BL * 8, ph);
              const bool aok = mbar_test(af, aph);
              bool bad = stale();
              if (!aok) mbar_wait(af, aph);
              mbar_arrive_if(rb + B_BF * 8, lead && !bad);
              if (bad) {
                  RETRY_COUNT(q < 1 ? 1 : q < 17 ? 0 : !g1_on ? 5 : q < 24 ? 2 : 6);
                  const int e = (q > 8) + (q > 16) + (q > 23), s = (q - (e < 3 ? 1 + 8 * e : 24)) * 2 + h;
                  const char* src = (const char*)(q < 1 ? &g_o[(a2s * 4 + s + 4) * 896] : e < 2 ? &g_hn[(rank * 16 + s) * 3584 + (g1j + 2 * e) * 896] : &g_g[(rank * 14 + s) * 3584 + (g2j + 2 * e - 4) * 896]);
                  int it = 0;
                  do {
                      if (++it > kSpinLimit) { TIMEOUT(111); break; }
                      const uint32_t* p = (const uint32_t*)(src + wo);
                      if (__any_sync(~0u, ((ld_rlx(p) ^ tag) | (ld_rlx(p + 1024) ^ tag) | (ld_rlx(p + 2048) ^ tag) | (ld_rlx(p + l3 / 4) ^ tag)) & 1)) continue;
                      if (lead) {
                          mbar_expect(BAR(B_RT + h), 14336);
                          bulk_g2s(dst, src, 14336, BAR(B_RT + h));
                      }
                      __syncwarp();
                      mbar_wait(BAR(B_RT + h), rph);
                      rph ^= 1;
                      bad = stale();
                  } while (bad);
                  mbar_arrive_if(rb + B_BF * 8, lead);
              }
              af += q < 0 ? 8 : q == 8 ? -112 : (0x810000u >> q) & 1 ? -96 : 16;
              slot += 2; dst += 28672;
              if (q > 0 && slot >= NB) { slot -= NB; dst -= NB * 14336; ph ^= 1; }
              if (q == 16) { wo = w0o ^ (g2j << 6); aph = 1; }
              if (q == 0) {
                  slot = h; dst = sb + SM_B + h * 14336; af = BAR(B_AF + h + (g1_on ? 0 : 2));
                  wo = w0o ^ ((g1_on ? g1j : g2j) << 6); q = g1_on ? 0 : 16;
              }
          }
        }
    } else {
        asm volatile("setmaxnreg.inc.sync.aligned.u32 232;");
        asm volatile("barrier.cluster.wait.aligned;" ::: "memory");
        const int wg = warp >> 2, w = warp & 3;
        const int g = lane >> 2, t = lane & 3;
        uint32_t tag;
        __nv_bfloat16 bias1;
        {
            const uint64_t dw = make_desc(sb + (hg & 1) * 16, 0, true);
            uint32_t a[28][4];
            float sm0[4] = {0.f, 0.f, 0.f, 0.f}, sm1[4] = {0.f, 0.f, 0.f, 0.f};
            {
                const int r = w * 16 + (lane & 15);
                const uint32_t rowa = sb + SM_X + wg * 57344 + r * 128;
                #pragma unroll
                for (int kb = 0; kb < 7; kb++) {
                    mbar_wait(BAR(B_XF + kb), 0);
                    #pragma unroll
                    for (int q = 0; q < 4; q++) {
                        const uint32_t addr = rowa + kb * 8192 + (((q * 2 + (lane >> 4)) ^ (r & 7)) << 4);
                        uint32_t (&f)[4] = a[kb * 4 + q];
                        asm volatile("ldmatrix.sync.aligned.m8n8.x4.shared.b16 {%0,%1,%2,%3}, [%4];"
                                     : "=r"(f[0]), "=r"(f[1]), "=r"(f[2]), "=r"(f[3]) : "r"(addr) : "memory");
                        if (q & 1) mma16816(sm1, f[0], f[1], f[2], f[3], 0x3F803F80u, 0x3F803F80u);
                        else       mma16816(sm0, f[0], f[1], f[2], f[3], 0x3F803F80u, 0x3F803F80u);
                    }
                }
            }
            const float mean0 = (sm0[0] + sm1[0]) * (1.f / kD), mean1 = (sm0[2] + sm1[2]) * (1.f / kD);
            const uint32_t mb0 = pack_bf16(mean0, mean0), mb1 = pack_bf16(mean1, mean1);
            pair_arrive(B_XC);
            TR(1);
            float ak[28], av[28], aq[28];
            float ss0 = 0.f, ss1 = 0.f, ss2 = 0.f, ss3 = 0.f;
            static_for<0, 7>([&](auto S_) {
                constexpr int s = decltype(S_)::value;
                #pragma unroll
                for (int q = 0; q < 4; q++) {
                    uint32_t (&f)[4] = a[s * 4 + q];
                    f[0] = sub_bf16x2(f[0], mb0); f[1] = sub_bf16x2(f[1], mb1);
                    f[2] = sub_bf16x2(f[2], mb0); f[3] = sub_bf16x2(f[3], mb1);
                }
                mbar_wait(BAR(B_WKVF + s), 0);
                wg_fence();
                static_for<0, 4>([&](auto Q_) {
                    constexpr int q = decltype(Q_)::value;
                    uint32_t (&f)[4] = a[s * 4 + q];
                    wgmma_rs_n56<SM_WKV + s * 16384 + q * 2048, (s | q) != 0>(ak, f[0], f[1], f[2], f[3], dw);
                    wgmma_rs_n56<SM_WKV + s * 16384 + q * 2048 + 8192, (s | q) != 0>(av, f[0], f[1], f[2], f[3], dw);
                });
                wg_commit();
                uint32_t p0 = sqr_bf16x2(a[s * 4][0]), p1 = sqr_bf16x2(a[s * 4][1]), p2 = sqr_bf16x2(a[s * 4][2]), p3 = sqr_bf16x2(a[s * 4][3]);
                #pragma unroll
                for (int q = 1; q < 4; q++) {
                    p0 = sqa_bf16x2(a[s * 4 + q][0], p0); p1 = sqa_bf16x2(a[s * 4 + q][1], p1);
                    p2 = sqa_bf16x2(a[s * 4 + q][2], p2); p3 = sqa_bf16x2(a[s * 4 + q][3], p3);
                }
                p0 = add_bf16x2(p0, p2); p1 = add_bf16x2(p1, p3);
                ss0 += bf_lo(p0); ss2 += bf_hi(p0); ss1 += bf_lo(p1); ss3 += bf_hi(p1);
                if (s == 4) { wg_wait<1>(); pair_arrive(B_KV3); }
            });
            auto q_chunk = [&](auto K0_, auto K1_) {
                wg_fence();
                static_for<decltype(K0_)::value, decltype(K1_)::value>([&](auto K_) {
                    constexpr int k = decltype(K_)::value;
                    wgmma_rs_n56<SM_WQ + k * 2048, k != 0>(aq, a[k][0], a[k][1], a[k][2], a[k][3], dw);
                });
                wg_commit();
            };
            #define QCHUNK(k0, k1) q_chunk(std::integral_constant<int, k0>{}, std::integral_constant<int, k1>{})
            const float dl0 = mean0 - bf_lo(mb0), dl1 = mean1 - bf_lo(mb1);
            const float rs0 = rsq(fmaxf(quad_sum(ss0 + ss2) * (1.f / kD) - dl0 * dl0, 0.f) + kEps);
            const float rs1 = rsq(fmaxf(quad_sum(ss1 + ss3) * (1.f / kD) - dl1 * dl1, 0.f) + kEps);
            float rk[3][2];
            rk[1][0] = __shfl_sync(~0u, rs0, t * 8); rk[1][1] = __shfl_sync(~0u, rs0, t * 8 + 4);
            rk[2][0] = __shfl_sync(~0u, rs1, t * 8); rk[2][1] = __shfl_sync(~0u, rs1, t * 8 + 4);
            const uint32_t stg = sb + SM_STG + wg * 8192 + lane * 16;
            uint4* hp = opaque_ptr(&g_halo[((ti * 8 + hg) * 2 + wg) * 128 + lane]);
            mbar_wait2(BAR(B_EP), 0, BAR(B_WQF), 0);
            tag = lds1(sb + SM_EPOCH);
            QCHUNK(0, QC0);
            wg_wait<1>();
            reg_fence(ak); reg_fence(av);
            TR(2);
            uint32_t kf[3][7], vf[3][7];
            #pragma unroll
            for (int c = 0; c < 7; c++) {
                kf[2][c] = pack_bf16(ak[4 * c + 2], ak[4 * c + 3]);
                vf[2][c] = movm(pack_bf16(av[4 * c + 2], av[4 * c + 3]));
            }
            const uint32_t om = ~lane & 1;
            if (w == 3) {
                stg4(hp,      set_par(kf[2][0], om, tag), kf[2][1], kf[2][2], kf[2][3]);
                stg4(hp + 32, set_par(kf[2][4], om, tag), kf[2][5], kf[2][6], vf[2][0]);
                stg4(hp + 64, set_par(vf[2][1], om, tag), vf[2][2], vf[2][3], vf[2][4]);
                stg4(hp + 96, set_par(vf[2][5], om, tag), vf[2][6], __float_as_uint(rk[2][0]), __float_as_uint(rk[2][1]));
            } else {
                sts4(stg + w * 2048 + 0,    kf[2][0], kf[2][1], kf[2][2], kf[2][3]);
                sts4(stg + w * 2048 + 512,  kf[2][4], kf[2][5], kf[2][6], vf[2][0]);
                sts4(stg + w * 2048 + 1024, vf[2][1], vf[2][2], vf[2][3], vf[2][4]);
                sts4(stg + w * 2048 + 1536, vf[2][5], vf[2][6], __float_as_uint(rk[2][0]), __float_as_uint(rk[2][1]));
            }
            pair_arrive(B_KVC);
            QCHUNK(QC0, QC1);
            #pragma unroll
            for (int c = 0; c < 7; c++) {
                kf[1][c] = pack_bf16(ak[4 * c], ak[4 * c + 1]);
                vf[1][c] = movm(pack_bf16(av[4 * c], av[4 * c + 1]));
            }
            QCHUNK(QC1, QC2);
            named_bar(1 + wg, 128);
            uint32_t* op = opaque_ptr((uint32_t*)&g_o[((ti * 2 + wg) * 56 + hg * 7) * 64] + w * 64 + lane);
            const uint32_t omk = opaque(((lane & 6) == w * 2 ? 0x11u << (lane & 1) * 8 : 0u) << (((lane >> 3) - hg * 7) & 3));
            uint32_t* ofl = opaque_ptr(&g_flag_o[((ti * 2 + wg) * 8 + hg) * FS]);
            QCHUNK(QC2, 28);
            #undef QCHUNK
            mbar_wait(BAR(w == 0 ? B_HL + wg : B_EP), 0);
            {
                const uint32_t sr = stg + ((w + 3) & 3) * 2048;
                const uint4 u0 = lds4(sr), u1 = lds4(sr + 512), u2 = lds4(sr + 1024), u3 = lds4(sr + 1536);
                kf[0][0] = u0.x; kf[0][1] = u0.y; kf[0][2] = u0.z; kf[0][3] = u0.w;
                kf[0][4] = u1.x; kf[0][5] = u1.y; kf[0][6] = u1.z; vf[0][0] = u1.w;
                vf[0][1] = u2.x; vf[0][2] = u2.y; vf[0][3] = u2.z; vf[0][4] = u2.w;
                vf[0][5] = u3.x; vf[0][6] = u3.y; rk[0][0] = __uint_as_float(u3.z); rk[0][1] = __uint_as_float(u3.w);
            }
            const bool gt0 = 2 * t > g, gt1 = 2 * t + 1 > g, no_prev = ti == 0 && w == 0;
            const float ke0 = gt0 ? rk[0][0] : rk[1][0], ke1 = gt1 ? rk[0][1] : rk[1][1];
            const float kf0 = gt0 ? rk[1][0] : rk[2][0], kf1 = gt1 ? rk[1][1] : rk[2][1];
            constexpr float kScale = 0.18898223650461362f * 1.4426950408889634f;
            const float se0 = ke0 * (rs0 * kScale), se1 = ke1 * (rs0 * kScale), sf0 = kf0 * (rs1 * kScale), sf1 = kf1 * (rs1 * kScale);
            const float NEG = -__int_as_float(0x7f800000);
            const float nb0 = gt0 && no_prev ? NEG : 0.f, nb1 = gt1 && no_prev ? NEG : 0.f;
            TR(3);
            wg_wait<0>();
            reg_fence(aq);
            if ((tid & 127) == 0) st_flag(ofl, tag);
            warp_arrive(BAR(B_A1D));
            TR(4);
            uint32_t qf[7][2];
            #pragma unroll
            for (int c = 0; c < 7; c++) {
                qf[c][0] = pack_bf16(aq[4 * c], aq[4 * c + 1]);
                qf[c][1] = pack_bf16(aq[4 * c + 2], aq[4 * c + 3]);
            }
            uint32_t ow[7][2];
            #pragma unroll
            for (int hd = 0; hd < 2; hd++) {
                const int c0 = hd * 3;
                const bool keep = hd == 0 ? (t < 2) : (t >= 2);
                const uint32_t q3a = keep ? qf[3][0] : 0u, q3b = keep ? qf[3][1] : 0u;
                float sc_[3][4];
                #pragma unroll
                for (int n = 0; n < 3; n++) {
                    sc_[n][0] = sc_[n][1] = sc_[n][2] = sc_[n][3] = 0.f;
                    if (hd == 0) {
                        mma16816(sc_[n], qf[0][0], qf[0][1], qf[1][0], qf[1][1], kf[n][0], kf[n][1]);
                        mma16816(sc_[n], qf[2][0], qf[2][1], q3a, q3b, kf[n][2], kf[n][3]);
                    } else {
                        mma16816(sc_[n], q3a, q3b, qf[4][0], qf[4][1], kf[n][3], kf[n][4]);
                        mma16816(sc_[n], qf[5][0], qf[5][1], qf[6][0], qf[6][1], kf[n][5], kf[n][6]);
                    }
                }
                const float e0 = fmaf(gt0 ? sc_[0][0] : sc_[1][0], se0, nb0), e1 = fmaf(gt1 ? sc_[0][1] : sc_[1][1], se1, nb1);
                const float f0 = (gt0 ? sc_[1][2] : sc_[2][2]) * sf0, f1 = (gt1 ? sc_[1][3] : sc_[2][3]) * sf1;
                const float me = quad_max(fmaxf(e0, e1)), mf = quad_max(fmaxf(f0, f1));
                const float p0 = ex2(e0 - me), p1 = ex2(e1 - me), r0 = ex2(f0 - mf), r1 = ex2(f1 - mf);
                const float ie = rcp(quad_sum(p0 + p1)), jf = rcp(quad_sum(r0 + r1));
                const uint32_t pp = pack_bf16(p0 * ke0 * ie, p1 * ke1 * ie), rp = pack_bf16(r0 * kf0 * jf, r1 * kf1 * jf);
                const uint32_t mk = (gt0 ? 0x0000ffffu : 0u) | (gt1 ? 0xffff0000u : 0u);
                #pragma unroll
                for (int c = 0; c < 4; c++) {
                    float o[4] = {0.f, 0.f, 0.f, 0.f};
                    mma16816(o, pp & mk, 0u, pp & ~mk, rp & mk, vf[0][c0 + c], vf[1][c0 + c]);
                    mma1688(o, 0u, rp & ~mk, vf[2][c0 + c]);
                    const uint32_t lo = pack_bf16(o[0], o[1]), hi = pack_bf16(o[2], o[3]);
                    if (hd == 1 && c == 0) { if (t >= 2) { ow[3][0] = lo; ow[3][1] = hi; } }
                    else { ow[c0 + c][0] = lo; ow[c0 + c][1] = hi; }
                }
            }
            #pragma unroll
            for (int c = 0; c < 7; c++) {
                stg1(op + c * 256,      set_par(ow[c][0], (omk >> (c & 3)) & 1, tag));
                stg1(op + c * 256 + 32, set_par(ow[c][1], (omk >> (8 + (c & 3))) & 1, tag));
            }
            TR(5);
        }
        {
            const int cg = a2j * 2 + wg;
            float acc2[28];
            mbar_wait(BAR(B_XRF), 0);
            {
                const uint32_t xa = sb + SM_XR + wg * 8192 + (w * 16 + (lane & 15)) * 128;
                #pragma unroll
                for (int c = 0; c < 4; c++) {
                    uint32_t xr[4];
                    asm volatile("ldmatrix.sync.aligned.m8n8.x4.shared.b16 {%0,%1,%2,%3}, [%4];"
                                 : "=r"(xr[0]), "=r"(xr[1]), "=r"(xr[2]), "=r"(xr[3])
                                 : "r"(xa + ((((c * 2 + wg + (lane >> 4)) ^ lane) & 7) << 4)) : "memory");
                    #pragma unroll
                    for (int e = 0; e < (c < 3 ? 4 : 2); e++) { acc2[8 * c + 2 * e] = bf_lo(xr[e]); acc2[8 * c + 2 * e + 1] = bf_hi(xr[e]); }
                }
            }
            uint32_t* spw = opaque_ptr(&g_stats[((a2s * 8 + cg) * 4 + w) * 32 + lane]);
            const uint32_t* spr = opaque_ptr(&g_stats[(a2s * 32 + w) * 32 + lane]);
            uint4* hp = opaque_ptr(&g_h[((a2s * 8 + w * 2) * 8 + cg) * 64 + lane]);
            uint32_t* np = opaque_ptr((uint32_t*)&g_hn[(a2s * 56 + cg * 7) * 64] + w * 64 + lane);
            uint32_t* nfl = opaque_ptr(&g_flag_h[(a2s * 4 + a2j) * FS]);
            const uint64_t dwo = make_desc(sb + SM_WKV + wg * (28672 + 16), 0, true);
            const uint64_t doa = make_desc(sb + SM_WQ, 1024, false, 128);
            bias1 = prm.b1[g1f * 64 + w * 16 + rank * 8 + g];
            const __nv_bfloat16 bias2a = prm.b2[ti * 128 + (w * 16 + g) * 2 + a2p], bias2b = prm.b2[ti * 128 + (w * 16 + 8 + g) * 2 + a2p];
            reg_fence(acc2);
            fence_async_smem();
            warp_arrive(BAR(B_XD));
            static_for<0, 4>([&](auto P_) {
                constexpr int P = decltype(P_)::value;
                mbar_wait(BAR(B_BF + NB + P), 0);
                if (P == 0) TR(6);
                wg_fence();
                static_for<0, 7>([&](auto K_) { constexpr int k = decltype(K_)::value;
                    wgmma_ss_n56<P * 14336 + k * 2048, (P >> 1) * 57344 + (P & 1) * 14336 + k * 2048>(acc2, doa, dwo); });
                if (P) wg_commit();
                if (P == 2) { wg_wait<1>(); warp_arrive(BAR(B_OC)); }
            });
            wg_wait<0>();
            reg_fence(acc2);
            TR(7);
            float s0 = 0.f, s1 = 0.f, q0 = 0.f, q1 = 0.f;
            #pragma unroll
            for (int c = 0; c < 7; c++) {
                s0 += acc2[4 * c] + acc2[4 * c + 1];     q0 = fmaf(acc2[4 * c], acc2[4 * c], fmaf(acc2[4 * c + 1], acc2[4 * c + 1], q0));
                s1 += acc2[4 * c + 2] + acc2[4 * c + 3]; q1 = fmaf(acc2[4 * c + 2], acc2[4 * c + 2], fmaf(acc2[4 * c + 3], acc2[4 * c + 3], q1));
            }
            const bool th = t >= 2, to = t & 1;
            const float sa = (th ? s1 : s0) + __shfl_xor_sync(~0u, th ? s0 : s1, 2), qa = (th ? q1 : q0) + __shfl_xor_sync(~0u, th ? q0 : q1, 2);
            const float part = (to ? qa : sa) + __shfl_xor_sync(~0u, to ? sa : qa, 1);
            stg1(spw, set_par(__float_as_uint(part), 1u, tag));
            if (tid == 128) st_flag(nfl, tag);
            const uint32_t tpoll = clk32() + SDELAY;
            TR(8);
            warp_arrive(BAR(B_HD));
            #pragma unroll
            for (int r = 0; r < 2; r++) {
                const float b2v = __bfloat162float(r ? bias2b : bias2a);
                uint32_t hw[7];
                #pragma unroll
                for (int c = 0; c < 7; c++) hw[c] = pack_bf16(acc2[4 * c + 2 * r] + b2v, acc2[4 * c + 2 * r + 1] + b2v);
                stg4(hp + r * 512, set_par(hw[0], ~lane & 1, tag), hw[1], hw[2], hw[3]);
                stg4(hp + r * 512 + 32, tag, hw[4], hw[5], hw[6]);
            }
            uint32_t nm[2][4];
            #pragma unroll
            for (int i = 0; i < 8; i++) nm[i >> 2][i & 3] = lane == ((cg * 7 + i) & 3) * 8 + w * 2 + (i >> 2);
            uint32_t us[8];
            spin_until(tpoll);
            {
                int it = 0;
                while (true) {
                    uint32_t bad = 0;
                    #pragma unroll
                    for (int i = 0; i < 8; i++) { us[i] = ld_rlx(spr + i * 128); bad |= us[i] ^ tag; }
                    if (!__any_sync(~0u, bad & 1)) break;
                    RETRY_COUNT(3);
                    if (++it > kSpinLimit) { TIMEOUT(103); break; }
                }
            }
            TR(9);
            const float tot = (((__uint_as_float(us[0]) + __uint_as_float(us[1])) + (__uint_as_float(us[2]) + __uint_as_float(us[3])))
                            + ((__uint_as_float(us[4]) + __uint_as_float(us[5])) + (__uint_as_float(us[6]) + __uint_as_float(us[7])))) * (1.f / kD);
            const float oth = __shfl_xor_sync(~0u, tot, 1);
            const float mean = to ? oth : tot;
            const float var = fmaxf(fmaf(-mean, mean, to ? tot : oth), 0.f);
            const float r1 = rsq(var + kEps);
            const float rra = 0.5f * r1 * rsq(fmaf(var * r1, r1, kEps)), mra = -mean * rra;
            const float rrb = __shfl_xor_sync(~0u, rra, 2), mrb = __shfl_xor_sync(~0u, mra, 2);
            const float rr0 = th ? rrb : rra, mr0 = th ? mrb : mra, rr1 = th ? rra : rrb, mr1 = th ? mra : mrb;
            #pragma unroll
            for (int c = 0; c < 7; c++) {
                stg1(np + c * 256,      set_par(pack_bf16(fmaf(acc2[4 * c], rr0, mr0), fmaf(acc2[4 * c + 1], rr0, mr0)), nm[0][c & 3], tag));
                stg1(np + c * 256 + 32, set_par(pack_bf16(fmaf(acc2[4 * c + 2], rr1, mr1), fmaf(acc2[4 * c + 3], rr1, mr1)), nm[1][c & 3], tag));
            }
            TR(10);
        }
        float acc[56];
        const uint32_t xch = opaque(sb + SM_XCH + w * 1920 + lane * 16);
        uint32_t peer_xch; const uint32_t peer_bar = pbar0;
        asm volatile("mapa.shared::cluster.u32 %0, %1, %2;" : "=r"(peer_xch) : "r"(xch), "r"(rank ^ 1));
        uint4 hr[4];
        const int tok = g2s * 64 + w * 16 + rank * 8 + g, pr = (tok & 127) >> 1;
        const uint4* hp = &g_h[((((tok >> 7) * 2 + (tok & 1)) * 8 + (pr >> 3)) * 8 + (g2j + 2 * wg) * 2) * 64 + (pr & 7) * 4 + t];
        auto load_h = [&]() {
            #pragma unroll
            for (int c = 0; c < 4; c++) hr[c] = ld_rlx4(hp + c * 32);
        };
        const uint32_t b1h = pack_bf16(0.5f * __bfloat162float(bias1), 0.5f * __bfloat162float(bias1));
        #pragma unroll
        for (int c = 0; c < 4; c++) hr[c] = make_uint4(b1h, b1h, b1h, b1h);
        if (!g1_on) { mbar_wait(BAR(B_GD), 0); load_h(); }
        uint32_t* const gp1 = (uint32_t*)&g_g[(g1f * 56 + (g1j + 2 * wg) * 14) * 64] + (w * 2 + rank) * 32 + lane;
        uint32_t* const gp2 = (uint32_t*)(prm.out + (size_t)(g2s * 64 + w * 16 + rank * 8 + (lane >> 4)) * kD + (g2j + 2 * wg) * 112) + (lane & 15) * 4;
        uint32_t gm[4];
        #pragma unroll
        for (int i = 0; i < 4; i++) gm[i] = lane == ((g1j * 2 + i) & 3) * 8 + w * 2 + rank;
        const bool lead = elect_one();
        const uint64_t da0 = make_desc(sb, 0, true), db0 = make_desc(sb + SM_B, 128, false);
        #pragma unroll 1
        for (int ge = g1_on ? 0 : 1; ge < 2; ge++) {
            if (ge) {
                int it = 0;
                while (true) {
                    uint32_t bad = 0;
                    #pragma unroll
                    for (int c = 0; c < 4; c++) bad |= hr[c].x ^ tag;
                    if (!__any_sync(~0u, bad & ~lane & 1)) break;
                    if (++it > kSpinLimit) { TIMEOUT(110); break; }
                    load_h();
                }
            }
            auto init_acc = [&](auto R_) {
                constexpr int o = decltype(R_)::value * 2;
                #pragma unroll
                for (int c = 0; c < 14; c++) {
                    const int i = c / 7 * 8 + c % 7 + (c % 7 >= 4);
                    const uint32_t hw = (i & 3) == 0 ? hr[i >> 2].x : (i & 3) == 1 ? hr[i >> 2].y : (i & 3) == 2 ? hr[i >> 2].z : hr[i >> 2].w;
                    acc[4 * c + o] = bf_lo(hw); acc[4 * c + 1 + o] = bf_hi(hw);
                    acc[4 * c + 2 - o] = 0.f;   acc[4 * c + 3 - o] = 0.f;
                }
                reg_fence(acc);
            };
            if (rank) init_acc(std::integral_constant<int, 1>{}); else init_acc(std::integral_constant<int, 0>{});
            const uint32_t slot0 = g1_on ? (ge ? 4 : 2 * wg) : 0;
            uint32_t ph = 0, rb = bar0 + slot0 * 8;
            uint64_t da = da0 + ge * 1024, db = db0 + slot0 * 896;
            uint32_t prev = BAR(B_WKVF);
            mbar_wait(BAR(B_EP), 0);
            if (wg == 1 || (ge && g1_on)) named_bar(5 - wg, 256);
            mbar_wait(rb + B_BF * 8, ph);
            TR(11 + ge * 4);
            #pragma unroll 1
            for (int n = ge ? 14 : 16;;) {
                wg_fence();
                wgmma_ss_n112<0,    0>(acc, da, db);
                wgmma_ss_n112<2048, 256>(acc, da, db);
                wgmma_ss_n112<4096, 512>(acc, da, db);
                wgmma_ss_n112<6144, 768>(acc, da, db);
                wg_commit();
                if (--n == 0 && ge + wg < 2) named_arrive(4 + wg, 256);
                const uint32_t cur = rb + B_BE * 8;
                da += 512; db += 896; rb += 8;
                if (rb == bar0 + NB * 8) { rb = bar0; db = db0; ph ^= 1; }
                wg_wait<1>();
                mbar_arrive_if(prev, lead);
                prev = cur;
                if (n == 0) break;
                if (!mbar_try(rb + B_BF * 8, ph)) mbar_wait(rb + B_BF * 8, ph);
            }
            const int use = ge * 2 + wg;
            const uint32_t xfree = BAR(use > (g1_on ? 0 : 2) ? B_RE + use - 1 : B_PD);
            const bool xok = mbar_test(xfree, 0);
            wg_wait<0>();
            reg_fence(acc);
            mbar_arrive_if(prev, lead);
            TR(12 + ge * 4);
            if (!xok) mbar_wait(xfree, 0);
            float v[28];
            auto reduce = [&](auto R_) {
                constexpr int o = decltype(R_)::value * 2;
                const uint32_t rf = peer_bar + (B_RF + use) * 8;
                float dly = __uint_as_float(0x3f800000u | lane); uint32_t pa = peer_xch;
                #pragma unroll
                for (int c = 0; c < 4; c++) {
                    const uint32_t p0 = pack_bf16(acc[16 * c + 2 - o], acc[16 * c + 3 - o]), p1 = pack_bf16(acc[16 * c + 6 - o], acc[16 * c + 7 - o]);
                    if (c < 3) {
                        const uint32_t p2 = pack_bf16(acc[16 * c + 10 - o], acc[16 * c + 11 - o]), p3 = pack_bf16(acc[16 * c + 14 - o], acc[16 * c + 15 - o]);
                        asm volatile("st.async.shared::cluster.mbarrier::complete_tx::bytes.v4.b32 [%0], {%1,%2,%3,%4}, [%5];"
                                     :: "r"(pa + c * 512), "r"(p0), "r"(p1), "r"(p2), "r"(p3), "r"(rf) : "memory");
                        if (use != 3) {
                            #pragma unroll
                            for (int i = 0; i < XPACE; i++) asm volatile("tanh.approx.f32 %0, %0;" : "+f"(dly) :: "memory");
                            pa += __float_as_uint(dly) >> 30;
                        }
                    } else {
                        asm volatile("st.async.shared::cluster.mbarrier::complete_tx::bytes.v2.b32 [%0], {%1,%2}, [%3];"
                                     :: "r"(pa + 1536 - lane * 8), "r"(p0), "r"(p1), "r"(rf) : "memory");
                    }
                }
                if (!ge) load_h();
                mbar_wait(BAR(B_RF + use), 0);
                #pragma unroll
                for (int c = 0; c < 4; c++) {
                    uint4 u;
                    if (c < 3) u = lds4(xch + c * 512); else { const uint2 u2 = lds2(xch + 1536 - lane * 8); u.x = u2.x; u.y = u2.y; }
                    v[8 * c]     = acc[16 * c + o] + bf_lo(u.x);     v[8 * c + 1] = acc[16 * c + 1 + o] + bf_hi(u.x);
                    v[8 * c + 2] = acc[16 * c + 4 + o] + bf_lo(u.y); v[8 * c + 3] = acc[16 * c + 5 + o] + bf_hi(u.y);
                    if (c < 3) {
                        v[8 * c + 4] = acc[16 * c + 8 + o] + bf_lo(u.z);  v[8 * c + 5] = acc[16 * c + 9 + o] + bf_hi(u.z);
                        v[8 * c + 6] = acc[16 * c + 12 + o] + bf_lo(u.w); v[8 * c + 7] = acc[16 * c + 13 + o] + bf_hi(u.w);
                    }
                }
            };
            if (rank) reduce(std::integral_constant<int, 1>{}); else reduce(std::integral_constant<int, 0>{});
            TR(13 + ge * 4);
            if (!ge) {
                #pragma unroll
                for (int c = 0; c < 14; c++) {
                    float r[2];
                    #pragma unroll
                    for (int e = 0; e < 2; e++) {
                        const float u = v[2 * c + e];
                        r[e] = fmaf(u, tanh_hw(u * fmaf(u * u, 8.f * 0.7978845608f * 0.044715f, 2.f * 0.7978845608f)), u);
                    }
                    stg1(gp1 + c * 256, set_par(pack_bf16(r[0], r[1]), gm[c & 3], tag));
                }
                named_bar(1 + wg, 128);
                if (w == 0 && lane == 0) {
                    asm volatile("st.shared.u32 [%0], %1;" :: "r"(sb + SM_TG + 8 + wg * 4), "r"(clk32() + XSPEC) : "memory");
                    mbar_arrive(BAR(B_GD + wg));
                }
                mbar_arrive_remote_if(peer_bar + (B_RE + use) * 8, lead);
            } else {
                const uint32_t stw = xch - lane * 16;
                uint32_t pk[14];
                #pragma unroll
                for (int c = 0; c < 14; c++) pk[c] = pack_bf16(v[2 * c], v[2 * c + 1]);
                __syncwarp();
                const uint32_t sa = stw + (lane & 7) * 240 + (lane >> 3) * 16;
                #pragma unroll
                for (int m = 0; m < 3; m++)
                    asm volatile("stmatrix.sync.aligned.m8n8.x4.shared.b16 [%0], {%1,%2,%3,%4};"
                                 :: "r"(sa + m * 64), "r"(pk[4 * m]), "r"(pk[4 * m + 1]), "r"(pk[4 * m + 2]), "r"(pk[4 * m + 3]) : "memory");
                asm volatile("stmatrix.sync.aligned.m8n8.x2.shared.b16 [%0], {%1,%2};" :: "r"(sa + 192), "r"(pk[12]), "r"(pk[13]) : "memory");
                __syncwarp();
                #pragma unroll
                for (int i = 0; i < 4; i++) {
                    const int r = 2 * i + (lane >> 4), ch = lane & 15;
                    if (ch < 14) { const uint4 u = lds4(stw + r * 240 + ch * 16); stg4(gp2 + i * 448, u.x, u.y, u.z, u.w); }
                }
                __syncwarp();
                mbar_arrive_remote_if(peer_bar + (B_RE + 2) * 8, lead && wg == 0);
            }
            TR(14 + ge * 4);
        }
        if (tid == 128) TRG(62);
        if (b == 0 && tid == 128) g_epoch = tag;
    }
}

typedef CUresult (*EncodeFn)(CUtensorMap*, CUtensorMapDataType, cuuint32_t, void*, const cuuint64_t*, const cuuint64_t*,
                             const cuuint32_t*, const cuuint32_t*, CUtensorMapInterleave, CUtensorMapSwizzle,
                             CUtensorMapL2promotion, CUtensorMapFloatOOBfill);

void make_map(EncodeFn enc, CUtensorMap* m, const void* base, uint64_t cols, uint64_t rows, uint32_t box_rows) {
    cuuint64_t dims[2] = {cols, rows};
    cuuint64_t strides[1] = {cols * 2};
    cuuint32_t box[2] = {64, box_rows};
    cuuint32_t es[2] = {1, 1};
    enc(m, CU_TENSOR_MAP_DATA_TYPE_BFLOAT16, 2, const_cast<void*>(base), dims, strides, box, es, CU_TENSOR_MAP_INTERLEAVE_NONE,
        CU_TENSOR_MAP_SWIZZLE_128B, CU_TENSOR_MAP_L2_PROMOTION_L2_128B, CU_TENSOR_MAP_FLOAT_OOB_FILL_NONE);
}

}

extern "C" void kernel_launch(void* const* d_in, const int* in_sizes, int n_in, void* d_out, int out_size) {
    (void)in_sizes; (void)n_in; (void)out_size;
    void* fn = nullptr;
    cudaDriverEntryPointQueryResult qr;
    cudaGetDriverEntryPoint("cuTensorMapEncodeTiled", &fn, cudaEnableDefault, &qr);
    EncodeFn enc = (EncodeFn)fn;
    CUtensorMap mX, mWqkv, mWo, mW1, mW2;
    make_map(enc, &mX, d_in[0], 2 * kD, kS / 2, 64);
    make_map(enc, &mWqkv, d_in[1], 3 * kD, kD, 64);
    make_map(enc, &mWo, d_in[2], kD, kD, 224);
    make_map(enc, &mW1, d_in[4], 2 * kF, kS / 2, 64);
    make_map(enc, &mW2, d_in[6], kS, kF, 64);
    Params prm;
    prm.x = (const __nv_bfloat16*)d_in[0];
    prm.wqkv = (const __nv_bfloat16*)d_in[1];
    prm.wo = (const __nv_bfloat16*)d_in[2];
    prm.w1 = (const __nv_bfloat16*)d_in[4];
    prm.b1 = (const __nv_bfloat16*)d_in[5];
    prm.w2 = (const __nv_bfloat16*)d_in[6];
    prm.b2 = (const __nv_bfloat16*)d_in[7];
    prm.out = (__nv_bfloat16*)d_out;
    cudaFuncSetAttribute(fused_kernel, cudaFuncAttributeMaxDynamicSharedMemorySize, SM_TOTAL);
    fused_kernel<<<128, 384, SM_TOTAL, cudaStreamPerThread>>>(mX, mWqkv, mWo, mW1, mW2, prm);
}
```

```cpp
#include <cuda_runtime.h>
#include <cuda.h>
#include <cuda_bf16.h>
#include <stdint.h>
#include <type_traits>

namespace {

constexpr int kS = 2048, kD = 448, kF = 1792;
constexpr float kEps = 1e-5f;

#define FS 32
__device__ __align__(1024) uint4    g_o[32 * 56 * 64];
__device__ __align__(1024) uint4    g_h[32 * 8 * 8 * 64];
__device__ __align__(1024) uint4    g_hn[32 * 56 * 64];
__device__ __align__(1024) uint4    g_g[28 * 56 * 64];
__device__ __align__(1024) uint4    g_halo[16 * 8 * 2 * 4 * 32];
__device__ __align__(1024) uint32_t g_stats[32 * 8 * 4 * 32];
__device__ __align__(1024) uint32_t g_flag_o[32 * 8 * FS];
__device__ __align__(1024) uint32_t g_flag_h[32 * 4 * FS];
__device__ uint32_t g_epoch;
#define TIMEOUT(code)
#define RETRY_COUNT(i)
#define CAP_DECL(n, k)
#define CAP(n)
#define CAP_SKIP(n)
#define TR2(idx)
#define TR(idx)
#define TRW(idx)
#define TRG(idx)

constexpr uint32_t SM_X    = 0;
constexpr uint32_t SM_WKV  = 114688;
constexpr uint32_t SM_XR   = 24576;
constexpr uint32_t SM_STG  = 40960;
constexpr uint32_t SM_WQ   = 57344;
constexpr uint32_t SM_XCH  = 0;
constexpr uint32_t SM_B    = 131072;
constexpr uint32_t SM_BAR  = 231424;
constexpr uint32_t SM_TOTAL = SM_BAR + 1024;
constexpr int NB = 7;
#define SH1 0
#define SH2 0
#define SH2N 5
#define SH3 0
#define NSPEC 4
#define XSPEC 850
#define C2 0
#define C3 0
#define CN2 8000
#define CN3 12000
constexpr int B_XF = 0, B_WKVF = 7, B_WQF = 14, B_XRF = 15, B_WOF = 16,
              B_XC = 18, B_KV3 = 19, B_KVC = 20,
              B_A1D = 21, B_XD = 22, B_OC = 23,
              B_BE = 24, B_RE = B_BE + NB,
              B_AF = B_RE + 3, B_BL = B_AF + 16  , B_BF = B_BL + NB + 4  ,
              B_RF = B_BF + NB + 4, B_EP = B_RF + 4, B_PD = B_EP + 1, B_RT = B_PD + 1, B_HL = B_RT + 2,
              B_HD = B_HL + 2  , B_GO = B_HD + 1, B_GD = B_GO + 1, B_COUNT = B_GD + 2;
#define WEARLY 6
#define PF0 126
#define TMPF 2
#define RSTE 2
#define POLLP 1
#define PROBEP 1
#define LOADP 1
#define LOADW 64
#define NOB 0
#define AEARLY 5
#define W1PACE 400
#define W2PACE 200
#define PFPACE 290
#define PFBAR (B_XF + 6)
#define DELTA 1696
#define DELTA2 DELTA
#define BPACE 230
#define BURST 2
#define W1OFF 350
#define W2OFF 2900
#define XPACE 0
#define PSTAG 200
constexpr uint32_t SM_EPOCH = SM_BAR + B_COUNT * 8, SM_TG = SM_EPOCH + 4  , SM_TG2 = SM_TG + 16  , SM_TR = SM_BAR + 768;

#define HDELAY 100
#define QC0 4
#define QC1 10
#define QC2 16
#define HPOS 1
#define XSPECB 700
#define PACE1 120
#define PACE2 400
#define RELOAD1 1
#define VCH 1
#define SOFF 0
#define SDELAY 400
#define PDELAY 500
#define NPRE 10
#define PREPACE 0
#define AFIRST 0
#define DELTAO 896
#define W1Q 3
constexpr uint32_t w2_rounds(int h) { uint32_t m = 0; for (int i = 0; i < 14; i++) { const int p = 25 + i * 20 / 13; if ((p & 1) == h) m |= 1u << (p / 2 + 1); } return m; }
constexpr uint32_t kAMask0 = w2_rounds(0), kAMask1 = w2_rounds(1) | ((1u << (16 - NPRE)) - 1) << W1Q;

constexpr int kSpinLimit = 1 << 15;
__device__ __forceinline__ bool elect_one() {
    uint32_t p;
    asm volatile("{ .reg .pred P; elect.sync _|P, 0xffffffff; selp.u32 %0, 1, 0, P; }" : "=r"(p));
    return p;
}
__device__ __forceinline__ void mbar_init(uint32_t bar, uint32_t cnt) { asm volatile("mbarrier.init.shared::cta.b64 [%0], %1;" :: "r"(bar), "r"(cnt)); }
__device__ __forceinline__ void mbar_expect(uint32_t bar, uint32_t bytes) { asm volatile("mbarrier.arrive.expect_tx.shared::cta.b64 _, [%0], %1;" :: "r"(bar), "r"(bytes) : "memory"); }
__device__ __forceinline__ void mbar_arrive(uint32_t bar) { asm volatile("mbarrier.arrive.shared::cta.b64 _, [%0];" :: "r"(bar) : "memory"); }
__device__ __forceinline__ void mbar_wait(uint32_t bar, uint32_t parity) {
    uint32_t ok; int it = 0;
    do {
        asm volatile("{ .reg .pred p; mbarrier.try_wait.parity.shared::cta.b64 p, [%1], %2; selp.u32 %0, 1, 0, p; }"
                     : "=r"(ok) : "r"(bar), "r"(parity) : "memory");
        if (++it > kSpinLimit) { TIMEOUT((bar & 1023) >> 3); break; }
    } while (!ok);
}
__device__ __forceinline__ bool mbar_try(uint32_t bar, uint32_t parity) {
    uint32_t ok;
    asm volatile("{ .reg .pred p; mbarrier.try_wait.parity.shared::cta.b64 p, [%1], %2; selp.u32 %0, 1, 0, p; }" : "=r"(ok) : "r"(bar), "r"(parity) : "memory");
    return ok;
}
__device__ __forceinline__ bool mbar_test(uint32_t bar, uint32_t parity) {
    uint32_t ok;
    asm volatile("{ .reg .pred p; mbarrier.test_wait.parity.shared::cta.b64 p, [%1], %2; selp.u32 %0, 1, 0, p; }" : "=r"(ok) : "r"(bar), "r"(parity) : "memory");
    return ok;
}
__device__ __forceinline__ void mbar_wait_fast(uint32_t bar, uint32_t parity) { if (!mbar_try(bar, parity)) mbar_wait(bar, parity); }
__device__ __forceinline__ void mbar_wait2(uint32_t bar0, uint32_t par0, uint32_t bar1, uint32_t par1) {
    uint32_t ok; int it = 0;
    do {
        asm volatile("{ .reg .pred p, q; mbarrier.try_wait.parity.shared::cta.b64 p, [%1], %2;\n"
                     "mbarrier.try_wait.parity.shared::cta.b64 q, [%3], %4; and.pred p, p, q; selp.u32 %0, 1, 0, p; }"
                     : "=r"(ok) : "r"(bar0), "r"(par0), "r"(bar1), "r"(par1) : "memory");
        if (++it > kSpinLimit) { TIMEOUT((bar0 & 1023) >> 3); break; }
    } while (!ok);
}
template <int N> __device__ __forceinline__ void reg_fence(float (&d)[N]) {
    #pragma unroll
    for (int i = 0; i < N; i++) asm volatile("" : "+f"(d[i]) :: "memory");
}
__device__ __forceinline__ void mbar_wait_cluster(uint32_t bar, uint32_t parity) {
    uint32_t ok; int it = 0;
    do {
        asm volatile("{ .reg .pred p; mbarrier.try_wait.parity.acquire.cluster.shared::cta.b64 p, [%1], %2; selp.u32 %0, 1, 0, p; }"
                     : "=r"(ok) : "r"(bar), "r"(parity) : "memory");
        if (++it > kSpinLimit) { TIMEOUT((bar & 1023) >> 3); break; }
    } while (!ok);
}
__device__ __forceinline__ void mbar_arrive_if(uint32_t bar, bool pred) {
    asm volatile("{ .reg .pred p; setp.ne.u32 p, %1, 0; @p mbarrier.arrive.shared::cta.b64 _, [%0]; }" :: "r"(bar), "r"((uint32_t)pred) : "memory");
}
template <int P> __device__ __forceinline__ void tick() {
    if (P > 1) { const uint32_t t = ((uint32_t)clock() | (P - 1)) + 1; while ((int)((uint32_t)clock() - t) < 0) {} }
}
__device__ __forceinline__ void warp_arrive(uint32_t bar) { __syncwarp(); if (elect_one()) mbar_arrive(bar); }
__device__ __forceinline__ void tma2d(uint32_t dst, const CUtensorMap* m, int c0, int c1, uint32_t bar) {
    asm volatile("cp.async.bulk.tensor.2d.shared::cluster.global.mbarrier::complete_tx::bytes [%0], [%1, {%3, %4}], [%2];"
                 :: "r"(dst), "l"(m), "r"(bar), "r"(c0), "r"(c1) : "memory");
}
__device__ __forceinline__ void tma2d_mc(uint32_t dst, const CUtensorMap* m, int c0, int c1, uint32_t bar) {
    asm volatile("cp.async.bulk.tensor.2d.shared::cluster.global.mbarrier::complete_tx::bytes.multicast::cluster [%0], [%1, {%3, %4}], [%2], %5;"
                 :: "r"(dst), "l"(m), "r"(bar), "r"(c0), "r"(c1), "h"((uint16_t)3) : "memory");
}
__device__ __forceinline__ void bulk_g2s_mc(uint32_t dst, const void* src, uint32_t bytes, uint32_t bar) {
    asm volatile("cp.async.bulk.shared::cluster.global.mbarrier::complete_tx::bytes.multicast::cluster [%0], [%1], %2, [%3], %4;"
                 :: "r"(dst), "l"(src), "r"(bytes), "r"(bar), "h"((uint16_t)3) : "memory");
}
__device__ __forceinline__ void mbar_arrive_remote_if(uint32_t cluster_bar, bool pred) {
    asm volatile("{ .reg .pred p; setp.ne.u32 p, %1, 0; @p mbarrier.arrive.shared::cluster.b64 _, [%0]; }" :: "r"(cluster_bar), "r"((uint32_t)pred) : "memory");
}
__device__ __forceinline__ void bulk_g2s(uint32_t dst, const void* src, uint32_t bytes, uint32_t bar) {
    asm volatile("cp.async.bulk.shared::cluster.global.mbarrier::complete_tx::bytes [%0], [%1], %2, [%3];"
                 :: "r"(dst), "l"(src), "r"(bytes), "r"(bar) : "memory");
}
__device__ __forceinline__ void wg_fence()  { asm volatile("wgmma.fence.sync.aligned;" ::: "memory"); }
__device__ __forceinline__ void wg_commit() { asm volatile("wgmma.commit_group.sync.aligned;" ::: "memory"); }
template <int N> __device__ __forceinline__ void wg_wait() { asm volatile("wgmma.wait_group.sync.aligned %0;" :: "n"(N) : "memory"); }
__device__ __forceinline__ void named_bar(int id, int n) { asm volatile("bar.sync %0, %1;" :: "r"(id), "r"(n) : "memory"); }
__device__ __forceinline__ void named_arrive(int id, int n) { asm volatile("bar.arrive %0, %1;" :: "r"(id), "r"(n) : "memory"); }
__device__ __forceinline__ bool mbar_try2(uint32_t bar0, uint32_t par0, uint32_t bar1, uint32_t par1) {
    uint32_t ok;
    asm volatile("{ .reg .pred p, q; mbarrier.test_wait.parity.shared::cta.b64 p, [%1], %2;\n"
                 "mbarrier.test_wait.parity.shared::cta.b64 q, [%3], %4; and.pred p, p, q; selp.u32 %0, 1, 0, p; }"
                 : "=r"(ok) : "r"(bar0), "r"(par0), "r"(bar1), "r"(par1) : "memory");
    return ok;
}
__device__ __forceinline__ void fence_gpu() { asm volatile("fence.release.gpu;" ::: "memory"); }
__device__ __forceinline__ void fence_async_global() { asm volatile("fence.proxy.async.global;" ::: "memory"); }
__device__ __forceinline__ void fence_async_smem() { asm volatile("fence.proxy.async.shared::cta;" ::: "memory"); }
__device__ __forceinline__ uint32_t gtime32() { uint64_t t; asm volatile("mov.u64 %0, %%globaltimer;" : "=l"(t) :: "memory"); return (uint32_t)t; }
__device__ __forceinline__ uint32_t clk32() { uint64_t t; asm volatile("mov.u64 %0, %%clock64;" : "=l"(t) :: "memory"); return (uint32_t)t; }
__device__ __forceinline__ void spin_until(uint32_t t) { while ((int)(clk32() - t) < 0) {} }
#define SLEEPNS 20
__device__ __forceinline__ void sleep_until(uint32_t t) { while ((int)(clk32() - t) < 0) { if (SLEEPNS) __nanosleep(SLEEPNS); } }
__device__ __forceinline__ void st_flag(uint32_t* p, uint32_t v) {
    const uint64_t w = ((uint64_t)gtime32() << 32) | v;
    asm volatile("st.relaxed.gpu.global.u64 [%0], %1;" :: "l"(p), "l"(w) : "memory");
}
__device__ __forceinline__ void ld_flag_if(uint64_t& v, const uint32_t* p, bool pred) {
    asm volatile("{ .reg .pred p; setp.ne.u32 p, %2, 0; @p ld.relaxed.gpu.global.u64 %0, [%1]; }" : "+l"(v) : "l"(p), "r"((uint32_t)pred) : "memory");
}
__device__ __forceinline__ uint32_t ld_acq(const uint32_t* p) { uint32_t v; asm volatile("ld.acquire.gpu.global.u32 %0, [%1];" : "=r"(v) : "l"(p) : "memory"); return v; }
__device__ __forceinline__ uint32_t ld_rlx(const uint32_t* p) { uint32_t v; asm volatile("ld.relaxed.gpu.global.u32 %0, [%1];" : "=r"(v) : "l"(p) : "memory"); return v; }
template <class T> __device__ __forceinline__ T* opaque_ptr(T* p) { asm volatile("" : "+l"(p)); return p; }
__device__ __forceinline__ uint4 ld_rlx4(const uint4* p) {
    uint4 v; asm volatile("ld.relaxed.gpu.global.v4.u32 {%0,%1,%2,%3}, [%4];" : "=r"(v.x), "=r"(v.y), "=r"(v.z), "=r"(v.w) : "l"(p) : "memory"); return v;
}
__device__ __forceinline__ void st_ll(uint4* p, uint32_t a, uint32_t b, uint32_t tag) {
    uint64_t lo = ((uint64_t)tag << 32) | a, hi = ((uint64_t)tag << 32) | b;
    asm volatile("st.relaxed.gpu.global.v2.u64 [%0], {%1,%2};" :: "l"(p), "l"(lo), "l"(hi) : "memory");
}
__device__ __forceinline__ bool ld_ll(const uint4* p, uint32_t& a, uint32_t& b, uint32_t tag) {
    uint64_t lo, hi;
    asm volatile("ld.relaxed.gpu.global.v2.u64 {%0,%1}, [%2];" : "=l"(lo), "=l"(hi) : "l"(p) : "memory");
    a = (uint32_t)lo; b = (uint32_t)hi;
    return (uint32_t)(lo >> 32) == tag && (uint32_t)(hi >> 32) == tag;
}
__device__ __forceinline__ uint2 ld_acq2(const uint2* p) {
    uint2 v; asm volatile("ld.acquire.gpu.global.v2.u32 {%0,%1}, [%2];" : "=r"(v.x), "=r"(v.y) : "l"(p) : "memory"); return v;
}
__device__ __forceinline__ uint2 ld_rlx2(const uint2* p) {
    uint2 v; asm volatile("ld.relaxed.gpu.global.v2.u32 {%0,%1}, [%2];" : "=r"(v.x), "=r"(v.y) : "l"(p) : "memory"); return v;
}
__device__ __forceinline__ void stg1(uint32_t* p, uint32_t v) { asm volatile("st.global.u32 [%0], %1;" :: "l"(p), "r"(v) : "memory"); }
__device__ __forceinline__ void stg2(void* p, uint32_t x, uint32_t y) { asm volatile("st.global.v2.u32 [%0], {%1,%2};" :: "l"(p), "r"(x), "r"(y) : "memory"); }
__device__ __forceinline__ void stg4(void* p, uint32_t x, uint32_t y, uint32_t z, uint32_t w) { asm volatile("st.global.v4.u32 [%0], {%1,%2,%3,%4};" :: "l"(p), "r"(x), "r"(y), "r"(z), "r"(w) : "memory"); }
__device__ __forceinline__ uint32_t lds1(uint32_t a) { uint32_t v; asm volatile("ld.shared.u32 %0, [%1];" : "=r"(v) : "r"(a) : "memory"); return v; }
__device__ __forceinline__ uint2 lds2(uint32_t a) { uint2 v; asm volatile("ld.shared.v2.u32 {%0,%1}, [%2];" : "=r"(v.x), "=r"(v.y) : "r"(a) : "memory"); return v; }
__device__ __forceinline__ uint32_t set_par(uint32_t v, uint32_t mask, uint32_t par) {
    uint32_t r; asm("lop3.b32 %0, %1, %2, %3, 0xb8;" : "=r"(r) : "r"(v), "r"(mask), "r"(par)); return r;
}
__device__ __forceinline__ void st_gen4(void* p, uint32_t x, uint32_t y, uint32_t z, uint32_t w) { asm volatile("st.v4.u32 [%0], {%1,%2,%3,%4};" :: "l"(p), "r"(x), "r"(y), "r"(z), "r"(w) : "memory"); }
__device__ __forceinline__ float tanh_hw(float x) { float r; asm("tanh.approx.f32 %0, %1;" : "=f"(r) : "f"(x)); return r; }
__device__ __forceinline__ bool bar_any(int id, int n, bool v) {
    uint32_t r;
    asm volatile("{ .reg .pred p, q; setp.ne.u32 p, %3, 0; bar.red.or.pred q, %1, %2, p; selp.u32 %0, 1, 0, q; }" : "=r"(r) : "r"(id), "r"(n), "r"((uint32_t)v) : "memory");
    return r;
}
__device__ __forceinline__ void sts4(uint32_t a, uint32_t x, uint32_t y, uint32_t z, uint32_t w) { asm volatile("st.shared.v4.u32 [%0], {%1,%2,%3,%4};" :: "r"(a), "r"(x), "r"(y), "r"(z), "r"(w) : "memory"); }
__device__ __forceinline__ uint4 lds4(uint32_t a) { uint4 v; asm volatile("ld.shared.v4.u32 {%0,%1,%2,%3}, [%4];" : "=r"(v.x), "=r"(v.y), "=r"(v.z), "=r"(v.w) : "r"(a) : "memory"); return v; }
__device__ __forceinline__ uint32_t pack_bf16(float lo, float hi) { uint32_t r; asm("cvt.rn.bf16x2.f32 %0, %1, %2;" : "=r"(r) : "f"(hi), "f"(lo)); return r; }
__device__ __forceinline__ float bf_lo(uint32_t v) { return __uint_as_float(v << 16); }
__device__ __forceinline__ float bf_hi(uint32_t v) { return __uint_as_float(v & 0xffff0000u); }
__device__ __forceinline__ uint32_t sub_bf16x2(uint32_t a, uint32_t b) { uint32_t r; asm volatile("sub.rn.bf16x2 %0, %1, %2;" : "=r"(r) : "r"(a), "r"(b)); return r; }
__device__ __forceinline__ uint32_t add_bf16x2(uint32_t a, uint32_t b) { uint32_t r; asm volatile("add.rn.bf16x2 %0, %1, %2;" : "=r"(r) : "r"(a), "r"(b)); return r; }
__device__ __forceinline__ uint32_t sqr_bf16x2(uint32_t a) { uint32_t r; asm volatile("mul.rn.bf16x2 %0, %1, %1;" : "=r"(r) : "r"(a)); return r; }
__device__ __forceinline__ uint32_t sqa_bf16x2(uint32_t a, uint32_t c) { uint32_t r; asm volatile("fma.rn.bf16x2 %0, %1, %1, %2;" : "=r"(r) : "r"(a), "r"(c)); return r; }
__device__ __forceinline__ uint32_t movm(uint32_t a) { uint32_t r; asm volatile("movmatrix.sync.aligned.m8n8.trans.b16 %0, %1;" : "=r"(r) : "r"(a)); return r; }
__device__ __forceinline__ float ex2(float x) { float r; asm("ex2.approx.ftz.f32 %0, %1;" : "=f"(r) : "f"(x)); return r; }
__device__ __forceinline__ float rsq(float x) { float r; asm("rsqrt.approx.ftz.f32 %0, %1;" : "=f"(r) : "f"(x)); return r; }
__device__ __forceinline__ float rcp(float x) { float r; asm("rcp.approx.ftz.f32 %0, %1;" : "=f"(r) : "f"(x)); return r; }
__device__ __forceinline__ void mma16816(float (&c)[4], uint32_t a0, uint32_t a1, uint32_t a2, uint32_t a3, uint32_t b0, uint32_t b1) {
    asm("mma.sync.aligned.m16n8k16.row.col.f32.bf16.bf16.f32 {%0,%1,%2,%3}, {%4,%5,%6,%7}, {%8,%9}, {%0,%1,%2,%3};"
        : "+f"(c[0]), "+f"(c[1]), "+f"(c[2]), "+f"(c[3]) : "r"(a0), "r"(a1), "r"(a2), "r"(a3), "r"(b0), "r"(b1));
}
__device__ __forceinline__ void mma1688(float (&c)[4], uint32_t a0, uint32_t a1, uint32_t b0) {
    asm("mma.sync.aligned.m16n8k8.row.col.f32.bf16.bf16.f32 {%0,%1,%2,%3}, {%4,%5}, {%6}, {%0,%1,%2,%3};"
        : "+f"(c[0]), "+f"(c[1]), "+f"(c[2]), "+f"(c[3]) : "r"(a0), "r"(a1), "r"(b0));
}
__device__ __forceinline__ float quad_sum(float v) { v += __shfl_xor_sync(~0u, v, 1); v += __shfl_xor_sync(~0u, v, 2); return v; }
__device__ __forceinline__ float quad_max(float v) { v = fmaxf(v, __shfl_xor_sync(~0u, v, 1)); v = fmaxf(v, __shfl_xor_sync(~0u, v, 2)); return v; }
__device__ __forceinline__ uint64_t make_desc(uint32_t addr, uint32_t lbo, bool swz, uint32_t sbo = 1024) {
    const uint32_t lo = __shfl_sync(~0u, ((addr & 0x3FFFF) >> 4) | ((lbo >> 4) << 16), 0);
    const uint32_t hi = __shfl_sync(~0u, (swz ? 0x40000000u : 0u) + (sbo >> 4) + (threadIdx.x & 31), 0);
    return ((uint64_t)hi << 32) | lo;
}
template <int I, int N, class F> __device__ __forceinline__ void static_for(F&& f) {
    if constexpr (I < N) { f(std::integral_constant<int, I>{}); static_for<I + 1, N>(f); }
}
__device__ __forceinline__ uint32_t opaque(uint32_t v) { asm volatile("" : "+r"(v)); return v; }
template <int BOFF, int SCALE_D>
__device__ __forceinline__ void wgmma_rs_n56(float (&d)[28], uint32_t a0, uint32_t a1, uint32_t a2, uint32_t a3, uint64_t db) {
    asm volatile("{ .reg .b64 db; add.s64 db, %32, %33;\n"
        "wgmma.mma_async.sync.aligned.m64n56k16.f32.bf16.bf16 "
        "{%0, %1, %2, %3, %4, %5, %6, %7, %8, %9, %10, %11, %12, %13, %14, %15, %16, %17, %18, %19, %20, %21, %22, %23, %24, %25, %26, %27}, "
        "{%28, %29, %30, %31}, db, %34, 1, 1, 1; }"
        : "+f"(d[0]), "+f"(d[1]), "+f"(d[2]), "+f"(d[3]), "+f"(d[4]), "+f"(d[5]), "+f"(d[6]), "+f"(d[7]),
        "+f"(d[8]), "+f"(d[9]), "+f"(d[10]), "+f"(d[11]), "+f"(d[12]), "+f"(d[13]), "+f"(d[14]), "+f"(d[15]),
        "+f"(d[16]), "+f"(d[17]), "+f"(d[18]), "+f"(d[19]), "+f"(d[20]), "+f"(d[21]), "+f"(d[22]), "+f"(d[23]),
        "+f"(d[24]), "+f"(d[25]), "+f"(d[26]), "+f"(d[27])
        : "r"(a0), "r"(a1), "r"(a2), "r"(a3), "l"(db), "n"(BOFF >> 4), "n"(SCALE_D));
}
template <int AOFF, int BOFF>
__device__ __forceinline__ void wgmma_ss_n56(float (&d)[28], uint64_t da, uint64_t db) {
    asm volatile("{ .reg .b64 da, db; add.s64 da, %28, %30; add.s64 db, %29, %31;\n"
        "wgmma.mma_async.sync.aligned.m64n56k16.f32.bf16.bf16 "
        "{%0, %1, %2, %3, %4, %5, %6, %7, %8, %9, %10, %11, %12, %13, %14, %15, %16, %17, %18, %19, %20, %21, %22, %23, %24, %25, %26, %27}, "
        "da, db, 1, 1, 1, 0, 1; }"
        : "+f"(d[0]), "+f"(d[1]), "+f"(d[2]), "+f"(d[3]), "+f"(d[4]), "+f"(d[5]), "+f"(d[6]), "+f"(d[7]),
        "+f"(d[8]), "+f"(d[9]), "+f"(d[10]), "+f"(d[11]), "+f"(d[12]), "+f"(d[13]), "+f"(d[14]), "+f"(d[15]),
        "+f"(d[16]), "+f"(d[17]), "+f"(d[18]), "+f"(d[19]), "+f"(d[20]), "+f"(d[21]), "+f"(d[22]), "+f"(d[23]),
        "+f"(d[24]), "+f"(d[25]), "+f"(d[26]), "+f"(d[27])
        : "l"(da), "l"(db), "n"(AOFF >> 4), "n"(BOFF >> 4));
}
template <int AOFF, int BOFF>
__device__ __forceinline__ void wgmma_ss_n112(float (&d)[56], uint64_t da, uint64_t db) {
    asm volatile("{ .reg .b64 da, db; add.s64 da, %56, %58; add.s64 db, %57, %59;\n"
        "wgmma.mma_async.sync.aligned.m64n112k16.f32.bf16.bf16 "
        "{%0, %1, %2, %3, %4, %5, %6, %7, %8, %9, %10, %11, %12, %13, %14, %15, %16, %17, %18, %19, %20, %21, %22, %23, %24, %25, %26, %27, %28, %29, %30, %31, %32, %33, %34, %35, %36, %37, %38, %39, %40, %41, %42, %43, %44, %45, %46, %47, %48, %49, %50, %51, %52, %53, %54, %55}, "
        "da, db, 1, 1, 1, 1, 1; }"
        : "+f"(d[0]), "+f"(d[1]), "+f"(d[2]), "+f"(d[3]), "+f"(d[4]), "+f"(d[5]), "+f"(d[6]), "+f"(d[7]),
        "+f"(d[8]), "+f"(d[9]), "+f"(d[10]), "+f"(d[11]), "+f"(d[12]), "+f"(d[13]), "+f"(d[14]), "+f"(d[15]),
        "+f"(d[16]), "+f"(d[17]), "+f"(d[18]), "+f"(d[19]), "+f"(d[20]), "+f"(d[21]), "+f"(d[22]), "+f"(d[23]),
        "+f"(d[24]), "+f"(d[25]), "+f"(d[26]), "+f"(d[27]), "+f"(d[28]), "+f"(d[29]), "+f"(d[30]), "+f"(d[31]),
        "+f"(d[32]), "+f"(d[33]), "+f"(d[34]), "+f"(d[35]), "+f"(d[36]), "+f"(d[37]), "+f"(d[38]), "+f"(d[39]),
        "+f"(d[40]), "+f"(d[41]), "+f"(d[42]), "+f"(d[43]), "+f"(d[44]), "+f"(d[45]), "+f"(d[46]), "+f"(d[47]),
        "+f"(d[48]), "+f"(d[49]), "+f"(d[50]), "+f"(d[51]), "+f"(d[52]), "+f"(d[53]), "+f"(d[54]), "+f"(d[55])
        : "l"(da), "l"(db), "n"(AOFF >> 4), "n"(BOFF >> 4));
}

struct Params {
    const __nv_bfloat16 *x, *wqkv, *wo, *w1, *w2, *b1, *b2;
    __nv_bfloat16* out;
};

__global__ void __cluster_dims__(2, 1, 1) __launch_bounds__(384, 1)
fused_kernel(const __grid_constant__ CUtensorMap mX, const __grid_constant__ CUtensorMap mWqkv,
             const __grid_constant__ CUtensorMap mWo, const __grid_constant__ CUtensorMap mW1,
             const __grid_constant__ CUtensorMap mW2, const Params prm)
{
    extern __shared__ __align__(1024) unsigned char smem_raw[];
    uint32_t sb = (uint32_t)__cvta_generic_to_shared(smem_raw);
    asm volatile("mov.u32 %0, %0;" : "+r"(sb));
    const uint32_t bar0 = sb + SM_BAR;
    auto BAR = [&](int i) { return bar0 + 8u * i; };

    const int tid = threadIdx.x, lane = tid & 31;
    const int warp = __shfl_sync(~0u, tid >> 5, 0);
    const int b = __shfl_sync(~0u, (int)blockIdx.x, 0);
    const int rank = b & 1;
    const int cl = (b >> 1) - 4, cq = ((cl - 32) * 37) >> 8;
    const int res = cl < 0 ? 0 : cl < 32 ? cl & 7 : cl - 31 - 7 * cq;
    const int rnd = cl < 0 ? cl + 8 : cl < 32 ? cl >> 3 : 4 + cq;
    const int hg = (res & 1) * 4 + (rnd & 3);
    const int ti = (res >> 1) * 4 + (rnd >> 2) * 2 + rank;
    const int a2p = res & 1, a2j = rnd & 3;
    const int a2s = ti * 2 + a2p;
    const bool g1_on = rnd != 7;
    const int g1j = (rnd < 6 ? rnd : res) & 1, g1f = rnd < 6 ? res * 3 + (rnd >> 1) : 24 + (res >> 1);
    const int g2j = rnd & 1, g2s = res * 4 + (rnd >> 1);
    uint32_t pbar0;
    asm volatile("mapa.shared::cluster.u32 %0, %1, %2;" : "=r"(pbar0) : "r"(bar0), "r"(rank ^ 1));
    auto pair_arrive = [&](int i) { __syncwarp(); const bool l = elect_one(); mbar_arrive_if(BAR(i), l); mbar_arrive_remote_if(pbar0 + 8u * i, l); };
    const int wcol = hg * 56 - (hg & 1) * 8;

    if (tid == 32) { TRG(60); TRW(59); }
    if (warp == 8) {
        if (elect_one()) {
            #pragma unroll
            for (int i = 0; i < B_WQF; i++) mbar_init(BAR(i), 1);
            asm volatile("fence.mbarrier_init.release.cluster;" ::: "memory");
            fence_async_smem();
            TRW(56);
            #pragma unroll 1
            for (int kb = 0; kb < 7; kb++) {
                mbar_expect(BAR(B_XF + kb), 16384);
                tma2d(sb + SM_X + kb * 8192, &mX, kb * 64, ti * 64, BAR(B_XF + kb));
                tma2d(sb + SM_X + 57344 + kb * 8192, &mX, kD + kb * 64, ti * 64, BAR(B_XF + kb));
                if (TMPF == 2 && kb == 0) asm volatile("prefetch.tensormap [%0];" :: "l"(&mWqkv) : "memory");
            }
        }
    } else if (warp > 8) {
        if (elect_one()) {
            if (warp == 9) {
                if (TMPF == 1) asm volatile("prefetch.tensormap [%0];" :: "l"(&mWqkv) : "memory");
                #pragma unroll
                for (int i = B_WQF; i < B_AF; i++) mbar_init(BAR(i), i < B_XC ? 1 : i < B_A1D ? 16 : i < B_BE ? 8 : 4);
            } else if (warp == 10) {
                #pragma unroll
                for (int i = B_AF; i < B_BL; i++) mbar_init(BAR(i), 1);
            } else {
                #pragma unroll
                for (int i = B_BL; i < B_COUNT; i++) mbar_init(BAR(i), i == B_HD ? 8 : 1);
            }
            asm volatile("fence.mbarrier_init.release.cluster;" ::: "memory");
            fence_async_smem();
        }
    } else {
        const char* p = tid < 112 ? (const char*)prm.x + (size_t)(ti * 8 + hg) * 14336 + tid * 128
                                  : (const char*)prm.wqkv + b * 2688 + 896 + (tid - 112) * 128;
        if (tid < PF0) asm volatile("prefetch.global.L2 [%0];" :: "l"(p));
    }
    __syncwarp();
    __syncthreads();
    asm volatile("barrier.cluster.arrive.relaxed.aligned;" ::: "memory");
    if (tid < 256) TR(0);
    if (tid == 0) TRG(61);

    if (warp >= 8) {
        asm volatile("setmaxnreg.dec.sync.aligned.u32 40;");
        asm volatile("barrier.cluster.wait.aligned;" ::: "memory");
        auto fetch_halo = [&](int p, uint32_t tag) {
            uint4 u[4];
            #pragma unroll
            for (int c = 0; c < 4; c++) u[c] = make_uint4(0u, 0u, 0u, 0u);
            const uint4* hp = opaque_ptr(&g_halo[(((ti - 1) * 8 + hg) * 2 + p) * 128 + lane]);
            mbar_wait(BAR(B_KVC), 0);
            if (p == 0) TRW(51);
            sleep_until(clk32() + HDELAY);
            if (ti > 0) {
                int it = 0;
                do {
                    #pragma unroll
                    for (int c = 0; c < 4; c++) u[c] = ld_rlx4(hp + c * 32);
                    if (it) RETRY_COUNT(4);
                    if (++it > kSpinLimit) { TIMEOUT(101); break; }
                } while (__any_sync(~0u, ((u[0].x ^ tag) | (u[1].x ^ tag) | (u[2].x ^ tag) | (u[3].x ^ tag)) & ~lane & 1));
            }
            #pragma unroll
            for (int c = 0; c < 4; c++) sts4(sb + SM_STG + p * 8192 + 3 * 2048 + lane * 16 + c * 512, u[c].x, u[c].y, u[c].z, u[c].w);
            warp_arrive(BAR(B_HL + p));
        };
        if (warp & 1) {
            uint32_t tag;
            if (warp == 11) {
                tag = *(volatile uint32_t*)&g_epoch + 1;
            #pragma unroll 1
            for (int i = 0; i < 8; i++) g_halo[(ti * 8 + hg) * 256 + i * 32 + lane] = make_uint4(~tag, 0u, 0u, 0u);
            ((uint4*)g_stats)[(a2s * 4 + a2j) * 64 + lane] = ((uint4*)g_stats)[(a2s * 4 + a2j) * 64 + 32 + lane] = make_uint4(~tag, ~tag, ~tag, ~tag);
            g_flag_h[(a2s * 4 + a2j) * FS + lane] = 0;
            g_flag_o[(ti * 16 + hg) * FS + lane] = g_flag_o[(ti * 16 + 8 + hg) * FS + lane] = 0;
            __syncwarp();
            if (lane == 0) {
                asm volatile("st.shared.v2.u32 [%0], {%1, %2};" :: "r"(sb + SM_EPOCH), "r"(tag), "r"(gtime32()) : "memory");
                mbar_arrive(BAR(B_EP));
            }
            if (lane < 4) mbar_expect(BAR(B_RF + lane), 7168);
            __syncwarp();
            TRW(44);
            } else {
                mbar_wait(BAR(B_EP), 0);
                tag = lds1(sb + SM_EPOCH);
            }
            fetch_halo((warp >> 1) & 1, tag);
        }
        if (warp < 10) {
          auto load_slab = [&](int s, bool second) {
              mbar_expect(BAR(B_AF + s), 8192);
              if (!second) tma2d(sb + s * 8192, &mW1, (s & 1) * kF + g1f * 64, (rank * 8 + (s >> 1)) * 64, BAR(B_AF + s));
              else         tma2d(sb + s * 8192, &mW2, g2s * 64, (rank * 14 + s - 2) * 64, BAR(B_AF + s));
          };
          if (warp == 8) {
            if (elect_one()) {
                #pragma unroll 1
                for (int s = 0; s < 7; s++) {
                    mbar_expect(BAR(B_WKVF + s), 16384);
                    tma2d_mc(sb + SM_WKV + s * 16384 + rank * 8192, &mWqkv, (1 + rank) * kD + wcol, s * 64, BAR(B_WKVF + s));
                }
            }
            __syncwarp();
            mbar_wait(BAR(B_XC), 0);
            if (elect_one()) {
                asm volatile("prefetch.tensormap [%0];" :: "l"(&mWo) : "memory");
                asm volatile("prefetch.tensormap [%0];" :: "l"(&mW1) : "memory");
                asm volatile("prefetch.tensormap [%0];" :: "l"(&mW2) : "memory");
                mbar_expect(BAR(B_WQF), 57344);
                #pragma unroll 1
                for (int s = rank; s < 7; s += 2) tma2d_mc(sb + SM_WQ + s * 8192, &mWqkv, wcol, s * 64, BAR(B_WQF));
                mbar_expect(BAR(B_XRF), 16384);
                tma2d(sb + SM_XR, &mX, a2p * kD + a2j * 112, ti * 64, BAR(B_XRF));
                tma2d(sb + SM_XR + 8192, &mX, a2p * kD + a2j * 112 + 48, ti * 64, BAR(B_XRF));
            }
            __syncwarp();
            #pragma unroll 1
            for (int h = 0; h < 2; h++) {
                mbar_wait(BAR(B_KV3 + h), 0);
                if (h) mbar_wait2(BAR(B_HL), 0, BAR(B_HL + 1), 0);
                if (elect_one()) {
                    mbar_expect(BAR(B_WOF + h), 57344);
                    tma2d_mc(sb + SM_WKV + h * 57344 + rank * 28672, &mWo, a2j * 112 + rank * 48, h * 224, BAR(B_WOF + h));
                    if (g1_on && h == AFIRST) { load_slab(0, false); load_slab(1, false); load_slab(2, false); }
                }
                __syncwarp();
            }
            if (g1_on) {
                mbar_wait2(BAR(B_XD), 0, BAR(B_BL + NB + 3), 0);
                #pragma unroll 1
                for (int i = 3; i < NPRE; i++) {
                    if (i == 7) mbar_wait(BAR(B_OC), 0);
                    if (elect_one()) load_slab(i, false);
                    __syncwarp();
                }
            } else {
                mbar_wait(BAR(B_HD), 0);
                mbar_arrive_remote_if(pbar0 + 8u * B_PD, lane == 0);
                mbar_wait(BAR(B_GO), 0);
                uint32_t tg = lds1(sb + SM_TG + 4);
                tg += max((int)(lds1(sb + SM_TG2) - tg), 0);
                int it = 0;
                while ((int)(gtime32() - tg) < 0 && ++it < 256) {}
                const uint32_t t0 = clk32();
                if (lane < 2) {
                    asm volatile("st.shared.u32 [%0], %1;" :: "r"(sb + SM_TG + 8 + lane * 4), "r"(t0 + (lane ? CN3 : CN2)) : "memory");
                    mbar_arrive(BAR(B_GD + lane));
                }
                __syncwarp();
                #pragma unroll 1
                for (int s = 2; s < 16; s++) {
                    sleep_until(t0 + W2OFF + s * W2PACE);
                    if (elect_one()) load_slab(s, true);
                    __syncwarp();
                }
            }
          } else {
            TRW(58);
            const uint32_t tag = lds1(sb + SM_EPOCH);
            if (lane < 4) mbar_expect(BAR(B_BL + NB + lane), 14336);
            #pragma unroll 1
            for (int e = 0; e < 2; e++) {
                const uint32_t* fp = e ? &g_flag_h[(rank * 64 + lane) * FS] : &g_flag_o[(a2s * 8 + (lane & 7)) * FS];
                if (e) {
                    mbar_wait2(BAR(B_BF + NB + 2), 0, BAR(B_BF + NB + 3), 0);
                    if (lane == 0) st_flag(&g_flag_h[(a2s * 4 + a2j) * FS], tag);
                    __syncwarp();
                    TRW(57);
                    sleep_until(clk32() + PDELAY);
                }
                uint64_t v0 = 0, v1 = e ? 0 : tag;
                int it = 0;
                do {
                    ld_flag_if(v0, fp, (uint32_t)v0 != tag); ld_flag_if(v1, fp + 32 * FS, (uint32_t)v1 != tag);
                    if (++it > kSpinLimit) { TIMEOUT(108); break; }
                } while (__any_sync(~0u, (uint32_t)v0 != tag || (uint32_t)v1 != tag));
                const uint32_t gbase = __shfl_sync(~0u, (uint32_t)(v0 >> 32), 0);
                const uint32_t tg = gbase + (e ? DELTA : DELTAO)
                                  + __reduce_max_sync(~0u, max((int)((uint32_t)(v0 >> 32) - gbase) - e * (lane >> 2) * SOFF, e ? (int)((uint32_t)(v1 >> 32) - gbase) - 8 * SOFF : 0));
                TRW(e ? 40 : 53);
                mbar_wait(BAR(B_A1D), 0);
                if (elect_one()) {
                    if (e) {
                        asm volatile("st.async.shared::cluster.mbarrier::complete_tx::bytes.b32 [%0], %1, [%2];"
                                     :: "r"(pbar0 + (SM_TG2 - SM_BAR)), "r"(tg), "r"(pbar0 + 8u * B_GO) : "memory");
                        asm volatile("st.shared.u32 [%0], %1;" :: "r"(sb + SM_TG + 4), "r"(tg) : "memory");
                        mbar_expect(BAR(B_GO), 4);
                    } else {
                        it = 0;
                        while ((int)(gtime32() - tg) < 0 && ++it < 256) {}
                        #pragma unroll
                        for (int i = 0; i < 4; i++) bulk_g2s(sb + SM_WQ + i * 14336, &g_o[(a2s * 4 + i) * 896], 14336, BAR(B_BL + NB + i));
                    }
                }
                __syncwarp();
            }
          }
          if (elect_one()) {
              const int h = ~warp & 1;
              const char* src1 = (const char*)&g_hn[(rank * 16 + h) * 3584 + g1j * 896];
              const char* src2 = (const char*)&g_g[(rank * 14 + h) * 3584 + g2j * 896];
              const long long jump = src2 - src1 - (16 * 57344 + 2 * 14336);
              const char* src = g1_on ? src1 - 2 * 57344 : src2;
              const uint32_t amask = g1_on ? (h ? kAMask1 : kAMask0) : 0u;
              uint32_t slot = g1_on ? NB - 2 + h : h, ph = g1_on ? 0 : 1, gate = g1_on ? 0 : 2, tmin = 0;
              CAP_DECL(ti_, 0);
              #pragma unroll 1
              for (int q = g1_on ? 0 : 17; q < 31; q++) {
                  const uint32_t eb = q ? BAR(B_BE) + slot * 8 : BAR(B_XF), dst = sb + SM_B + slot * 14336;
                  if ((0x1020003u >> q) & 1) {
                      mbar_wait(BAR(B_HD + gate), 0);
                      tmin = lds1(sb + SM_TG + gate * 4);
                      if (gate < 2) {
                          tmin += max((int)(lds1(gate ? sb + SM_TG2 : sb + SM_TG) - tmin), 0);
                          int it = 0;
                          while ((int)(gtime32() - tmin) < 0 && ++it < 256) {}
                          tmin = clk32();
                      }
                      tmin += h * PACE1;
                      gate++;
                  }
                  spin_until(tmin);
                  tmin += PACE2;
                  if (!mbar_try(eb, ph)) mbar_wait(eb, ph);
                  if (q) {
                      bulk_g2s(dst, src, 14336, eb + (B_BL - B_BE) * 8);
                      mbar_expect(eb + (B_BL - B_BE) * 8, 14336);
                      CAP(ti_);
                  }
                  mbar_arrive_remote_if(pbar0 + 8u * B_PD, h && q == 12);
                  if ((amask >> q) & 1) {
                      if (q < 12) load_slab(NPRE - W1Q + q, false);
                      else load_slab(2 + ((2 * q + h - 27) * 13 + 19) / 20, true);
                  }
                  src += 2 * 57344 + (q == 8 ? 2 * 14336 - 16 * 57344 : q == 16 ? jump : q == 23 ? 2 * 14336 - 14 * 57344 : 0);
                  slot += 2;
                  if (slot >= NB) { slot -= NB; ph ^= 1; }
              }
          }
        } else {
          if (warp == 10) {
            mbar_wait(BAR(PFBAR), 0);
            const char* p1 = (const char*)prm.w1 + (size_t)b * 57344 + lane * 128;
            const char* p2 = (const char*)prm.w2 + (size_t)b * 57344 + lane * 128;
            if (lane < 27) asm volatile("prefetch.global.L2 [%0];" :: "l"(lane < 25 ? (const char*)prm.wo + min(b * 25 + lane, 3135) * 128
                                                                          : lane == 25 ? (const char*)prm.b1 + (b % 28) * 128 : (const char*)prm.b2 + (b & 31) * 128));
            uint32_t tnext = (uint32_t)clock();
            #pragma unroll 1
            for (int i = 0; i < 28; i++) {
                asm volatile("prefetch.global.L2 [%0];" :: "l"(i < 14 ? p1 + i * 4096 : p2 + (i - 14) * 4096));
                tnext += PFPACE;
                while ((int)((uint32_t)clock() - tnext) < 0) __nanosleep(40);
            }
            mbar_wait(BAR(B_EP), 0);
          }
          const uint32_t tag = lds1(sb + SM_EPOCH);
          const int h = warp & 1;
          const bool lead = elect_one();
          const uint32_t w0o = lane * 132, l3 = lane < 16 ? 12288 : 0;
          uint32_t wo = w0o ^ (h << 6), slot = NB + h, dst = sb + SM_WQ + h * 14336, ph = 0, rph = 0, af = BAR(B_WOF), aph = 0;
          #pragma unroll 1
          for (int q = -1; q < 31; q++) {
              const uint32_t rb = bar0 + slot * 8;
              auto stale = [&]() {
                  uint32_t d;
                  asm volatile("{ .reg .b32 x, y, z, u;\n"
                               "ld.shared.u32 x, [%1]; ld.shared.u32 y, [%1 + 4096]; ld.shared.u32 z, [%1 + 8192]; ld.shared.u32 u, [%2];\n"
                               "lop3.b32 x, x, y, %3, 0x7e; lop3.b32 z, z, u, %3, 0x7e; lop3.b32 %0, x, z, 1, 0xa8; }"
                               : "=r"(d) : "r"(dst + wo), "r"(dst + wo + l3), "r"(tag) : "memory");
                  return __any_sync(~0u, d);
              };
              mbar_wait(rb + B_BF * 8, ph ^ 1);
              mbar_wait(rb + B_BL * 8, ph);
              const bool aok = mbar_test(af, aph);
              bool bad = stale();
              if (!aok) mbar_wait(af, aph);
              mbar_arrive_if(rb + B_BF * 8, lead && !bad);
              if (bad) {
                  RETRY_COUNT(q < 1 ? 1 : q < 17 ? 0 : !g1_on ? 5 : q < 24 ? 2 : 6);
                  const int e = (q > 8) + (q > 16) + (q > 23), s = (q - (e < 3 ? 1 + 8 * e : 24)) * 2 + h;
                  const char* src = (const char*)(q < 1 ? &g_o[(a2s * 4 + s + 4) * 896] : e < 2 ? &g_hn[(rank * 16 + s) * 3584 + (g1j + 2 * e) * 896] : &g_g[(rank * 14 + s) * 3584 + (g2j + 2 * e - 4) * 896]);
                  int it = 0;
                  do {
                      if (++it > kSpinLimit) { TIMEOUT(111); break; }
                      const uint32_t* p = (const uint32_t*)(src + wo);
                      if (it > RELOAD1 && __any_sync(~0u, ((ld_rlx(p) ^ tag) | (ld_rlx(p + 1024) ^ tag) | (ld_rlx(p + 2048) ^ tag) | (ld_rlx(p + l3 / 4) ^ tag)) & 1)) continue;
                      if (lead) {
                          mbar_expect(BAR(B_RT + h), 14336);
                          bulk_g2s(dst, src, 14336, BAR(B_RT + h));
                      }
                      __syncwarp();
                      mbar_wait(BAR(B_RT + h), rph);
                      rph ^= 1;
                      bad = stale();
                  } while (bad);
                  mbar_arrive_if(rb + B_BF * 8, lead);
              }
              af += q < 0 ? 8 : q == 8 ? -112 : (0x810000u >> q) & 1 ? -96 : 16;
              slot += 2; dst += 28672;
              if (q > 0 && slot >= NB) { slot -= NB; dst -= NB * 14336; ph ^= 1; }
              if (q == 16) { wo = w0o ^ (g2j << 6); aph = 1; }
              if (q == 0) {
                  slot = h; dst = sb + SM_B + h * 14336; af = BAR(B_AF + h + (g1_on ? 0 : 2));
                  wo = w0o ^ ((g1_on ? g1j : g2j) << 6); q = g1_on ? 0 : 16;
              }
          }
        }
    } else {
        asm volatile("setmaxnreg.inc.sync.aligned.u32 232;");
        asm volatile("barrier.cluster.wait.aligned;" ::: "memory");
        const int wg = warp >> 2, w = warp & 3;
        const int g = lane >> 2, t = lane & 3;
        uint32_t tag;
        __nv_bfloat16 bias1;
        {
            const uint64_t dw = make_desc(sb + (hg & 1) * 16, 0, true);
            uint32_t a[28][4];
            float sm0[4] = {0.f, 0.f, 0.f, 0.f}, sm1[4] = {0.f, 0.f, 0.f, 0.f};
            {
                const int r = w * 16 + (lane & 15);
                const uint32_t rowa = sb + SM_X + wg * 57344 + r * 128;
                #pragma unroll
                for (int kb = 0; kb < 7; kb++) {
                    mbar_wait(BAR(B_XF + kb), 0);
                    #pragma unroll
                    for (int q = 0; q < 4; q++) {
                        const uint32_t addr = rowa + kb * 8192 + (((q * 2 + (lane >> 4)) ^ (r & 7)) << 4);
                        uint32_t (&f)[4] = a[kb * 4 + q];
                        asm volatile("ldmatrix.sync.aligned.m8n8.x4.shared.b16 {%0,%1,%2,%3}, [%4];"
                                     : "=r"(f[0]), "=r"(f[1]), "=r"(f[2]), "=r"(f[3]) : "r"(addr) : "memory");
                        if (q & 1) mma16816(sm1, f[0], f[1], f[2], f[3], 0x3F803F80u, 0x3F803F80u);
                        else       mma16816(sm0, f[0], f[1], f[2], f[3], 0x3F803F80u, 0x3F803F80u);
                    }
                }
            }
            const float mean0 = (sm0[0] + sm1[0]) * (1.f / kD), mean1 = (sm0[2] + sm1[2]) * (1.f / kD);
            const uint32_t mb0 = pack_bf16(mean0, mean0), mb1 = pack_bf16(mean1, mean1);
            pair_arrive(B_XC);
            TR(1);
            float ak[28], av[28], aq[28];
            float ss0 = 0.f, ss1 = 0.f, ss2 = 0.f, ss3 = 0.f;
            uint32_t p0, p1;
            static_for<0, 7>([&](auto S_) {
                constexpr int s = decltype(S_)::value;
                #pragma unroll
                for (int q = 0; q < 4; q++) {
                    uint32_t (&f)[4] = a[s * 4 + q];
                    f[0] = sub_bf16x2(f[0], mb0); f[1] = sub_bf16x2(f[1], mb1);
                    f[2] = sub_bf16x2(f[2], mb0); f[3] = sub_bf16x2(f[3], mb1);
                }
                mbar_wait(BAR(B_WKVF + s), 0);
                wg_fence();
                static_for<0, 4>([&](auto Q_) {
                    constexpr int q = decltype(Q_)::value;
                    uint32_t (&f)[4] = a[s * 4 + q];
                    wgmma_rs_n56<SM_WKV + s * 16384 + q * 2048, (s | q) != 0>(ak, f[0], f[1], f[2], f[3], dw);
                    wgmma_rs_n56<SM_WKV + s * 16384 + q * 2048 + 8192, (s | q) != 0>(av, f[0], f[1], f[2], f[3], dw);
                });
                wg_commit();
                if (s == 4) { wg_wait<1>(); pair_arrive(B_KV3); }
                #pragma unroll
                for (int q = 0; q < 8; q++) {
                    const uint32_t u0 = a[s * 4 + q / 2][(q & 1) * 2], u1 = a[s * 4 + q / 2][(q & 1) * 2 + 1];
                    if (q == 0 && (VCH == 1 || (s & 1) || s == 0)) { p0 = sqr_bf16x2(u0); p1 = sqr_bf16x2(u1); }
                    else { p0 = sqa_bf16x2(u0, p0); p1 = sqa_bf16x2(u1, p1); }
                }
                if (VCH == 1 || !(s & 1)) { ss0 += bf_lo(p0); ss2 += bf_hi(p0); ss1 += bf_lo(p1); ss3 += bf_hi(p1); }
            });
            auto q_chunk = [&](auto K0_, auto K1_) {
                wg_fence();
                static_for<decltype(K0_)::value, decltype(K1_)::value>([&](auto K_) {
                    constexpr int k = decltype(K_)::value;
                    wgmma_rs_n56<SM_WQ + k * 2048, k != 0>(aq, a[k][0], a[k][1], a[k][2], a[k][3], dw);
                });
                wg_commit();
            };
            #define QCHUNK(k0, k1) q_chunk(std::integral_constant<int, k0>{}, std::integral_constant<int, k1>{})
            const float dl0 = mean0 - bf_lo(mb0), dl1 = mean1 - bf_lo(mb1);
            const float rs0 = rsq(fmaxf(quad_sum(ss0 + ss2) * (1.f / kD) - dl0 * dl0, 0.f) + kEps);
            const float rs1 = rsq(fmaxf(quad_sum(ss1 + ss3) * (1.f / kD) - dl1 * dl1, 0.f) + kEps);
            float rk[3][2];
            rk[1][0] = __shfl_sync(~0u, rs0, t * 8); rk[1][1] = __shfl_sync(~0u, rs0, t * 8 + 4);
            rk[2][0] = __shfl_sync(~0u, rs1, t * 8); rk[2][1] = __shfl_sync(~0u, rs1, t * 8 + 4);
            const uint32_t stg = sb + SM_STG + wg * 8192 + lane * 16;
            uint4* hp = (w == 3 ? &g_halo[((ti * 8 + hg) * 2 + wg) * 128] : (uint4*)(smem_raw + SM_STG + wg * 8192 + w * 2048)) + lane;
            mbar_wait2(BAR(B_EP), 0, BAR(B_WQF), 0);
            tag = lds1(sb + SM_EPOCH);
            QCHUNK(0, QC0);
            wg_wait<1>();
            reg_fence(ak); reg_fence(av);
            TR(2);
            uint32_t kf[3][7], vf[3][7];
            #pragma unroll
            for (int c = 0; c < 7; c++) {
                kf[2][c] = pack_bf16(ak[4 * c + 2], ak[4 * c + 3]);
                vf[2][c] = movm(pack_bf16(av[4 * c + 2], av[4 * c + 3]));
            }
            const uint32_t om = ~lane & 1;
            kf[2][0] = set_par(kf[2][0], om, tag); kf[2][4] = set_par(kf[2][4], om, tag);
            vf[2][1] = set_par(vf[2][1], om, tag); vf[2][5] = set_par(vf[2][5], om, tag);
            st_gen4(hp,      kf[2][0], kf[2][1], kf[2][2], kf[2][3]);
            st_gen4(hp + 32, kf[2][4], kf[2][5], kf[2][6], vf[2][0]);
            st_gen4(hp + 64, vf[2][1], vf[2][2], vf[2][3], vf[2][4]);
            st_gen4(hp + 96, vf[2][5], vf[2][6], __float_as_uint(rk[2][0]), __float_as_uint(rk[2][1]));
            pair_arrive(B_KVC);
            QCHUNK(QC0, QC1);
            #pragma unroll
            for (int c = 0; c < 7; c++) {
                kf[1][c] = pack_bf16(ak[4 * c], ak[4 * c + 1]);
                vf[1][c] = movm(pack_bf16(av[4 * c], av[4 * c + 1]));
            }
            QCHUNK(QC1, QC2);
            named_bar(1 + wg, 128);
            uint32_t* op = opaque_ptr((uint32_t*)&g_o[((ti * 2 + wg) * 56 + hg * 7) * 64] + w * 64 + lane);
            const uint32_t omk = opaque(((lane & 6) == w * 2 ? 0x11u << (lane & 1) * 8 : 0u) << (((lane >> 3) - hg * 7) & 3));
            uint32_t* ofl = opaque_ptr(&g_flag_o[((ti * 2 + wg) * 8 + hg) * FS]);
            QCHUNK(QC2, 28);
            #undef QCHUNK
            const bool gt0 = 2 * t > g, gt1 = 2 * t + 1 > g, no_prev = ti == 0 && w == 0;
            const float kf0 = gt0 ? rk[1][0] : rk[2][0], kf1 = gt1 ? rk[1][1] : rk[2][1];
            constexpr float kScale = 0.18898223650461362f * 1.4426950408889634f;
            const float sq0 = rs0 * kScale, sf0 = kf0 * (rs1 * kScale), sf1 = kf1 * (rs1 * kScale);
            const float NEG = -__int_as_float(0x7f800000);
            const float nb0 = gt0 && no_prev ? NEG : 0.f, nb1 = gt1 && no_prev ? NEG : 0.f;
            const uint32_t sr = stg + ((w + 3) & 3) * 2048, hbar = BAR(w == 0 ? B_HL + wg : B_EP);
            mbar_wait(BAR(B_EP), 0);
            wg_wait<0>();
            reg_fence(aq);
            warp_arrive(BAR(B_A1D));
            TR(3);
            uint32_t qf[8][2];
            #pragma unroll
            for (int c = 0; c < 7; c++) {
                qf[c + (c > 3)][0] = pack_bf16(aq[4 * c], aq[4 * c + 1]);
                qf[c + (c > 3)][1] = pack_bf16(aq[4 * c + 2], aq[4 * c + 3]);
            }
            qf[4][0] = t >= 2 ? qf[3][0] : 0u; qf[4][1] = t >= 2 ? qf[3][1] : 0u;
            qf[3][0] = t < 2 ? qf[3][0] : 0u;  qf[3][1] = t < 2 ? qf[3][1] : 0u;
            float sc[2][3][4];
            auto scores = [&](int n) {
                #pragma unroll
                for (int hd = 0; hd < 2; hd++) {
                    sc[hd][n][0] = sc[hd][n][1] = sc[hd][n][2] = sc[hd][n][3] = 0.f;
                    mma16816(sc[hd][n], qf[4 * hd][0], qf[4 * hd][1], qf[4 * hd + 1][0], qf[4 * hd + 1][1], kf[n][3 * hd], kf[n][3 * hd + 1]);
                    mma16816(sc[hd][n], qf[4 * hd + 2][0], qf[4 * hd + 2][1], qf[4 * hd + 3][0], qf[4 * hd + 3][1], kf[n][3 * hd + 2], kf[n][3 * hd + 3]);
                }
            };
            scores(1); scores(2);
            mbar_wait(hbar, 0);
            {
                const uint4 u0 = lds4(sr), u1 = lds4(sr + 512), u3 = lds4(sr + 1536), u2 = lds4(sr + 1024);
                kf[0][0] = u0.x; kf[0][1] = u0.y; kf[0][2] = u0.z; kf[0][3] = u0.w;
                kf[0][4] = u1.x; kf[0][5] = u1.y; kf[0][6] = u1.z; vf[0][0] = u1.w;
                vf[0][1] = u2.x; vf[0][2] = u2.y; vf[0][3] = u2.z; vf[0][4] = u2.w;
                vf[0][5] = u3.x; vf[0][6] = u3.y; rk[0][0] = __uint_as_float(u3.z); rk[0][1] = __uint_as_float(u3.w);
            }
            if ((tid & 127) == 0) st_flag(ofl, tag);
            TR(4);
            scores(0);
            const float ke0 = gt0 ? rk[0][0] : rk[1][0], ke1 = gt1 ? rk[0][1] : rk[1][1];
            const float se0 = ke0 * sq0, se1 = ke1 * sq0;
            uint32_t ow[7][2];
            #pragma unroll
            for (int hd = 0; hd < 2; hd++) {
                const int c0 = hd * 3;
                float (&sc_)[3][4] = sc[hd];
                const float e0 = fmaf(gt0 ? sc_[0][0] : sc_[1][0], se0, nb0), e1 = fmaf(gt1 ? sc_[0][1] : sc_[1][1], se1, nb1);
                const float f0 = (gt0 ? sc_[1][2] : sc_[2][2]) * sf0, f1 = (gt1 ? sc_[1][3] : sc_[2][3]) * sf1;
                const float me = quad_max(fmaxf(e0, e1)), mf = quad_max(fmaxf(f0, f1));
                const float p0 = ex2(e0 - me), p1 = ex2(e1 - me), r0 = ex2(f0 - mf), r1 = ex2(f1 - mf);
                const float ie = rcp(quad_sum(p0 + p1)), jf = rcp(quad_sum(r0 + r1));
                const uint32_t pp = pack_bf16(p0 * ke0 * ie, p1 * ke1 * ie), rp = pack_bf16(r0 * kf0 * jf, r1 * kf1 * jf);
                const uint32_t mk = (gt0 ? 0x0000ffffu : 0u) | (gt1 ? 0xffff0000u : 0u);
                #pragma unroll
                for (int c = 0; c < 4; c++) {
                    float o[4] = {0.f, 0.f, 0.f, 0.f};
                    mma16816(o, pp & mk, 0u, pp & ~mk, rp & mk, vf[0][c0 + c], vf[1][c0 + c]);
                    mma1688(o, 0u, rp & ~mk, vf[2][c0 + c]);
                    const uint32_t lo = pack_bf16(o[0], o[1]), hi = pack_bf16(o[2], o[3]);
                    if (hd == 1 && c == 0) { if (t >= 2) { ow[3][0] = lo; ow[3][1] = hi; } }
                    else { ow[c0 + c][0] = lo; ow[c0 + c][1] = hi; }
                }
            }
            #pragma unroll
            for (int c = 0; c < 7; c++) {
                stg1(op + c * 256,      set_par(ow[c][0], (omk >> (c & 3)) & 1, tag));
                stg1(op + c * 256 + 32, set_par(ow[c][1], (omk >> (8 + (c & 3))) & 1, tag));
            }
            TR(5);
        }
        {
            const int cg = a2j * 2 + wg;
            float acc2[28];
            mbar_wait(BAR(B_XRF), 0);
            {
                const uint32_t xa = sb + SM_XR + wg * 8192 + (w * 16 + (lane & 15)) * 128;
                #pragma unroll
                for (int c = 0; c < 4; c++) {
                    uint32_t xr[4];
                    asm volatile("ldmatrix.sync.aligned.m8n8.x4.shared.b16 {%0,%1,%2,%3}, [%4];"
                                 : "=r"(xr[0]), "=r"(xr[1]), "=r"(xr[2]), "=r"(xr[3])
                                 : "r"(xa + ((((c * 2 + wg + (lane >> 4)) ^ lane) & 7) << 4)) : "memory");
                    #pragma unroll
                    for (int e = 0; e < (c < 3 ? 4 : 2); e++) { acc2[8 * c + 2 * e] = bf_lo(xr[e]); acc2[8 * c + 2 * e + 1] = bf_hi(xr[e]); }
                }
            }
            uint32_t* spw = opaque_ptr(&g_stats[((a2s * 8 + cg) * 4 + w) * 32 + lane]);
            const uint32_t* spr = opaque_ptr(&g_stats[(a2s * 32 + w) * 32 + lane]);
            uint4* hp = opaque_ptr(&g_h[((a2s * 8 + w * 2) * 8 + cg) * 64 + lane]);
            uint32_t* np = opaque_ptr((uint32_t*)&g_hn[(a2s * 56 + cg * 7) * 64] + w * 64 + lane);
            const uint64_t dwo = make_desc(sb + SM_WKV + wg * (28672 + 16), 0, true);
            const uint64_t doa = make_desc(sb + SM_WQ, 1024, false, 128);
            bias1 = prm.b1[g1f * 64 + w * 16 + rank * 8 + g];
            const __nv_bfloat16 bias2a = prm.b2[ti * 128 + (w * 16 + g) * 2 + a2p], bias2b = prm.b2[ti * 128 + (w * 16 + 8 + g) * 2 + a2p];
            reg_fence(acc2);
            fence_async_smem();
            warp_arrive(BAR(B_XD));
            static_for<0, 4>([&](auto P_) {
                constexpr int P = decltype(P_)::value;
                mbar_wait(BAR(B_BF + NB + P), 0);
                if (P == 0) TR(6);
                wg_fence();
                static_for<0, 7>([&](auto K_) { constexpr int k = decltype(K_)::value;
                    wgmma_ss_n56<P * 14336 + k * 2048, (P >> 1) * 57344 + (P & 1) * 14336 + k * 2048>(acc2, doa, dwo); });
                if (P) wg_commit();
                if (P == 2) { wg_wait<1>(); warp_arrive(BAR(B_OC)); }
            });
            wg_wait<0>();
            reg_fence(acc2);
            TR(7);
            float s0 = 0.f, s1 = 0.f, q0 = 0.f, q1 = 0.f;
            #pragma unroll
            for (int c = 0; c < 7; c++) {
                s0 += acc2[4 * c] + acc2[4 * c + 1];     q0 = fmaf(acc2[4 * c], acc2[4 * c], fmaf(acc2[4 * c + 1], acc2[4 * c + 1], q0));
                s1 += acc2[4 * c + 2] + acc2[4 * c + 3]; q1 = fmaf(acc2[4 * c + 2], acc2[4 * c + 2], fmaf(acc2[4 * c + 3], acc2[4 * c + 3], q1));
            }
            const bool th = t >= 2, to = t & 1;
            const float sa = (th ? s1 : s0) + __shfl_xor_sync(~0u, th ? s0 : s1, 2), qa = (th ? q1 : q0) + __shfl_xor_sync(~0u, th ? q0 : q1, 2);
            const float part = (to ? qa : sa) + __shfl_xor_sync(~0u, to ? sa : qa, 1);
            stg1(spw, set_par(__float_as_uint(part), 1u, tag));
            const uint32_t tpoll = clk32() + SDELAY;
            TR(8);
            warp_arrive(BAR(B_HD));
            uint32_t hw[2][7], nm[2][4], us[8];
            #pragma unroll
            for (int r = 0; r < 2; r++) {
                const float b2v = __bfloat162float(r ? bias2b : bias2a);
                #pragma unroll
                for (int c = 0; c < 7; c++) hw[r][c] = pack_bf16(acc2[4 * c + 2 * r] + b2v, acc2[4 * c + 2 * r + 1] + b2v);
                hw[r][0] = set_par(hw[r][0], ~lane & 1, tag);
            }
            auto store_h = [&]() {
                #pragma unroll
                for (int r = 0; r < 2; r++) {
                    stg4(hp + r * 512, hw[r][0], hw[r][1], hw[r][2], hw[r][3]);
                    stg4(hp + r * 512 + 32, tag, hw[r][4], hw[r][5], hw[r][6]);
                }
            };
            if (HPOS == 0) store_h();
            spin_until(tpoll);
            #pragma unroll
            for (int i = 0; i < 8; i++) us[i] = ld_rlx(spr + i * 128);
            if (HPOS == 1) store_h();
            #pragma unroll
            for (int i = 0; i < 8; i++) nm[i >> 2][i & 3] = lane == ((cg * 7 + i) & 3) * 8 + w * 2 + (i >> 2);
            {
                int it = 0;
                while (true) {
                    uint32_t bad = 0;
                    #pragma unroll
                    for (int i = 0; i < 8; i++) bad |= us[i] ^ tag;
                    if (!__any_sync(~0u, bad & 1)) break;
                    RETRY_COUNT(3);
                    if (++it > kSpinLimit) { TIMEOUT(103); break; }
                    #pragma unroll
                    for (int i = 0; i < 8; i++) us[i] = ld_rlx(spr + i * 128);
                }
            }
            TR(9);
            const float tot = (((__uint_as_float(us[0]) + __uint_as_float(us[1])) + (__uint_as_float(us[2]) + __uint_as_float(us[3])))
                            + ((__uint_as_float(us[4]) + __uint_as_float(us[5])) + (__uint_as_float(us[6]) + __uint_as_float(us[7])))) * (1.f / kD);
            const float oth = __shfl_xor_sync(~0u, tot, 1);
            const float mean = to ? oth : tot;
            const float var = fmaxf(fmaf(-mean, mean, to ? tot : oth), 0.f);
            const float r1 = rsq(var + kEps);
            const float rra = 0.5f * r1 * rsq(fmaf(var * r1, r1, kEps)), mra = -mean * rra;
            const float rrb = __shfl_xor_sync(~0u, rra, 2), mrb = __shfl_xor_sync(~0u, mra, 2);
            const float rr0 = th ? rrb : rra, mr0 = th ? mrb : mra, rr1 = th ? rra : rrb, mr1 = th ? mra : mrb;
            #pragma unroll
            for (int c = 0; c < 7; c++) {
                stg1(np + c * 256,      set_par(pack_bf16(fmaf(acc2[4 * c], rr0, mr0), fmaf(acc2[4 * c + 1], rr0, mr0)), nm[0][c & 3], tag));
                stg1(np + c * 256 + 32, set_par(pack_bf16(fmaf(acc2[4 * c + 2], rr1, mr1), fmaf(acc2[4 * c + 3], rr1, mr1)), nm[1][c & 3], tag));
            }
            TR(10);
            if (HPOS == 2) store_h();
        }
        float acc[56];
        const uint32_t xch = opaque(sb + SM_XCH + w * 1920 + lane * 16);
        uint32_t peer_xch; const uint32_t peer_bar = pbar0;
        asm volatile("mapa.shared::cluster.u32 %0, %1, %2;" : "=r"(peer_xch) : "r"(xch), "r"(rank ^ 1));
        uint4 hr[4];
        const int tok = g2s * 64 + w * 16 + rank * 8 + g, pr = (tok & 127) >> 1;
        const uint4* hp = &g_h[((((tok >> 7) * 2 + (tok & 1)) * 8 + (pr >> 3)) * 8 + (g2j + 2 * wg) * 2) * 64 + (pr & 7) * 4 + t];
        auto load_h = [&]() {
            #pragma unroll
            for (int c = 0; c < 4; c++) hr[c] = ld_rlx4(hp + c * 32);
        };
        const uint32_t b1h = pack_bf16(0.5f * __bfloat162float(bias1), 0.5f * __bfloat162float(bias1));
        #pragma unroll
        for (int c = 0; c < 4; c++) hr[c] = make_uint4(b1h, b1h, b1h, b1h);
        if (!g1_on) { mbar_wait(BAR(B_GD), 0); load_h(); }
        uint32_t* const gp1 = (uint32_t*)&g_g[(g1f * 56 + (g1j + 2 * wg) * 14) * 64] + (w * 2 + rank) * 32 + lane;
        uint32_t* const gp2 = (uint32_t*)(prm.out + (size_t)(g2s * 64 + w * 16 + rank * 8 + (lane >> 4)) * kD + (g2j + 2 * wg) * 112) + (lane & 15) * 4;
        uint32_t gm[4];
        #pragma unroll
        for (int i = 0; i < 4; i++) gm[i] = lane == ((g1j * 2 + i) & 3) * 8 + w * 2 + rank;
        const bool lead = elect_one();
        const uint64_t da0 = make_desc(sb, 0, true), db0 = make_desc(sb + SM_B, 128, false);
        #pragma unroll 1
        for (int ge = g1_on ? 0 : 1; ge < 2; ge++) {
            if (ge) {
                int it = 0;
                while (true) {
                    uint32_t bad = 0;
                    #pragma unroll
                    for (int c = 0; c < 4; c++) bad |= hr[c].x ^ tag;
                    if (!__any_sync(~0u, bad & ~lane & 1)) break;
                    if (++it > kSpinLimit) { TIMEOUT(110); break; }
                    load_h();
                }
            }
            auto init_acc = [&](auto R_) {
                constexpr int o = decltype(R_)::value * 2;
                #pragma unroll
                for (int c = 0; c < 14; c++) {
                    const int i = c / 7 * 8 + c % 7 + (c % 7 >= 4);
                    const uint32_t hw = (i & 3) == 0 ? hr[i >> 2].x : (i & 3) == 1 ? hr[i >> 2].y : (i & 3) == 2 ? hr[i >> 2].z : hr[i >> 2].w;
                    acc[4 * c + o] = bf_lo(hw); acc[4 * c + 1 + o] = bf_hi(hw);
                    acc[4 * c + 2 - o] = 0.f;   acc[4 * c + 3 - o] = 0.f;
                }
                reg_fence(acc);
            };
            if (rank) init_acc(std::integral_constant<int, 1>{}); else init_acc(std::integral_constant<int, 0>{});
            const uint32_t slot0 = g1_on ? (ge ? 4 : 2 * wg) : 0;
            uint32_t ph = 0, rb = bar0 + slot0 * 8;
            uint64_t da = da0 + ge * 1024, db = db0 + slot0 * 896;
            uint32_t prev = BAR(B_WKVF);
            mbar_wait(BAR(B_EP), 0);
            if (wg == 1 || (ge && g1_on)) named_bar(5 - wg, 256);
            mbar_wait(rb + B_BF * 8, ph);
            TR(11 + ge * 4);
            #pragma unroll 1
            for (int n = ge ? 14 : 16;;) {
                wg_fence();
                wgmma_ss_n112<0,    0>(acc, da, db);
                wgmma_ss_n112<2048, 256>(acc, da, db);
                wgmma_ss_n112<4096, 512>(acc, da, db);
                wgmma_ss_n112<6144, 768>(acc, da, db);
                wg_commit();
                if (--n == 0 && ge + wg < 2) named_arrive(4 + wg, 256);
                const uint32_t cur = rb + B_BE * 8;
                da += 512; db += 896; rb += 8;
                if (rb == bar0 + NB * 8) { rb = bar0; db = db0; ph ^= 1; }
                wg_wait<1>();
                mbar_arrive_if(prev, lead);
                prev = cur;
                if (n == 0) break;
                if (!mbar_try(rb + B_BF * 8, ph)) mbar_wait(rb + B_BF * 8, ph);
            }
            const int use = ge * 2 + wg;
            const uint32_t xfree = BAR(use > (g1_on ? 0 : 2) ? B_RE + use - 1 : B_PD);
            const bool xok = mbar_test(xfree, 0);
            wg_wait<0>();
            reg_fence(acc);
            mbar_arrive_if(prev, lead);
            TR(12 + ge * 4);
            if (!xok) mbar_wait(xfree, 0);
            float v[28];
            auto reduce = [&](auto R_) {
                constexpr int o = decltype(R_)::value * 2;
                const uint32_t rf = peer_bar + (B_RF + use) * 8;
                float dly = __uint_as_float(0x3f800000u | lane); uint32_t pa = peer_xch;
                #pragma unroll
                for (int c = 0; c < 4; c++) {
                    const uint32_t p0 = pack_bf16(acc[16 * c + 2 - o], acc[16 * c + 3 - o]), p1 = pack_bf16(acc[16 * c + 6 - o], acc[16 * c + 7 - o]);
                    if (c < 3) {
                        const uint32_t p2 = pack_bf16(acc[16 * c + 10 - o], acc[16 * c + 11 - o]), p3 = pack_bf16(acc[16 * c + 14 - o], acc[16 * c + 15 - o]);
                        asm volatile("st.async.shared::cluster.mbarrier::complete_tx::bytes.v4.b32 [%0], {%1,%2,%3,%4}, [%5];"
                                     :: "r"(pa + c * 512), "r"(p0), "r"(p1), "r"(p2), "r"(p3), "r"(rf) : "memory");
                        if (use != 3) {
                            #pragma unroll
                            for (int i = 0; i < XPACE; i++) asm volatile("tanh.approx.f32 %0, %0;" : "+f"(dly) :: "memory");
                            pa += __float_as_uint(dly) >> 30;
                        }
                    } else {
                        asm volatile("st.async.shared::cluster.mbarrier::complete_tx::bytes.v2.b32 [%0], {%1,%2}, [%3];"
                                     :: "r"(pa + 1536 - lane * 8), "r"(p0), "r"(p1), "r"(rf) : "memory");
                    }
                }
                if (!ge) load_h();
                mbar_wait(BAR(B_RF + use), 0);
                #pragma unroll
                for (int c = 0; c < 4; c++) {
                    uint4 u;
                    if (c < 3) u = lds4(xch + c * 512); else { const uint2 u2 = lds2(xch + 1536 - lane * 8); u.x = u2.x; u.y = u2.y; }
                    v[8 * c]     = acc[16 * c + o] + bf_lo(u.x);     v[8 * c + 1] = acc[16 * c + 1 + o] + bf_hi(u.x);
                    v[8 * c + 2] = acc[16 * c + 4 + o] + bf_lo(u.y); v[8 * c + 3] = acc[16 * c + 5 + o] + bf_hi(u.y);
                    if (c < 3) {
                        v[8 * c + 4] = acc[16 * c + 8 + o] + bf_lo(u.z);  v[8 * c + 5] = acc[16 * c + 9 + o] + bf_hi(u.z);
                        v[8 * c + 6] = acc[16 * c + 12 + o] + bf_lo(u.w); v[8 * c + 7] = acc[16 * c + 13 + o] + bf_hi(u.w);
                    }
                }
            };
            if (rank) reduce(std::integral_constant<int, 1>{}); else reduce(std::integral_constant<int, 0>{});
            TR(13 + ge * 4);
            if (!ge) {
                #pragma unroll
                for (int c = 0; c < 14; c++) {
                    float r[2];
                    #pragma unroll
                    for (int e = 0; e < 2; e++) {
                        const float u = v[2 * c + e];
                        r[e] = fmaf(u, tanh_hw(u * fmaf(u * u, 8.f * 0.7978845608f * 0.044715f, 2.f * 0.7978845608f)), u);
                    }
                    stg1(gp1 + c * 256, set_par(pack_bf16(r[0], r[1]), gm[c & 3], tag));
                }
                named_bar(1 + wg, 128);
                if (w == 0 && lane == 0) {
                    asm volatile("st.shared.u32 [%0], %1;" :: "r"(sb + SM_TG + 8 + wg * 4), "r"(clk32() + (wg ? XSPECB : XSPEC)) : "memory");
                    mbar_arrive(BAR(B_GD + wg));
                }
                mbar_arrive_remote_if(peer_bar + (B_RE + use) * 8, lead);
            } else {
                const uint32_t stw = xch - lane * 16;
                uint32_t pk[14];
                #pragma unroll
                for (int c = 0; c < 14; c++) pk[c] = pack_bf16(v[2 * c], v[2 * c + 1]);
                __syncwarp();
                const uint32_t sa = stw + (lane & 7) * 240 + (lane >> 3) * 16;
                #pragma unroll
                for (int m = 0; m < 3; m++)
                    asm volatile("stmatrix.sync.aligned.m8n8.x4.shared.b16 [%0], {%1,%2,%3,%4};"
                                 :: "r"(sa + m * 64), "r"(pk[4 * m]), "r"(pk[4 * m + 1]), "r"(pk[4 * m + 2]), "r"(pk[4 * m + 3]) : "memory");
                asm volatile("stmatrix.sync.aligned.m8n8.x2.shared.b16 [%0], {%1,%2};" :: "r"(sa + 192), "r"(pk[12]), "r"(pk[13]) : "memory");
                __syncwarp();
                #pragma unroll
                for (int i = 0; i < 4; i++) {
                    const int r = 2 * i + (lane >> 4), ch = lane & 15;
                    if (ch < 14) { const uint4 u = lds4(stw + r * 240 + ch * 16); stg4(gp2 + i * 448, u.x, u.y, u.z, u.w); }
                }
                __syncwarp();
                mbar_arrive_remote_if(peer_bar + (B_RE + 2) * 8, lead && wg == 0);
            }
            TR(14 + ge * 4);
        }
        if (tid == 128) TRG(62);
        if (b == 0 && tid == 128) g_epoch = tag;
    }
}

typedef CUresult (*EncodeFn)(CUtensorMap*, CUtensorMapDataType, cuuint32_t, void*, const cuuint64_t*, const cuuint64_t*,
                             const cuuint32_t*, const cuuint32_t*, CUtensorMapInterleave, CUtensorMapSwizzle,
                             CUtensorMapL2promotion, CUtensorMapFloatOOBfill);

void make_map(EncodeFn enc, CUtensorMap* m, const void* base, uint64_t cols, uint64_t rows, uint32_t box_rows) {
    cuuint64_t dims[2] = {cols, rows};
    cuuint64_t strides[1] = {cols * 2};
    cuuint32_t box[2] = {64, box_rows};
    cuuint32_t es[2] = {1, 1};
    enc(m, CU_TENSOR_MAP_DATA_TYPE_BFLOAT16, 2, const_cast<void*>(base), dims, strides, box, es, CU_TENSOR_MAP_INTERLEAVE_NONE,
        CU_TENSOR_MAP_SWIZZLE_128B, CU_TENSOR_MAP_L2_PROMOTION_L2_128B, CU_TENSOR_MAP_FLOAT_OOB_FILL_NONE);
}

}

extern "C" void kernel_launch(void* const* d_in, const int* in_sizes, int n_in, void* d_out, int out_size) {
    (void)in_sizes; (void)n_in; (void)out_size;
    void* fn = nullptr;
    cudaDriverEntryPointQueryResult qr;
    cudaGetDriverEntryPoint("cuTensorMapEncodeTiled", &fn, cudaEnableDefault, &qr);
    EncodeFn enc = (EncodeFn)fn;
    CUtensorMap mX, mWqkv, mWo, mW1, mW2;
    make_map(enc, &mX, d_in[0], 2 * kD, kS / 2, 64);
    make_map(enc, &mWqkv, d_in[1], 3 * kD, kD, 64);
    make_map(enc, &mWo, d_in[2], kD, kD, 224);
    make_map(enc, &mW1, d_in[4], 2 * kF, kS / 2, 64);
    make_map(enc, &mW2, d_in[6], kS, kF, 64);
    Params prm;
    prm.x = (const __nv_bfloat16*)d_in[0];
    prm.wqkv = (const __nv_bfloat16*)d_in[1];
    prm.wo = (const __nv_bfloat16*)d_in[2];
    prm.w1 = (const __nv_bfloat16*)d_in[4];
    prm.b1 = (const __nv_bfloat16*)d_in[5];
    prm.w2 = (const __nv_bfloat16*)d_in[6];
    prm.b2 = (const __nv_bfloat16*)d_in[7];
    prm.out = (__nv_bfloat16*)d_out;
    cudaFuncSetAttribute(fused_kernel, cudaFuncAttributeMaxDynamicSharedMemorySize, SM_TOTAL);
    fused_kernel<<<128, 384, SM_TOTAL, cudaStreamPerThread>>>(mX, mWqkv, mWo, mW1, mW2, prm);
}
```

```cpp
#include <cuda_runtime.h>
#include <cuda.h>
#include <cuda_bf16.h>
#include <stdint.h>
#include <type_traits>

namespace {

constexpr int kS = 2048, kD = 448, kF = 1792;
constexpr float kEps = 1e-5f;

#define FS 32
struct Scratch {
    uint4    o[32 * 56 * 64];
    uint4    h[32 * 8 * 8 * 64];
    uint4    hn[32 * 56 * 64];
    uint4    g[28 * 56 * 64];
    uint4    halo[16 * 8 * 2 * 4 * 32];
    uint32_t stats[32 * 8 * 4 * 32];
    uint32_t flag_o[32 * 8 * FS];
    uint32_t flag_h[32 * 4 * FS];
    uint32_t epoch;
};
__device__ __align__(1024) Scratch g_scratch;
#define TIMEOUT(code)
#define RETRY_COUNT(i)
#define CAP_DECL(n, k)
#define CAP(n)
#define CAP_SKIP(n)
#define TR2(idx)
#define TR(idx)
#define TRW(idx)
#define TRG(idx)

constexpr uint32_t SM_WKV  = 114688;
constexpr uint32_t SM_XR   = 24576;
constexpr uint32_t SM_STG  = 40960;
constexpr uint32_t SM_WQ   = 57344;
constexpr uint32_t SM_XCH  = 0;
constexpr uint32_t SM_B    = 131072;
constexpr uint32_t SM_BAR  = 231424;
constexpr uint32_t SM_TOTAL = SM_BAR + 1024;
constexpr int NB = 7;
#define SH1 0
#define SH2 0
#define SH2N 5
#define SH3 0
#define NSPEC 4
#define XSPEC 850
#define C2 0
#define C3 0
#define CN2 8000
#define CN3 12000
constexpr int B_XF = 0, B_WKVF = 7, B_WQF = 14, B_XRF = 15, B_WOF = 16,
              B_XC = 18, B_KV3 = 19, B_KVC = 20,
              B_A1D = 21, B_XD = 22, B_OC = 23,
              B_BE = 24, B_RE = B_BE + NB,
              B_AF = B_RE + 3, B_BL = B_AF + 16  , B_BF = B_BL + NB + 4  ,
              B_RF = B_BF + NB + 4, B_EP = B_RF + 4, B_PD = B_EP + 1, B_RT = B_PD + 1, B_HL = B_RT + 2,
              B_HD = B_HL + 2  , B_GO = B_HD + 1, B_GD = B_GO + 1, B_COUNT = B_GD + 2;
#define WEARLY 6
#define PF0 126
#define TMPF 2
#define RSTE 2
#define POLLP 1
#define PROBEP 1
#define LOADP 1
#define LOADW 64
#define NOB 0
#define AEARLY 5
#define W1PACE 400
#define W2PACE 200
#define PFPACE 230
#define PFBAR (B_XF + 6)
#define DELTA 1696
#define DELTA2 DELTA
#define BPACE 230
#define BURST 2
#define W1OFF 350
#define W2OFF 2900
#define XPACE 0
#define PSTAG 200
constexpr uint32_t SM_EPOCH = SM_BAR + B_COUNT * 8, SM_TG = SM_EPOCH + 4  , SM_TG2 = SM_TG + 16  , SM_TR = SM_BAR + 768;

#define HDELAY 0
#define QC0 4
#define QC1 10
#define QC2 16
#define HPOS 1
#define XSPECB 700
#define PACE1 120
#define PACE2 400
#define RELOAD1 1
#define VCH 1
#define SOFF 0
#define XW 2
#define XLAG 0
#define PFX 3
#define SDELAY 400
#define PDELAY 500
#define NPRE 10
#define PREPACE 0
#define AFIRST 0
#define DELTAO 928
#define W1Q 3
constexpr uint32_t w2_rounds(int h) { uint32_t m = 0; for (int i = 0; i < 14; i++) { const int p = 25 + i * 20 / 13; if ((p & 1) == h) m |= 1u << (p / 2 + 1); } return m; }
constexpr uint32_t kAMask0 = w2_rounds(0), kAMask1 = w2_rounds(1) | ((1u << (16 - NPRE)) - 1) << W1Q;

constexpr int kSpinLimit = 1 << 15;
__device__ __forceinline__ bool elect_one() {
    uint32_t p;
    asm volatile("{ .reg .pred P; elect.sync _|P, 0xffffffff; selp.u32 %0, 1, 0, P; }" : "=r"(p));
    return p;
}
__device__ __forceinline__ void mbar_init(uint32_t bar, uint32_t cnt) { asm volatile("mbarrier.init.shared::cta.b64 [%0], %1;" :: "r"(bar), "r"(cnt)); }
__device__ __forceinline__ void mbar_expect(uint32_t bar, uint32_t bytes) { asm volatile("mbarrier.arrive.expect_tx.shared::cta.b64 _, [%0], %1;" :: "r"(bar), "r"(bytes) : "memory"); }
__device__ __forceinline__ void mbar_arrive(uint32_t bar) { asm volatile("mbarrier.arrive.shared::cta.b64 _, [%0];" :: "r"(bar) : "memory"); }
__device__ __forceinline__ void mbar_wait(uint32_t bar, uint32_t parity) {
    uint32_t ok; int it = 0;
    do {
        asm volatile("{ .reg .pred p; mbarrier.try_wait.parity.shared::cta.b64 p, [%1], %2; selp.u32 %0, 1, 0, p; }"
                     : "=r"(ok) : "r"(bar), "r"(parity) : "memory");
        if (++it > kSpinLimit) { TIMEOUT((bar & 1023) >> 3); break; }
    } while (!ok);
}
__device__ __forceinline__ bool mbar_try(uint32_t bar, uint32_t parity) {
    uint32_t ok;
    asm volatile("{ .reg .pred p; mbarrier.try_wait.parity.shared::cta.b64 p, [%1], %2; selp.u32 %0, 1, 0, p; }" : "=r"(ok) : "r"(bar), "r"(parity) : "memory");
    return ok;
}
__device__ __forceinline__ bool mbar_test(uint32_t bar, uint32_t parity) {
    uint32_t ok;
    asm volatile("{ .reg .pred p; mbarrier.test_wait.parity.shared::cta.b64 p, [%1], %2; selp.u32 %0, 1, 0, p; }" : "=r"(ok) : "r"(bar), "r"(parity) : "memory");
    return ok;
}
__device__ __forceinline__ void mbar_wait_fast(uint32_t bar, uint32_t parity) { if (!mbar_try(bar, parity)) mbar_wait(bar, parity); }
__device__ __forceinline__ void mbar_wait2(uint32_t bar0, uint32_t par0, uint32_t bar1, uint32_t par1) {
    uint32_t ok; int it = 0;
    do {
        asm volatile("{ .reg .pred p, q; mbarrier.try_wait.parity.shared::cta.b64 p, [%1], %2;\n"
                     "mbarrier.try_wait.parity.shared::cta.b64 q, [%3], %4; and.pred p, p, q; selp.u32 %0, 1, 0, p; }"
                     : "=r"(ok) : "r"(bar0), "r"(par0), "r"(bar1), "r"(par1) : "memory");
        if (++it > kSpinLimit) { TIMEOUT((bar0 & 1023) >> 3); break; }
    } while (!ok);
}
template <int N> __device__ __forceinline__ void reg_fence(float (&d)[N]) {
    #pragma unroll
    for (int i = 0; i < N; i++) asm volatile("" : "+f"(d[i]) :: "memory");
}
__device__ __forceinline__ void mbar_wait_cluster(uint32_t bar, uint32_t parity) {
    uint32_t ok; int it = 0;
    do {
        asm volatile("{ .reg .pred p; mbarrier.try_wait.parity.acquire.cluster.shared::cta.b64 p, [%1], %2; selp.u32 %0, 1, 0, p; }"
                     : "=r"(ok) : "r"(bar), "r"(parity) : "memory");
        if (++it > kSpinLimit) { TIMEOUT((bar & 1023) >> 3); break; }
    } while (!ok);
}
__device__ __forceinline__ void mbar_arrive_if(uint32_t bar, bool pred) {
    asm volatile("{ .reg .pred p; setp.ne.u32 p, %1, 0; @p mbarrier.arrive.shared::cta.b64 _, [%0]; }" :: "r"(bar), "r"((uint32_t)pred) : "memory");
}
template <int P> __device__ __forceinline__ void tick() {
    if (P > 1) { const uint32_t t = ((uint32_t)clock() | (P - 1)) + 1; while ((int)((uint32_t)clock() - t) < 0) {} }
}
__device__ __forceinline__ void warp_arrive(uint32_t bar) { __syncwarp(); if (elect_one()) mbar_arrive(bar); }
__device__ __forceinline__ void tma2d(uint32_t dst, const CUtensorMap* m, int c0, int c1, uint32_t bar) {
    asm volatile("cp.async.bulk.tensor.2d.shared::cluster.global.mbarrier::complete_tx::bytes [%0], [%1, {%3, %4}], [%2];"
                 :: "r"(dst), "l"(m), "r"(bar), "r"(c0), "r"(c1) : "memory");
}
__device__ __forceinline__ void tma3d(uint32_t dst, const CUtensorMap* m, int c0, int c1, int c2, uint32_t bar) {
    asm volatile("cp.async.bulk.tensor.3d.shared::cluster.global.mbarrier::complete_tx::bytes [%0], [%1, {%3, %4, %5}], [%2];"
                 :: "r"(dst), "l"(m), "r"(bar), "r"(c0), "r"(c1), "r"(c2) : "memory");
}
__device__ __forceinline__ void tma2d_mc(uint32_t dst, const CUtensorMap* m, int c0, int c1, uint32_t bar) {
    asm volatile("cp.async.bulk.tensor.2d.shared::cluster.global.mbarrier::complete_tx::bytes.multicast::cluster [%0], [%1, {%3, %4}], [%2], %5;"
                 :: "r"(dst), "l"(m), "r"(bar), "r"(c0), "r"(c1), "h"((uint16_t)3) : "memory");
}
__device__ __forceinline__ void bulk_g2s_mc(uint32_t dst, const void* src, uint32_t bytes, uint32_t bar) {
    asm volatile("cp.async.bulk.shared::cluster.global.mbarrier::complete_tx::bytes.multicast::cluster [%0], [%1], %2, [%3], %4;"
                 :: "r"(dst), "l"(src), "r"(bytes), "r"(bar), "h"((uint16_t)3) : "memory");
}
__device__ __forceinline__ void mbar_arrive_remote_if(uint32_t cluster_bar, bool pred) {
    asm volatile("{ .reg .pred p; setp.ne.u32 p, %1, 0; @p mbarrier.arrive.shared::cluster.b64 _, [%0]; }" :: "r"(cluster_bar), "r"((uint32_t)pred) : "memory");
}
__device__ __forceinline__ void bulk_g2s(uint32_t dst, const void* src, uint32_t bytes, uint32_t bar) {
    asm volatile("cp.async.bulk.shared::cluster.global.mbarrier::complete_tx::bytes [%0], [%1], %2, [%3];"
                 :: "r"(dst), "l"(src), "r"(bytes), "r"(bar) : "memory");
}
__device__ __forceinline__ void wg_fence()  { asm volatile("wgmma.fence.sync.aligned;" ::: "memory"); }
__device__ __forceinline__ void wg_commit() { asm volatile("wgmma.commit_group.sync.aligned;" ::: "memory"); }
template <int N> __device__ __forceinline__ void wg_wait() { asm volatile("wgmma.wait_group.sync.aligned %0;" :: "n"(N) : "memory"); }
__device__ __forceinline__ void named_bar(int id, int n) { asm volatile("bar.sync %0, %1;" :: "r"(id), "r"(n) : "memory"); }
__device__ __forceinline__ void named_arrive(int id, int n) { asm volatile("bar.arrive %0, %1;" :: "r"(id), "r"(n) : "memory"); }
__device__ __forceinline__ bool mbar_try2(uint32_t bar0, uint32_t par0, uint32_t bar1, uint32_t par1) {
    uint32_t ok;
    asm volatile("{ .reg .pred p, q; mbarrier.test_wait.parity.shared::cta.b64 p, [%1], %2;\n"
                 "mbarrier.test_wait.parity.shared::cta.b64 q, [%3], %4; and.pred p, p, q; selp.u32 %0, 1, 0, p; }"
                 : "=r"(ok) : "r"(bar0), "r"(par0), "r"(bar1), "r"(par1) : "memory");
    return ok;
}
__device__ __forceinline__ void fence_gpu() { asm volatile("fence.release.gpu;" ::: "memory"); }
__device__ __forceinline__ void fence_async_global() { asm volatile("fence.proxy.async.global;" ::: "memory"); }
__device__ __forceinline__ void fence_async_smem() { asm volatile("fence.proxy.async.shared::cta;" ::: "memory"); }
__device__ __forceinline__ uint32_t gtime32() { uint64_t t; asm volatile("mov.u64 %0, %%globaltimer;" : "=l"(t) :: "memory"); return (uint32_t)t; }
__device__ __forceinline__ uint32_t clk32() { uint64_t t; asm volatile("mov.u64 %0, %%clock64;" : "=l"(t) :: "memory"); return (uint32_t)t; }
__device__ __forceinline__ void spin_until(uint32_t t) { while ((int)(clk32() - t) < 0) {} }
#define SLEEPNS 20
__device__ __forceinline__ void sleep_until(uint32_t t) { while ((int)(clk32() - t) < 0) { if (SLEEPNS) __nanosleep(SLEEPNS); } }
__device__ __forceinline__ void st_flag(uint32_t* p, uint32_t v) {
    const uint64_t w = ((uint64_t)gtime32() << 32) | v;
    asm volatile("st.relaxed.gpu.global.u64 [%0], %1;" :: "l"(p), "l"(w) : "memory");
}
__device__ __forceinline__ void ld_flag_if(uint64_t& v, const uint32_t* p, bool pred) {
    asm volatile("{ .reg .pred p; setp.ne.u32 p, %2, 0; @p ld.relaxed.gpu.global.u64 %0, [%1]; }" : "+l"(v) : "l"(p), "r"((uint32_t)pred) : "memory");
}
__device__ __forceinline__ uint32_t ld_acq(const uint32_t* p) { uint32_t v; asm volatile("ld.acquire.gpu.global.u32 %0, [%1];" : "=r"(v) : "l"(p) : "memory"); return v; }
__device__ __forceinline__ uint32_t ld_rlx(const uint32_t* p) { uint32_t v; asm volatile("ld.relaxed.gpu.global.u32 %0, [%1];" : "=r"(v) : "l"(p) : "memory"); return v; }
template <class T> __device__ __forceinline__ T* opaque_ptr(T* p) { asm volatile("" : "+l"(p)); return p; }
__device__ __forceinline__ uint4 ld_rlx4(const uint4* p) {
    uint4 v; asm volatile("ld.relaxed.gpu.global.v4.u32 {%0,%1,%2,%3}, [%4];" : "=r"(v.x), "=r"(v.y), "=r"(v.z), "=r"(v.w) : "l"(p) : "memory"); return v;
}
__device__ __forceinline__ void st_ll(uint4* p, uint32_t a, uint32_t b, uint32_t tag) {
    uint64_t lo = ((uint64_t)tag << 32) | a, hi = ((uint64_t)tag << 32) | b;
    asm volatile("st.relaxed.gpu.global.v2.u64 [%0], {%1,%2};" :: "l"(p), "l"(lo), "l"(hi) : "memory");
}
__device__ __forceinline__ bool ld_ll(const uint4* p, uint32_t& a, uint32_t& b, uint32_t tag) {
    uint64_t lo, hi;
    asm volatile("ld.relaxed.gpu.global.v2.u64 {%0,%1}, [%2];" : "=l"(lo), "=l"(hi) : "l"(p) : "memory");
    a = (uint32_t)lo; b = (uint32_t)hi;
    return (uint32_t)(lo >> 32) == tag && (uint32_t)(hi >> 32) == tag;
}
__device__ __forceinline__ uint2 ld_acq2(const uint2* p) {
    uint2 v; asm volatile("ld.acquire.gpu.global.v2.u32 {%0,%1}, [%2];" : "=r"(v.x), "=r"(v.y) : "l"(p) : "memory"); return v;
}
__device__ __forceinline__ uint2 ld_rlx2(const uint2* p) {
    uint2 v; asm volatile("ld.relaxed.gpu.global.v2.u32 {%0,%1}, [%2];" : "=r"(v.x), "=r"(v.y) : "l"(p) : "memory"); return v;
}
__device__ __forceinline__ void stg1(uint32_t* p, uint32_t v) { asm volatile("st.global.u32 [%0], %1;" :: "l"(p), "r"(v) : "memory"); }
__device__ __forceinline__ void stg2(void* p, uint32_t x, uint32_t y) { asm volatile("st.global.v2.u32 [%0], {%1,%2};" :: "l"(p), "r"(x), "r"(y) : "memory"); }
__device__ __forceinline__ void stg4(void* p, uint32_t x, uint32_t y, uint32_t z, uint32_t w) { asm volatile("st.global.v4.u32 [%0], {%1,%2,%3,%4};" :: "l"(p), "r"(x), "r"(y), "r"(z), "r"(w) : "memory"); }
__device__ __forceinline__ uint32_t lds1(uint32_t a) { uint32_t v; asm volatile("ld.shared.u32 %0, [%1];" : "=r"(v) : "r"(a) : "memory"); return v; }
__device__ __forceinline__ uint2 lds2(uint32_t a) { uint2 v; asm volatile("ld.shared.v2.u32 {%0,%1}, [%2];" : "=r"(v.x), "=r"(v.y) : "r"(a) : "memory"); return v; }
__device__ __forceinline__ uint32_t set_par(uint32_t v, uint32_t mask, uint32_t par) {
    uint32_t r; asm("lop3.b32 %0, %1, %2, %3, 0xb8;" : "=r"(r) : "r"(v), "r"(mask), "r"(par)); return r;
}
__device__ __forceinline__ void st_gen4(void* p, uint32_t x, uint32_t y, uint32_t z, uint32_t w) { asm volatile("st.v4.u32 [%0], {%1,%2,%3,%4};" :: "l"(p), "r"(x), "r"(y), "r"(z), "r"(w) : "memory"); }
__device__ __forceinline__ float tanh_hw(float x) { float r; asm("tanh.approx.f32 %0, %1;" : "=f"(r) : "f"(x)); return r; }
__device__ __forceinline__ bool bar_any(int id, int n, bool v) {
    uint32_t r;
    asm volatile("{ .reg .pred p, q; setp.ne.u32 p, %3, 0; bar.red.or.pred q, %1, %2, p; selp.u32 %0, 1, 0, q; }" : "=r"(r) : "r"(id), "r"(n), "r"((uint32_t)v) : "memory");
    return r;
}
__device__ __forceinline__ void sts4(uint32_t a, uint32_t x, uint32_t y, uint32_t z, uint32_t w) { asm volatile("st.shared.v4.u32 [%0], {%1,%2,%3,%4};" :: "r"(a), "r"(x), "r"(y), "r"(z), "r"(w) : "memory"); }
__device__ __forceinline__ uint4 lds4(uint32_t a) { uint4 v; asm volatile("ld.shared.v4.u32 {%0,%1,%2,%3}, [%4];" : "=r"(v.x), "=r"(v.y), "=r"(v.z), "=r"(v.w) : "r"(a) : "memory"); return v; }
__device__ __forceinline__ uint32_t pack_bf16(float lo, float hi) { uint32_t r; asm("cvt.rn.bf16x2.f32 %0, %1, %2;" : "=r"(r) : "f"(hi), "f"(lo)); return r; }
__device__ __forceinline__ float bf_lo(uint32_t v) { return __uint_as_float(v << 16); }
__device__ __forceinline__ float bf_hi(uint32_t v) { return __uint_as_float(v & 0xffff0000u); }
__device__ __forceinline__ uint32_t sub_bf16x2(uint32_t a, uint32_t b) { uint32_t r; asm volatile("sub.rn.bf16x2 %0, %1, %2;" : "=r"(r) : "r"(a), "r"(b)); return r; }
__device__ __forceinline__ uint32_t add_bf16x2(uint32_t a, uint32_t b) { uint32_t r; asm volatile("add.rn.bf16x2 %0, %1, %2;" : "=r"(r) : "r"(a), "r"(b)); return r; }
__device__ __forceinline__ uint32_t sqr_bf16x2(uint32_t a) { uint32_t r; asm volatile("mul.rn.bf16x2 %0, %1, %1;" : "=r"(r) : "r"(a)); return r; }
__device__ __forceinline__ uint32_t sqa_bf16x2(uint32_t a, uint32_t c) { uint32_t r; asm volatile("fma.rn.bf16x2 %0, %1, %1, %2;" : "=r"(r) : "r"(a), "r"(c)); return r; }
__device__ __forceinline__ uint32_t movm(uint32_t a) { uint32_t r; asm volatile("movmatrix.sync.aligned.m8n8.trans.b16 %0, %1;" : "=r"(r) : "r"(a)); return r; }
__device__ __forceinline__ float ex2(float x) { float r; asm("ex2.approx.ftz.f32 %0, %1;" : "=f"(r) : "f"(x)); return r; }
__device__ __forceinline__ float rsq(float x) { float r; asm("rsqrt.approx.ftz.f32 %0, %1;" : "=f"(r) : "f"(x)); return r; }
__device__ __forceinline__ float rcp(float x) { float r; asm("rcp.approx.ftz.f32 %0, %1;" : "=f"(r) : "f"(x)); return r; }
__device__ __forceinline__ void mma16816(float (&c)[4], uint32_t a0, uint32_t a1, uint32_t a2, uint32_t a3, uint32_t b0, uint32_t b1) {
    asm("mma.sync.aligned.m16n8k16.row.col.f32.bf16.bf16.f32 {%0,%1,%2,%3}, {%4,%5,%6,%7}, {%8,%9}, {%0,%1,%2,%3};"
        : "+f"(c[0]), "+f"(c[1]), "+f"(c[2]), "+f"(c[3]) : "r"(a0), "r"(a1), "r"(a2), "r"(a3), "r"(b0), "r"(b1));
}
__device__ __forceinline__ void mma1688(float (&c)[4], uint32_t a0, uint32_t a1, uint32_t b0) {
    asm("mma.sync.aligned.m16n8k8.row.col.f32.bf16.bf16.f32 {%0,%1,%2,%3}, {%4,%5}, {%6}, {%0,%1,%2,%3};"
        : "+f"(c[0]), "+f"(c[1]), "+f"(c[2]), "+f"(c[3]) : "r"(a0), "r"(a1), "r"(b0));
}
__device__ __forceinline__ float quad_sum(float v) { v += __shfl_xor_sync(~0u, v, 1); v += __shfl_xor_sync(~0u, v, 2); return v; }
__device__ __forceinline__ float quad_max(float v) { v = fmaxf(v, __shfl_xor_sync(~0u, v, 1)); v = fmaxf(v, __shfl_xor_sync(~0u, v, 2)); return v; }
__device__ __forceinline__ uint64_t make_desc(uint32_t addr, uint32_t lbo, bool swz, uint32_t sbo = 1024) {
    const uint32_t lo = __shfl_sync(~0u, ((addr & 0x3FFFF) >> 4) | ((lbo >> 4) << 16), 0);
    const uint32_t hi = __shfl_sync(~0u, (swz ? 0x40000000u : 0u) + (sbo >> 4) + (threadIdx.x & 31), 0);
    return ((uint64_t)hi << 32) | lo;
}
template <int I, int N, class F> __device__ __forceinline__ void static_for(F&& f) {
    if constexpr (I < N) { f(std::integral_constant<int, I>{}); static_for<I + 1, N>(f); }
}
__device__ __forceinline__ uint32_t opaque(uint32_t v) { asm volatile("" : "+r"(v)); return v; }
template <int BOFF, int SCALE_D>
__device__ __forceinline__ void wgmma_rs_n56(float (&d)[28], uint32_t a0, uint32_t a1, uint32_t a2, uint32_t a3, uint64_t db) {
    asm volatile("{ .reg .b64 db; add.s64 db, %32, %33;\n"
        "wgmma.mma_async.sync.aligned.m64n56k16.f32.bf16.bf16 "
        "{%0, %1, %2, %3, %4, %5, %6, %7, %8, %9, %10, %11, %12, %13, %14, %15, %16, %17, %18, %19, %20, %21, %22, %23, %24, %25, %26, %27}, "
        "{%28, %29, %30, %31}, db, %34, 1, 1, 1; }"
        : "+f"(d[0]), "+f"(d[1]), "+f"(d[2]), "+f"(d[3]), "+f"(d[4]), "+f"(d[5]), "+f"(d[6]), "+f"(d[7]),
        "+f"(d[8]), "+f"(d[9]), "+f"(d[10]), "+f"(d[11]), "+f"(d[12]), "+f"(d[13]), "+f"(d[14]), "+f"(d[15]),
        "+f"(d[16]), "+f"(d[17]), "+f"(d[18]), "+f"(d[19]), "+f"(d[20]), "+f"(d[21]), "+f"(d[22]), "+f"(d[23]),
        "+f"(d[24]), "+f"(d[25]), "+f"(d[26]), "+f"(d[27])
        : "r"(a0), "r"(a1), "r"(a2), "r"(a3), "l"(db), "n"(BOFF >> 4), "n"(SCALE_D));
}
template <int AOFF, int BOFF>
__device__ __forceinline__ void wgmma_ss_n56(float (&d)[28], uint64_t da, uint64_t db) {
    asm volatile("{ .reg .b64 da, db; add.s64 da, %28, %30; add.s64 db, %29, %31;\n"
        "wgmma.mma_async.sync.aligned.m64n56k16.f32.bf16.bf16 "
        "{%0, %1, %2, %3, %4, %5, %6, %7, %8, %9, %10, %11, %12, %13, %14, %15, %16, %17, %18, %19, %20, %21, %22, %23, %24, %25, %26, %27}, "
        "da, db, 1, 1, 1, 0, 1; }"
        : "+f"(d[0]), "+f"(d[1]), "+f"(d[2]), "+f"(d[3]), "+f"(d[4]), "+f"(d[5]), "+f"(d[6]), "+f"(d[7]),
        "+f"(d[8]), "+f"(d[9]), "+f"(d[10]), "+f"(d[11]), "+f"(d[12]), "+f"(d[13]), "+f"(d[14]), "+f"(d[15]),
        "+f"(d[16]), "+f"(d[17]), "+f"(d[18]), "+f"(d[19]), "+f"(d[20]), "+f"(d[21]), "+f"(d[22]), "+f"(d[23]),
        "+f"(d[24]), "+f"(d[25]), "+f"(d[26]), "+f"(d[27])
        : "l"(da), "l"(db), "n"(AOFF >> 4), "n"(BOFF >> 4));
}
template <int AOFF, int BOFF>
__device__ __forceinline__ void wgmma_ss_n112(float (&d)[56], uint64_t da, uint64_t db) {
    asm volatile("{ .reg .b64 da, db; add.s64 da, %56, %58; add.s64 db, %57, %59;\n"
        "wgmma.mma_async.sync.aligned.m64n112k16.f32.bf16.bf16 "
        "{%0, %1, %2, %3, %4, %5, %6, %7, %8, %9, %10, %11, %12, %13, %14, %15, %16, %17, %18, %19, %20, %21, %22, %23, %24, %25, %26, %27, %28, %29, %30, %31, %32, %33, %34, %35, %36, %37, %38, %39, %40, %41, %42, %43, %44, %45, %46, %47, %48, %49, %50, %51, %52, %53, %54, %55}, "
        "da, db, 1, 1, 1, 1, 1; }"
        : "+f"(d[0]), "+f"(d[1]), "+f"(d[2]), "+f"(d[3]), "+f"(d[4]), "+f"(d[5]), "+f"(d[6]), "+f"(d[7]),
        "+f"(d[8]), "+f"(d[9]), "+f"(d[10]), "+f"(d[11]), "+f"(d[12]), "+f"(d[13]), "+f"(d[14]), "+f"(d[15]),
        "+f"(d[16]), "+f"(d[17]), "+f"(d[18]), "+f"(d[19]), "+f"(d[20]), "+f"(d[21]), "+f"(d[22]), "+f"(d[23]),
        "+f"(d[24]), "+f"(d[25]), "+f"(d[26]), "+f"(d[27]), "+f"(d[28]), "+f"(d[29]), "+f"(d[30]), "+f"(d[31]),
        "+f"(d[32]), "+f"(d[33]), "+f"(d[34]), "+f"(d[35]), "+f"(d[36]), "+f"(d[37]), "+f"(d[38]), "+f"(d[39]),
        "+f"(d[40]), "+f"(d[41]), "+f"(d[42]), "+f"(d[43]), "+f"(d[44]), "+f"(d[45]), "+f"(d[46]), "+f"(d[47]),
        "+f"(d[48]), "+f"(d[49]), "+f"(d[50]), "+f"(d[51]), "+f"(d[52]), "+f"(d[53]), "+f"(d[54]), "+f"(d[55])
        : "l"(da), "l"(db), "n"(AOFF >> 4), "n"(BOFF >> 4));
}

struct Params {
    const __nv_bfloat16 *x, *wqkv;
    Scratch* sc;
    const __nv_bfloat16 *wo, *w1, *w2, *b1, *b2;
    __nv_bfloat16* out;
};

__global__ void __cluster_dims__(2, 1, 1) __launch_bounds__(384, 1)
fused_kernel(const Params prm, const __grid_constant__ CUtensorMap mX2, const __grid_constant__ CUtensorMap mX, const __grid_constant__ CUtensorMap mWqkv,
             const __grid_constant__ CUtensorMap mWo, const __grid_constant__ CUtensorMap mW1,
             const __grid_constant__ CUtensorMap mW2)
{
    extern __shared__ __align__(1024) unsigned char smem_raw[];
    if (threadIdx.x < PF0) {
        const char* p = threadIdx.x < 112 ? (const char*)prm.x + blockIdx.x * 14336 + threadIdx.x * 128
                                          : (const char*)prm.wqkv + blockIdx.x * 2688 + threadIdx.x * 128 + (896 - 112 * 128);
        asm volatile("prefetch.global.L2 [%0];" :: "l"(p) : "memory");
    }
    if (threadIdx.x == 128) { asm volatile("prefetch.tensormap [%0];" :: "l"(&mX2) : "memory"); asm volatile("prefetch.tensormap [%0];" :: "l"(&mWqkv) : "memory"); }
    uint32_t sb = (uint32_t)__cvta_generic_to_shared(smem_raw);
    asm volatile("mov.u32 %0, %0;" : "+r"(sb));
    const uint32_t bar0 = sb + SM_BAR;
    auto BAR = [&](int i) { return bar0 + 8u * i; };

    const int tid = threadIdx.x, lane = tid & 31;
    const int warp = __shfl_sync(~0u, tid >> 5, 0);
    const int b = __shfl_sync(~0u, (int)blockIdx.x, 0);
    const int rank = b & 1;
    const int cl = (b >> 1) - 4, cq = ((cl - 32) * 37) >> 8;
    const int res = cl < 0 ? 0 : cl < 32 ? cl & 7 : cl - 31 - 7 * cq;
    const int rnd = cl < 0 ? cl + 8 : cl < 32 ? cl >> 3 : 4 + cq;
    const int hg = (res & 1) * 4 + (rnd & 3);
    const int ti = (res >> 1) * 4 + (rnd >> 2) * 2 + rank;
    const int a2p = res & 1, a2j = rnd & 3;
    const int a2s = ti * 2 + a2p;
    const bool g1_on = rnd != 7;
    const int g1j = (rnd < 6 ? rnd : res) & 1, g1f = rnd < 6 ? res * 3 + (rnd >> 1) : 24 + (res >> 1);
    const int g2j = rnd & 1, g2s = res * 4 + (rnd >> 1);
    uint32_t pbar0;
    asm volatile("mapa.shared::cluster.u32 %0, %1, %2;" : "=r"(pbar0) : "r"(bar0), "r"(rank ^ 1));
    auto pair_arrive = [&](int i) { __syncwarp(); const bool l = elect_one(); mbar_arrive_if(BAR(i), l); mbar_arrive_remote_if(pbar0 + 8u * i, l); };
    const int wcol = hg * 56 - (hg & 1) * 8;

    if (warp == 8) {
        if (elect_one()) {
            #pragma unroll
            for (int i = 0; i < B_WQF; i++) mbar_init(BAR(i), 1);
            asm volatile("fence.mbarrier_init.release.cluster;" ::: "memory");
            fence_async_smem();
            #pragma unroll
            for (int kb = 0; kb < 7; kb++) {
                tma3d(sb + kb * 16384, &mX2, kb * 64, ti * 64, 0, BAR(B_XF + kb));
                mbar_expect(BAR(B_XF + kb), 16384);
                if (kb == 0 && PFX != 3) asm volatile("prefetch.tensormap [%0];" :: "l"(&mWqkv) : "memory");
            }
        }
    } else if (warp > 8) {
        if (elect_one()) {
            if (warp == 9) {
                #pragma unroll
                for (int i = B_WQF; i < B_AF; i++) mbar_init(BAR(i), i < B_XC ? 1 : i < B_A1D ? 16 : i < B_BE ? 8 : 4);
            } else if (warp == 10) {
                #pragma unroll
                for (int i = B_AF; i < B_BL; i++) mbar_init(BAR(i), 1);
            } else {
                #pragma unroll
                for (int i = B_BL; i < B_COUNT; i++) mbar_init(BAR(i), i == B_HD ? 8 : 1);
            }
            asm volatile("fence.mbarrier_init.release.cluster;" ::: "memory");
            fence_async_smem();
        }
    }
    __syncwarp();
    __syncthreads();
    asm volatile("barrier.cluster.arrive.relaxed.aligned;" ::: "memory");
    if (tid < 256) TR(0);
    if (tid == 0) TRG(61);

    if (warp >= 8) {
        asm volatile("setmaxnreg.dec.sync.aligned.u32 40;");
        asm volatile("barrier.cluster.wait.aligned;" ::: "memory");
        auto fetch_halo = [&](int p, uint32_t tag) {
            uint4 u[4];
            #pragma unroll
            for (int c = 0; c < 4; c++) u[c] = make_uint4(0u, 0u, 0u, 0u);
            const uint4* hp = opaque_ptr(&prm.sc->halo[(((ti - 1) * 8 + hg) * 2 + p) * 128 + lane]);
            mbar_wait(BAR(B_KVC), 0);
            if (p == 0) TRW(51);
            sleep_until(clk32() + HDELAY);
            if (ti > 0) {
                int it = 0;
                do {
                    #pragma unroll
                    for (int c = 0; c < 4; c++) u[c] = ld_rlx4(hp + c * 32);
                    if (it) RETRY_COUNT(4);
                    if (++it > kSpinLimit) { TIMEOUT(101); break; }
                } while (__any_sync(~0u, ((u[0].x ^ tag) | (u[1].x ^ tag) | (u[2].x ^ tag) | (u[3].x ^ tag)) & ~lane & 1));
            }
            #pragma unroll
            for (int c = 0; c < 4; c++) sts4(sb + SM_STG + p * 8192 + 3 * 2048 + lane * 16 + c * 512, u[c].x, u[c].y, u[c].z, u[c].w);
            warp_arrive(BAR(B_HL + p));
        };
        if (warp & 1) {
            uint32_t tag;
            if (warp == 11) {
                tag = *(volatile uint32_t*)&prm.sc->epoch + 1;
            #pragma unroll 1
            for (int i = 0; i < 8; i++) prm.sc->halo[(ti * 8 + hg) * 256 + i * 32 + lane] = make_uint4(~tag, 0u, 0u, 0u);
            ((uint4*)prm.sc->stats)[(a2s * 4 + a2j) * 64 + lane] = ((uint4*)prm.sc->stats)[(a2s * 4 + a2j) * 64 + 32 + lane] = make_uint4(~tag, ~tag, ~tag, ~tag);
            prm.sc->flag_h[(a2s * 4 + a2j) * FS + lane] = 0;
            prm.sc->flag_o[(ti * 16 + hg) * FS + lane] = prm.sc->flag_o[(ti * 16 + 8 + hg) * FS + lane] = 0;
            __syncwarp();
            if (lane == 0) {
                asm volatile("st.shared.v2.u32 [%0], {%1, %2};" :: "r"(sb + SM_EPOCH), "r"(tag), "r"(gtime32()) : "memory");
                mbar_arrive(BAR(B_EP));
            }
            if (lane < 4) mbar_expect(BAR(B_RF + lane), 7168);
            __syncwarp();
            TRW(44);
            } else {
                mbar_wait(BAR(B_EP), 0);
                tag = lds1(sb + SM_EPOCH);
            }
            fetch_halo((warp >> 1) & 1, tag);
        }
        if (warp < 10) {
          auto load_slab = [&](int s, bool second) {
              mbar_expect(BAR(B_AF + s), 8192);
              if (!second) tma2d(sb + s * 8192, &mW1, (s & 1) * kF + g1f * 64, (rank * 8 + (s >> 1)) * 64, BAR(B_AF + s));
              else         tma2d(sb + s * 8192, &mW2, g2s * 64, (rank * 14 + s - 2) * 64, BAR(B_AF + s));
          };
          if (warp == 8) {
            if (elect_one()) {
                #pragma unroll 1
                for (int s = 0; s < 7; s++) {
                    mbar_expect(BAR(B_WKVF + s), 16384);
                    tma2d_mc(sb + SM_WKV + s * 16384 + rank * 8192, &mWqkv, (1 + rank) * kD + wcol, s * 64, BAR(B_WKVF + s));
                }
            }
            __syncwarp();
            mbar_wait(BAR(B_XC), 0);
            if (elect_one()) {
                asm volatile("prefetch.tensormap [%0];" :: "l"(&mX) : "memory");
                asm volatile("prefetch.tensormap [%0];" :: "l"(&mWo) : "memory");
                asm volatile("prefetch.tensormap [%0];" :: "l"(&mW1) : "memory");
                asm volatile("prefetch.tensormap [%0];" :: "l"(&mW2) : "memory");
                mbar_expect(BAR(B_WQF), 57344);
                #pragma unroll 1
                for (int s = rank; s < 7; s += 2) tma2d_mc(sb + SM_WQ + s * 8192, &mWqkv, wcol, s * 64, BAR(B_WQF));
                mbar_expect(BAR(B_XRF), 16384);
                tma2d(sb + SM_XR, &mX, a2p * kD + a2j * 112, ti * 64, BAR(B_XRF));
                tma2d(sb + SM_XR + 8192, &mX, a2p * kD + a2j * 112 + 48, ti * 64, BAR(B_XRF));
            }
            __syncwarp();
            #pragma unroll 1
            for (int h = 0; h < 2; h++) {
                mbar_wait(BAR(B_KV3 + h), 0);
                if (h) mbar_wait2(BAR(B_HL), 0, BAR(B_HL + 1), 0);
                if (elect_one()) {
                    mbar_expect(BAR(B_WOF + h), 57344);
                    tma2d_mc(sb + SM_WKV + h * 57344 + rank * 28672, &mWo, a2j * 112 + rank * 48, h * 224, BAR(B_WOF + h));
                    if (g1_on && h == AFIRST) { load_slab(0, false); load_slab(1, false); load_slab(2, false); }
                }
                __syncwarp();
            }
            if (g1_on) {
                mbar_wait2(BAR(B_XD), 0, BAR(B_BL + NB + 3), 0);
                #pragma unroll 1
                for (int i = 3; i < NPRE; i++) {
                    if (i == 7) mbar_wait(BAR(B_OC), 0);
                    if (elect_one()) load_slab(i, false);
                    __syncwarp();
                }
            } else {
                mbar_wait(BAR(B_HD), 0);
                mbar_arrive_remote_if(pbar0 + 8u * B_PD, lane == 0);
                mbar_wait(BAR(B_GO), 0);
                uint32_t tg = lds1(sb + SM_TG + 4);
                tg += max((int)(lds1(sb + SM_TG2) - tg), 0);
                int it = 0;
                while ((int)(gtime32() - tg) < 0 && ++it < 256) {}
                const uint32_t t0 = clk32();
                if (lane < 2) {
                    asm volatile("st.shared.u32 [%0], %1;" :: "r"(sb + SM_TG + 8 + lane * 4), "r"(t0 + (lane ? CN3 : CN2)) : "memory");
                    mbar_arrive(BAR(B_GD + lane));
                }
                __syncwarp();
                #pragma unroll 1
                for (int s = 2; s < 16; s++) {
                    sleep_until(t0 + W2OFF + s * W2PACE);
                    if (elect_one()) load_slab(s, true);
                    __syncwarp();
                }
            }
          } else {
            TRW(58);
            const uint32_t tag = lds1(sb + SM_EPOCH);
            if (lane < 4) mbar_expect(BAR(B_BL + NB + lane), 14336);
            #pragma unroll 1
            for (int e = 0; e < 2; e++) {
                const uint32_t* fp = e ? &prm.sc->flag_h[(rank * 64 + lane) * FS] : &prm.sc->flag_o[(a2s * 8 + (lane & 7)) * FS];
                if (e) {
                    mbar_wait2(BAR(B_BF + NB + 2), 0, BAR(B_BF + NB + 3), 0);
                    if (lane == 0) st_flag(&prm.sc->flag_h[(a2s * 4 + a2j) * FS], tag);
                    __syncwarp();
                    TRW(57);
                    sleep_until(clk32() + PDELAY);
                }
                uint64_t v0 = 0, v1 = e ? 0 : tag;
                int it = 0;
                do {
                    ld_flag_if(v0, fp, (uint32_t)v0 != tag); ld_flag_if(v1, fp + 32 * FS, (uint32_t)v1 != tag);
                    if (++it > kSpinLimit) { TIMEOUT(108); break; }
                } while (__any_sync(~0u, (uint32_t)v0 != tag || (uint32_t)v1 != tag));
                const uint32_t gbase = __shfl_sync(~0u, (uint32_t)(v0 >> 32), 0);
                const uint32_t tg = gbase + (e ? DELTA : DELTAO)
                                  + __reduce_max_sync(~0u, max((int)((uint32_t)(v0 >> 32) - gbase) - e * (lane >> 2) * SOFF, e ? (int)((uint32_t)(v1 >> 32) - gbase) - 8 * SOFF : 0));
                TRW(e ? 40 : 53);
                mbar_wait(BAR(B_A1D), 0);
                if (elect_one()) {
                    if (e) {
                        asm volatile("st.async.shared::cluster.mbarrier::complete_tx::bytes.b32 [%0], %1, [%2];"
                                     :: "r"(pbar0 + (SM_TG2 - SM_BAR)), "r"(tg), "r"(pbar0 + 8u * B_GO) : "memory");
                        asm volatile("st.shared.u32 [%0], %1;" :: "r"(sb + SM_TG + 4), "r"(tg) : "memory");
                        mbar_expect(BAR(B_GO), 4);
                    } else {
                        it = 0;
                        while ((int)(gtime32() - tg) < 0 && ++it < 256) {}
                        #pragma unroll
                        for (int i = 0; i < 4; i++) bulk_g2s(sb + SM_WQ + i * 14336, &prm.sc->o[(a2s * 4 + i) * 896], 14336, BAR(B_BL + NB + i));
                    }
                }
                __syncwarp();
            }
          }
          if (elect_one()) {
              const int h = ~warp & 1;
              const char* src1 = (const char*)&prm.sc->hn[(rank * 16 + h) * 3584 + g1j * 896];
              const char* src2 = (const char*)&prm.sc->g[(rank * 14 + h) * 3584 + g2j * 896];
              const long long jump = src2 - src1 - (16 * 57344 + 2 * 14336);
              const char* src = g1_on ? src1 - 2 * 57344 : src2;
              const uint32_t amask = g1_on ? (h ? kAMask1 : kAMask0) : 0u;
              uint32_t slot = g1_on ? NB - 2 + h : h, ph = g1_on ? 0 : 1, gate = g1_on ? 0 : 2, tmin = 0;
              CAP_DECL(ti_, 0);
              #pragma unroll 1
              for (int q = g1_on ? 0 : 17; q < 31; q++) {
                  const uint32_t eb = q ? BAR(B_BE) + slot * 8 : BAR(B_XF), dst = sb + SM_B + slot * 14336;
                  if ((0x1020003u >> q) & 1) {
                      mbar_wait(BAR(B_HD + gate), 0);
                      tmin = lds1(sb + SM_TG + gate * 4);
                      if (gate < 2) {
                          tmin += max((int)(lds1(gate ? sb + SM_TG2 : sb + SM_TG) - tmin), 0);
                          int it = 0;
                          while ((int)(gtime32() - tmin) < 0 && ++it < 256) {}
                          tmin = clk32();
                      }
                      tmin += h * PACE1;
                      gate++;
                  }
                  spin_until(tmin);
                  tmin += PACE2;
                  if (!mbar_try(eb, ph)) mbar_wait(eb, ph);
                  if (q) {
                      bulk_g2s(dst, src, 14336, eb + (B_BL - B_BE) * 8);
                      mbar_expect(eb + (B_BL - B_BE) * 8, 14336);
                      CAP(ti_);
                  }
                  mbar_arrive_remote_if(pbar0 + 8u * B_PD, h && q == 12);
                  if ((amask >> q) & 1) {
                      if (q < 12) load_slab(NPRE - W1Q + q, false);
                      else load_slab(2 + ((2 * q + h - 27) * 13 + 19) / 20, true);
                  }
                  src += 2 * 57344 + (q == 8 ? 2 * 14336 - 16 * 57344 : q == 16 ? jump : q == 23 ? 2 * 14336 - 14 * 57344 : 0);
                  slot += 2;
                  if (slot >= NB) { slot -= NB; ph ^= 1; }
              }
          }
        } else {
          if (warp == 10) {
            mbar_wait(BAR(PFBAR), 0);
            const char* p1 = (const char*)prm.w1 + (size_t)b * 57344 + lane * 128;
            const char* p2 = (const char*)prm.w2 + (size_t)b * 57344 + lane * 128;
            if (lane < 27) asm volatile("prefetch.global.L2 [%0];" :: "l"(lane < 25 ? (const char*)prm.wo + min(b * 25 + lane, 3135) * 128
                                                                          : lane == 25 ? (const char*)prm.b1 + (b % 28) * 128 : (const char*)prm.b2 + (b & 31) * 128));
            uint32_t tnext = clk32();
            #pragma unroll 1
            for (int i = 0; i < 28; i++) {
                while ((int)(clk32() - tnext) < 0) __nanosleep(40);
                asm volatile("prefetch.global.L2 [%0];" :: "l"(i < 14 ? p1 + i * 4096 : p2 + (i - 14) * 4096));
                tnext += PFPACE;
            }
            mbar_wait(BAR(B_EP), 0);
          }
          const uint32_t tag = lds1(sb + SM_EPOCH);
          const int h = warp & 1;
          const bool lead = elect_one();
          const uint32_t w0o = lane * 132, l3 = lane < 16 ? 12288 : 0;
          uint32_t wo = w0o ^ (h << 6), slot = NB + h, dst = sb + SM_WQ + h * 14336, ph = 0, rph = 0, af = BAR(B_WOF), aph = 0;
          #pragma unroll 1
          for (int q = -1; q < 31; q++) {
              const uint32_t rb = bar0 + slot * 8;
              auto stale = [&]() {
                  uint32_t d;
                  asm volatile("{ .reg .b32 x, y, z, u;\n"
                               "ld.shared.u32 x, [%1]; ld.shared.u32 y, [%1 + 4096]; ld.shared.u32 z, [%1 + 8192]; ld.shared.u32 u, [%2];\n"
                               "lop3.b32 x, x, y, %3, 0x7e; lop3.b32 z, z, u, %3, 0x7e; lop3.b32 %0, x, z, 1, 0xa8; }"
                               : "=r"(d) : "r"(dst + wo), "r"(dst + wo + l3), "r"(tag) : "memory");
                  return __any_sync(~0u, d);
              };
              mbar_wait(rb + B_BF * 8, ph ^ 1);
              mbar_wait(rb + B_BL * 8, ph);
              const bool aok = mbar_test(af, aph);
              bool bad = stale();
              if (!aok) mbar_wait(af, aph);
              mbar_arrive_if(rb + B_BF * 8, lead && !bad);
              if (bad) {
                  RETRY_COUNT(q < 1 ? 1 : q < 17 ? 0 : !g1_on ? 5 : q < 24 ? 2 : 6);
                  const int e = (q > 8) + (q > 16) + (q > 23), s = (q - (e < 3 ? 1 + 8 * e : 24)) * 2 + h;
                  const char* src = (const char*)(q < 1 ? &prm.sc->o[(a2s * 4 + s + 4) * 896] : e < 2 ? &prm.sc->hn[(rank * 16 + s) * 3584 + (g1j + 2 * e) * 896] : &prm.sc->g[(rank * 14 + s) * 3584 + (g2j + 2 * e - 4) * 896]);
                  int it = 0;
                  do {
                      if (++it > kSpinLimit) { TIMEOUT(111); break; }
                      const uint32_t* p = (const uint32_t*)(src + wo);
                      if (it > RELOAD1 && __any_sync(~0u, ((ld_rlx(p) ^ tag) | (ld_rlx(p + 1024) ^ tag) | (ld_rlx(p + 2048) ^ tag) | (ld_rlx(p + l3 / 4) ^ tag)) & 1)) continue;
                      if (lead) {
                          mbar_expect(BAR(B_RT + h), 14336);
                          bulk_g2s(dst, src, 14336, BAR(B_RT + h));
                      }
                      __syncwarp();
                      mbar_wait(BAR(B_RT + h), rph);
                      rph ^= 1;
                      bad = stale();
                  } while (bad);
                  mbar_arrive_if(rb + B_BF * 8, lead);
              }
              af += q < 0 ? 8 : q == 8 ? -112 : (0x810000u >> q) & 1 ? -96 : 16;
              slot += 2; dst += 28672;
              if (q > 0 && slot >= NB) { slot -= NB; dst -= NB * 14336; ph ^= 1; }
              if (q == 16) { wo = w0o ^ (g2j << 6); aph = 1; }
              if (q == 0) {
                  slot = h; dst = sb + SM_B + h * 14336; af = BAR(B_AF + h + (g1_on ? 0 : 2));
                  wo = w0o ^ ((g1_on ? g1j : g2j) << 6); q = g1_on ? 0 : 16;
              }
          }
        }
    } else {
        asm volatile("setmaxnreg.inc.sync.aligned.u32 232;");
        asm volatile("barrier.cluster.wait.aligned;" ::: "memory");
        const int wg = warp >> 2, w = warp & 3;
        const int g = lane >> 2, t = lane & 3;
        uint32_t tag;
        __nv_bfloat16 bias1;
        {
            const uint64_t dw = make_desc(sb + (hg & 1) * 16, 0, true);
            uint32_t a[28][4];
            float sm[4][4] = {};
            {
                const int r = w * 16 + (lane & 15);
                const uint32_t rowa = sb + wg * 8192 + r * 128;
                #pragma unroll
                for (int k = 0; k < 28; k++) {
                    if (XW == 1 && (k & 3) == 0) mbar_wait(BAR(B_XF + (k >> 2)), 0);
                    if (XW == 2 && k == 0) mbar_wait(BAR(B_XF), 0);
                    if (XW == 2 && (k & 7) == 4) mbar_wait2(BAR(B_XF + (k >> 2)), 0, BAR(B_XF + (k >> 2) + 1), 0);
                    const uint32_t addr = rowa + (k >> 2) * 16384 + ((((k & 3) * 2 + (lane >> 4)) ^ (r & 7)) << 4);
                    uint32_t (&f)[4] = a[k];
                    asm volatile("ldmatrix.sync.aligned.m8n8.x4.shared.b16 {%0,%1,%2,%3}, [%4];"
                                 : "=r"(f[0]), "=r"(f[1]), "=r"(f[2]), "=r"(f[3]) : "r"(addr) : "memory");
                    if (XLAG == 0) mma16816(sm[k & 3], f[0], f[1], f[2], f[3], 0x3F803F80u, 0x3F803F80u);
                    else if (k >= 4) mma16816(sm[k & 3], a[k - 4][0], a[k - 4][1], a[k - 4][2], a[k - 4][3], 0x3F803F80u, 0x3F803F80u);
                }
                if (XLAG) {
                    #pragma unroll
                    for (int k = 24; k < 28; k++) mma16816(sm[k & 3], a[k][0], a[k][1], a[k][2], a[k][3], 0x3F803F80u, 0x3F803F80u);
                }
            }
            const float mean0 = ((sm[0][0] + sm[1][0]) + (sm[2][0] + sm[3][0])) * (1.f / kD);
            const float mean1 = ((sm[0][2] + sm[1][2]) + (sm[2][2] + sm[3][2])) * (1.f / kD);
            const uint32_t mb0 = pack_bf16(mean0, mean0), mb1 = pack_bf16(mean1, mean1);
            pair_arrive(B_XC);
            TR(1);
            float ak[28], av[28], aq[28];
            float ss0 = 0.f, ss1 = 0.f, ss2 = 0.f, ss3 = 0.f;
            uint32_t p0, p1;
            static_for<0, 7>([&](auto S_) {
                constexpr int s = decltype(S_)::value;
                #pragma unroll
                for (int q = 0; q < 4; q++) {
                    uint32_t (&f)[4] = a[s * 4 + q];
                    f[0] = sub_bf16x2(f[0], mb0); f[1] = sub_bf16x2(f[1], mb1);
                    f[2] = sub_bf16x2(f[2], mb0); f[3] = sub_bf16x2(f[3], mb1);
                }
                mbar_wait(BAR(B_WKVF + s), 0);
                wg_fence();
                static_for<0, 4>([&](auto Q_) {
                    constexpr int q = decltype(Q_)::value;
                    uint32_t (&f)[4] = a[s * 4 + q];
                    wgmma_rs_n56<SM_WKV + s * 16384 + q * 2048, (s | q) != 0>(ak, f[0], f[1], f[2], f[3], dw);
                    wgmma_rs_n56<SM_WKV + s * 16384 + q * 2048 + 8192, (s | q) != 0>(av, f[0], f[1], f[2], f[3], dw);
                });
                wg_commit();
                if (s == 4) { wg_wait<1>(); pair_arrive(B_KV3); }
                #pragma unroll
                for (int q = 0; q < 8; q++) {
                    const uint32_t u0 = a[s * 4 + q / 2][(q & 1) * 2], u1 = a[s * 4 + q / 2][(q & 1) * 2 + 1];
                    if (q == 0 && (VCH == 1 || (s & 1) || s == 0)) { p0 = sqr_bf16x2(u0); p1 = sqr_bf16x2(u1); }
                    else { p0 = sqa_bf16x2(u0, p0); p1 = sqa_bf16x2(u1, p1); }
                }
                if (VCH == 1 || !(s & 1)) { ss0 += bf_lo(p0); ss2 += bf_hi(p0); ss1 += bf_lo(p1); ss3 += bf_hi(p1); }
            });
            auto q_chunk = [&](auto K0_, auto K1_) {
                wg_fence();
                static_for<decltype(K0_)::value, decltype(K1_)::value>([&](auto K_) {
                    constexpr int k = decltype(K_)::value;
                    wgmma_rs_n56<SM_WQ + k * 2048, k != 0>(aq, a[k][0], a[k][1], a[k][2], a[k][3], dw);
                });
                wg_commit();
            };
            #define QCHUNK(k0, k1) q_chunk(std::integral_constant<int, k0>{}, std::integral_constant<int, k1>{})
            const float dl0 = mean0 - bf_lo(mb0), dl1 = mean1 - bf_lo(mb1);
            const float rs0 = rsq(fmaxf(quad_sum(ss0 + ss2) * (1.f / kD) - dl0 * dl0, 0.f) + kEps);
            const float rs1 = rsq(fmaxf(quad_sum(ss1 + ss3) * (1.f / kD) - dl1 * dl1, 0.f) + kEps);
            float rk[3][2];
            rk[1][0] = __shfl_sync(~0u, rs0, t * 8); rk[1][1] = __shfl_sync(~0u, rs0, t * 8 + 4);
            rk[2][0] = __shfl_sync(~0u, rs1, t * 8); rk[2][1] = __shfl_sync(~0u, rs1, t * 8 + 4);
            const uint32_t stg = sb + SM_STG + wg * 8192 + lane * 16;
            uint4* hp = (w == 3 ? &prm.sc->halo[((ti * 8 + hg) * 2 + wg) * 128] : (uint4*)(smem_raw + SM_STG + wg * 8192 + w * 2048)) + lane;
            mbar_wait2(BAR(B_EP), 0, BAR(B_WQF), 0);
            tag = lds1(sb + SM_EPOCH);
            QCHUNK(0, QC0);
            wg_wait<1>();
            reg_fence(ak); reg_fence(av);
            TR(2);
            uint32_t kf[3][7], vf[3][7];
            #pragma unroll
            for (int c = 0; c < 7; c++) {
                kf[2][c] = pack_bf16(ak[4 * c + 2], ak[4 * c + 3]);
                vf[2][c] = movm(pack_bf16(av[4 * c + 2], av[4 * c + 3]));
            }
            const uint32_t om = ~lane & 1;
            kf[2][0] = set_par(kf[2][0], om, tag); kf[2][4] = set_par(kf[2][4], om, tag);
            vf[2][1] = set_par(vf[2][1], om, tag); vf[2][5] = set_par(vf[2][5], om, tag);
            st_gen4(hp,      kf[2][0], kf[2][1], kf[2][2], kf[2][3]);
            st_gen4(hp + 32, kf[2][4], kf[2][5], kf[2][6], vf[2][0]);
            st_gen4(hp + 64, vf[2][1], vf[2][2], vf[2][3], vf[2][4]);
            st_gen4(hp + 96, vf[2][5], vf[2][6], __float_as_uint(rk[2][0]), __float_as_uint(rk[2][1]));
            pair_arrive(B_KVC);
            QCHUNK(QC0, QC1);
            #pragma unroll
            for (int c = 0; c < 7; c++) {
                kf[1][c] = pack_bf16(ak[4 * c], ak[4 * c + 1]);
                vf[1][c] = movm(pack_bf16(av[4 * c], av[4 * c + 1]));
            }
            QCHUNK(QC1, QC2);
            named_bar(1 + wg, 128);
            uint32_t* op = opaque_ptr((uint32_t*)&prm.sc->o[((ti * 2 + wg) * 56 + hg * 7) * 64] + w * 64 + lane);
            const uint32_t omk = opaque(((lane & 6) == w * 2 ? 0x11u << (lane & 1) * 8 : 0u) << (((lane >> 3) - hg * 7) & 3));
            uint32_t* ofl = opaque_ptr(&prm.sc->flag_o[((ti * 2 + wg) * 8 + hg) * FS]);
            QCHUNK(QC2, 28);
            #undef QCHUNK
            const bool gt0 = 2 * t > g, gt1 = 2 * t + 1 > g, no_prev = ti == 0 && w == 0;
            const float kf0 = gt0 ? rk[1][0] : rk[2][0], kf1 = gt1 ? rk[1][1] : rk[2][1];
            constexpr float kScale = 0.18898223650461362f * 1.4426950408889634f;
            const float sq0 = rs0 * kScale, sf0 = kf0 * (rs1 * kScale), sf1 = kf1 * (rs1 * kScale);
            const float NEG = -__int_as_float(0x7f800000);
            const float nb0 = gt0 && no_prev ? NEG : 0.f, nb1 = gt1 && no_prev ? NEG : 0.f;
            const uint32_t sr = stg + ((w + 3) & 3) * 2048, hbar = BAR(w == 0 ? B_HL + wg : B_EP);
            mbar_wait(BAR(B_EP), 0);
            wg_wait<0>();
            reg_fence(aq);
            warp_arrive(BAR(B_A1D));
            TR(3);
            uint32_t qf[8][2];
            #pragma unroll
            for (int c = 0; c < 7; c++) {
                qf[c + (c > 3)][0] = pack_bf16(aq[4 * c], aq[4 * c + 1]);
                qf[c + (c > 3)][1] = pack_bf16(aq[4 * c + 2], aq[4 * c + 3]);
            }
            qf[4][0] = t >= 2 ? qf[3][0] : 0u; qf[4][1] = t >= 2 ? qf[3][1] : 0u;
            qf[3][0] = t < 2 ? qf[3][0] : 0u;  qf[3][1] = t < 2 ? qf[3][1] : 0u;
            float sc[2][3][4];
            auto scores = [&](int n) {
                #pragma unroll
                for (int hd = 0; hd < 2; hd++) {
                    sc[hd][n][0] = sc[hd][n][1] = sc[hd][n][2] = sc[hd][n][3] = 0.f;
                    mma16816(sc[hd][n], qf[4 * hd][0], qf[4 * hd][1], qf[4 * hd + 1][0], qf[4 * hd + 1][1], kf[n][3 * hd], kf[n][3 * hd + 1]);
                    mma16816(sc[hd][n], qf[4 * hd + 2][0], qf[4 * hd + 2][1], qf[4 * hd + 3][0], qf[4 * hd + 3][1], kf[n][3 * hd + 2], kf[n][3 * hd + 3]);
                }
            };
            scores(1); scores(2);
            mbar_wait(hbar, 0);
            {
                const uint4 u0 = lds4(sr), u1 = lds4(sr + 512), u3 = lds4(sr + 1536), u2 = lds4(sr + 1024);
                kf[0][0] = u0.x; kf[0][1] = u0.y; kf[0][2] = u0.z; kf[0][3] = u0.w;
                kf[0][4] = u1.x; kf[0][5] = u1.y; kf[0][6] = u1.z; vf[0][0] = u1.w;
                vf[0][1] = u2.x; vf[0][2] = u2.y; vf[0][3] = u2.z; vf[0][4] = u2.w;
                vf[0][5] = u3.x; vf[0][6] = u3.y; rk[0][0] = __uint_as_float(u3.z); rk[0][1] = __uint_as_float(u3.w);
            }
            if ((tid & 127) == 0) st_flag(ofl, tag);
            TR(4);
            scores(0);
            const float ke0 = gt0 ? rk[0][0] : rk[1][0], ke1 = gt1 ? rk[0][1] : rk[1][1];
            const float se0 = ke0 * sq0, se1 = ke1 * sq0;
            uint32_t ow[7][2];
            #pragma unroll
            for (int hd = 0; hd < 2; hd++) {
                const int c0 = hd * 3;
                float (&sc_)[3][4] = sc[hd];
                const float e0 = fmaf(gt0 ? sc_[0][0] : sc_[1][0], se0, nb0), e1 = fmaf(gt1 ? sc_[0][1] : sc_[1][1], se1, nb1);
                const float f0 = (gt0 ? sc_[1][2] : sc_[2][2]) * sf0, f1 = (gt1 ? sc_[1][3] : sc_[2][3]) * sf1;
                const float me = quad_max(fmaxf(e0, e1)), mf = quad_max(fmaxf(f0, f1));
                const float p0 = ex2(e0 - me), p1 = ex2(e1 - me), r0 = ex2(f0 - mf), r1 = ex2(f1 - mf);
                const float ie = rcp(quad_sum(p0 + p1)), jf = rcp(quad_sum(r0 + r1));
                const uint32_t pp = pack_bf16(p0 * ke0 * ie, p1 * ke1 * ie), rp = pack_bf16(r0 * kf0 * jf, r1 * kf1 * jf);
                const uint32_t mk = (gt0 ? 0x0000ffffu : 0u) | (gt1 ? 0xffff0000u : 0u);
                #pragma unroll
                for (int c = 0; c < 4; c++) {
                    float o[4] = {0.f, 0.f, 0.f, 0.f};
                    mma16816(o, pp & mk, 0u, pp & ~mk, rp & mk, vf[0][c0 + c], vf[1][c0 + c]);
                    mma1688(o, 0u, rp & ~mk, vf[2][c0 + c]);
                    const uint32_t lo = pack_bf16(o[0], o[1]), hi = pack_bf16(o[2], o[3]);
                    if (hd == 1 && c == 0) { if (t >= 2) { ow[3][0] = lo; ow[3][1] = hi; } }
                    else { ow[c0 + c][0] = lo; ow[c0 + c][1] = hi; }
                }
            }
            #pragma unroll
            for (int c = 0; c < 7; c++) {
                stg1(op + c * 256,      set_par(ow[c][0], (omk >> (c & 3)) & 1, tag));
                stg1(op + c * 256 + 32, set_par(ow[c][1], (omk >> (8 + (c & 3))) & 1, tag));
            }
            TR(5);
        }
        {
            const int cg = a2j * 2 + wg;
            float acc2[28];
            mbar_wait(BAR(B_XRF), 0);
            {
                const uint32_t xa = sb + SM_XR + wg * 8192 + (w * 16 + (lane & 15)) * 128;
                #pragma unroll
                for (int c = 0; c < 4; c++) {
                    uint32_t xr[4];
                    asm volatile("ldmatrix.sync.aligned.m8n8.x4.shared.b16 {%0,%1,%2,%3}, [%4];"
                                 : "=r"(xr[0]), "=r"(xr[1]), "=r"(xr[2]), "=r"(xr[3])
                                 : "r"(xa + ((((c * 2 + wg + (lane >> 4)) ^ lane) & 7) << 4)) : "memory");
                    #pragma unroll
                    for (int e = 0; e < (c < 3 ? 4 : 2); e++) { acc2[8 * c + 2 * e] = bf_lo(xr[e]); acc2[8 * c + 2 * e + 1] = bf_hi(xr[e]); }
                }
            }
            uint32_t* spw = opaque_ptr(&prm.sc->stats[((a2s * 8 + cg) * 4 + w) * 32 + lane]);
            const uint32_t* spr = opaque_ptr(&prm.sc->stats[(a2s * 32 + w) * 32 + lane]);
            uint4* hp = opaque_ptr(&prm.sc->h[((a2s * 8 + w * 2) * 8 + cg) * 64 + lane]);
            uint32_t* np = opaque_ptr((uint32_t*)&prm.sc->hn[(a2s * 56 + cg * 7) * 64] + w * 64 + lane);
            const uint64_t dwo = make_desc(sb + SM_WKV + wg * (28672 + 16), 0, true);
            const uint64_t doa = make_desc(sb + SM_WQ, 1024, false, 128);
            bias1 = prm.b1[g1f * 64 + w * 16 + rank * 8 + g];
            const __nv_bfloat16 bias2a = prm.b2[ti * 128 + (w * 16 + g) * 2 + a2p], bias2b = prm.b2[ti * 128 + (w * 16 + 8 + g) * 2 + a2p];
            reg_fence(acc2);
            fence_async_smem();
            warp_arrive(BAR(B_XD));
            static_for<0, 4>([&](auto P_) {
                constexpr int P = decltype(P_)::value;
                mbar_wait(BAR(B_BF + NB + P), 0);
                if (P == 0) TR(6);
                wg_fence();
                static_for<0, 7>([&](auto K_) { constexpr int k = decltype(K_)::value;
                    wgmma_ss_n56<P * 14336 + k * 2048, (P >> 1) * 57344 + (P & 1) * 14336 + k * 2048>(acc2, doa, dwo); });
                if (P) wg_commit();
                if (P == 2) { wg_wait<1>(); warp_arrive(BAR(B_OC)); }
            });
            wg_wait<0>();
            reg_fence(acc2);
            TR(7);
            float s0 = 0.f, s1 = 0.f, q0 = 0.f, q1 = 0.f;
            #pragma unroll
            for (int c = 0; c < 7; c++) {
                s0 += acc2[4 * c] + acc2[4 * c + 1];     q0 = fmaf(acc2[4 * c], acc2[4 * c], fmaf(acc2[4 * c + 1], acc2[4 * c + 1], q0));
                s1 += acc2[4 * c + 2] + acc2[4 * c + 3]; q1 = fmaf(acc2[4 * c + 2], acc2[4 * c + 2], fmaf(acc2[4 * c + 3], acc2[4 * c + 3], q1));
            }
            const bool th = t >= 2, to = t & 1;
            const float sa = (th ? s1 : s0) + __shfl_xor_sync(~0u, th ? s0 : s1, 2), qa = (th ? q1 : q0) + __shfl_xor_sync(~0u, th ? q0 : q1, 2);
            const float part = (to ? qa : sa) + __shfl_xor_sync(~0u, to ? sa : qa, 1);
            stg1(spw, set_par(__float_as_uint(part), 1u, tag));
            const uint32_t tpoll = clk32() + SDELAY;
            TR(8);
            warp_arrive(BAR(B_HD));
            uint32_t hw[2][7], nm[2][4], us[8];
            #pragma unroll
            for (int r = 0; r < 2; r++) {
                const float b2v = __bfloat162float(r ? bias2b : bias2a);
                #pragma unroll
                for (int c = 0; c < 7; c++) hw[r][c] = pack_bf16(acc2[4 * c + 2 * r] + b2v, acc2[4 * c + 2 * r + 1] + b2v);
                hw[r][0] = set_par(hw[r][0], ~lane & 1, tag);
            }
            auto store_h = [&]() {
                #pragma unroll
                for (int r = 0; r < 2; r++) {
                    stg4(hp + r * 512, hw[r][0], hw[r][1], hw[r][2], hw[r][3]);
                    stg4(hp + r * 512 + 32, tag, hw[r][4], hw[r][5], hw[r][6]);
                }
            };
            if (HPOS == 0) store_h();
            spin_until(tpoll);
            #pragma unroll
            for (int i = 0; i < 8; i++) us[i] = ld_rlx(spr + i * 128);
            if (HPOS == 1) store_h();
            #pragma unroll
            for (int i = 0; i < 8; i++) nm[i >> 2][i & 3] = lane == ((cg * 7 + i) & 3) * 8 + w * 2 + (i >> 2);
            {
                int it = 0;
                while (true) {
                    uint32_t bad = 0;
                    #pragma unroll
                    for (int i = 0; i < 8; i++) bad |= us[i] ^ tag;
                    if (!__any_sync(~0u, bad & 1)) break;
                    RETRY_COUNT(3);
                    if (++it > kSpinLimit) { TIMEOUT(103); break; }
                    #pragma unroll
                    for (int i = 0; i < 8; i++) us[i] = ld_rlx(spr + i * 128);
                }
            }
            TR(9);
            const float tot = (((__uint_as_float(us[0]) + __uint_as_float(us[1])) + (__uint_as_float(us[2]) + __uint_as_float(us[3])))
                            + ((__uint_as_float(us[4]) + __uint_as_float(us[5])) + (__uint_as_float(us[6]) + __uint_as_float(us[7])))) * (1.f / kD);
            const float oth = __shfl_xor_sync(~0u, tot, 1);
            const float mean = to ? oth : tot;
            const float var = fmaxf(fmaf(-mean, mean, to ? tot : oth), 0.f);
            const float r1 = rsq(var + kEps);
            const float rra = 0.5f * r1 * rsq(fmaf(var * r1, r1, kEps)), mra = -mean * rra;
            const float rrb = __shfl_xor_sync(~0u, rra, 2), mrb = __shfl_xor_sync(~0u, mra, 2);
            const float rr0 = th ? rrb : rra, mr0 = th ? mrb : mra, rr1 = th ? rra : rrb, mr1 = th ? mra : mrb;
            #pragma unroll
            for (int c = 0; c < 7; c++) {
                stg1(np + c * 256,      set_par(pack_bf16(fmaf(acc2[4 * c], rr0, mr0), fmaf(acc2[4 * c + 1], rr0, mr0)), nm[0][c & 3], tag));
                stg1(np + c * 256 + 32, set_par(pack_bf16(fmaf(acc2[4 * c + 2], rr1, mr1), fmaf(acc2[4 * c + 3], rr1, mr1)), nm[1][c & 3], tag));
            }
            TR(10);
            if (HPOS == 2) store_h();
        }
        float acc[56];
        const uint32_t xch = opaque(sb + SM_XCH + w * 1920 + lane * 16);
        uint32_t peer_xch; const uint32_t peer_bar = pbar0;
        asm volatile("mapa.shared::cluster.u32 %0, %1, %2;" : "=r"(peer_xch) : "r"(xch), "r"(rank ^ 1));
        uint4 hr[4];
        const int tok = g2s * 64 + w * 16 + rank * 8 + g, pr = (tok & 127) >> 1;
        const uint4* hp = &prm.sc->h[((((tok >> 7) * 2 + (tok & 1)) * 8 + (pr >> 3)) * 8 + (g2j + 2 * wg) * 2) * 64 + (pr & 7) * 4 + t];
        auto load_h = [&]() {
            #pragma unroll
            for (int c = 0; c < 4; c++) hr[c] = ld_rlx4(hp + c * 32);
        };
        const uint32_t b1h = pack_bf16(0.5f * __bfloat162float(bias1), 0.5f * __bfloat162float(bias1));
        #pragma unroll
        for (int c = 0; c < 4; c++) hr[c] = make_uint4(b1h, b1h, b1h, b1h);
        if (!g1_on) { mbar_wait(BAR(B_GD), 0); load_h(); }
        uint32_t* const gp1 = (uint32_t*)&prm.sc->g[(g1f * 56 + (g1j + 2 * wg) * 14) * 64] + (w * 2 + rank) * 32 + lane;
        uint32_t* const gp2 = (uint32_t*)(prm.out + (size_t)(g2s * 64 + w * 16 + rank * 8 + (lane >> 4)) * kD + (g2j + 2 * wg) * 112) + (lane & 15) * 4;
        uint32_t gm[4];
        #pragma unroll
        for (int i = 0; i < 4; i++) gm[i] = lane == ((g1j * 2 + i) & 3) * 8 + w * 2 + rank;
        const bool lead = elect_one();
        const uint64_t da0 = make_desc(sb, 0, true), db0 = make_desc(sb + SM_B, 128, false);
        #pragma unroll 1
        for (int ge = g1_on ? 0 : 1; ge < 2; ge++) {
            if (ge) {
                int it = 0;
                while (true) {
                    uint32_t bad = 0;
                    #pragma unroll
                    for (int c = 0; c < 4; c++) bad |= hr[c].x ^ tag;
                    if (!__any_sync(~0u, bad & ~lane & 1)) break;
                    if (++it > kSpinLimit) { TIMEOUT(110); break; }
                    load_h();
                }
            }
            auto init_acc = [&](auto R_) {
                constexpr int o = decltype(R_)::value * 2;
                #pragma unroll
                for (int c = 0; c < 14; c++) {
                    const int i = c / 7 * 8 + c % 7 + (c % 7 >= 4);
                    const uint32_t hw = (i & 3) == 0 ? hr[i >> 2].x : (i & 3) == 1 ? hr[i >> 2].y : (i & 3) == 2 ? hr[i >> 2].z : hr[i >> 2].w;
                    acc[4 * c + o] = bf_lo(hw); acc[4 * c + 1 + o] = bf_hi(hw);
                    acc[4 * c + 2 - o] = 0.f;   acc[4 * c + 3 - o] = 0.f;
                }
                reg_fence(acc);
            };
            if (rank) init_acc(std::integral_constant<int, 1>{}); else init_acc(std::integral_constant<int, 0>{});
            const uint32_t slot0 = g1_on ? (ge ? 4 : 2 * wg) : 0;
            uint32_t ph = 0, rb = bar0 + slot0 * 8;
            uint64_t da = da0 + ge * 1024, db = db0 + slot0 * 896;
            uint32_t prev = BAR(B_WKVF);
            mbar_wait(BAR(B_EP), 0);
            if (wg == 1 || (ge && g1_on)) named_bar(5 - wg, 256);
            mbar_wait(rb + B_BF * 8, ph);
            TR(11 + ge * 4);
            #pragma unroll 1
            for (int n = ge ? 14 : 16;;) {
                wg_fence();
                wgmma_ss_n112<0,    0>(acc, da, db);
                wgmma_ss_n112<2048, 256>(acc, da, db);
                wgmma_ss_n112<4096, 512>(acc, da, db);
                wgmma_ss_n112<6144, 768>(acc, da, db);
                wg_commit();
                if (--n == 0 && ge + wg < 2) named_arrive(4 + wg, 256);
                const uint32_t cur = rb + B_BE * 8;
                da += 512; db += 896; rb += 8;
                if (rb == bar0 + NB * 8) { rb = bar0; db = db0; ph ^= 1; }
                wg_wait<1>();
                mbar_arrive_if(prev, lead);
                prev = cur;
                if (n == 0) break;
                if (!mbar_try(rb + B_BF * 8, ph)) mbar_wait(rb + B_BF * 8, ph);
            }
            const int use = ge * 2 + wg;
            const uint32_t xfree = BAR(use > (g1_on ? 0 : 2) ? B_RE + use - 1 : B_PD);
            const bool xok = mbar_test(xfree, 0);
            wg_wait<0>();
            reg_fence(acc);
            mbar_arrive_if(prev, lead);
            TR(12 + ge * 4);
            if (!xok) mbar_wait(xfree, 0);
            float v[28];
            auto reduce = [&](auto R_) {
                constexpr int o = decltype(R_)::value * 2;
                const uint32_t rf = peer_bar + (B_RF + use) * 8;
                float dly = __uint_as_float(0x3f800000u | lane); uint32_t pa = peer_xch;
                #pragma unroll
                for (int c = 0; c < 4; c++) {
                    const uint32_t p0 = pack_bf16(acc[16 * c + 2 - o], acc[16 * c + 3 - o]), p1 = pack_bf16(acc[16 * c + 6 - o], acc[16 * c + 7 - o]);
                    if (c < 3) {
                        const uint32_t p2 = pack_bf16(acc[16 * c + 10 - o], acc[16 * c + 11 - o]), p3 = pack_bf16(acc[16 * c + 14 - o], acc[16 * c + 15 - o]);
                        asm volatile("st.async.shared::cluster.mbarrier::complete_tx::bytes.v4.b32 [%0], {%1,%2,%3,%4}, [%5];"
                                     :: "r"(pa + c * 512), "r"(p0), "r"(p1), "r"(p2), "r"(p3), "r"(rf) : "memory");
                        if (use != 3) {
                            #pragma unroll
                            for (int i = 0; i < XPACE; i++) asm volatile("tanh.approx.f32 %0, %0;" : "+f"(dly) :: "memory");
                            pa += __float_as_uint(dly) >> 30;
                        }
                    } else {
                        asm volatile("st.async.shared::cluster.mbarrier::complete_tx::bytes.v2.b32 [%0], {%1,%2}, [%3];"
                                     :: "r"(pa + 1536 - lane * 8), "r"(p0), "r"(p1), "r"(rf) : "memory");
                    }
                }
                if (!ge) load_h();
                mbar_wait(BAR(B_RF + use), 0);
                #pragma unroll
                for (int c = 0; c < 4; c++) {
                    uint4 u;
                    if (c < 3) u = lds4(xch + c * 512); else { const uint2 u2 = lds2(xch + 1536 - lane * 8); u.x = u2.x; u.y = u2.y; }
                    v[8 * c]     = acc[16 * c + o] + bf_lo(u.x);     v[8 * c + 1] = acc[16 * c + 1 + o] + bf_hi(u.x);
                    v[8 * c + 2] = acc[16 * c + 4 + o] + bf_lo(u.y); v[8 * c + 3] = acc[16 * c + 5 + o] + bf_hi(u.y);
                    if (c < 3) {
                        v[8 * c + 4] = acc[16 * c + 8 + o] + bf_lo(u.z);  v[8 * c + 5] = acc[16 * c + 9 + o] + bf_hi(u.z);
                        v[8 * c + 6] = acc[16 * c + 12 + o] + bf_lo(u.w); v[8 * c + 7] = acc[16 * c + 13 + o] + bf_hi(u.w);
                    }
                }
            };
            if (rank) reduce(std::integral_constant<int, 1>{}); else reduce(std::integral_constant<int, 0>{});
            TR(13 + ge * 4);
            if (!ge) {
                #pragma unroll
                for (int c = 0; c < 14; c++) {
                    float r[2];
                    #pragma unroll
                    for (int e = 0; e < 2; e++) {
                        const float u = v[2 * c + e];
                        r[e] = fmaf(u, tanh_hw(u * fmaf(u * u, 8.f * 0.7978845608f * 0.044715f, 2.f * 0.7978845608f)), u);
                    }
                    stg1(gp1 + c * 256, set_par(pack_bf16(r[0], r[1]), gm[c & 3], tag));
                }
                named_bar(1 + wg, 128);
                if (w == 0 && lane == 0) {
                    asm volatile("st.shared.u32 [%0], %1;" :: "r"(sb + SM_TG + 8 + wg * 4), "r"(clk32() + (wg ? XSPECB : XSPEC)) : "memory");
                    mbar_arrive(BAR(B_GD + wg));
                }
                mbar_arrive_remote_if(peer_bar + (B_RE + use) * 8, lead);
            } else {
                const uint32_t stw = xch - lane * 16;
                uint32_t pk[14];
                #pragma unroll
                for (int c = 0; c < 14; c++) pk[c] = pack_bf16(v[2 * c], v[2 * c + 1]);
                __syncwarp();
                const uint32_t sa = stw + (lane & 7) * 240 + (lane >> 3) * 16;
                #pragma unroll
                for (int m = 0; m < 3; m++)
                    asm volatile("stmatrix.sync.aligned.m8n8.x4.shared.b16 [%0], {%1,%2,%3,%4};"
                                 :: "r"(sa + m * 64), "r"(pk[4 * m]), "r"(pk[4 * m + 1]), "r"(pk[4 * m + 2]), "r"(pk[4 * m + 3]) : "memory");
                asm volatile("stmatrix.sync.aligned.m8n8.x2.shared.b16 [%0], {%1,%2};" :: "r"(sa + 192), "r"(pk[12]), "r"(pk[13]) : "memory");
                __syncwarp();
                #pragma unroll
                for (int i = 0; i < 4; i++) {
                    const int r = 2 * i + (lane >> 4), ch = lane & 15;
                    if (ch < 14) { const uint4 u = lds4(stw + r * 240 + ch * 16); stg4(gp2 + i * 448, u.x, u.y, u.z, u.w); }
                }
                __syncwarp();
                mbar_arrive_remote_if(peer_bar + (B_RE + 2) * 8, lead && wg == 0);
            }
            TR(14 + ge * 4);
        }
        if (tid == 128) TRG(62);
        if (b == 0 && tid == 128) prm.sc->epoch = tag;
    }
}

typedef CUresult (*EncodeFn)(CUtensorMap*, CUtensorMapDataType, cuuint32_t, void*, const cuuint64_t*, const cuuint64_t*,
                             const cuuint32_t*, const cuuint32_t*, CUtensorMapInterleave, CUtensorMapSwizzle,
                             CUtensorMapL2promotion, CUtensorMapFloatOOBfill);

void make_map(EncodeFn enc, CUtensorMap* m, const void* base, uint64_t cols, uint64_t rows, uint32_t box_rows) {
    cuuint64_t dims[2] = {cols, rows};
    cuuint64_t strides[1] = {cols * 2};
    cuuint32_t box[2] = {64, box_rows};
    cuuint32_t es[2] = {1, 1};
    enc(m, CU_TENSOR_MAP_DATA_TYPE_BFLOAT16, 2, const_cast<void*>(base), dims, strides, box, es, CU_TENSOR_MAP_INTERLEAVE_NONE,
        CU_TENSOR_MAP_SWIZZLE_128B, CU_TENSOR_MAP_L2_PROMOTION_L2_128B, CU_TENSOR_MAP_FLOAT_OOB_FILL_NONE);
}

}

extern "C" void kernel_launch(void* const* d_in, const int* in_sizes, int n_in, void* d_out, int out_size) {
    (void)in_sizes; (void)n_in; (void)out_size;
    void* fn = nullptr;
    cudaDriverEntryPointQueryResult qr;
    cudaGetDriverEntryPoint("cuTensorMapEncodeTiled", &fn, cudaEnableDefault, &qr);
    EncodeFn enc = (EncodeFn)fn;
    CUtensorMap mX2, mX, mWqkv, mWo, mW1, mW2;
    {
        cuuint64_t dims[3] = {kD, kS / 2, 2}, strides[2] = {4 * kD, 2 * kD};
        cuuint32_t box[3] = {64, 64, 2}, es[3] = {1, 1, 1};
        enc(&mX2, CU_TENSOR_MAP_DATA_TYPE_BFLOAT16, 3, d_in[0], dims, strides, box, es, CU_TENSOR_MAP_INTERLEAVE_NONE,
            CU_TENSOR_MAP_SWIZZLE_128B, CU_TENSOR_MAP_L2_PROMOTION_L2_128B, CU_TENSOR_MAP_FLOAT_OOB_FILL_NONE);
    }
    make_map(enc, &mX, d_in[0], 2 * kD, kS / 2, 64);
    make_map(enc, &mWqkv, d_in[1], 3 * kD, kD, 64);
    make_map(enc, &mWo, d_in[2], kD, kD, 224);
    make_map(enc, &mW1, d_in[4], 2 * kF, kS / 2, 64);
    make_map(enc, &mW2, d_in[6], kS, kF, 64);
    Params prm;
    prm.x = (const __nv_bfloat16*)d_in[0];
    prm.wqkv = (const __nv_bfloat16*)d_in[1];
    prm.wo = (const __nv_bfloat16*)d_in[2];
    prm.w1 = (const __nv_bfloat16*)d_in[4];
    prm.b1 = (const __nv_bfloat16*)d_in[5];
    prm.w2 = (const __nv_bfloat16*)d_in[6];
    prm.b2 = (const __nv_bfloat16*)d_in[7];
    prm.out = (__nv_bfloat16*)d_out;
    cudaGetSymbolAddress((void**)&prm.sc, g_scratch);
    cudaFuncSetAttribute(fused_kernel, cudaFuncAttributeMaxDynamicSharedMemorySize, SM_TOTAL);
    fused_kernel<<<128, 384, SM_TOTAL, cudaStreamPerThread>>>(prm, mX2, mX, mWqkv, mWo, mW1, mW2);
}
```

```cpp
#include <cuda_runtime.h>
#include <cuda.h>
#include <cuda_bf16.h>
#include <stdint.h>
#include <type_traits>

namespace {

constexpr int kS = 2048, kD = 448, kF = 1792;
constexpr float kEps = 1e-5f;

#define FS 32
struct Scratch {
    uint4    o[32 * 56 * 64];
    uint4    h[32 * 8 * 8 * 64];
    uint4    hn[32 * 56 * 64];
    uint4    g[28 * 56 * 64];
    uint4    halo[16 * 8 * 2 * 4 * 32];
    uint32_t stats[32 * 8 * 4 * 32];
    uint32_t flag_o[32 * 8 * FS];
    uint32_t flag_h[32 * 4 * FS];
    uint32_t epoch;
};
__device__ __align__(1024) Scratch g_scratch;
#define TIMEOUT(code)
#define RETRY_COUNT(i)
#define CAP_DECL(n, k)
#define CAP(n)
#define CAP_SKIP(n)
#define TR2(idx)
#define TR(idx)
#define TRW(idx)
#define TRG(idx)

constexpr uint32_t SM_WKV  = 114688;
constexpr uint32_t SM_XR   = 24576;
constexpr uint32_t SM_STG  = 40960;
constexpr uint32_t SM_WQ   = 57344;
constexpr uint32_t SM_XCH  = 0;
constexpr uint32_t SM_B    = 131072;
constexpr uint32_t SM_BAR  = 231424;
constexpr uint32_t SM_TOTAL = SM_BAR + 1024;
constexpr int NB = 7;
#define SH1 0
#define SH2 0
#define SH2N 5
#define SH3 0
#define NSPEC 4
#define XSPEC 850
#define C2 0
#define C3 0
#define CN2 8000
#define CN3 12000
constexpr int B_XF = 0, B_WKVF = 7, B_WQF = 14, B_XRF = 15, B_WOF = 16,
              B_XC = 18, B_KV3 = 19, B_KVC = 20,
              B_A1D = 21, B_XD = 22, B_OC = 23,
              B_BE = 24, B_RE = B_BE + NB,
              B_AF = B_RE + 3, B_BL = B_AF + 16  , B_BF = B_BL + NB + 4  ,
              B_RF = B_BF + NB + 4, B_EP = B_RF + 4, B_PD = B_EP + 1, B_RT = B_PD + 1, B_HL = B_RT + 2,
              B_HD = B_HL + 2  , B_GO = B_HD + 1, B_GD = B_GO + 1, B_COUNT = B_GD + 2;
#define WEARLY 6
#define PF0 126
#define TMPF 2
#define RSTE 2
#define POLLP 1
#define PROBEP 1
#define LOADP 1
#define LOADW 64
#define NOB 0
#define AEARLY 5
#define W1PACE 400
#define W2PACE 200
#define PFPACE 230
#define PFBAR (B_XF + 6)
#define DELTA 1696
#define DELTA2 DELTA
#define BPACE 230
#define BURST 2
#define W1OFF 350
#define W2OFF 2900
#define XPACE 0
#define PSTAG 200
constexpr uint32_t SM_EPOCH = SM_BAR + B_COUNT * 8, SM_TG = SM_EPOCH + 4  , SM_TG2 = SM_TG + 16  , SM_TR = SM_BAR + 768;

#define HDELAY 0
#define QC0 4
#define QC1 10
#define QC2 16
#define HPOS 1
#define XSPECB 700
#define PACE1 120
#define PACE2 400
#define RELOAD1 1
#define VCH 1
#define SOFF 0
#define XW 1
#define XLAG 0
#define PFX 3
#define PFD 250
#define SDELAY 400
#define PDELAY 500
#define NPRE 10
#define PREPACE 0
#define AFIRST 0
#define DELTAO 928
#define W1Q 3
constexpr uint32_t w2_rounds(int h) { uint32_t m = 0; for (int i = 0; i < 14; i++) { const int p = 25 + i * 20 / 13; if ((p & 1) == h) m |= 1u << (p / 2 + 1); } return m; }
constexpr uint32_t kAMask0 = w2_rounds(0), kAMask1 = w2_rounds(1) | ((1u << (16 - NPRE)) - 1) << W1Q;

constexpr int kSpinLimit = 1 << 15;
__device__ __forceinline__ bool elect_one() {
    uint32_t p;
    asm volatile("{ .reg .pred P; elect.sync _|P, 0xffffffff; selp.u32 %0, 1, 0, P; }" : "=r"(p));
    return p;
}
__device__ __forceinline__ void mbar_init(uint32_t bar, uint32_t cnt) { asm volatile("mbarrier.init.shared::cta.b64 [%0], %1;" :: "r"(bar), "r"(cnt)); }
__device__ __forceinline__ void mbar_expect(uint32_t bar, uint32_t bytes) { asm volatile("mbarrier.arrive.expect_tx.shared::cta.b64 _, [%0], %1;" :: "r"(bar), "r"(bytes) : "memory"); }
__device__ __forceinline__ void mbar_arrive(uint32_t bar) { asm volatile("mbarrier.arrive.shared::cta.b64 _, [%0];" :: "r"(bar) : "memory"); }
__device__ __forceinline__ void mbar_wait(uint32_t bar, uint32_t parity) {
    uint32_t ok; int it = 0;
    do {
        asm volatile("{ .reg .pred p; mbarrier.try_wait.parity.shared::cta.b64 p, [%1], %2; selp.u32 %0, 1, 0, p; }"
                     : "=r"(ok) : "r"(bar), "r"(parity) : "memory");
        if (++it > kSpinLimit) { TIMEOUT((bar & 1023) >> 3); break; }
    } while (!ok);
}
__device__ __forceinline__ bool mbar_try(uint32_t bar, uint32_t parity) {
    uint32_t ok;
    asm volatile("{ .reg .pred p; mbarrier.try_wait.parity.shared::cta.b64 p, [%1], %2; selp.u32 %0, 1, 0, p; }" : "=r"(ok) : "r"(bar), "r"(parity) : "memory");
    return ok;
}
__device__ __forceinline__ bool mbar_test(uint32_t bar, uint32_t parity) {
    uint32_t ok;
    asm volatile("{ .reg .pred p; mbarrier.test_wait.parity.shared::cta.b64 p, [%1], %2; selp.u32 %0, 1, 0, p; }" : "=r"(ok) : "r"(bar), "r"(parity) : "memory");
    return ok;
}
__device__ __forceinline__ void mbar_wait_fast(uint32_t bar, uint32_t parity) { if (!mbar_try(bar, parity)) mbar_wait(bar, parity); }
__device__ __forceinline__ void mbar_wait2(uint32_t bar0, uint32_t par0, uint32_t bar1, uint32_t par1) {
    uint32_t ok; int it = 0;
    do {
        asm volatile("{ .reg .pred p, q; mbarrier.try_wait.parity.shared::cta.b64 p, [%1], %2;\n"
                     "mbarrier.try_wait.parity.shared::cta.b64 q, [%3], %4; and.pred p, p, q; selp.u32 %0, 1, 0, p; }"
                     : "=r"(ok) : "r"(bar0), "r"(par0), "r"(bar1), "r"(par1) : "memory");
        if (++it > kSpinLimit) { TIMEOUT((bar0 & 1023) >> 3); break; }
    } while (!ok);
}
template <int N> __device__ __forceinline__ void reg_fence(float (&d)[N]) {
    #pragma unroll
    for (int i = 0; i < N; i++) asm volatile("" : "+f"(d[i]) :: "memory");
}
__device__ __forceinline__ void mbar_wait_cluster(uint32_t bar, uint32_t parity) {
    uint32_t ok; int it = 0;
    do {
        asm volatile("{ .reg .pred p; mbarrier.try_wait.parity.acquire.cluster.shared::cta.b64 p, [%1], %2; selp.u32 %0, 1, 0, p; }"
                     : "=r"(ok) : "r"(bar), "r"(parity) : "memory");
        if (++it > kSpinLimit) { TIMEOUT((bar & 1023) >> 3); break; }
    } while (!ok);
}
__device__ __forceinline__ void mbar_arrive_if(uint32_t bar, bool pred) {
    asm volatile("{ .reg .pred p; setp.ne.u32 p, %1, 0; @p mbarrier.arrive.shared::cta.b64 _, [%0]; }" :: "r"(bar), "r"((uint32_t)pred) : "memory");
}
template <int P> __device__ __forceinline__ void tick() {
    if (P > 1) { const uint32_t t = ((uint32_t)clock() | (P - 1)) + 1; while ((int)((uint32_t)clock() - t) < 0) {} }
}
__device__ __forceinline__ void warp_arrive(uint32_t bar) { __syncwarp(); if (elect_one()) mbar_arrive(bar); }
__device__ __forceinline__ void tma2d(uint32_t dst, const CUtensorMap* m, int c0, int c1, uint32_t bar) {
    asm volatile("cp.async.bulk.tensor.2d.shared::cluster.global.mbarrier::complete_tx::bytes [%0], [%1, {%3, %4}], [%2];"
                 :: "r"(dst), "l"(m), "r"(bar), "r"(c0), "r"(c1) : "memory");
}
__device__ __forceinline__ void tma3d(uint32_t dst, const CUtensorMap* m, int c0, int c1, int c2, uint32_t bar) {
    asm volatile("cp.async.bulk.tensor.3d.shared::cluster.global.mbarrier::complete_tx::bytes [%0], [%1, {%3, %4, %5}], [%2];"
                 :: "r"(dst), "l"(m), "r"(bar), "r"(c0), "r"(c1), "r"(c2) : "memory");
}
__device__ __forceinline__ void tma2d_mc(uint32_t dst, const CUtensorMap* m, int c0, int c1, uint32_t bar) {
    asm volatile("cp.async.bulk.tensor.2d.shared::cluster.global.mbarrier::complete_tx::bytes.multicast::cluster [%0], [%1, {%3, %4}], [%2], %5;"
                 :: "r"(dst), "l"(m), "r"(bar), "r"(c0), "r"(c1), "h"((uint16_t)3) : "memory");
}
__device__ __forceinline__ void bulk_g2s_mc(uint32_t dst, const void* src, uint32_t bytes, uint32_t bar) {
    asm volatile("cp.async.bulk.shared::cluster.global.mbarrier::complete_tx::bytes.multicast::cluster [%0], [%1], %2, [%3], %4;"
                 :: "r"(dst), "l"(src), "r"(bytes), "r"(bar), "h"((uint16_t)3) : "memory");
}
__device__ __forceinline__ void mbar_arrive_remote_if(uint32_t cluster_bar, bool pred) {
    asm volatile("{ .reg .pred p; setp.ne.u32 p, %1, 0; @p mbarrier.arrive.shared::cluster.b64 _, [%0]; }" :: "r"(cluster_bar), "r"((uint32_t)pred) : "memory");
}
__device__ __forceinline__ void bulk_g2s(uint32_t dst, const void* src, uint32_t bytes, uint32_t bar) {
    asm volatile("cp.async.bulk.shared::cluster.global.mbarrier::complete_tx::bytes [%0], [%1], %2, [%3];"
                 :: "r"(dst), "l"(src), "r"(bytes), "r"(bar) : "memory");
}
__device__ __forceinline__ void wg_fence()  { asm volatile("wgmma.fence.sync.aligned;" ::: "memory"); }
__device__ __forceinline__ void wg_commit() { asm volatile("wgmma.commit_group.sync.aligned;" ::: "memory"); }
template <int N> __device__ __forceinline__ void wg_wait() { asm volatile("wgmma.wait_group.sync.aligned %0;" :: "n"(N) : "memory"); }
__device__ __forceinline__ void named_bar(int id, int n) { asm volatile("bar.sync %0, %1;" :: "r"(id), "r"(n) : "memory"); }
__device__ __forceinline__ void named_arrive(int id, int n) { asm volatile("bar.arrive %0, %1;" :: "r"(id), "r"(n) : "memory"); }
__device__ __forceinline__ bool mbar_try2(uint32_t bar0, uint32_t par0, uint32_t bar1, uint32_t par1) {
    uint32_t ok;
    asm volatile("{ .reg .pred p, q; mbarrier.test_wait.parity.shared::cta.b64 p, [%1], %2;\n"
                 "mbarrier.test_wait.parity.shared::cta.b64 q, [%3], %4; and.pred p, p, q; selp.u32 %0, 1, 0, p; }"
                 : "=r"(ok) : "r"(bar0), "r"(par0), "r"(bar1), "r"(par1) : "memory");
    return ok;
}
__device__ __forceinline__ void fence_gpu() { asm volatile("fence.release.gpu;" ::: "memory"); }
__device__ __forceinline__ void fence_async_global() { asm volatile("fence.proxy.async.global;" ::: "memory"); }
__device__ __forceinline__ void fence_async_smem() { asm volatile("fence.proxy.async.shared::cta;" ::: "memory"); }
__device__ __forceinline__ uint32_t gtime32() { uint64_t t; asm volatile("mov.u64 %0, %%globaltimer;" : "=l"(t) :: "memory"); return (uint32_t)t; }
__device__ __forceinline__ uint32_t clk32() { uint64_t t; asm volatile("mov.u64 %0, %%clock64;" : "=l"(t) :: "memory"); return (uint32_t)t; }
__device__ __forceinline__ void spin_until(uint32_t t) { while ((int)(clk32() - t) < 0) {} }
#define SLEEPNS 20
__device__ __forceinline__ void sleep_until(uint32_t t) { while ((int)(clk32() - t) < 0) { if (SLEEPNS) __nanosleep(SLEEPNS); } }
__device__ __forceinline__ void st_flag(uint32_t* p, uint32_t v) {
    const uint64_t w = ((uint64_t)gtime32() << 32) | v;
    asm volatile("st.relaxed.gpu.global.u64 [%0], %1;" :: "l"(p), "l"(w) : "memory");
}
__device__ __forceinline__ void ld_flag_if(uint64_t& v, const uint32_t* p, bool pred) {
    asm volatile("{ .reg .pred p; setp.ne.u32 p, %2, 0; @p ld.relaxed.gpu.global.u64 %0, [%1]; }" : "+l"(v) : "l"(p), "r"((uint32_t)pred) : "memory");
}
__device__ __forceinline__ uint32_t ld_acq(const uint32_t* p) { uint32_t v; asm volatile("ld.acquire.gpu.global.u32 %0, [%1];" : "=r"(v) : "l"(p) : "memory"); return v; }
__device__ __forceinline__ uint32_t ld_rlx(const uint32_t* p) { uint32_t v; asm volatile("ld.relaxed.gpu.global.u32 %0, [%1];" : "=r"(v) : "l"(p) : "memory"); return v; }
template <class T> __device__ __forceinline__ T* opaque_ptr(T* p) { asm volatile("" : "+l"(p)); return p; }
__device__ __forceinline__ uint4 ld_rlx4(const uint4* p) {
    uint4 v; asm volatile("ld.relaxed.gpu.global.v4.u32 {%0,%1,%2,%3}, [%4];" : "=r"(v.x), "=r"(v.y), "=r"(v.z), "=r"(v.w) : "l"(p) : "memory"); return v;
}
__device__ __forceinline__ void st_ll(uint4* p, uint32_t a, uint32_t b, uint32_t tag) {
    uint64_t lo = ((uint64_t)tag << 32) | a, hi = ((uint64_t)tag << 32) | b;
    asm volatile("st.relaxed.gpu.global.v2.u64 [%0], {%1,%2};" :: "l"(p), "l"(lo), "l"(hi) : "memory");
}
__device__ __forceinline__ bool ld_ll(const uint4* p, uint32_t& a, uint32_t& b, uint32_t tag) {
    uint64_t lo, hi;
    asm volatile("ld.relaxed.gpu.global.v2.u64 {%0,%1}, [%2];" : "=l"(lo), "=l"(hi) : "l"(p) : "memory");
    a = (uint32_t)lo; b = (uint32_t)hi;
    return (uint32_t)(lo >> 32) == tag && (uint32_t)(hi >> 32) == tag;
}
__device__ __forceinline__ uint2 ld_acq2(const uint2* p) {
    uint2 v; asm volatile("ld.acquire.gpu.global.v2.u32 {%0,%1}, [%2];" : "=r"(v.x), "=r"(v.y) : "l"(p) : "memory"); return v;
}
__device__ __forceinline__ uint2 ld_rlx2(const uint2* p) {
    uint2 v; asm volatile("ld.relaxed.gpu.global.v2.u32 {%0,%1}, [%2];" : "=r"(v.x), "=r"(v.y) : "l"(p) : "memory"); return v;
}
__device__ __forceinline__ void stg1(uint32_t* p, uint32_t v) { asm volatile("st.global.u32 [%0], %1;" :: "l"(p), "r"(v) : "memory"); }
__device__ __forceinline__ void stg2(void* p, uint32_t x, uint32_t y) { asm volatile("st.global.v2.u32 [%0], {%1,%2};" :: "l"(p), "r"(x), "r"(y) : "memory"); }
__device__ __forceinline__ void stg4(void* p, uint32_t x, uint32_t y, uint32_t z, uint32_t w) { asm volatile("st.global.v4.u32 [%0], {%1,%2,%3,%4};" :: "l"(p), "r"(x), "r"(y), "r"(z), "r"(w) : "memory"); }
__device__ __forceinline__ uint32_t lds1(uint32_t a) { uint32_t v; asm volatile("ld.shared.u32 %0, [%1];" : "=r"(v) : "r"(a) : "memory"); return v; }
__device__ __forceinline__ uint2 lds2(uint32_t a) { uint2 v; asm volatile("ld.shared.v2.u32 {%0,%1}, [%2];" : "=r"(v.x), "=r"(v.y) : "r"(a) : "memory"); return v; }
__device__ __forceinline__ uint32_t set_par(uint32_t v, uint32_t mask, uint32_t par) {
    uint32_t r; asm("lop3.b32 %0, %1, %2, %3, 0xb8;" : "=r"(r) : "r"(v), "r"(mask), "r"(par)); return r;
}
__device__ __forceinline__ void st_gen4(void* p, uint32_t x, uint32_t y, uint32_t z, uint32_t w) { asm volatile("st.v4.u32 [%0], {%1,%2,%3,%4};" :: "l"(p), "r"(x), "r"(y), "r"(z), "r"(w) : "memory"); }
__device__ __forceinline__ float tanh_hw(float x) { float r; asm("tanh.approx.f32 %0, %1;" : "=f"(r) : "f"(x)); return r; }
__device__ __forceinline__ bool bar_any(int id, int n, bool v) {
    uint32_t r;
    asm volatile("{ .reg .pred p, q; setp.ne.u32 p, %3, 0; bar.red.or.pred q, %1, %2, p; selp.u32 %0, 1, 0, q; }" : "=r"(r) : "r"(id), "r"(n), "r"((uint32_t)v) : "memory");
    return r;
}
__device__ __forceinline__ void sts4(uint32_t a, uint32_t x, uint32_t y, uint32_t z, uint32_t w) { asm volatile("st.shared.v4.u32 [%0], {%1,%2,%3,%4};" :: "r"(a), "r"(x), "r"(y), "r"(z), "r"(w) : "memory"); }
__device__ __forceinline__ uint4 lds4(uint32_t a) { uint4 v; asm volatile("ld.shared.v4.u32 {%0,%1,%2,%3}, [%4];" : "=r"(v.x), "=r"(v.y), "=r"(v.z), "=r"(v.w) : "r"(a) : "memory"); return v; }
__device__ __forceinline__ uint32_t pack_bf16(float lo, float hi) { uint32_t r; asm("cvt.rn.bf16x2.f32 %0, %1, %2;" : "=r"(r) : "f"(hi), "f"(lo)); return r; }
__device__ __forceinline__ float bf_lo(uint32_t v) { return __uint_as_float(v << 16); }
__device__ __forceinline__ float bf_hi(uint32_t v) { return __uint_as_float(v & 0xffff0000u); }
__device__ __forceinline__ uint32_t sub_bf16x2(uint32_t a, uint32_t b) { uint32_t r; asm volatile("sub.rn.bf16x2 %0, %1, %2;" : "=r"(r) : "r"(a), "r"(b)); return r; }
__device__ __forceinline__ uint32_t add_bf16x2(uint32_t a, uint32_t b) { uint32_t r; asm volatile("add.rn.bf16x2 %0, %1, %2;" : "=r"(r) : "r"(a), "r"(b)); return r; }
__device__ __forceinline__ uint32_t sqr_bf16x2(uint32_t a) { uint32_t r; asm volatile("mul.rn.bf16x2 %0, %1, %1;" : "=r"(r) : "r"(a)); return r; }
__device__ __forceinline__ uint32_t sqa_bf16x2(uint32_t a, uint32_t c) { uint32_t r; asm volatile("fma.rn.bf16x2 %0, %1, %1, %2;" : "=r"(r) : "r"(a), "r"(c)); return r; }
__device__ __forceinline__ uint32_t movm(uint32_t a) { uint32_t r; asm volatile("movmatrix.sync.aligned.m8n8.trans.b16 %0, %1;" : "=r"(r) : "r"(a)); return r; }
__device__ __forceinline__ float ex2(float x) { float r; asm("ex2.approx.ftz.f32 %0, %1;" : "=f"(r) : "f"(x)); return r; }
__device__ __forceinline__ float rsq(float x) { float r; asm("rsqrt.approx.ftz.f32 %0, %1;" : "=f"(r) : "f"(x)); return r; }
__device__ __forceinline__ float rcp(float x) { float r; asm("rcp.approx.ftz.f32 %0, %1;" : "=f"(r) : "f"(x)); return r; }
__device__ __forceinline__ void mma16816(float (&c)[4], uint32_t a0, uint32_t a1, uint32_t a2, uint32_t a3, uint32_t b0, uint32_t b1) {
    asm("mma.sync.aligned.m16n8k16.row.col.f32.bf16.bf16.f32 {%0,%1,%2,%3}, {%4,%5,%6,%7}, {%8,%9}, {%0,%1,%2,%3};"
        : "+f"(c[0]), "+f"(c[1]), "+f"(c[2]), "+f"(c[3]) : "r"(a0), "r"(a1), "r"(a2), "r"(a3), "r"(b0), "r"(b1));
}
__device__ __forceinline__ void mma1688(float (&c)[4], uint32_t a0, uint32_t a1, uint32_t b0) {
    asm("mma.sync.aligned.m16n8k8.row.col.f32.bf16.bf16.f32 {%0,%1,%2,%3}, {%4,%5}, {%6}, {%0,%1,%2,%3};"
        : "+f"(c[0]), "+f"(c[1]), "+f"(c[2]), "+f"(c[3]) : "r"(a0), "r"(a1), "r"(b0));
}
__device__ __forceinline__ float quad_sum(float v) { v += __shfl_xor_sync(~0u, v, 1); v += __shfl_xor_sync(~0u, v, 2); return v; }
__device__ __forceinline__ float quad_max(float v) { v = fmaxf(v, __shfl_xor_sync(~0u, v, 1)); v = fmaxf(v, __shfl_xor_sync(~0u, v, 2)); return v; }
__device__ __forceinline__ uint64_t make_desc(uint32_t addr, uint32_t lbo, bool swz, uint32_t sbo = 1024) {
    const uint32_t lo = __shfl_sync(~0u, ((addr & 0x3FFFF) >> 4) | ((lbo >> 4) << 16), 0);
    const uint32_t hi = __shfl_sync(~0u, (swz ? 0x40000000u : 0u) + (sbo >> 4) + (threadIdx.x & 31), 0);
    return ((uint64_t)hi << 32) | lo;
}
template <int I, int N, class F> __device__ __forceinline__ void static_for(F&& f) {
    if constexpr (I < N) { f(std::integral_constant<int, I>{}); static_for<I + 1, N>(f); }
}
__device__ __forceinline__ uint32_t opaque(uint32_t v) { asm volatile("" : "+r"(v)); return v; }
template <int BOFF, int SCALE_D>
__device__ __forceinline__ void wgmma_rs_n56(float (&d)[28], uint32_t a0, uint32_t a1, uint32_t a2, uint32_t a3, uint64_t db) {
    asm volatile("{ .reg .b64 db; add.s64 db, %32, %33;\n"
        "wgmma.mma_async.sync.aligned.m64n56k16.f32.bf16.bf16 "
        "{%0, %1, %2, %3, %4, %5, %6, %7, %8, %9, %10, %11, %12, %13, %14, %15, %16, %17, %18, %19, %20, %21, %22, %23, %24, %25, %26, %27}, "
        "{%28, %29, %30, %31}, db, %34, 1, 1, 1; }"
        : "+f"(d[0]), "+f"(d[1]), "+f"(d[2]), "+f"(d[3]), "+f"(d[4]), "+f"(d[5]), "+f"(d[6]), "+f"(d[7]),
        "+f"(d[8]), "+f"(d[9]), "+f"(d[10]), "+f"(d[11]), "+f"(d[12]), "+f"(d[13]), "+f"(d[14]), "+f"(d[15]),
        "+f"(d[16]), "+f"(d[17]), "+f"(d[18]), "+f"(d[19]), "+f"(d[20]), "+f"(d[21]), "+f"(d[22]), "+f"(d[23]),
        "+f"(d[24]), "+f"(d[25]), "+f"(d[26]), "+f"(d[27])
        : "r"(a0), "r"(a1), "r"(a2), "r"(a3), "l"(db), "n"(BOFF >> 4), "n"(SCALE_D));
}
template <int AOFF, int BOFF>
__device__ __forceinline__ void wgmma_ss_n56(float (&d)[28], uint64_t da, uint64_t db) {
    asm volatile("{ .reg .b64 da, db; add.s64 da, %28, %30; add.s64 db, %29, %31;\n"
        "wgmma.mma_async.sync.aligned.m64n56k16.f32.bf16.bf16 "
        "{%0, %1, %2, %3, %4, %5, %6, %7, %8, %9, %10, %11, %12, %13, %14, %15, %16, %17, %18, %19, %20, %21, %22, %23, %24, %25, %26, %27}, "
        "da, db, 1, 1, 1, 0, 1; }"
        : "+f"(d[0]), "+f"(d[1]), "+f"(d[2]), "+f"(d[3]), "+f"(d[4]), "+f"(d[5]), "+f"(d[6]), "+f"(d[7]),
        "+f"(d[8]), "+f"(d[9]), "+f"(d[10]), "+f"(d[11]), "+f"(d[12]), "+f"(d[13]), "+f"(d[14]), "+f"(d[15]),
        "+f"(d[16]), "+f"(d[17]), "+f"(d[18]), "+f"(d[19]), "+f"(d[20]), "+f"(d[21]), "+f"(d[22]), "+f"(d[23]),
        "+f"(d[24]), "+f"(d[25]), "+f"(d[26]), "+f"(d[27])
        : "l"(da), "l"(db), "n"(AOFF >> 4), "n"(BOFF >> 4));
}
template <int AOFF, int BOFF>
__device__ __forceinline__ void wgmma_ss_n112(float (&d)[56], uint64_t da, uint64_t db) {
    asm volatile("{ .reg .b64 da, db; add.s64 da, %56, %58; add.s64 db, %57, %59;\n"
        "wgmma.mma_async.sync.aligned.m64n112k16.f32.bf16.bf16 "
        "{%0, %1, %2, %3, %4, %5, %6, %7, %8, %9, %10, %11, %12, %13, %14, %15, %16, %17, %18, %19, %20, %21, %22, %23, %24, %25, %26, %27, %28, %29, %30, %31, %32, %33, %34, %35, %36, %37, %38, %39, %40, %41, %42, %43, %44, %45, %46, %47, %48, %49, %50, %51, %52, %53, %54, %55}, "
        "da, db, 1, 1, 1, 1, 1; }"
        : "+f"(d[0]), "+f"(d[1]), "+f"(d[2]), "+f"(d[3]), "+f"(d[4]), "+f"(d[5]), "+f"(d[6]), "+f"(d[7]),
        "+f"(d[8]), "+f"(d[9]), "+f"(d[10]), "+f"(d[11]), "+f"(d[12]), "+f"(d[13]), "+f"(d[14]), "+f"(d[15]),
        "+f"(d[16]), "+f"(d[17]), "+f"(d[18]), "+f"(d[19]), "+f"(d[20]), "+f"(d[21]), "+f"(d[22]), "+f"(d[23]),
        "+f"(d[24]), "+f"(d[25]), "+f"(d[26]), "+f"(d[27]), "+f"(d[28]), "+f"(d[29]), "+f"(d[30]), "+f"(d[31]),
        "+f"(d[32]), "+f"(d[33]), "+f"(d[34]), "+f"(d[35]), "+f"(d[36]), "+f"(d[37]), "+f"(d[38]), "+f"(d[39]),
        "+f"(d[40]), "+f"(d[41]), "+f"(d[42]), "+f"(d[43]), "+f"(d[44]), "+f"(d[45]), "+f"(d[46]), "+f"(d[47]),
        "+f"(d[48]), "+f"(d[49]), "+f"(d[50]), "+f"(d[51]), "+f"(d[52]), "+f"(d[53]), "+f"(d[54]), "+f"(d[55])
        : "l"(da), "l"(db), "n"(AOFF >> 4), "n"(BOFF >> 4));
}

struct Params {
    const __nv_bfloat16 *x, *wqkv;
    Scratch* sc;
    const __nv_bfloat16 *wo, *w1, *w2, *b1, *b2;
    __nv_bfloat16* out;
};

__global__ void __cluster_dims__(2, 1, 1) __launch_bounds__(384, 1)
fused_kernel(const Params prm, const __grid_constant__ CUtensorMap mX2, const __grid_constant__ CUtensorMap mX, const __grid_constant__ CUtensorMap mWqkv,
             const __grid_constant__ CUtensorMap mWo, const __grid_constant__ CUtensorMap mW1,
             const __grid_constant__ CUtensorMap mW2)
{
    extern __shared__ __align__(1024) unsigned char smem_raw[];
    if (threadIdx.x < 126) {
        const uint32_t i = threadIdx.x, t = clk32() + (i >> 5) * PFD;
        const char* px = (const char*)prm.x + (blockIdx.x * 16 + (i & 15)) * 896 + (i >> 4) * 128;
        const char* pw = (const char*)prm.wqkv + blockIdx.x * 2688 + i * 128 + (896 - 112 * 128);
        spin_until(t);
        asm volatile("prefetch.global.L2 [%0];" :: "l"(i < 112 ? px : pw) : "memory");
    }
    if (threadIdx.x == 128) { asm volatile("prefetch.tensormap [%0];" :: "l"(&mX2) : "memory"); asm volatile("prefetch.tensormap [%0];" :: "l"(&mWqkv) : "memory"); }
    uint32_t sb = (uint32_t)__cvta_generic_to_shared(smem_raw);
    asm volatile("mov.u32 %0, %0;" : "+r"(sb));
    const uint32_t bar0 = sb + SM_BAR;
    auto BAR = [&](int i) { return bar0 + 8u * i; };

    const int tid = threadIdx.x, lane = tid & 31;
    const int warp = __shfl_sync(~0u, tid >> 5, 0);
    const int b = __shfl_sync(~0u, (int)blockIdx.x, 0);
    const int rank = b & 1;
    const int cl = (b >> 1) - 4, cq = ((cl - 32) * 37) >> 8;
    const int res = cl < 0 ? 0 : cl < 32 ? cl & 7 : cl - 31 - 7 * cq;
    const int rnd = cl < 0 ? cl + 8 : cl < 32 ? cl >> 3 : 4 + cq;
    const int hg = (res & 1) * 4 + (rnd & 3);
    const int ti = (res >> 1) * 4 + (rnd >> 2) * 2 + rank;
    const int a2p = res & 1, a2j = rnd & 3;
    const int a2s = ti * 2 + a2p;
    const bool g1_on = rnd != 7;
    const int g1j = (rnd < 6 ? rnd : res) & 1, g1f = rnd < 6 ? res * 3 + (rnd >> 1) : 24 + (res >> 1);
    const int g2j = rnd & 1, g2s = res * 4 + (rnd >> 1);
    uint32_t pbar0;
    asm volatile("mapa.shared::cluster.u32 %0, %1, %2;" : "=r"(pbar0) : "r"(bar0), "r"(rank ^ 1));
    auto pair_arrive = [&](int i) { __syncwarp(); const bool l = elect_one(); mbar_arrive_if(BAR(i), l); mbar_arrive_remote_if(pbar0 + 8u * i, l); };
    const int wcol = hg * 56 - (hg & 1) * 8;

    if (warp == 8) {
        if (elect_one()) {
            #pragma unroll
            for (int i = 0; i < B_WQF; i++) mbar_init(BAR(i), 1);
            asm volatile("fence.mbarrier_init.release.cluster;" ::: "memory");
            fence_async_smem();
            #pragma unroll
            for (int kb = 0; kb < 7; kb++) {
                tma3d(sb + kb * 16384, &mX2, kb * 64, ti * 64, 0, BAR(B_XF + kb));
                mbar_expect(BAR(B_XF + kb), 16384);
                if (kb == 0 && PFX != 3) asm volatile("prefetch.tensormap [%0];" :: "l"(&mWqkv) : "memory");
            }
        }
    } else if (warp > 8) {
        if (elect_one()) {
            if (warp == 9) {
                #pragma unroll
                for (int i = B_WQF; i < B_AF; i++) mbar_init(BAR(i), i < B_XC ? 1 : i < B_A1D ? 16 : i < B_BE ? 8 : 4);
            } else if (warp == 10) {
                #pragma unroll
                for (int i = B_AF; i < B_BL; i++) mbar_init(BAR(i), 1);
            } else {
                #pragma unroll
                for (int i = B_BL; i < B_COUNT; i++) mbar_init(BAR(i), i == B_HD ? 8 : 1);
            }
            asm volatile("fence.mbarrier_init.release.cluster;" ::: "memory");
            fence_async_smem();
        }
    }
    __syncwarp();
    __syncthreads();
    asm volatile("barrier.cluster.arrive.relaxed.aligned;" ::: "memory");
    if (tid < 256) TR(0);
    if (tid == 0) TRG(61);

    if (warp >= 8) {
        asm volatile("setmaxnreg.dec.sync.aligned.u32 40;");
        asm volatile("barrier.cluster.wait.aligned;" ::: "memory");
        auto fetch_halo = [&](int p, uint32_t tag) {
            uint4 u[4];
            #pragma unroll
            for (int c = 0; c < 4; c++) u[c] = make_uint4(0u, 0u, 0u, 0u);
            const uint4* hp = opaque_ptr(&prm.sc->halo[(((ti - 1) * 8 + hg) * 2 + p) * 128 + lane]);
            mbar_wait(BAR(B_KVC), 0);
            if (p == 0) TRW(51);
            sleep_until(clk32() + HDELAY);
            if (ti > 0) {
                int it = 0;
                do {
                    #pragma unroll
                    for (int c = 0; c < 4; c++) u[c] = ld_rlx4(hp + c * 32);
                    if (it) RETRY_COUNT(4);
                    if (++it > kSpinLimit) { TIMEOUT(101); break; }
                } while (__any_sync(~0u, ((u[0].x ^ tag) | (u[1].x ^ tag) | (u[2].x ^ tag) | (u[3].x ^ tag)) & ~lane & 1));
            }
            #pragma unroll
            for (int c = 0; c < 4; c++) sts4(sb + SM_STG + p * 8192 + 3 * 2048 + lane * 16 + c * 512, u[c].x, u[c].y, u[c].z, u[c].w);
            warp_arrive(BAR(B_HL + p));
        };
        if (warp & 1) {
            uint32_t tag;
            if (warp == 11) {
                tag = *(volatile uint32_t*)&prm.sc->epoch + 1;
            #pragma unroll 1
            for (int i = 0; i < 8; i++) prm.sc->halo[(ti * 8 + hg) * 256 + i * 32 + lane] = make_uint4(~tag, 0u, 0u, 0u);
            ((uint4*)prm.sc->stats)[(a2s * 4 + a2j) * 64 + lane] = ((uint4*)prm.sc->stats)[(a2s * 4 + a2j) * 64 + 32 + lane] = make_uint4(~tag, ~tag, ~tag, ~tag);
            prm.sc->flag_h[(a2s * 4 + a2j) * FS + lane] = 0;
            prm.sc->flag_o[(ti * 16 + hg) * FS + lane] = prm.sc->flag_o[(ti * 16 + 8 + hg) * FS + lane] = 0;
            __syncwarp();
            if (lane == 0) {
                asm volatile("st.shared.v2.u32 [%0], {%1, %2};" :: "r"(sb + SM_EPOCH), "r"(tag), "r"(gtime32()) : "memory");
                mbar_arrive(BAR(B_EP));
            }
            if (lane < 4) mbar_expect(BAR(B_RF + lane), 7168);
            __syncwarp();
            TRW(44);
            } else {
                mbar_wait(BAR(B_EP), 0);
                tag = lds1(sb + SM_EPOCH);
            }
            fetch_halo((warp >> 1) & 1, tag);
        }
        if (warp < 10) {
          auto load_slab = [&](int s, bool second) {
              mbar_expect(BAR(B_AF + s), 8192);
              if (!second) tma2d(sb + s * 8192, &mW1, (s & 1) * kF + g1f * 64, (rank * 8 + (s >> 1)) * 64, BAR(B_AF + s));
              else         tma2d(sb + s * 8192, &mW2, g2s * 64, (rank * 14 + s - 2) * 64, BAR(B_AF + s));
          };
          if (warp == 8) {
            if (elect_one()) {
                #pragma unroll 1
                for (int s = 0; s < 7; s++) {
                    mbar_expect(BAR(B_WKVF + s), 16384);
                    tma2d_mc(sb + SM_WKV + s * 16384 + rank * 8192, &mWqkv, (1 + rank) * kD + wcol, s * 64, BAR(B_WKVF + s));
                }
            }
            __syncwarp();
            mbar_wait(BAR(B_XC), 0);
            if (elect_one()) {
                asm volatile("prefetch.tensormap [%0];" :: "l"(&mX) : "memory");
                asm volatile("prefetch.tensormap [%0];" :: "l"(&mWo) : "memory");
                asm volatile("prefetch.tensormap [%0];" :: "l"(&mW1) : "memory");
                asm volatile("prefetch.tensormap [%0];" :: "l"(&mW2) : "memory");
                mbar_expect(BAR(B_WQF), 57344);
                #pragma unroll 1
                for (int s = rank; s < 7; s += 2) tma2d_mc(sb + SM_WQ + s * 8192, &mWqkv, wcol, s * 64, BAR(B_WQF));
                mbar_expect(BAR(B_XRF), 16384);
                tma2d(sb + SM_XR, &mX, a2p * kD + a2j * 112, ti * 64, BAR(B_XRF));
                tma2d(sb + SM_XR + 8192, &mX, a2p * kD + a2j * 112 + 48, ti * 64, BAR(B_XRF));
            }
            __syncwarp();
            #pragma unroll 1
            for (int h = 0; h < 2; h++) {
                mbar_wait(BAR(B_KV3 + h), 0);
                if (h) mbar_wait2(BAR(B_HL), 0, BAR(B_HL + 1), 0);
                if (elect_one()) {
                    mbar_expect(BAR(B_WOF + h), 57344);
                    tma2d_mc(sb + SM_WKV + h * 57344 + rank * 28672, &mWo, a2j * 112 + rank * 48, h * 224, BAR(B_WOF + h));
                    if (g1_on && h == AFIRST) { load_slab(0, false); load_slab(1, false); load_slab(2, false); }
                }
                __syncwarp();
            }
            if (g1_on) {
                mbar_wait2(BAR(B_XD), 0, BAR(B_BL + NB + 3), 0);
                #pragma unroll 1
                for (int i = 3; i < NPRE; i++) {
                    if (i == 7) mbar_wait(BAR(B_OC), 0);
                    if (elect_one()) load_slab(i, false);
                    __syncwarp();
                }
            } else {
                mbar_wait(BAR(B_HD), 0);
                mbar_arrive_remote_if(pbar0 + 8u * B_PD, lane == 0);
                mbar_wait(BAR(B_GO), 0);
                uint32_t tg = lds1(sb + SM_TG + 4);
                tg += max((int)(lds1(sb + SM_TG2) - tg), 0);
                int it = 0;
                while ((int)(gtime32() - tg) < 0 && ++it < 256) {}
                const uint32_t t0 = clk32();
                if (lane < 2) {
                    asm volatile("st.shared.u32 [%0], %1;" :: "r"(sb + SM_TG + 8 + lane * 4), "r"(t0 + (lane ? CN3 : CN2)) : "memory");
                    mbar_arrive(BAR(B_GD + lane));
                }
                __syncwarp();
                #pragma unroll 1
                for (int s = 2; s < 16; s++) {
                    sleep_until(t0 + W2OFF + s * W2PACE);
                    if (elect_one()) load_slab(s, true);
                    __syncwarp();
                }
            }
          } else {
            TRW(58);
            const uint32_t tag = lds1(sb + SM_EPOCH);
            if (lane < 4) mbar_expect(BAR(B_BL + NB + lane), 14336);
            #pragma unroll 1
            for (int e = 0; e < 2; e++) {
                const uint32_t* fp = e ? &prm.sc->flag_h[(rank * 64 + lane) * FS] : &prm.sc->flag_o[(a2s * 8 + (lane & 7)) * FS];
                if (e) {
                    mbar_wait2(BAR(B_BF + NB + 2), 0, BAR(B_BF + NB + 3), 0);
                    if (lane == 0) st_flag(&prm.sc->flag_h[(a2s * 4 + a2j) * FS], tag);
                    __syncwarp();
                    TRW(57);
                    sleep_until(clk32() + PDELAY);
                }
                uint64_t v0 = 0, v1 = e ? 0 : tag;
                int it = 0;
                do {
                    ld_flag_if(v0, fp, (uint32_t)v0 != tag); ld_flag_if(v1, fp + 32 * FS, (uint32_t)v1 != tag);
                    if (++it > kSpinLimit) { TIMEOUT(108); break; }
                } while (__any_sync(~0u, (uint32_t)v0 != tag || (uint32_t)v1 != tag));
                const uint32_t gbase = __shfl_sync(~0u, (uint32_t)(v0 >> 32), 0);
                const uint32_t tg = gbase + (e ? DELTA : DELTAO)
                                  + __reduce_max_sync(~0u, max((int)((uint32_t)(v0 >> 32) - gbase) - e * (lane >> 2) * SOFF, e ? (int)((uint32_t)(v1 >> 32) - gbase) - 8 * SOFF : 0));
                TRW(e ? 40 : 53);
                mbar_wait(BAR(B_A1D), 0);
                if (elect_one()) {
                    if (e) {
                        asm volatile("st.async.shared::cluster.mbarrier::complete_tx::bytes.b32 [%0], %1, [%2];"
                                     :: "r"(pbar0 + (SM_TG2 - SM_BAR)), "r"(tg), "r"(pbar0 + 8u * B_GO) : "memory");
                        asm volatile("st.shared.u32 [%0], %1;" :: "r"(sb + SM_TG + 4), "r"(tg) : "memory");
                        mbar_expect(BAR(B_GO), 4);
                    } else {
                        it = 0;
                        while ((int)(gtime32() - tg) < 0 && ++it < 256) {}
                        #pragma unroll
                        for (int i = 0; i < 4; i++) bulk_g2s(sb + SM_WQ + i * 14336, &prm.sc->o[(a2s * 4 + i) * 896], 14336, BAR(B_BL + NB + i));
                    }
                }
                __syncwarp();
            }
          }
          if (elect_one()) {
              const int h = ~warp & 1;
              const char* src1 = (const char*)&prm.sc->hn[(rank * 16 + h) * 3584 + g1j * 896];
              const char* src2 = (const char*)&prm.sc->g[(rank * 14 + h) * 3584 + g2j * 896];
              const long long jump = src2 - src1 - (16 * 57344 + 2 * 14336);
              const char* src = g1_on ? src1 - 2 * 57344 : src2;
              const uint32_t amask = g1_on ? (h ? kAMask1 : kAMask0) : 0u;
              uint32_t slot = g1_on ? NB - 2 + h : h, ph = g1_on ? 0 : 1, gate = g1_on ? 0 : 2, tmin = 0;
              CAP_DECL(ti_, 0);
              #pragma unroll 1
              for (int q = g1_on ? 0 : 17; q < 31; q++) {
                  const uint32_t eb = q ? BAR(B_BE) + slot * 8 : BAR(B_XF), dst = sb + SM_B + slot * 14336;
                  if ((0x1020003u >> q) & 1) {
                      mbar_wait(BAR(B_HD + gate), 0);
                      tmin = lds1(sb + SM_TG + gate * 4);
                      if (gate < 2) {
                          tmin += max((int)(lds1(gate ? sb + SM_TG2 : sb + SM_TG) - tmin), 0);
                          int it = 0;
                          while ((int)(gtime32() - tmin) < 0 && ++it < 256) {}
                          tmin = clk32();
                      }
                      tmin += h * PACE1;
                      gate++;
                  }
                  spin_until(tmin);
                  tmin += PACE2;
                  if (!mbar_try(eb, ph)) mbar_wait(eb, ph);
                  if (q) {
                      bulk_g2s(dst, src, 14336, eb + (B_BL - B_BE) * 8);
                      mbar_expect(eb + (B_BL - B_BE) * 8, 14336);
                      CAP(ti_);
                  }
                  mbar_arrive_remote_if(pbar0 + 8u * B_PD, h && q == 12);
                  if ((amask >> q) & 1) {
                      if (q < 12) load_slab(NPRE - W1Q + q, false);
                      else load_slab(2 + ((2 * q + h - 27) * 13 + 19) / 20, true);
                  }
                  src += 2 * 57344 + (q == 8 ? 2 * 14336 - 16 * 57344 : q == 16 ? jump : q == 23 ? 2 * 14336 - 14 * 57344 : 0);
                  slot += 2;
                  if (slot >= NB) { slot -= NB; ph ^= 1; }
              }
          }
        } else {
          if (warp == 10) {
            mbar_wait(BAR(PFBAR), 0);
            const char* p1 = (const char*)prm.w1 + (size_t)b * 57344 + lane * 128;
            const char* p2 = (const char*)prm.w2 + (size_t)b * 57344 + lane * 128;
            if (lane < 27) asm volatile("prefetch.global.L2 [%0];" :: "l"(lane < 25 ? (const char*)prm.wo + min(b * 25 + lane, 3135) * 128
                                                                          : lane == 25 ? (const char*)prm.b1 + (b % 28) * 128 : (const char*)prm.b2 + (b & 31) * 128));
            uint32_t tnext = clk32();
            #pragma unroll 1
            for (int i = 0; i < 28; i++) {
                while ((int)(clk32() - tnext) < 0) __nanosleep(40);
                asm volatile("prefetch.global.L2 [%0];" :: "l"(i < 14 ? p1 + i * 4096 : p2 + (i - 14) * 4096));
                tnext += PFPACE;
            }
            mbar_wait(BAR(B_EP), 0);
          }
          const uint32_t tag = lds1(sb + SM_EPOCH);
          const int h = warp & 1;
          const bool lead = elect_one();
          const uint32_t w0o = lane * 132, l3 = lane < 16 ? 12288 : 0;
          uint32_t wo = w0o ^ (h << 6), slot = NB + h, dst = sb + SM_WQ + h * 14336, ph = 0, rph = 0, af = BAR(B_WOF), aph = 0;
          #pragma unroll 1
          for (int q = -1; q < 31; q++) {
              const uint32_t rb = bar0 + slot * 8;
              auto stale = [&]() {
                  uint32_t d;
                  asm volatile("{ .reg .b32 x, y, z, u;\n"
                               "ld.shared.u32 x, [%1]; ld.shared.u32 y, [%1 + 4096]; ld.shared.u32 z, [%1 + 8192]; ld.shared.u32 u, [%2];\n"
                               "lop3.b32 x, x, y, %3, 0x7e; lop3.b32 z, z, u, %3, 0x7e; lop3.b32 %0, x, z, 1, 0xa8; }"
                               : "=r"(d) : "r"(dst + wo), "r"(dst + wo + l3), "r"(tag) : "memory");
                  return __any_sync(~0u, d);
              };
              mbar_wait(rb + B_BF * 8, ph ^ 1);
              mbar_wait(rb + B_BL * 8, ph);
              const bool aok = mbar_test(af, aph);
              bool bad = stale();
              if (!aok) mbar_wait(af, aph);
              mbar_arrive_if(rb + B_BF * 8, lead && !bad);
              if (bad) {
                  RETRY_COUNT(q < 1 ? 1 : q < 17 ? 0 : !g1_on ? 5 : q < 24 ? 2 : 6);
                  const int e = (q > 8) + (q > 16) + (q > 23), s = (q - (e < 3 ? 1 + 8 * e : 24)) * 2 + h;
                  const char* src = (const char*)(q < 1 ? &prm.sc->o[(a2s * 4 + s + 4) * 896] : e < 2 ? &prm.sc->hn[(rank * 16 + s) * 3584 + (g1j + 2 * e) * 896] : &prm.sc->g[(rank * 14 + s) * 3584 + (g2j + 2 * e - 4) * 896]);
                  int it = 0;
                  do {
                      if (++it > kSpinLimit) { TIMEOUT(111); break; }
                      const uint32_t* p = (const uint32_t*)(src + wo);
                      if (it > RELOAD1 && __any_sync(~0u, ((ld_rlx(p) ^ tag) | (ld_rlx(p + 1024) ^ tag) | (ld_rlx(p + 2048) ^ tag) | (ld_rlx(p + l3 / 4) ^ tag)) & 1)) continue;
                      if (lead) {
                          mbar_expect(BAR(B_RT + h), 14336);
                          bulk_g2s(dst, src, 14336, BAR(B_RT + h));
                      }
                      __syncwarp();
                      mbar_wait(BAR(B_RT + h), rph);
                      rph ^= 1;
                      bad = stale();
                  } while (bad);
                  mbar_arrive_if(rb + B_BF * 8, lead);
              }
              af += q < 0 ? 8 : q == 8 ? -112 : (0x810000u >> q) & 1 ? -96 : 16;
              slot += 2; dst += 28672;
              if (q > 0 && slot >= NB) { slot -= NB; dst -= NB * 14336; ph ^= 1; }
              if (q == 16) { wo = w0o ^ (g2j << 6); aph = 1; }
              if (q == 0) {
                  slot = h; dst = sb + SM_B + h * 14336; af = BAR(B_AF + h + (g1_on ? 0 : 2));
                  wo = w0o ^ ((g1_on ? g1j : g2j) << 6); q = g1_on ? 0 : 16;
              }
          }
        }
    } else {
        asm volatile("setmaxnreg.inc.sync.aligned.u32 232;");
        asm volatile("barrier.cluster.wait.aligned;" ::: "memory");
        const int wg = warp >> 2, w = warp & 3;
        const int g = lane >> 2, t = lane & 3;
        uint32_t tag;
        __nv_bfloat16 bias1;
        {
            const uint64_t dw = make_desc(sb + (hg & 1) * 16, 0, true);
            uint32_t a[28][4];
            float sm[4][4] = {};
            {
                const int r = w * 16 + (lane & 15);
                const uint32_t rowa = sb + wg * 8192 + r * 128;
                #pragma unroll
                for (int k = 0; k < 28; k++) {
                    if (XW == 1 && (k & 3) == 0) mbar_wait(BAR(B_XF + (k >> 2)), 0);
                    if (XW == 2 && k == 0) mbar_wait(BAR(B_XF), 0);
                    if (XW == 2 && (k & 7) == 4) mbar_wait2(BAR(B_XF + (k >> 2)), 0, BAR(B_XF + (k >> 2) + 1), 0);
                    const uint32_t addr = rowa + (k >> 2) * 16384 + ((((k & 3) * 2 + (lane >> 4)) ^ (r & 7)) << 4);
                    uint32_t (&f)[4] = a[k];
                    asm volatile("ldmatrix.sync.aligned.m8n8.x4.shared.b16 {%0,%1,%2,%3}, [%4];"
                                 : "=r"(f[0]), "=r"(f[1]), "=r"(f[2]), "=r"(f[3]) : "r"(addr) : "memory");
                    if (XLAG == 0) mma16816(sm[k & 3], f[0], f[1], f[2], f[3], 0x3F803F80u, 0x3F803F80u);
                    else if (k >= 4) mma16816(sm[k & 3], a[k - 4][0], a[k - 4][1], a[k - 4][2], a[k - 4][3], 0x3F803F80u, 0x3F803F80u);
                }
                if (XLAG) {
                    #pragma unroll
                    for (int k = 24; k < 28; k++) mma16816(sm[k & 3], a[k][0], a[k][1], a[k][2], a[k][3], 0x3F803F80u, 0x3F803F80u);
                }
            }
            const float mean0 = ((sm[0][0] + sm[1][0]) + (sm[2][0] + sm[3][0])) * (1.f / kD);
            const float mean1 = ((sm[0][2] + sm[1][2]) + (sm[2][2] + sm[3][2])) * (1.f / kD);
            const uint32_t mb0 = pack_bf16(mean0, mean0), mb1 = pack_bf16(mean1, mean1);
            pair_arrive(B_XC);
            TR(1);
            float ak[28], av[28], aq[28];
            float ss0 = 0.f, ss1 = 0.f, ss2 = 0.f, ss3 = 0.f;
            uint32_t p0, p1;
            static_for<0, 7>([&](auto S_) {
                constexpr int s = decltype(S_)::value;
                #pragma unroll
                for (int q = 0; q < 4; q++) {
                    uint32_t (&f)[4] = a[s * 4 + q];
                    f[0] = sub_bf16x2(f[0], mb0); f[1] = sub_bf16x2(f[1], mb1);
                    f[2] = sub_bf16x2(f[2], mb0); f[3] = sub_bf16x2(f[3], mb1);
                }
                mbar_wait(BAR(B_WKVF + s), 0);
                wg_fence();
                static_for<0, 4>([&](auto Q_) {
                    constexpr int q = decltype(Q_)::value;
                    uint32_t (&f)[4] = a[s * 4 + q];
                    wgmma_rs_n56<SM_WKV + s * 16384 + q * 2048, (s | q) != 0>(ak, f[0], f[1], f[2], f[3], dw);
                    wgmma_rs_n56<SM_WKV + s * 16384 + q * 2048 + 8192, (s | q) != 0>(av, f[0], f[1], f[2], f[3], dw);
                });
                wg_commit();
                if (s == 4) { wg_wait<1>(); pair_arrive(B_KV3); }
                #pragma unroll
                for (int q = 0; q < 8; q++) {
                    const uint32_t u0 = a[s * 4 + q / 2][(q & 1) * 2], u1 = a[s * 4 + q / 2][(q & 1) * 2 + 1];
                    if (q == 0 && (VCH == 1 || (s & 1) || s == 0)) { p0 = sqr_bf16x2(u0); p1 = sqr_bf16x2(u1); }
                    else { p0 = sqa_bf16x2(u0, p0); p1 = sqa_bf16x2(u1, p1); }
                }
                if (VCH == 1 || !(s & 1)) { ss0 += bf_lo(p0); ss2 += bf_hi(p0); ss1 += bf_lo(p1); ss3 += bf_hi(p1); }
            });
            auto q_chunk = [&](auto K0_, auto K1_) {
                wg_fence();
                static_for<decltype(K0_)::value, decltype(K1_)::value>([&](auto K_) {
                    constexpr int k = decltype(K_)::value;
                    wgmma_rs_n56<SM_WQ + k * 2048, k != 0>(aq, a[k][0], a[k][1], a[k][2], a[k][3], dw);
                });
                wg_commit();
            };
            #define QCHUNK(k0, k1) q_chunk(std::integral_constant<int, k0>{}, std::integral_constant<int, k1>{})
            const float dl0 = mean0 - bf_lo(mb0), dl1 = mean1 - bf_lo(mb1);
            const float rs0 = rsq(fmaxf(quad_sum(ss0 + ss2) * (1.f / kD) - dl0 * dl0, 0.f) + kEps);
            const float rs1 = rsq(fmaxf(quad_sum(ss1 + ss3) * (1.f / kD) - dl1 * dl1, 0.f) + kEps);
            float rk[3][2];
            rk[1][0] = __shfl_sync(~0u, rs0, t * 8); rk[1][1] = __shfl_sync(~0u, rs0, t * 8 + 4);
            rk[2][0] = __shfl_sync(~0u, rs1, t * 8); rk[2][1] = __shfl_sync(~0u, rs1, t * 8 + 4);
            const uint32_t stg = sb + SM_STG + wg * 8192 + lane * 16;
            uint4* hp = (w == 3 ? &prm.sc->halo[((ti * 8 + hg) * 2 + wg) * 128] : (uint4*)(smem_raw + SM_STG + wg * 8192 + w * 2048)) + lane;
            mbar_wait2(BAR(B_EP), 0, BAR(B_WQF), 0);
            tag = lds1(sb + SM_EPOCH);
            QCHUNK(0, QC0);
            wg_wait<1>();
            reg_fence(ak); reg_fence(av);
            TR(2);
            uint32_t kf[3][7], vf[3][7];
            #pragma unroll
            for (int c = 0; c < 7; c++) {
                kf[2][c] = pack_bf16(ak[4 * c + 2], ak[4 * c + 3]);
                vf[2][c] = movm(pack_bf16(av[4 * c + 2], av[4 * c + 3]));
            }
            const uint32_t om = ~lane & 1;
            kf[2][0] = set_par(kf[2][0], om, tag); kf[2][4] = set_par(kf[2][4], om, tag);
            vf[2][1] = set_par(vf[2][1], om, tag); vf[2][5] = set_par(vf[2][5], om, tag);
            st_gen4(hp,      kf[2][0], kf[2][1], kf[2][2], kf[2][3]);
            st_gen4(hp + 32, kf[2][4], kf[2][5], kf[2][6], vf[2][0]);
            st_gen4(hp + 64, vf[2][1], vf[2][2], vf[2][3], vf[2][4]);
            st_gen4(hp + 96, vf[2][5], vf[2][6], __float_as_uint(rk[2][0]), __float_as_uint(rk[2][1]));
            pair_arrive(B_KVC);
            QCHUNK(QC0, QC1);
            #pragma unroll
            for (int c = 0; c < 7; c++) {
                kf[1][c] = pack_bf16(ak[4 * c], ak[4 * c + 1]);
                vf[1][c] = movm(pack_bf16(av[4 * c], av[4 * c + 1]));
            }
            QCHUNK(QC1, QC2);
            named_bar(1 + wg, 128);
            uint32_t* op = opaque_ptr((uint32_t*)&prm.sc->o[((ti * 2 + wg) * 56 + hg * 7) * 64] + w * 64 + lane);
            const uint32_t omk = opaque(((lane & 6) == w * 2 ? 0x11u << (lane & 1) * 8 : 0u) << (((lane >> 3) - hg * 7) & 3));
            uint32_t* ofl = opaque_ptr(&prm.sc->flag_o[((ti * 2 + wg) * 8 + hg) * FS]);
            QCHUNK(QC2, 28);
            #undef QCHUNK
            const bool gt0 = 2 * t > g, gt1 = 2 * t + 1 > g, no_prev = ti == 0 && w == 0;
            const float kf0 = gt0 ? rk[1][0] : rk[2][0], kf1 = gt1 ? rk[1][1] : rk[2][1];
            constexpr float kScale = 0.18898223650461362f * 1.4426950408889634f;
            const float sq0 = rs0 * kScale, sf0 = kf0 * (rs1 * kScale), sf1 = kf1 * (rs1 * kScale);
            const float NEG = -__int_as_float(0x7f800000);
            const float nb0 = gt0 && no_prev ? NEG : 0.f, nb1 = gt1 && no_prev ? NEG : 0.f;
            const uint32_t sr = stg + ((w + 3) & 3) * 2048, hbar = BAR(w == 0 ? B_HL + wg : B_EP);
            mbar_wait(BAR(B_EP), 0);
            wg_wait<0>();
            reg_fence(aq);
            warp_arrive(BAR(B_A1D));
            TR(3);
            uint32_t qf[8][2];
            #pragma unroll
            for (int c = 0; c < 7; c++) {
                qf[c + (c > 3)][0] = pack_bf16(aq[4 * c], aq[4 * c + 1]);
                qf[c + (c > 3)][1] = pack_bf16(aq[4 * c + 2], aq[4 * c + 3]);
            }
            qf[4][0] = t >= 2 ? qf[3][0] : 0u; qf[4][1] = t >= 2 ? qf[3][1] : 0u;
            qf[3][0] = t < 2 ? qf[3][0] : 0u;  qf[3][1] = t < 2 ? qf[3][1] : 0u;
            float sc[2][3][4];
            auto scores = [&](int n) {
                #pragma unroll
                for (int hd = 0; hd < 2; hd++) {
                    sc[hd][n][0] = sc[hd][n][1] = sc[hd][n][2] = sc[hd][n][3] = 0.f;
                    mma16816(sc[hd][n], qf[4 * hd][0], qf[4 * hd][1], qf[4 * hd + 1][0], qf[4 * hd + 1][1], kf[n][3 * hd], kf[n][3 * hd + 1]);
                    mma16816(sc[hd][n], qf[4 * hd + 2][0], qf[4 * hd + 2][1], qf[4 * hd + 3][0], qf[4 * hd + 3][1], kf[n][3 * hd + 2], kf[n][3 * hd + 3]);
                }
            };
            scores(1); scores(2);
            mbar_wait(hbar, 0);
            {
                const uint4 u0 = lds4(sr), u1 = lds4(sr + 512), u3 = lds4(sr + 1536), u2 = lds4(sr + 1024);
                kf[0][0] = u0.x; kf[0][1] = u0.y; kf[0][2] = u0.z; kf[0][3] = u0.w;
                kf[0][4] = u1.x; kf[0][5] = u1.y; kf[0][6] = u1.z; vf[0][0] = u1.w;
                vf[0][1] = u2.x; vf[0][2] = u2.y; vf[0][3] = u2.z; vf[0][4] = u2.w;
                vf[0][5] = u3.x; vf[0][6] = u3.y; rk[0][0] = __uint_as_float(u3.z); rk[0][1] = __uint_as_float(u3.w);
            }
            if ((tid & 127) == 0) st_flag(ofl, tag);
            TR(4);
            scores(0);
            const float ke0 = gt0 ? rk[0][0] : rk[1][0], ke1 = gt1 ? rk[0][1] : rk[1][1];
            const float se0 = ke0 * sq0, se1 = ke1 * sq0;
            uint32_t ow[7][2];
            #pragma unroll
            for (int hd = 0; hd < 2; hd++) {
                const int c0 = hd * 3;
                float (&sc_)[3][4] = sc[hd];
                const float e0 = fmaf(gt0 ? sc_[0][0] : sc_[1][0], se0, nb0), e1 = fmaf(gt1 ? sc_[0][1] : sc_[1][1], se1, nb1);
                const float f0 = (gt0 ? sc_[1][2] : sc_[2][2]) * sf0, f1 = (gt1 ? sc_[1][3] : sc_[2][3]) * sf1;
                const float me = quad_max(fmaxf(e0, e1)), mf = quad_max(fmaxf(f0, f1));
                const float p0 = ex2(e0 - me), p1 = ex2(e1 - me), r0 = ex2(f0 - mf), r1 = ex2(f1 - mf);
                const float ie = rcp(quad_sum(p0 + p1)), jf = rcp(quad_sum(r0 + r1));
                const uint32_t pp = pack_bf16(p0 * ke0 * ie, p1 * ke1 * ie), rp = pack_bf16(r0 * kf0 * jf, r1 * kf1 * jf);
                const uint32_t mk = (gt0 ? 0x0000ffffu : 0u) | (gt1 ? 0xffff0000u : 0u);
                #pragma unroll
                for (int c = 0; c < 4; c++) {
                    float o[4] = {0.f, 0.f, 0.f, 0.f};
                    mma16816(o, pp & mk, 0u, pp & ~mk, rp & mk, vf[0][c0 + c], vf[1][c0 + c]);
                    mma1688(o, 0u, rp & ~mk, vf[2][c0 + c]);
                    const uint32_t lo = pack_bf16(o[0], o[1]), hi = pack_bf16(o[2], o[3]);
                    if (hd == 1 && c == 0) { if (t >= 2) { ow[3][0] = lo; ow[3][1] = hi; } }
                    else { ow[c0 + c][0] = lo; ow[c0 + c][1] = hi; }
                }
            }
            #pragma unroll
            for (int c = 0; c < 7; c++) {
                stg1(op + c * 256,      set_par(ow[c][0], (omk >> (c & 3)) & 1, tag));
                stg1(op + c * 256 + 32, set_par(ow[c][1], (omk >> (8 + (c & 3))) & 1, tag));
            }
            TR(5);
        }
        {
            const int cg = a2j * 2 + wg;
            float acc2[28];
            mbar_wait(BAR(B_XRF), 0);
            {
                const uint32_t xa = sb + SM_XR + wg * 8192 + (w * 16 + (lane & 15)) * 128;
                #pragma unroll
                for (int c = 0; c < 4; c++) {
                    uint32_t xr[4];
                    asm volatile("ldmatrix.sync.aligned.m8n8.x4.shared.b16 {%0,%1,%2,%3}, [%4];"
                                 : "=r"(xr[0]), "=r"(xr[1]), "=r"(xr[2]), "=r"(xr[3])
                                 : "r"(xa + ((((c * 2 + wg + (lane >> 4)) ^ lane) & 7) << 4)) : "memory");
                    #pragma unroll
                    for (int e = 0; e < (c < 3 ? 4 : 2); e++) { acc2[8 * c + 2 * e] = bf_lo(xr[e]); acc2[8 * c + 2 * e + 1] = bf_hi(xr[e]); }
                }
            }
            uint32_t* spw = opaque_ptr(&prm.sc->stats[((a2s * 8 + cg) * 4 + w) * 32 + lane]);
            const uint32_t* spr = opaque_ptr(&prm.sc->stats[(a2s * 32 + w) * 32 + lane]);
            uint4* hp = opaque_ptr(&prm.sc->h[((a2s * 8 + w * 2) * 8 + cg) * 64 + lane]);
            uint32_t* np = opaque_ptr((uint32_t*)&prm.sc->hn[(a2s * 56 + cg * 7) * 64] + w * 64 + lane);
            const uint64_t dwo = make_desc(sb + SM_WKV + wg * (28672 + 16), 0, true);
            const uint64_t doa = make_desc(sb + SM_WQ, 1024, false, 128);
            bias1 = prm.b1[g1f * 64 + w * 16 + rank * 8 + g];
            const __nv_bfloat16 bias2a = prm.b2[ti * 128 + (w * 16 + g) * 2 + a2p], bias2b = prm.b2[ti * 128 + (w * 16 + 8 + g) * 2 + a2p];
            reg_fence(acc2);
            fence_async_smem();
            warp_arrive(BAR(B_XD));
            static_for<0, 4>([&](auto P_) {
                constexpr int P = decltype(P_)::value;
                mbar_wait(BAR(B_BF + NB + P), 0);
                if (P == 0) TR(6);
                wg_fence();
                static_for<0, 7>([&](auto K_) { constexpr int k = decltype(K_)::value;
                    wgmma_ss_n56<P * 14336 + k * 2048, (P >> 1) * 57344 + (P & 1) * 14336 + k * 2048>(acc2, doa, dwo); });
                if (P) wg_commit();
                if (P == 2) { wg_wait<1>(); warp_arrive(BAR(B_OC)); }
            });
            wg_wait<0>();
            reg_fence(acc2);
            TR(7);
            float s0 = 0.f, s1 = 0.f, q0 = 0.f, q1 = 0.f;
            #pragma unroll
            for (int c = 0; c < 7; c++) {
                s0 += acc2[4 * c] + acc2[4 * c + 1];     q0 = fmaf(acc2[4 * c], acc2[4 * c], fmaf(acc2[4 * c + 1], acc2[4 * c + 1], q0));
                s1 += acc2[4 * c + 2] + acc2[4 * c + 3]; q1 = fmaf(acc2[4 * c + 2], acc2[4 * c + 2], fmaf(acc2[4 * c + 3], acc2[4 * c + 3], q1));
            }
            const bool th = t >= 2, to = t & 1;
            const float sa = (th ? s1 : s0) + __shfl_xor_sync(~0u, th ? s0 : s1, 2), qa = (th ? q1 : q0) + __shfl_xor_sync(~0u, th ? q0 : q1, 2);
            const float part = (to ? qa : sa) + __shfl_xor_sync(~0u, to ? sa : qa, 1);
            stg1(spw, set_par(__float_as_uint(part), 1u, tag));
            const uint32_t tpoll = clk32() + SDELAY;
            TR(8);
            warp_arrive(BAR(B_HD));
            uint32_t hw[2][7], nm[2][4], us[8];
            #pragma unroll
            for (int r = 0; r < 2; r++) {
                const float b2v = __bfloat162float(r ? bias2b : bias2a);
                #pragma unroll
                for (int c = 0; c < 7; c++) hw[r][c] = pack_bf16(acc2[4 * c + 2 * r] + b2v, acc2[4 * c + 2 * r + 1] + b2v);
                hw[r][0] = set_par(hw[r][0], ~lane & 1, tag);
            }
            auto store_h = [&]() {
                #pragma unroll
                for (int r = 0; r < 2; r++) {
                    stg4(hp + r * 512, hw[r][0], hw[r][1], hw[r][2], hw[r][3]);
                    stg4(hp + r * 512 + 32, tag, hw[r][4], hw[r][5], hw[r][6]);
                }
            };
            if (HPOS == 0) store_h();
            spin_until(tpoll);
            #pragma unroll
            for (int i = 0; i < 8; i++) us[i] = ld_rlx(spr + i * 128);
            if (HPOS == 1) store_h();
            #pragma unroll
            for (int i = 0; i < 8; i++) nm[i >> 2][i & 3] = lane == ((cg * 7 + i) & 3) * 8 + w * 2 + (i >> 2);
            {
                int it = 0;
                while (true) {
                    uint32_t bad = 0;
                    #pragma unroll
                    for (int i = 0; i < 8; i++) bad |= us[i] ^ tag;
                    if (!__any_sync(~0u, bad & 1)) break;
                    RETRY_COUNT(3);
                    if (++it > kSpinLimit) { TIMEOUT(103); break; }
                    #pragma unroll
                    for (int i = 0; i < 8; i++) us[i] = ld_rlx(spr + i * 128);
                }
            }
            TR(9);
            const float tot = (((__uint_as_float(us[0]) + __uint_as_float(us[1])) + (__uint_as_float(us[2]) + __uint_as_float(us[3])))
                            + ((__uint_as_float(us[4]) + __uint_as_float(us[5])) + (__uint_as_float(us[6]) + __uint_as_float(us[7])))) * (1.f / kD);
            const float oth = __shfl_xor_sync(~0u, tot, 1);
            const float mean = to ? oth : tot;
            const float var = fmaxf(fmaf(-mean, mean, to ? tot : oth), 0.f);
            const float r1 = rsq(var + kEps);
            const float rra = 0.5f * r1 * rsq(fmaf(var * r1, r1, kEps)), mra = -mean * rra;
            const float rrb = __shfl_xor_sync(~0u, rra, 2), mrb = __shfl_xor_sync(~0u, mra, 2);
            const float rr0 = th ? rrb : rra, mr0 = th ? mrb : mra, rr1 = th ? rra : rrb, mr1 = th ? mra : mrb;
            #pragma unroll
            for (int c = 0; c < 7; c++) {
                stg1(np + c * 256,      set_par(pack_bf16(fmaf(acc2[4 * c], rr0, mr0), fmaf(acc2[4 * c + 1], rr0, mr0)), nm[0][c & 3], tag));
                stg1(np + c * 256 + 32, set_par(pack_bf16(fmaf(acc2[4 * c + 2], rr1, mr1), fmaf(acc2[4 * c + 3], rr1, mr1)), nm[1][c & 3], tag));
            }
            TR(10);
            if (HPOS == 2) store_h();
        }
        float acc[56];
        const uint32_t xch = opaque(sb + SM_XCH + w * 1920 + lane * 16);
        uint32_t peer_xch; const uint32_t peer_bar = pbar0;
        asm volatile("mapa.shared::cluster.u32 %0, %1, %2;" : "=r"(peer_xch) : "r"(xch), "r"(rank ^ 1));
        uint4 hr[4];
        const int tok = g2s * 64 + w * 16 + rank * 8 + g, pr = (tok & 127) >> 1;
        const uint4* hp = &prm.sc->h[((((tok >> 7) * 2 + (tok & 1)) * 8 + (pr >> 3)) * 8 + (g2j + 2 * wg) * 2) * 64 + (pr & 7) * 4 + t];
        auto load_h = [&]() {
            #pragma unroll
            for (int c = 0; c < 4; c++) hr[c] = ld_rlx4(hp + c * 32);
        };
        const uint32_t b1h = pack_bf16(0.5f * __bfloat162float(bias1), 0.5f * __bfloat162float(bias1));
        #pragma unroll
        for (int c = 0; c < 4; c++) hr[c] = make_uint4(b1h, b1h, b1h, b1h);
        if (!g1_on) { mbar_wait(BAR(B_GD), 0); load_h(); }
        uint32_t* const gp1 = (uint32_t*)&prm.sc->g[(g1f * 56 + (g1j + 2 * wg) * 14) * 64] + (w * 2 + rank) * 32 + lane;
        uint32_t* const gp2 = (uint32_t*)(prm.out + (size_t)(g2s * 64 + w * 16 + rank * 8 + (lane >> 4)) * kD + (g2j + 2 * wg) * 112) + (lane & 15) * 4;
        uint32_t gm[4];
        #pragma unroll
        for (int i = 0; i < 4; i++) gm[i] = lane == ((g1j * 2 + i) & 3) * 8 + w * 2 + rank;
        const bool lead = elect_one();
        const uint64_t da0 = make_desc(sb, 0, true), db0 = make_desc(sb + SM_B, 128, false);
        #pragma unroll 1
        for (int ge = g1_on ? 0 : 1; ge < 2; ge++) {
            if (ge) {
                int it = 0;
                while (true) {
                    uint32_t bad = 0;
                    #pragma unroll
                    for (int c = 0; c < 4; c++) bad |= hr[c].x ^ tag;
                    if (!__any_sync(~0u, bad & ~lane & 1)) break;
                    if (++it > kSpinLimit) { TIMEOUT(110); break; }
                    load_h();
                }
            }
            auto init_acc = [&](auto R_) {
                constexpr int o = decltype(R_)::value * 2;
                #pragma unroll
                for (int c = 0; c < 14; c++) {
                    const int i = c / 7 * 8 + c % 7 + (c % 7 >= 4);
                    const uint32_t hw = (i & 3) == 0 ? hr[i >> 2].x : (i & 3) == 1 ? hr[i >> 2].y : (i & 3) == 2 ? hr[i >> 2].z : hr[i >> 2].w;
                    acc[4 * c + o] = bf_lo(hw); acc[4 * c + 1 + o] = bf_hi(hw);
                    acc[4 * c + 2 - o] = 0.f;   acc[4 * c + 3 - o] = 0.f;
                }
                reg_fence(acc);
            };
            if (rank) init_acc(std::integral_constant<int, 1>{}); else init_acc(std::integral_constant<int, 0>{});
            const uint32_t slot0 = g1_on ? (ge ? 4 : 2 * wg) : 0;
            uint32_t ph = 0, rb = bar0 + slot0 * 8;
            uint64_t da = da0 + ge * 1024, db = db0 + slot0 * 896;
            uint32_t prev = BAR(B_WKVF);
            mbar_wait(BAR(B_EP), 0);
            if (wg == 1 || (ge && g1_on)) named_bar(5 - wg, 256);
            mbar_wait(rb + B_BF * 8, ph);
            TR(11 + ge * 4);
            #pragma unroll 1
            for (int n = ge ? 14 : 16;;) {
                wg_fence();
                wgmma_ss_n112<0,    0>(acc, da, db);
                wgmma_ss_n112<2048, 256>(acc, da, db);
                wgmma_ss_n112<4096, 512>(acc, da, db);
                wgmma_ss_n112<6144, 768>(acc, da, db);
                wg_commit();
                if (--n == 0 && ge + wg < 2) named_arrive(4 + wg, 256);
                const uint32_t cur = rb + B_BE * 8;
                da += 512; db += 896; rb += 8;
                if (rb == bar0 + NB * 8) { rb = bar0; db = db0; ph ^= 1; }
                wg_wait<1>();
                mbar_arrive_if(prev, lead);
                prev = cur;
                if (n == 0) break;
                if (!mbar_try(rb + B_BF * 8, ph)) mbar_wait(rb + B_BF * 8, ph);
            }
            const int use = ge * 2 + wg;
            const uint32_t xfree = BAR(use > (g1_on ? 0 : 2) ? B_RE + use - 1 : B_PD);
            const bool xok = mbar_test(xfree, 0);
            wg_wait<0>();
            reg_fence(acc);
            mbar_arrive_if(prev, lead);
            TR(12 + ge * 4);
            if (!xok) mbar_wait(xfree, 0);
            float v[28];
            auto reduce = [&](auto R_) {
                constexpr int o = decltype(R_)::value * 2;
                const uint32_t rf = peer_bar + (B_RF + use) * 8;
                float dly = __uint_as_float(0x3f800000u | lane); uint32_t pa = peer_xch;
                #pragma unroll
                for (int c = 0; c < 4; c++) {
                    const uint32_t p0 = pack_bf16(acc[16 * c + 2 - o], acc[16 * c + 3 - o]), p1 = pack_bf16(acc[16 * c + 6 - o], acc[16 * c + 7 - o]);
                    if (c < 3) {
                        const uint32_t p2 = pack_bf16(acc[16 * c + 10 - o], acc[16 * c + 11 - o]), p3 = pack_bf16(acc[16 * c + 14 - o], acc[16 * c + 15 - o]);
                        asm volatile("st.async.shared::cluster.mbarrier::complete_tx::bytes.v4.b32 [%0], {%1,%2,%3,%4}, [%5];"
                                     :: "r"(pa + c * 512), "r"(p0), "r"(p1), "r"(p2), "r"(p3), "r"(rf) : "memory");
                        if (use != 3) {
                            #pragma unroll
                            for (int i = 0; i < XPACE; i++) asm volatile("tanh.approx.f32 %0, %0;" : "+f"(dly) :: "memory");
                            pa += __float_as_uint(dly) >> 30;
                        }
                    } else {
                        asm volatile("st.async.shared::cluster.mbarrier::complete_tx::bytes.v2.b32 [%0], {%1,%2}, [%3];"
                                     :: "r"(pa + 1536 - lane * 8), "r"(p0), "r"(p1), "r"(rf) : "memory");
                    }
                }
                if (!ge) load_h();
                mbar_wait(BAR(B_RF + use), 0);
                #pragma unroll
                for (int c = 0; c < 4; c++) {
                    uint4 u;
                    if (c < 3) u = lds4(xch + c * 512); else { const uint2 u2 = lds2(xch + 1536 - lane * 8); u.x = u2.x; u.y = u2.y; }
                    v[8 * c]     = acc[16 * c + o] + bf_lo(u.x);     v[8 * c + 1] = acc[16 * c + 1 + o] + bf_hi(u.x);
                    v[8 * c + 2] = acc[16 * c + 4 + o] + bf_lo(u.y); v[8 * c + 3] = acc[16 * c + 5 + o] + bf_hi(u.y);
                    if (c < 3) {
                        v[8 * c + 4] = acc[16 * c + 8 + o] + bf_lo(u.z);  v[8 * c + 5] = acc[16 * c + 9 + o] + bf_hi(u.z);
                        v[8 * c + 6] = acc[16 * c + 12 + o] + bf_lo(u.w); v[8 * c + 7] = acc[16 * c + 13 + o] + bf_hi(u.w);
                    }
                }
            };
            if (rank) reduce(std::integral_constant<int, 1>{}); else reduce(std::integral_constant<int, 0>{});
            TR(13 + ge * 4);
            if (!ge) {
                #pragma unroll
                for (int c = 0; c < 14; c++) {
                    float r[2];
                    #pragma unroll
                    for (int e = 0; e < 2; e++) {
                        const float u = v[2 * c + e];
                        r[e] = fmaf(u, tanh_hw(u * fmaf(u * u, 8.f * 0.7978845608f * 0.044715f, 2.f * 0.7978845608f)), u);
                    }
                    stg1(gp1 + c * 256, set_par(pack_bf16(r[0], r[1]), gm[c & 3], tag));
                }
                named_bar(1 + wg, 128);
                if (w == 0 && lane == 0) {
                    asm volatile("st.shared.u32 [%0], %1;" :: "r"(sb + SM_TG + 8 + wg * 4), "r"(clk32() + (wg ? XSPECB : XSPEC)) : "memory");
                    mbar_arrive(BAR(B_GD + wg));
                }
                mbar_arrive_remote_if(peer_bar + (B_RE + use) * 8, lead);
            } else {
                const uint32_t stw = xch - lane * 16;
                uint32_t pk[14];
                #pragma unroll
                for (int c = 0; c < 14; c++) pk[c] = pack_bf16(v[2 * c], v[2 * c + 1]);
                __syncwarp();
                const uint32_t sa = stw + (lane & 7) * 240 + (lane >> 3) * 16;
                #pragma unroll
                for (int m = 0; m < 3; m++)
                    asm volatile("stmatrix.sync.aligned.m8n8.x4.shared.b16 [%0], {%1,%2,%3,%4};"
                                 :: "r"(sa + m * 64), "r"(pk[4 * m]), "r"(pk[4 * m + 1]), "r"(pk[4 * m + 2]), "r"(pk[4 * m + 3]) : "memory");
                asm volatile("stmatrix.sync.aligned.m8n8.x2.shared.b16 [%0], {%1,%2};" :: "r"(sa + 192), "r"(pk[12]), "r"(pk[13]) : "memory");
                __syncwarp();
                #pragma unroll
                for (int i = 0; i < 4; i++) {
                    const int r = 2 * i + (lane >> 4), ch = lane & 15;
                    if (ch < 14) { const uint4 u = lds4(stw + r * 240 + ch * 16); stg4(gp2 + i * 448, u.x, u.y, u.z, u.w); }
                }
                __syncwarp();
                mbar_arrive_remote_if(peer_bar + (B_RE + 2) * 8, lead && wg == 0);
            }
            TR(14 + ge * 4);
        }
        if (tid == 128) TRG(62);
        if (b == 0 && tid == 128) prm.sc->epoch = tag;
    }
}

typedef CUresult (*EncodeFn)(CUtensorMap*, CUtensorMapDataType, cuuint32_t, void*, const cuuint64_t*, const cuuint64_t*,
                             const cuuint32_t*, const cuuint32_t*, CUtensorMapInterleave, CUtensorMapSwizzle,
                             CUtensorMapL2promotion, CUtensorMapFloatOOBfill);

void make_map(EncodeFn enc, CUtensorMap* m, const void* base, uint64_t cols, uint64_t rows, uint32_t box_rows) {
    cuuint64_t dims[2] = {cols, rows};
    cuuint64_t strides[1] = {cols * 2};
    cuuint32_t box[2] = {64, box_rows};
    cuuint32_t es[2] = {1, 1};
    enc(m, CU_TENSOR_MAP_DATA_TYPE_BFLOAT16, 2, const_cast<void*>(base), dims, strides, box, es, CU_TENSOR_MAP_INTERLEAVE_NONE,
        CU_TENSOR_MAP_SWIZZLE_128B, CU_TENSOR_MAP_L2_PROMOTION_L2_128B, CU_TENSOR_MAP_FLOAT_OOB_FILL_NONE);
}

}

extern "C" void kernel_launch(void* const* d_in, const int* in_sizes, int n_in, void* d_out, int out_size) {
    (void)in_sizes; (void)n_in; (void)out_size;
    void* fn = nullptr;
    cudaDriverEntryPointQueryResult qr;
    cudaGetDriverEntryPoint("cuTensorMapEncodeTiled", &fn, cudaEnableDefault, &qr);
    EncodeFn enc = (EncodeFn)fn;
    CUtensorMap mX2, mX, mWqkv, mWo, mW1, mW2;
    {
        cuuint64_t dims[3] = {kD, kS / 2, 2}, strides[2] = {4 * kD, 2 * kD};
        cuuint32_t box[3] = {64, 64, 2}, es[3] = {1, 1, 1};
        enc(&mX2, CU_TENSOR_MAP_DATA_TYPE_BFLOAT16, 3, d_in[0], dims, strides, box, es, CU_TENSOR_MAP_INTERLEAVE_NONE,
            CU_TENSOR_MAP_SWIZZLE_128B, CU_TENSOR_MAP_L2_PROMOTION_L2_128B, CU_TENSOR_MAP_FLOAT_OOB_FILL_NONE);
    }
    make_map(enc, &mX, d_in[0], 2 * kD, kS / 2, 64);
    make_map(enc, &mWqkv, d_in[1], 3 * kD, kD, 64);
    make_map(enc, &mWo, d_in[2], kD, kD, 224);
    make_map(enc, &mW1, d_in[4], 2 * kF, kS / 2, 64);
    make_map(enc, &mW2, d_in[6], kS, kF, 64);
    Params prm;
    prm.x = (const __nv_bfloat16*)d_in[0];
    prm.wqkv = (const __nv_bfloat16*)d_in[1];
    prm.wo = (const __nv_bfloat16*)d_in[2];
    prm.w1 = (const __nv_bfloat16*)d_in[4];
    prm.b1 = (const __nv_bfloat16*)d_in[5];
    prm.w2 = (const __nv_bfloat16*)d_in[6];
    prm.b2 = (const __nv_bfloat16*)d_in[7];
    prm.out = (__nv_bfloat16*)d_out;
    cudaGetSymbolAddress((void**)&prm.sc, g_scratch);
    cudaFuncSetAttribute(fused_kernel, cudaFuncAttributeMaxDynamicSharedMemorySize, SM_TOTAL);
    fused_kernel<<<128, 384, SM_TOTAL, cudaStreamPerThread>>>(prm, mX2, mX, mWqkv, mWo, mW1, mW2);
}
```

```cpp
#include <cuda_runtime.h>
#include <cuda.h>
#include <cuda_bf16.h>
#include <stdint.h>
#include <type_traits>

namespace {

constexpr int kS = 2048, kD = 448, kF = 1792;
constexpr float kEps = 1e-5f;

#define FS 32
struct Scratch {
    uint4    o[32 * 56 * 64];
    uint4    h[32 * 8 * 8 * 64];
    uint4    hn[32 * 56 * 64];
    uint4    g[28 * 56 * 64];
    uint4    halo[16 * 8 * 2 * 4 * 32];
    uint32_t stats[32 * 8 * 4 * 32];
    uint32_t flag_o[32 * 8 * FS];
    uint32_t flag_h[32 * 4 * FS];
    uint32_t epoch;
};
__device__ __align__(1024) Scratch g_scratch;
#define TIMEOUT(code)
#define RETRY_COUNT(i)
#define CAP_DECL(n, k)
#define CAP(n)
#define CAP_SKIP(n)
#define EV(i, dep)
#define TR2(idx)
#define TR(idx)
#define TRW(idx)
#define TRG(idx)

constexpr uint32_t SM_WKV  = 114688;
constexpr uint32_t SM_XR   = 24576;
constexpr uint32_t SM_STG  = 40960;
constexpr uint32_t SM_WQ   = 57344;
constexpr uint32_t SM_XCH  = 0;
constexpr uint32_t SM_B    = 131072;
constexpr uint32_t SM_BAR  = 231424;
constexpr uint32_t SM_TOTAL = SM_BAR + 1024;
constexpr int NB = 7;
#define SH1 0
#define SH2 0
#define SH2N 5
#define SH3 0
#define NSPEC 4
#define XSPEC 500
#define C2 0
#define C3 0
#define CN2 7200
#define CN3 11000
constexpr int B_XF = 0, B_WKVF = 7, B_WQF = 14, B_XRF = 15, B_WOF = 16,
              B_XC = 18, B_KV3 = 19, B_KVC = 20,
              B_A1D = 21, B_XD = 22, B_OC = 23,
              B_BE = 24, B_RE = B_BE + NB,
              B_PL = B_RE + 3, B_AF = B_PL + 1, B_BL = B_AF + 1  , B_OL = B_BL + 2 * NB  ,
              B_BF = B_OL + 4  , B_OF = B_BF + NB, B_RF = B_OF + 4, B_EP = B_RF + 8, B_PD = B_EP + 1, B_RT = B_PD + 1, B_HL = B_RT + 2,
              B_HD = B_HL + 2  , B_GO = B_HD + 1, B_GD = B_GO + 1, B_COUNT = B_GD + 2;
#define WEARLY 6
#define PF0 126
#define TMPF 2
#define RSTE 2
#define POLLP 1
#define PROBEP 1
#define LOADP 1
#define LOADW 64
#define NOB 0
#define AEARLY 5
#define W1PACE 400
#define W2PACE 200
#define PFPACE 230
#define PFBAR (B_XF + 6)
#define DELTA 1792
#define DELTA2 DELTA
#define BPACE 230
#define BURST 2
#define W1OFF 350
#define W2OFF 2900
#define XPACE 0
#define PSTAG 200
constexpr uint32_t SM_EPOCH = SM_BAR + B_COUNT * 8, SM_TG = SM_EPOCH + 4  , SM_TG2 = SM_TG + 16  , SM_TR = SM_BAR + 768;

#define HDELAY 0
#define QC0 4
#define QC1 10
#define QC2 16
#define HPOS 1
#define XSPECB 850
#define PACE1 120
#define PACE2 400
#define RELOAD1 1
#define VCH 1
#define SOFF 0
#define XW 1
#define XLAG 0
#define PFX 3
#define PFD 250
#define SDELAY 400
#define PDELAY 500
#define NPRE 10
#define PREPACE 0
#define AFIRST 0
#define DELTAO 928
#define NS 0
#define GCH 14
#define OCH 14
#define ICH 14
#define PACKO
#define NR 8
#define HMODE 2
#define HOFF0 (-100)
#define HOFF1 900
#define STAG1 0
#define STAG2 400
#define PLOFF (-250)
#define W1Q 3
#define APOS1 ((1ull << 4) | (1ull << 8) | (1ull << 12) | (1ull << 5) | (1ull << 9) | (1ull << 13))
#define APOS2 (0x5555555ull << 17)
constexpr uint32_t seg_mask(int h, int p0, int p1) {
    uint32_t m = 0; int n = 0;
    for (int p = p0; p < p1; p++) if ((p & 1) == h) m |= (uint32_t)(((APOS1 | APOS2) >> p) & 1) << n++;
    return m | 1u << n;
}
constexpr uint64_t seg_masks(int h) {
    return 2 | (uint64_t)seg_mask(h, 0, 16) << 10 | (uint64_t)seg_mask(h, 16, 32) << 20
             | (uint64_t)seg_mask(h, 32, 46) << 30 | (uint64_t)seg_mask(h, 46, 60) << 40;
}
constexpr uint64_t kSegMasks0 = seg_masks(0), kSegMasks1 = seg_masks(1);

constexpr int kSpinLimit = 1 << 15;
__device__ __forceinline__ bool elect_one() {
    uint32_t p;
    asm volatile("{ .reg .pred P; elect.sync _|P, 0xffffffff; selp.u32 %0, 1, 0, P; }" : "=r"(p));
    return p;
}
__device__ __forceinline__ void mbar_init(uint32_t bar, uint32_t cnt) { asm volatile("mbarrier.init.shared::cta.b64 [%0], %1;" :: "r"(bar), "r"(cnt)); }
__device__ __forceinline__ void mbar_expect(uint32_t bar, uint32_t bytes) { asm volatile("mbarrier.arrive.expect_tx.shared::cta.b64 _, [%0], %1;" :: "r"(bar), "r"(bytes) : "memory"); }
__device__ __forceinline__ void mbar_expect_more(uint32_t bar, uint32_t bytes) { asm volatile("mbarrier.expect_tx.relaxed.cta.shared::cta.b64 [%0], %1;" :: "r"(bar), "r"(bytes) : "memory"); }
__device__ __forceinline__ void mbar_arrive(uint32_t bar) { asm volatile("mbarrier.arrive.shared::cta.b64 _, [%0];" :: "r"(bar) : "memory"); }
__device__ __forceinline__ void mbar_wait(uint32_t bar, uint32_t parity) {
    uint32_t ok; int it = 0;
    do {
        asm volatile("{ .reg .pred p; mbarrier.try_wait.parity.shared::cta.b64 p, [%1], %2; selp.u32 %0, 1, 0, p; }"
                     : "=r"(ok) : "r"(bar), "r"(parity) : "memory");
        if (++it > kSpinLimit) { TIMEOUT((bar & 1023) >> 3); break; }
    } while (!ok);
}
__device__ __forceinline__ bool mbar_try(uint32_t bar, uint32_t parity) {
    uint32_t ok;
    asm volatile("{ .reg .pred p; mbarrier.try_wait.parity.shared::cta.b64 p, [%1], %2; selp.u32 %0, 1, 0, p; }" : "=r"(ok) : "r"(bar), "r"(parity) : "memory");
    return ok;
}
__device__ __forceinline__ bool mbar_test(uint32_t bar, uint32_t parity) {
    uint32_t ok;
    asm volatile("{ .reg .pred p; mbarrier.test_wait.parity.shared::cta.b64 p, [%1], %2; selp.u32 %0, 1, 0, p; }" : "=r"(ok) : "r"(bar), "r"(parity) : "memory");
    return ok;
}
__device__ __forceinline__ void mbar_wait_fast(uint32_t bar, uint32_t parity) { if (!mbar_try(bar, parity)) mbar_wait(bar, parity); }
__device__ __forceinline__ void mbar_wait2(uint32_t bar0, uint32_t par0, uint32_t bar1, uint32_t par1) {
    uint32_t ok; int it = 0;
    do {
        asm volatile("{ .reg .pred p, q; mbarrier.try_wait.parity.shared::cta.b64 p, [%1], %2;\n"
                     "mbarrier.try_wait.parity.shared::cta.b64 q, [%3], %4; and.pred p, p, q; selp.u32 %0, 1, 0, p; }"
                     : "=r"(ok) : "r"(bar0), "r"(par0), "r"(bar1), "r"(par1) : "memory");
        if (++it > kSpinLimit) { TIMEOUT((bar0 & 1023) >> 3); break; }
    } while (!ok);
}
__device__ __forceinline__ void sched_fence(uint32_t v) {
    asm volatile("{ .reg .pred p; .reg .b32 x; mov.b32 x, %0;\nL: setp.eq.u32 p, x, 0xffffffff; @p mov.u32 x, %%clock; @p bra L; }" :: "r"(v) : "memory");
}
template <int N> __device__ __forceinline__ void reg_fence(float (&d)[N]) {
    #pragma unroll
    for (int i = 0; i < N; i++) asm volatile("" : "+f"(d[i]) :: "memory");
}
__device__ __forceinline__ void mbar_wait_cluster(uint32_t bar, uint32_t parity) {
    uint32_t ok; int it = 0;
    do {
        asm volatile("{ .reg .pred p; mbarrier.try_wait.parity.acquire.cluster.shared::cta.b64 p, [%1], %2; selp.u32 %0, 1, 0, p; }"
                     : "=r"(ok) : "r"(bar), "r"(parity) : "memory");
        if (++it > kSpinLimit) { TIMEOUT((bar & 1023) >> 3); break; }
    } while (!ok);
}
__device__ __forceinline__ void mbar_arrive_if(uint32_t bar, bool pred) {
    asm volatile("{ .reg .pred p; setp.ne.u32 p, %1, 0; @p mbarrier.arrive.shared::cta.b64 _, [%0]; }" :: "r"(bar), "r"((uint32_t)pred) : "memory");
}
template <int P> __device__ __forceinline__ void tick() {
    if (P > 1) { const uint32_t t = ((uint32_t)clock() | (P - 1)) + 1; while ((int)((uint32_t)clock() - t) < 0) {} }
}
__device__ __forceinline__ void warp_arrive(uint32_t bar) { __syncwarp(); if (elect_one()) mbar_arrive(bar); }
__device__ __forceinline__ void tma2d(uint32_t dst, const CUtensorMap* m, int c0, int c1, uint32_t bar) {
    asm volatile("cp.async.bulk.tensor.2d.shared::cluster.global.mbarrier::complete_tx::bytes [%0], [%1, {%3, %4}], [%2];"
                 :: "r"(dst), "l"(m), "r"(bar), "r"(c0), "r"(c1) : "memory");
}
__device__ __forceinline__ void tma3d(uint32_t dst, const CUtensorMap* m, int c0, int c1, int c2, uint32_t bar) {
    asm volatile("cp.async.bulk.tensor.3d.shared::cluster.global.mbarrier::complete_tx::bytes [%0], [%1, {%3, %4, %5}], [%2];"
                 :: "r"(dst), "l"(m), "r"(bar), "r"(c0), "r"(c1), "r"(c2) : "memory");
}
__device__ __forceinline__ void tma2d_mc(uint32_t dst, const CUtensorMap* m, int c0, int c1, uint32_t bar) {
    asm volatile("cp.async.bulk.tensor.2d.shared::cluster.global.mbarrier::complete_tx::bytes.multicast::cluster [%0], [%1, {%3, %4}], [%2], %5;"
                 :: "r"(dst), "l"(m), "r"(bar), "r"(c0), "r"(c1), "h"((uint16_t)3) : "memory");
}
__device__ __forceinline__ void bulk_g2s_mc(uint32_t dst, const void* src, uint32_t bytes, uint32_t bar) {
    asm volatile("cp.async.bulk.shared::cluster.global.mbarrier::complete_tx::bytes.multicast::cluster [%0], [%1], %2, [%3], %4;"
                 :: "r"(dst), "l"(src), "r"(bytes), "r"(bar), "h"((uint16_t)3) : "memory");
}
__device__ __forceinline__ void mbar_arrive_remote_if(uint32_t cluster_bar, bool pred) {
    asm volatile("{ .reg .pred p; setp.ne.u32 p, %1, 0; @p mbarrier.arrive.shared::cluster.b64 _, [%0]; }" :: "r"(cluster_bar), "r"((uint32_t)pred) : "memory");
}
__device__ __forceinline__ void bulk_g2s(uint32_t dst, const void* src, uint32_t bytes, uint32_t bar) {
    asm volatile("cp.async.bulk.shared::cluster.global.mbarrier::complete_tx::bytes [%0], [%1], %2, [%3];"
                 :: "r"(dst), "l"(src), "r"(bytes), "r"(bar) : "memory");
}
__device__ __forceinline__ void wg_fence()  { asm volatile("wgmma.fence.sync.aligned;" ::: "memory"); }
__device__ __forceinline__ void wg_commit() { asm volatile("wgmma.commit_group.sync.aligned;" ::: "memory"); }
template <int N> __device__ __forceinline__ void wg_wait() { asm volatile("wgmma.wait_group.sync.aligned %0;" :: "n"(N) : "memory"); }
__device__ __forceinline__ void named_bar(int id, int n) { asm volatile("bar.sync %0, %1;" :: "r"(id), "r"(n) : "memory"); }
__device__ __forceinline__ void named_arrive(int id, int n) { asm volatile("bar.arrive %0, %1;" :: "r"(id), "r"(n) : "memory"); }
__device__ __forceinline__ bool mbar_try2(uint32_t bar0, uint32_t par0, uint32_t bar1, uint32_t par1) {
    uint32_t ok;
    asm volatile("{ .reg .pred p, q; mbarrier.test_wait.parity.shared::cta.b64 p, [%1], %2;\n"
                 "mbarrier.test_wait.parity.shared::cta.b64 q, [%3], %4; and.pred p, p, q; selp.u32 %0, 1, 0, p; }"
                 : "=r"(ok) : "r"(bar0), "r"(par0), "r"(bar1), "r"(par1) : "memory");
    return ok;
}
__device__ __forceinline__ void fence_gpu() { asm volatile("fence.release.gpu;" ::: "memory"); }
__device__ __forceinline__ void fence_async_global() { asm volatile("fence.proxy.async.global;" ::: "memory"); }
__device__ __forceinline__ void fence_async_smem() { asm volatile("fence.proxy.async.shared::cta;" ::: "memory"); }
__device__ __forceinline__ uint32_t gtime32() { uint64_t t; asm volatile("mov.u64 %0, %%globaltimer;" : "=l"(t) :: "memory"); return (uint32_t)t; }
__device__ __forceinline__ uint32_t clk32() { uint64_t t; asm volatile("mov.u64 %0, %%clock64;" : "=l"(t) :: "memory"); return (uint32_t)t; }
__device__ __forceinline__ void spin_until(uint32_t t) { while ((int)(clk32() - t) < 0) {} }
#define SLEEPNS 20
__device__ __forceinline__ void sleep_until(uint32_t t) { while ((int)(clk32() - t) < 0) { if (SLEEPNS) __nanosleep(SLEEPNS); } }
__device__ __forceinline__ void st_flag(uint32_t* p, uint32_t v) {
    const uint64_t w = ((uint64_t)gtime32() << 32) | v;
    asm volatile("st.relaxed.gpu.global.u64 [%0], %1;" :: "l"(p), "l"(w) : "memory");
}
__device__ __forceinline__ void ld_flag_if(uint64_t& v, const uint32_t* p, bool pred) {
    asm volatile("{ .reg .pred p; setp.ne.u32 p, %2, 0; @p ld.relaxed.gpu.global.u64 %0, [%1]; }" : "+l"(v) : "l"(p), "r"((uint32_t)pred) : "memory");
}
__device__ __forceinline__ uint32_t ld_acq(const uint32_t* p) { uint32_t v; asm volatile("ld.acquire.gpu.global.u32 %0, [%1];" : "=r"(v) : "l"(p) : "memory"); return v; }
__device__ __forceinline__ uint32_t ld_rlx(const uint32_t* p) { uint32_t v; asm volatile("ld.relaxed.gpu.global.u32 %0, [%1];" : "=r"(v) : "l"(p) : "memory"); return v; }
template <class T> __device__ __forceinline__ T* opaque_ptr(T* p) { asm volatile("" : "+l"(p)); return p; }
__device__ __forceinline__ uint4 ld_rlx4(const uint4* p) {
    uint4 v; asm volatile("ld.relaxed.gpu.global.v4.u32 {%0,%1,%2,%3}, [%4];" : "=r"(v.x), "=r"(v.y), "=r"(v.z), "=r"(v.w) : "l"(p) : "memory"); return v;
}
__device__ __forceinline__ void st_ll(uint4* p, uint32_t a, uint32_t b, uint32_t tag) {
    uint64_t lo = ((uint64_t)tag << 32) | a, hi = ((uint64_t)tag << 32) | b;
    asm volatile("st.relaxed.gpu.global.v2.u64 [%0], {%1,%2};" :: "l"(p), "l"(lo), "l"(hi) : "memory");
}
__device__ __forceinline__ bool ld_ll(const uint4* p, uint32_t& a, uint32_t& b, uint32_t tag) {
    uint64_t lo, hi;
    asm volatile("ld.relaxed.gpu.global.v2.u64 {%0,%1}, [%2];" : "=l"(lo), "=l"(hi) : "l"(p) : "memory");
    a = (uint32_t)lo; b = (uint32_t)hi;
    return (uint32_t)(lo >> 32) == tag && (uint32_t)(hi >> 32) == tag;
}
__device__ __forceinline__ uint2 ld_acq2(const uint2* p) {
    uint2 v; asm volatile("ld.acquire.gpu.global.v2.u32 {%0,%1}, [%2];" : "=r"(v.x), "=r"(v.y) : "l"(p) : "memory"); return v;
}
__device__ __forceinline__ uint2 ld_rlx2(const uint2* p) {
    uint2 v; asm volatile("ld.relaxed.gpu.global.v2.u32 {%0,%1}, [%2];" : "=r"(v.x), "=r"(v.y) : "l"(p) : "memory"); return v;
}
__device__ __forceinline__ void stg1(uint32_t* p, uint32_t v) { asm volatile("st.global.u32 [%0], %1;" :: "l"(p), "r"(v) : "memory"); }
__device__ __forceinline__ void stg2(void* p, uint32_t x, uint32_t y) { asm volatile("st.global.v2.u32 [%0], {%1,%2};" :: "l"(p), "r"(x), "r"(y) : "memory"); }
__device__ __forceinline__ void stg4(void* p, uint32_t x, uint32_t y, uint32_t z, uint32_t w) { asm volatile("st.global.v4.u32 [%0], {%1,%2,%3,%4};" :: "l"(p), "r"(x), "r"(y), "r"(z), "r"(w) : "memory"); }
__device__ __forceinline__ uint32_t lds1(uint32_t a) { uint32_t v; asm volatile("ld.shared.u32 %0, [%1];" : "=r"(v) : "r"(a) : "memory"); return v; }
__device__ __forceinline__ uint2 lds2(uint32_t a) { uint2 v; asm volatile("ld.shared.v2.u32 {%0,%1}, [%2];" : "=r"(v.x), "=r"(v.y) : "r"(a) : "memory"); return v; }
__device__ __forceinline__ uint32_t set_par(uint32_t v, uint32_t mask, uint32_t par) {
    uint32_t r; asm("lop3.b32 %0, %1, %2, %3, 0xb8;" : "=r"(r) : "r"(v), "r"(mask), "r"(par)); return r;
}
__device__ __forceinline__ void st_gen4(void* p, uint32_t x, uint32_t y, uint32_t z, uint32_t w) { asm volatile("st.v4.u32 [%0], {%1,%2,%3,%4};" :: "l"(p), "r"(x), "r"(y), "r"(z), "r"(w) : "memory"); }
__device__ __forceinline__ float tanh_hw(float x) { float r; asm("tanh.approx.f32 %0, %1;" : "=f"(r) : "f"(x)); return r; }
__device__ __forceinline__ bool bar_any(int id, int n, bool v) {
    uint32_t r;
    asm volatile("{ .reg .pred p, q; setp.ne.u32 p, %3, 0; bar.red.or.pred q, %1, %2, p; selp.u32 %0, 1, 0, q; }" : "=r"(r) : "r"(id), "r"(n), "r"((uint32_t)v) : "memory");
    return r;
}
__device__ __forceinline__ void sts4(uint32_t a, uint32_t x, uint32_t y, uint32_t z, uint32_t w) { asm volatile("st.shared.v4.u32 [%0], {%1,%2,%3,%4};" :: "r"(a), "r"(x), "r"(y), "r"(z), "r"(w) : "memory"); }
__device__ __forceinline__ uint4 lds4(uint32_t a) { uint4 v; asm volatile("ld.shared.v4.u32 {%0,%1,%2,%3}, [%4];" : "=r"(v.x), "=r"(v.y), "=r"(v.z), "=r"(v.w) : "r"(a) : "memory"); return v; }
__device__ __forceinline__ uint32_t pack_bf16(float lo, float hi) { uint32_t r; asm("cvt.rn.bf16x2.f32 %0, %1, %2;" : "=r"(r) : "f"(hi), "f"(lo)); return r; }
__device__ __forceinline__ float bf_lo(uint32_t v) { return __uint_as_float(v << 16); }
__device__ __forceinline__ float bf_hi(uint32_t v) { return __uint_as_float(v & 0xffff0000u); }
__device__ __forceinline__ uint32_t sub_bf16x2(uint32_t a, uint32_t b) { uint32_t r; asm volatile("sub.rn.bf16x2 %0, %1, %2;" : "=r"(r) : "r"(a), "r"(b)); return r; }
__device__ __forceinline__ uint32_t add_bf16x2(uint32_t a, uint32_t b) { uint32_t r; asm volatile("add.rn.bf16x2 %0, %1, %2;" : "=r"(r) : "r"(a), "r"(b)); return r; }
__device__ __forceinline__ uint32_t sqr_bf16x2(uint32_t a) { uint32_t r; asm volatile("mul.rn.bf16x2 %0, %1, %1;" : "=r"(r) : "r"(a)); return r; }
__device__ __forceinline__ uint32_t sqa_bf16x2(uint32_t a, uint32_t c) { uint32_t r; asm volatile("fma.rn.bf16x2 %0, %1, %1, %2;" : "=r"(r) : "r"(a), "r"(c)); return r; }
__device__ __forceinline__ uint32_t movm(uint32_t a) { uint32_t r; asm volatile("movmatrix.sync.aligned.m8n8.trans.b16 %0, %1;" : "=r"(r) : "r"(a)); return r; }
__device__ __forceinline__ float ex2(float x) { float r; asm("ex2.approx.ftz.f32 %0, %1;" : "=f"(r) : "f"(x)); return r; }
__device__ __forceinline__ float rsq(float x) { float r; asm("rsqrt.approx.ftz.f32 %0, %1;" : "=f"(r) : "f"(x)); return r; }
__device__ __forceinline__ float rcp(float x) { float r; asm("rcp.approx.ftz.f32 %0, %1;" : "=f"(r) : "f"(x)); return r; }
__device__ __forceinline__ void mma16816(float (&c)[4], uint32_t a0, uint32_t a1, uint32_t a2, uint32_t a3, uint32_t b0, uint32_t b1) {
    asm("mma.sync.aligned.m16n8k16.row.col.f32.bf16.bf16.f32 {%0,%1,%2,%3}, {%4,%5,%6,%7}, {%8,%9}, {%0,%1,%2,%3};"
        : "+f"(c[0]), "+f"(c[1]), "+f"(c[2]), "+f"(c[3]) : "r"(a0), "r"(a1), "r"(a2), "r"(a3), "r"(b0), "r"(b1));
}
__device__ __forceinline__ void mma1688(float (&c)[4], uint32_t a0, uint32_t a1, uint32_t b0) {
    asm("mma.sync.aligned.m16n8k8.row.col.f32.bf16.bf16.f32 {%0,%1,%2,%3}, {%4,%5}, {%6}, {%0,%1,%2,%3};"
        : "+f"(c[0]), "+f"(c[1]), "+f"(c[2]), "+f"(c[3]) : "r"(a0), "r"(a1), "r"(b0));
}
__device__ __forceinline__ float quad_sum(float v) { v += __shfl_xor_sync(~0u, v, 1); v += __shfl_xor_sync(~0u, v, 2); return v; }
__device__ __forceinline__ float quad_max(float v) { v = fmaxf(v, __shfl_xor_sync(~0u, v, 1)); v = fmaxf(v, __shfl_xor_sync(~0u, v, 2)); return v; }
__device__ __forceinline__ uint64_t make_desc(uint32_t addr, uint32_t lbo, bool swz, uint32_t sbo = 1024) {
    const uint32_t lo = __shfl_sync(~0u, ((addr & 0x3FFFF) >> 4) | ((lbo >> 4) << 16), 0);
    const uint32_t hi = __shfl_sync(~0u, (swz ? 0x40000000u : 0u) + (sbo >> 4) + (threadIdx.x & 31), 0);
    return ((uint64_t)hi << 32) | lo;
}
template <int I, int N, class F> __device__ __forceinline__ void static_for(F&& f) {
    if constexpr (I < N) { f(std::integral_constant<int, I>{}); static_for<I + 1, N>(f); }
}
__device__ __forceinline__ uint32_t opaque(uint32_t v) { asm volatile("" : "+r"(v)); return v; }
template <int BOFF, int SCALE_D>
__device__ __forceinline__ void wgmma_rs_n56(float (&d)[28], uint32_t a0, uint32_t a1, uint32_t a2, uint32_t a3, uint64_t db) {
    asm volatile("{ .reg .b64 db; add.s64 db, %32, %33;\n"
        "wgmma.mma_async.sync.aligned.m64n56k16.f32.bf16.bf16 "
        "{%0, %1, %2, %3, %4, %5, %6, %7, %8, %9, %10, %11, %12, %13, %14, %15, %16, %17, %18, %19, %20, %21, %22, %23, %24, %25, %26, %27}, "
        "{%28, %29, %30, %31}, db, %34, 1, 1, 1; }"
        : "+f"(d[0]), "+f"(d[1]), "+f"(d[2]), "+f"(d[3]), "+f"(d[4]), "+f"(d[5]), "+f"(d[6]), "+f"(d[7]),
        "+f"(d[8]), "+f"(d[9]), "+f"(d[10]), "+f"(d[11]), "+f"(d[12]), "+f"(d[13]), "+f"(d[14]), "+f"(d[15]),
        "+f"(d[16]), "+f"(d[17]), "+f"(d[18]), "+f"(d[19]), "+f"(d[20]), "+f"(d[21]), "+f"(d[22]), "+f"(d[23]),
        "+f"(d[24]), "+f"(d[25]), "+f"(d[26]), "+f"(d[27])
        : "r"(a0), "r"(a1), "r"(a2), "r"(a3), "l"(db), "n"(BOFF >> 4), "n"(SCALE_D));
}
template <int AOFF, int BOFF, int MMAJOR>
__device__ __forceinline__ void wgmma_ss_n56(float (&d)[28], uint64_t da, uint64_t db, uint32_t keep = 1) {
    asm volatile("{ .reg .b64 da, db; .reg .pred p; setp.ne.u32 p, %33, 0; add.s64 da, %28, %30; add.s64 db, %29, %31;\n"
        "wgmma.mma_async.sync.aligned.m64n56k16.f32.bf16.bf16 "
        "{%0, %1, %2, %3, %4, %5, %6, %7, %8, %9, %10, %11, %12, %13, %14, %15, %16, %17, %18, %19, %20, %21, %22, %23, %24, %25, %26, %27}, "
        "da, db, p, 1, 1, %32, 1; }"
        : "+f"(d[0]), "+f"(d[1]), "+f"(d[2]), "+f"(d[3]), "+f"(d[4]), "+f"(d[5]), "+f"(d[6]), "+f"(d[7]),
        "+f"(d[8]), "+f"(d[9]), "+f"(d[10]), "+f"(d[11]), "+f"(d[12]), "+f"(d[13]), "+f"(d[14]), "+f"(d[15]),
        "+f"(d[16]), "+f"(d[17]), "+f"(d[18]), "+f"(d[19]), "+f"(d[20]), "+f"(d[21]), "+f"(d[22]), "+f"(d[23]),
        "+f"(d[24]), "+f"(d[25]), "+f"(d[26]), "+f"(d[27])
        : "l"(da), "l"(db), "n"(AOFF >> 4), "n"(BOFF >> 4), "n"(MMAJOR), "r"(keep));
}
template <int AOFF, int BOFF, int MMAJOR>
__device__ __forceinline__ void wgmma_ss_n112(float (&d)[28], float (&e)[28], uint64_t da, uint64_t db, uint32_t keep = 1) {
    asm volatile("{ .reg .b64 da, db; .reg .pred p; setp.ne.u32 p, %61, 0; add.s64 da, %56, %58; add.s64 db, %57, %59;\n"
        "wgmma.mma_async.sync.aligned.m64n112k16.f32.bf16.bf16 "
        "{%0, %1, %2, %3, %4, %5, %6, %7, %8, %9, %10, %11, %12, %13, %14, %15, %16, %17, %18, %19, %20, %21, %22, %23, %24, %25, %26, %27, %28, %29, %30, %31, %32, %33, %34, %35, %36, %37, %38, %39, %40, %41, %42, %43, %44, %45, %46, %47, %48, %49, %50, %51, %52, %53, %54, %55}, "
        "da, db, p, 1, 1, %60, 1; }"
        : "+f"(d[0]), "+f"(d[1]), "+f"(d[2]), "+f"(d[3]), "+f"(d[4]), "+f"(d[5]), "+f"(d[6]), "+f"(d[7]),
        "+f"(d[8]), "+f"(d[9]), "+f"(d[10]), "+f"(d[11]), "+f"(d[12]), "+f"(d[13]), "+f"(d[14]), "+f"(d[15]),
        "+f"(d[16]), "+f"(d[17]), "+f"(d[18]), "+f"(d[19]), "+f"(d[20]), "+f"(d[21]), "+f"(d[22]), "+f"(d[23]),
        "+f"(d[24]), "+f"(d[25]), "+f"(d[26]), "+f"(d[27]), "+f"(e[0]), "+f"(e[1]), "+f"(e[2]), "+f"(e[3]),
        "+f"(e[4]), "+f"(e[5]), "+f"(e[6]), "+f"(e[7]), "+f"(e[8]), "+f"(e[9]), "+f"(e[10]), "+f"(e[11]),
        "+f"(e[12]), "+f"(e[13]), "+f"(e[14]), "+f"(e[15]), "+f"(e[16]), "+f"(e[17]), "+f"(e[18]), "+f"(e[19]),
        "+f"(e[20]), "+f"(e[21]), "+f"(e[22]), "+f"(e[23]), "+f"(e[24]), "+f"(e[25]), "+f"(e[26]), "+f"(e[27])
        : "l"(da), "l"(db), "n"(AOFF >> 4), "n"(BOFF >> 4), "n"(MMAJOR), "r"(keep));
}
template <int BOFF, int SCALE_D>
__device__ __forceinline__ void wgmma_rs_n112(float (&d)[28], float (&e)[28], uint32_t a0, uint32_t a1, uint32_t a2, uint32_t a3, uint64_t db) {
    asm volatile("{ .reg .b64 db; add.s64 db, %60, %61;\n"
        "wgmma.mma_async.sync.aligned.m64n112k16.f32.bf16.bf16 "
        "{%0, %1, %2, %3, %4, %5, %6, %7, %8, %9, %10, %11, %12, %13, %14, %15, %16, %17, %18, %19, %20, %21, %22, %23, %24, %25, %26, %27, %28, %29, %30, %31, %32, %33, %34, %35, %36, %37, %38, %39, %40, %41, %42, %43, %44, %45, %46, %47, %48, %49, %50, %51, %52, %53, %54, %55}, "
        "{%56, %57, %58, %59}, db, %62, 1, 1, 1; }"
        : "+f"(d[0]), "+f"(d[1]), "+f"(d[2]), "+f"(d[3]), "+f"(d[4]), "+f"(d[5]), "+f"(d[6]), "+f"(d[7]),
        "+f"(d[8]), "+f"(d[9]), "+f"(d[10]), "+f"(d[11]), "+f"(d[12]), "+f"(d[13]), "+f"(d[14]), "+f"(d[15]),
        "+f"(d[16]), "+f"(d[17]), "+f"(d[18]), "+f"(d[19]), "+f"(d[20]), "+f"(d[21]), "+f"(d[22]), "+f"(d[23]),
        "+f"(d[24]), "+f"(d[25]), "+f"(d[26]), "+f"(d[27]), "+f"(e[0]), "+f"(e[1]), "+f"(e[2]), "+f"(e[3]),
        "+f"(e[4]), "+f"(e[5]), "+f"(e[6]), "+f"(e[7]), "+f"(e[8]), "+f"(e[9]), "+f"(e[10]), "+f"(e[11]),
        "+f"(e[12]), "+f"(e[13]), "+f"(e[14]), "+f"(e[15]), "+f"(e[16]), "+f"(e[17]), "+f"(e[18]), "+f"(e[19]),
        "+f"(e[20]), "+f"(e[21]), "+f"(e[22]), "+f"(e[23]), "+f"(e[24]), "+f"(e[25]), "+f"(e[26]), "+f"(e[27])
        : "r"(a0), "r"(a1), "r"(a2), "r"(a3), "l"(db), "n"(BOFF >> 4), "n"(SCALE_D));
}

struct Params {
    const __nv_bfloat16 *x, *wqkv;
    Scratch* sc;
    const __nv_bfloat16 *wo, *w1, *w2, *b1, *b2;
    __nv_bfloat16* out;
};

__global__ void __cluster_dims__(2, 1, 1) __launch_bounds__(384, 1)
fused_kernel(const Params prm, const __grid_constant__ CUtensorMap mX2, const __grid_constant__ CUtensorMap mX, const __grid_constant__ CUtensorMap mWqkv,
             const __grid_constant__ CUtensorMap mWo, const __grid_constant__ CUtensorMap mW1,
             const __grid_constant__ CUtensorMap mW2)
{
    extern __shared__ __align__(1024) unsigned char smem_raw[];
    if (threadIdx.x < 126) {
        const uint32_t i = threadIdx.x, t = clk32() + (i >> 5) * PFD;
        const char* px = (const char*)prm.x + (blockIdx.x * 16 + (i & 15)) * 896 + (i >> 4) * 128;
        const char* pw = (const char*)prm.wqkv + blockIdx.x * 2688 + i * 128 + (896 - 112 * 128);
        spin_until(t);
        asm volatile("prefetch.global.L2 [%0];" :: "l"(i < 112 ? px : pw) : "memory");
    }
    if (threadIdx.x == 128) { asm volatile("prefetch.tensormap [%0];" :: "l"(&mX2) : "memory"); asm volatile("prefetch.tensormap [%0];" :: "l"(&mWqkv) : "memory"); }
    uint32_t sb = (uint32_t)__cvta_generic_to_shared(smem_raw);
    asm volatile("mov.u32 %0, %0;" : "+r"(sb));
    const uint32_t bar0 = sb + SM_BAR;
    auto BAR = [&](int i) { return bar0 + 8u * i; };

    const int tid = threadIdx.x, lane = tid & 31;
    const int warp = __shfl_sync(~0u, tid >> 5, 0);
    const int b = __shfl_sync(~0u, (int)blockIdx.x, 0);
    const int rank = b & 1;
    const int cl = (b >> 1) - 4, cq = ((cl - 32) * 37) >> 8;
    const int res = cl < 0 ? 0 : cl < 32 ? cl & 7 : cl - 31 - 7 * cq;
    const int rnd = cl < 0 ? cl + 8 : cl < 32 ? cl >> 3 : 4 + cq;
    const int hg = (res & 1) * 4 + (rnd & 3);
    const int ti = (res >> 1) * 4 + (rnd >> 2) * 2 + rank;
    const int a2p = res & 1, a2j = rnd & 3;
    const int a2s = ti * 2 + a2p;
    const bool g1_on = rnd != 7;
    const int g1j = (rnd < 6 ? rnd : res) & 1, g1f = rnd < 6 ? res * 3 + (rnd >> 1) : 24 + (res >> 1);
    const int g2j = rnd & 1, g2s = res * 4 + (rnd >> 1);
    uint32_t pbar0;
    asm volatile("mapa.shared::cluster.u32 %0, %1, %2;" : "=r"(pbar0) : "r"(bar0), "r"(rank ^ 1));
    auto pair_arrive = [&](int i) { __syncwarp(); const bool l = elect_one(); mbar_arrive_if(BAR(i), l); mbar_arrive_remote_if(pbar0 + 8u * i, l); };
    const int wcol = hg * 56 - (hg & 1) * 8;

    if (warp == 8) {
        if (elect_one()) {
            #pragma unroll
            for (int i = 0; i < B_WQF; i++) mbar_init(BAR(i), 1);
            asm volatile("fence.mbarrier_init.release.cluster;" ::: "memory");
            fence_async_smem();
            #pragma unroll
            for (int kb = 0; kb < 7; kb++) {
                tma3d(sb + kb * 16384, &mX2, kb * 64, ti * 64, 0, BAR(B_XF + kb));
                mbar_expect(BAR(B_XF + kb), 16384);
                if (kb == 0 && PFX != 3) asm volatile("prefetch.tensormap [%0];" :: "l"(&mWqkv) : "memory");
            }
        }
    } else if (warp > 8) {
        if (elect_one()) {
            if (warp == 9) {
                #pragma unroll
                for (int i = B_WQF; i < B_AF; i++) mbar_init(BAR(i), i < B_XC ? 1 : i < B_A1D ? 16 : i < B_BE ? 8 : 4);
            } else if (warp == 10) {
                #pragma unroll
                for (int i = B_AF; i < B_BF; i++) mbar_init(BAR(i), 1);
            } else {
                #pragma unroll
                for (int i = B_BF; i < B_COUNT; i++) mbar_init(BAR(i), i == B_HD ? 8 : 1);
            }
            asm volatile("fence.mbarrier_init.release.cluster;" ::: "memory");
            fence_async_smem();
        }
    }
    __syncwarp();
    __syncthreads();
    asm volatile("barrier.cluster.arrive.relaxed.aligned;" ::: "memory");
    if (tid < 256) TR(0);
    if (tid == 0) TRG(61);

    if (warp >= 8) {
        asm volatile("setmaxnreg.dec.sync.aligned.u32 40;");
        asm volatile("barrier.cluster.wait.aligned;" ::: "memory");
        auto fetch_halo = [&](int p, uint32_t tag) {
            uint4 u[4];
            #pragma unroll
            for (int c = 0; c < 4; c++) u[c] = make_uint4(0u, 0u, 0u, 0u);
            const uint4* hp = opaque_ptr(&prm.sc->halo[(((ti - 1) * 8 + hg) * 2 + p) * 128 + lane]);
            mbar_wait(BAR(B_KVC), 0);
            if (p == 0) TRW(51);
            sleep_until(clk32() + HDELAY);
            if (ti > 0) {
                int it = 0;
                do {
                    #pragma unroll
                    for (int c = 0; c < 4; c++) u[c] = ld_rlx4(hp + c * 32);
                    if (it) RETRY_COUNT(4);
                    if (++it > kSpinLimit) { TIMEOUT(101); break; }
                } while (__any_sync(~0u, ((u[0].x ^ tag) | (u[1].x ^ tag) | (u[2].x ^ tag) | (u[3].x ^ tag)) & ~lane & 1));
            }
            #pragma unroll
            for (int c = 0; c < 4; c++) sts4(sb + SM_STG + p * 8192 + 3 * 2048 + lane * 16 + c * 512, u[c].x, u[c].y, u[c].z, u[c].w);
            warp_arrive(BAR(B_HL + p));
        };
        if (warp & 1) {
            uint32_t tag;
            if (warp == 11) {
                tag = *(volatile uint32_t*)&prm.sc->epoch + 1;
            #pragma unroll 1
            for (int i = 0; i < 8; i++) prm.sc->halo[(ti * 8 + hg) * 256 + i * 32 + lane] = make_uint4(~tag, 0u, 0u, 0u);
            ((uint4*)prm.sc->stats)[(a2s * 4 + a2j) * 64 + lane] = ((uint4*)prm.sc->stats)[(a2s * 4 + a2j) * 64 + 32 + lane] = make_uint4(~tag, ~tag, ~tag, ~tag);
            prm.sc->flag_h[(a2s * 4 + a2j) * FS + lane] = 0;
            prm.sc->flag_o[(ti * 16 + hg) * FS + lane] = prm.sc->flag_o[(ti * 16 + 8 + hg) * FS + lane] = 0;
            __syncwarp();
            if (lane == 0) {
                asm volatile("st.shared.v2.u32 [%0], {%1, %2};" :: "r"(sb + SM_EPOCH), "r"(tag), "r"(gtime32()) : "memory");
                mbar_arrive(BAR(B_EP));
            }
            if (lane < 8) mbar_expect(BAR(B_RF + lane), 1792);
            __syncwarp();
            TRW(44);
            } else {
                mbar_wait(BAR(B_EP), 0);
                tag = lds1(sb + SM_EPOCH);
            }
            fetch_halo((warp >> 1) & 1, tag);
        }
        if (warp < 10) {
          auto load_slab = [&](int s, bool second) {
              if (!second) tma2d(sb + s * 8192, &mW1, (s & 1) * kF + g1f * 64, (rank * 8 + (s >> 1)) * 64, BAR(B_AF));
              else         tma2d(sb + s * 8192, &mW2, g2s * 64, (rank * 14 + s - 1) * 64, BAR(B_AF));
          };
          if (warp == 8) {
            if (elect_one()) {
                #pragma unroll 1
                for (int s = 0; s < 7; s++) {
                    mbar_expect(BAR(B_WKVF + s), 16384);
                    tma2d_mc(sb + SM_WKV + s * 16384 + rank * 8192, &mWqkv, (1 + rank) * kD + wcol, s * 64, BAR(B_WKVF + s));
                }
            }
            __syncwarp();
            mbar_wait(BAR(B_XC), 0);
            if (elect_one()) {
                asm volatile("prefetch.tensormap [%0];" :: "l"(&mX) : "memory");
                asm volatile("prefetch.tensormap [%0];" :: "l"(&mWo) : "memory");
                asm volatile("prefetch.tensormap [%0];" :: "l"(&mW1) : "memory");
                asm volatile("prefetch.tensormap [%0];" :: "l"(&mW2) : "memory");
                mbar_expect(BAR(B_AF), (g1_on ? NPRE : 14) * 8192);
                mbar_expect(BAR(B_WQF), 57344);
                #pragma unroll 1
                for (int s = rank; s < 7; s += 2) tma2d_mc(sb + SM_WQ + s * 8192, &mWqkv, wcol, s * 64, BAR(B_WQF));
                mbar_expect(BAR(B_XRF), 16384);
                tma2d(sb + SM_XR, &mX, a2p * kD + a2j * 112, ti * 64, BAR(B_XRF));
                tma2d(sb + SM_XR + 8192, &mX, a2p * kD + a2j * 112 + 48, ti * 64, BAR(B_XRF));
            }
            __syncwarp();
            #pragma unroll 1
            for (int h = 0; h < 2; h++) {
                mbar_wait(BAR(B_KV3 + h), 0);
                if (h) mbar_wait2(BAR(B_HL), 0, BAR(B_HL + 1), 0);
                if (elect_one()) {
                    mbar_expect(BAR(B_WOF + h), 57344);
                    tma2d_mc(sb + SM_WKV + h * 57344 + rank * 28672, &mWo, a2j * 112 + rank * 48, h * 224, BAR(B_WOF + h));
                    if (g1_on && h == AFIRST) { load_slab(0, false); load_slab(1, false); load_slab(2, false); }
                }
                __syncwarp();
            }
            if (g1_on) {
                mbar_wait2(BAR(B_XD), 0, BAR(B_OL + 3), 0);
                #pragma unroll 1
                for (int i = 3; i < NPRE; i++) {
                    if (i == 7) mbar_wait(BAR(B_OC), 0);
                    if (elect_one()) load_slab(i, false);
                    __syncwarp();
                }
            } else {
                mbar_wait(BAR(B_HD), 0);
                mbar_arrive_remote_if(pbar0 + 8u * B_PD, lane == 0);
                mbar_wait(BAR(B_GO), 0);
                uint32_t tg = lds1(sb + SM_TG + 4);
                tg += max((int)(lds1(sb + SM_TG2) - tg), 0);
                int it = 0;
                while ((int)(gtime32() - tg) < 0 && ++it < 256) {}
                const uint32_t t0 = clk32();
                if (lane < 2) {
                    asm volatile("st.shared.u32 [%0], %1;" :: "r"(sb + SM_TG + 8 + lane * 4), "r"(t0 + (lane ? CN3 : CN2)) : "memory");
                    mbar_arrive(BAR(B_GD + lane));
                }
                __syncwarp();
                #pragma unroll 1
                for (int s = 1; s < 15; s++) {
                    sleep_until(t0 + W2OFF + s * W2PACE);
                    if (elect_one()) load_slab(s, true);
                    __syncwarp();
                }
            }
          } else {
            TRW(58);
            const uint32_t tag = lds1(sb + SM_EPOCH);
            if (lane < 4) mbar_expect(BAR(B_OL + lane), 14336);
            #pragma unroll 1
            for (int e = 0; e < 2; e++) {
                const uint32_t* fp = e ? &prm.sc->flag_h[(rank * 64 + lane) * FS] : &prm.sc->flag_o[(a2s * 8 + (lane & 7)) * FS];
                if (e) {
                    mbar_wait2(BAR(B_OF + 2), 0, BAR(B_OF + 3), 0);
                    if (lane == 0) st_flag(&prm.sc->flag_h[(a2s * 4 + a2j) * FS], tag);
                    __syncwarp();
                    TRW(57);
                    sleep_until(clk32() + PDELAY);
                }
                uint64_t v0 = 0, v1 = e ? 0 : tag;
                int it = 0;
                do {
                    ld_flag_if(v0, fp, (uint32_t)v0 != tag); ld_flag_if(v1, fp + 32 * FS, (uint32_t)v1 != tag);
                    if (++it > kSpinLimit) { TIMEOUT(108); break; }
                } while (__any_sync(~0u, (uint32_t)v0 != tag || (uint32_t)v1 != tag));
                const uint32_t gbase = __shfl_sync(~0u, (uint32_t)(v0 >> 32), 0);
                const uint32_t tg = gbase + (e ? DELTA : DELTAO)
                                  + __reduce_max_sync(~0u, max((int)((uint32_t)(v0 >> 32) - gbase) - e * (lane >> 2) * SOFF, e ? (int)((uint32_t)(v1 >> 32) - gbase) - 8 * SOFF : 0));
                TRW(e ? 40 : 53);
                mbar_wait(BAR(B_A1D), 0);
                if (elect_one()) {
                    if (e) {
                        asm volatile("st.async.shared::cluster.mbarrier::complete_tx::bytes.b32 [%0], %1, [%2];"
                                     :: "r"(pbar0 + (SM_TG2 - SM_BAR)), "r"(tg), "r"(pbar0 + 8u * B_GO) : "memory");
                        asm volatile("st.shared.u32 [%0], %1;" :: "r"(sb + SM_TG + 4), "r"(tg) : "memory");
                        mbar_expect(BAR(B_GO), 4);
                    } else {
                        it = 0;
                        while ((int)(gtime32() - tg) < 0 && ++it < 256) {}
                        #pragma unroll
                        for (int i = 0; i < 4; i++) bulk_g2s(sb + SM_WQ + i * 14336, &prm.sc->o[(a2s * 4 + i) * 896], 14336, BAR(B_OL + i));
                    }
                }
                __syncwarp();
            }
          }
          if (elect_one()) {
              const int h = ~warp & 1;
              constexpr uint32_t T = 57344, BO = 2 * 14336;
              const char* src1 = (const char*)&prm.sc->hn[(rank * 16 + h) * 3584 + g1j * 896];
              const char* src2 = (const char*)&prm.sc->g[(rank * 14 + h) * 3584 + g2j * 896];
              uint64_t masks = g1_on ? (h ? kSegMasks1 : kSegMasks0) : 0x80 | 0x80 << 10;
              const uint32_t bl = BAR(B_BL + h * NB);
              uint32_t s8 = (g1_on ? NB - 2 + h : h) * 8, ph = 1, tmin = 0;
              const CUtensorMap* am = &mW1;
              uint32_t ad = sb + (NPRE + h) * 8192, astep = 16384; int ac0 = h * kF + g1f * 64, ac1 = (rank * 8 + NPRE / 2) * 64;
              CAP_DECL(ti_, 0);
              #pragma unroll 1
              for (int seg = g1_on ? 0 : 3; seg < 5; seg++) {
                  const char* src = (seg < 3 ? src1 : src2) + (~seg & 1) * BO;
                  uint32_t m = (uint32_t)masks & 0x3ff;
                  masks >>= 10;
                  if (seg == 2) {
                      mbar_wait(BAR(B_PL), 0);
                      mbar_arrive_remote_if(pbar0 + 8u * B_PD, h);
                      am = &mW2; ad = sb + 8192; astep = 8192; ac0 = g2s * 64; ac1 = rank * 14 * 64;
                  } else {
                      const int gate = seg - (seg > 2);
                      mbar_wait(BAR(B_HD + gate), 0);
                      tmin = lds1(sb + SM_TG + gate * 4);
                      if (gate < 2) {
                          tmin += max((int)(lds1(gate ? sb + SM_TG2 : sb + SM_TG) - tmin), 0);
                          int it = 0;
                          while ((int)(gtime32() - tmin) < 0 && ++it < 256) {}
                          tmin = clk32();
                      }
                      tmin += h * PACE1;
                  }
                  #pragma unroll 1
                  do {
                      const uint32_t dst = sb + SM_B + s8 * 1792;
                      spin_until(tmin);
                      mbar_wait_fast(BAR(B_BE) + s8, ph);
                      if (seg) {
                          bulk_g2s(dst, src, 14336, bl + s8);
                          mbar_expect(bl + s8, 14336);
                          CAP(ti_);
                      }
                      tmin += PACE2;
                      src += 2 * T;
                      s8 += 16;
                      if (s8 >= NB * 8) { s8 -= NB * 8; ph ^= 1; }
                      if (m & 1) {
                          mbar_expect_more(bl + s8, 8192);
                          tma2d(ad, am, ac0, ac1, bl + s8);
                          ad += astep; ac1 += 64;
                      }
                      m >>= 1;
                  } while (m != 1);
                  if (seg == 0) ph = 1;
              }
          }
        } else {
          if (warp == 10) {
            mbar_wait(BAR(PFBAR), 0);
            const char* p1 = (const char*)prm.w1 + (size_t)b * 57344 + lane * 128;
            const char* p2 = (const char*)prm.w2 + (size_t)b * 57344 + lane * 128;
            if (lane < 27) asm volatile("prefetch.global.L2 [%0];" :: "l"(lane < 25 ? (const char*)prm.wo + min(b * 25 + lane, 3135) * 128
                                                                          : lane == 25 ? (const char*)prm.b1 + (b % 28) * 128 : (const char*)prm.b2 + (b & 31) * 128));
            uint32_t tnext = clk32();
            #pragma unroll 1
            for (int i = 0; i < 28; i++) {
                while ((int)(clk32() - tnext) < 0) __nanosleep(40);
                asm volatile("prefetch.global.L2 [%0];" :: "l"(i < 14 ? p1 + i * 4096 : p2 + (i - 14) * 4096));
                tnext += PFPACE;
            }
            mbar_wait(BAR(B_EP), 0);
          }
          const uint32_t tag = lds1(sb + SM_EPOCH);
          const int h = warp & 1;
          const bool lead = elect_one();
          const uint32_t wo = lane * 132, l3 = lane < 16 ? 12288 : 0;
          uint32_t base = sb + SM_WQ, bl = BAR(B_OL), bf = BAR(B_OF), m = 4, rph = 0;
          #pragma unroll 1
          for (int e = 0; e < 2; e++) {
              uint32_t s8 = h * 8;
              #pragma unroll 1
              do {
                  const uint32_t dst = base + s8 * 1792;
                  auto stale = [&]() {
                      uint32_t d;
                      asm volatile("{ .reg .b32 x, y, z, u;\n"
                                   "ld.shared.u32 x, [%1]; ld.shared.u32 y, [%1 + 4096]; ld.shared.u32 z, [%1 + 8192]; ld.shared.u32 u, [%2];\n"
                                   "lop3.b32 x, x, y, %3, 0x7e; lop3.b32 z, z, u, %3, 0x7e; lop3.b32 %0, x, z, 1, 0xa8; }"
                                   : "=r"(d) : "r"(dst + wo), "r"(dst + (wo + l3)), "r"(tag) : "memory");
                      return __any_sync(~0u, d);
                  };
                  mbar_wait_fast(bl + s8, m & 1);
                  bool bad = stale();
                  mbar_arrive_if(bf + s8, lead && !bad);
                  if (bad) {
                      const int p = 2 * __clz(m) - 2 + h;
                      RETRY_COUNT(!e ? 1 : p < 32 ? 0 : !g1_on ? 5 : p < 46 ? 2 : 6);
                      const int st = (p > 15) + (p > 31) + (p > 45), s = p - (st < 3 ? 16 * st : 46);
                      const char* src = (const char*)(!e ? &prm.sc->o[(a2s * 4 + p - 56) * 896] : st < 2 ? &prm.sc->hn[(rank * 16 + s) * 3584 + (g1j + 2 * st) * 896]
                                                                                                      : &prm.sc->g[(rank * 14 + s) * 3584 + (g2j + 2 * st - 4) * 896]);
                      int it = 0;
                      do {
                          if (++it > kSpinLimit) { TIMEOUT(111); break; }
                          const uint32_t* q = (const uint32_t*)(src + wo);
                          if (it > RELOAD1 && __any_sync(~0u, ((ld_rlx(q) ^ tag) | (ld_rlx(q + 1024) ^ tag) | (ld_rlx(q + 2048) ^ tag) | (ld_rlx(q + l3 / 4) ^ tag)) & 1)) continue;
                          if (lead) {
                              mbar_expect(BAR(B_RT + h), 14336);
                              bulk_g2s(dst, src, 14336, BAR(B_RT + h));
                          }
                          __syncwarp();
                          mbar_wait(BAR(B_RT + h), rph);
                          rph ^= 1;
                          bad = stale();
                      } while (bad);
                      mbar_arrive_if(bf + s8, lead);
                  }
                  s8 += 16;
                  if (s8 >= NB * 8) s8 -= NB * 8;
                  m >>= 1;
              } while (m != 1);
              base = sb + SM_B; bl = BAR(B_BL + h * NB); bf = BAR(B_BF); m = g1_on ? 0x4fe03f80 : 0x7f80;
          }
        }
    } else {
        asm volatile("setmaxnreg.inc.sync.aligned.u32 232;");
        asm volatile("barrier.cluster.wait.aligned;" ::: "memory");
        const int wg = warp >> 2, w = warp & 3;
        const int g = lane >> 2, t = lane & 3;
        uint32_t tag;
        __nv_bfloat16 bias1a, bias1b;
        {
            const uint64_t dw = make_desc(sb + (hg & 1) * 16, 0, true);
            uint32_t a[28][4];
            float sm[4][4] = {};
            {
                const int r = w * 16 + (lane & 15);
                const uint32_t rowa = sb + wg * 8192 + r * 128;
                #pragma unroll
                for (int k = 0; k < 28; k++) {
                    if (XW == 1 && (k & 3) == 0) mbar_wait(BAR(B_XF + (k >> 2)), 0);
                    if (XW == 2 && k == 0) mbar_wait(BAR(B_XF), 0);
                    if (XW == 2 && (k & 7) == 4) mbar_wait2(BAR(B_XF + (k >> 2)), 0, BAR(B_XF + (k >> 2) + 1), 0);
                    const uint32_t addr = rowa + (k >> 2) * 16384 + ((((k & 3) * 2 + (lane >> 4)) ^ (r & 7)) << 4);
                    uint32_t (&f)[4] = a[k];
                    asm volatile("ldmatrix.sync.aligned.m8n8.x4.shared.b16 {%0,%1,%2,%3}, [%4];"
                                 : "=r"(f[0]), "=r"(f[1]), "=r"(f[2]), "=r"(f[3]) : "r"(addr) : "memory");
                    if (XLAG == 0) mma16816(sm[k & 3], f[0], f[1], f[2], f[3], 0x3F803F80u, 0x3F803F80u);
                    else if (k >= 4) mma16816(sm[k & 3], a[k - 4][0], a[k - 4][1], a[k - 4][2], a[k - 4][3], 0x3F803F80u, 0x3F803F80u);
                }
                if (XLAG) {
                    #pragma unroll
                    for (int k = 24; k < 28; k++) mma16816(sm[k & 3], a[k][0], a[k][1], a[k][2], a[k][3], 0x3F803F80u, 0x3F803F80u);
                }
            }
            const float mean0 = ((sm[0][0] + sm[1][0]) + (sm[2][0] + sm[3][0])) * (1.f / kD);
            const float mean1 = ((sm[0][2] + sm[1][2]) + (sm[2][2] + sm[3][2])) * (1.f / kD);
            const uint32_t mb0 = pack_bf16(mean0, mean0), mb1 = pack_bf16(mean1, mean1);
            pair_arrive(B_XC);
            TR(1);
            float ak[28], av[28], aq[28];
            float ss0 = 0.f, ss1 = 0.f, ss2 = 0.f, ss3 = 0.f;
            uint32_t p0, p1;
            static_for<0, 7>([&](auto S_) {
                constexpr int s = decltype(S_)::value;
                #pragma unroll
                for (int q = 0; q < 4; q++) {
                    uint32_t (&f)[4] = a[s * 4 + q];
                    f[0] = sub_bf16x2(f[0], mb0); f[1] = sub_bf16x2(f[1], mb1);
                    f[2] = sub_bf16x2(f[2], mb0); f[3] = sub_bf16x2(f[3], mb1);
                }
                mbar_wait(BAR(B_WKVF + s), 0);
                wg_fence();
                static_for<0, 4>([&](auto Q_) {
                    constexpr int q = decltype(Q_)::value;
                    uint32_t (&f)[4] = a[s * 4 + q];
                    wgmma_rs_n56<SM_WKV + s * 16384 + q * 2048, (s | q) != 0>(ak, f[0], f[1], f[2], f[3], dw);
                    wgmma_rs_n56<SM_WKV + s * 16384 + q * 2048 + 8192, (s | q) != 0>(av, f[0], f[1], f[2], f[3], dw);
                });
                wg_commit();
                if (s == 4) { wg_wait<1>(); pair_arrive(B_KV3); }
                #pragma unroll
                for (int q = 0; q < 8; q++) {
                    const uint32_t u0 = a[s * 4 + q / 2][(q & 1) * 2], u1 = a[s * 4 + q / 2][(q & 1) * 2 + 1];
                    if (q == 0 && (VCH == 1 || (s & 1) || s == 0)) { p0 = sqr_bf16x2(u0); p1 = sqr_bf16x2(u1); }
                    else { p0 = sqa_bf16x2(u0, p0); p1 = sqa_bf16x2(u1, p1); }
                }
                if (VCH == 1 || !(s & 1)) { ss0 += bf_lo(p0); ss2 += bf_hi(p0); ss1 += bf_lo(p1); ss3 += bf_hi(p1); }
            });
            auto q_chunk = [&](auto K0_, auto K1_) {
                wg_fence();
                static_for<decltype(K0_)::value, decltype(K1_)::value>([&](auto K_) {
                    constexpr int k = decltype(K_)::value;
                    wgmma_rs_n56<SM_WQ + k * 2048, k != 0>(aq, a[k][0], a[k][1], a[k][2], a[k][3], dw);
                });
                wg_commit();
            };
            #define QCHUNK(k0, k1) q_chunk(std::integral_constant<int, k0>{}, std::integral_constant<int, k1>{})
            const float dl0 = mean0 - bf_lo(mb0), dl1 = mean1 - bf_lo(mb1);
            const float rs0 = rsq(fmaxf(quad_sum(ss0 + ss2) * (1.f / kD) - dl0 * dl0, 0.f) + kEps);
            const float rs1 = rsq(fmaxf(quad_sum(ss1 + ss3) * (1.f / kD) - dl1 * dl1, 0.f) + kEps);
            float rk[3][2];
            rk[1][0] = __shfl_sync(~0u, rs0, t * 8); rk[1][1] = __shfl_sync(~0u, rs0, t * 8 + 4);
            rk[2][0] = __shfl_sync(~0u, rs1, t * 8); rk[2][1] = __shfl_sync(~0u, rs1, t * 8 + 4);
            const uint32_t stg = sb + SM_STG + wg * 8192 + lane * 16;
            uint4* hp = (w == 3 ? &prm.sc->halo[((ti * 8 + hg) * 2 + wg) * 128] : (uint4*)(smem_raw + SM_STG + wg * 8192 + w * 2048)) + lane;
            mbar_wait2(BAR(B_EP), 0, BAR(B_WQF), 0);
            tag = lds1(sb + SM_EPOCH);
            QCHUNK(0, QC0);
            wg_wait<1>();
            reg_fence(ak); reg_fence(av);
            TR(2);
            uint32_t kf[3][7], vf[3][7];
            #pragma unroll
            for (int c = 0; c < 7; c++) {
                kf[2][c] = pack_bf16(ak[4 * c + 2], ak[4 * c + 3]);
                vf[2][c] = movm(pack_bf16(av[4 * c + 2], av[4 * c + 3]));
            }
            const uint32_t om = ~lane & 1;
            kf[2][0] = set_par(kf[2][0], om, tag); kf[2][4] = set_par(kf[2][4], om, tag);
            vf[2][1] = set_par(vf[2][1], om, tag); vf[2][5] = set_par(vf[2][5], om, tag);
            st_gen4(hp,      kf[2][0], kf[2][1], kf[2][2], kf[2][3]);
            st_gen4(hp + 32, kf[2][4], kf[2][5], kf[2][6], vf[2][0]);
            st_gen4(hp + 64, vf[2][1], vf[2][2], vf[2][3], vf[2][4]);
            st_gen4(hp + 96, vf[2][5], vf[2][6], __float_as_uint(rk[2][0]), __float_as_uint(rk[2][1]));
            pair_arrive(B_KVC);
            QCHUNK(QC0, QC1);
            #pragma unroll
            for (int c = 0; c < 7; c++) {
                kf[1][c] = pack_bf16(ak[4 * c], ak[4 * c + 1]);
                vf[1][c] = movm(pack_bf16(av[4 * c], av[4 * c + 1]));
            }
            QCHUNK(QC1, QC2);
            named_bar(1 + wg, 128);
            uint32_t* op = opaque_ptr((uint32_t*)&prm.sc->o[((ti * 2 + wg) * 56 + hg * 7) * 64] + w * 64 + lane);
            const uint32_t omk = opaque(((lane & 6) == w * 2 ? 0x11u << (lane & 1) * 8 : 0u) << (((lane >> 3) + (hg & 1)) & 3));
            uint32_t* ofl = opaque_ptr(&prm.sc->flag_o[((ti * 2 + wg) * 8 + hg) * FS]);
            QCHUNK(QC2, 28);
            #undef QCHUNK
            const bool gt0 = 2 * t > g, gt1 = 2 * t + 1 > g, no_prev = ti == 0 && w == 0;
            const float kf0 = gt0 ? rk[1][0] : rk[2][0], kf1 = gt1 ? rk[1][1] : rk[2][1];
            constexpr float kScale = 0.18898223650461362f * 1.4426950408889634f;
            const float sq0 = rs0 * kScale, sf0 = kf0 * (rs1 * kScale), sf1 = kf1 * (rs1 * kScale);
            const float NEG = -__int_as_float(0x7f800000);
            const float nb0 = gt0 && no_prev ? NEG : 0.f, nb1 = gt1 && no_prev ? NEG : 0.f;
            const uint32_t sr = stg + ((w + 3) & 3) * 2048, hbar = BAR(w == 0 ? B_HL + wg : B_EP);
            mbar_wait(BAR(B_EP), 0);
            wg_wait<0>();
            reg_fence(aq);
            warp_arrive(BAR(B_A1D));
            TR(3);
            uint32_t qf[8][2];
            #pragma unroll
            for (int c = 0; c < 7; c++) {
                qf[c + (c > 3)][0] = pack_bf16(aq[4 * c], aq[4 * c + 1]);
                qf[c + (c > 3)][1] = pack_bf16(aq[4 * c + 2], aq[4 * c + 3]);
            }
            qf[4][0] = t >= 2 ? qf[3][0] : 0u; qf[4][1] = t >= 2 ? qf[3][1] : 0u;
            qf[3][0] = t < 2 ? qf[3][0] : 0u;  qf[3][1] = t < 2 ? qf[3][1] : 0u;
            float sc[2][3][4];
            auto scores = [&](int n) {
                #pragma unroll
                for (int hd = 0; hd < 2; hd++) {
                    sc[hd][n][0] = sc[hd][n][1] = sc[hd][n][2] = sc[hd][n][3] = 0.f;
                    mma16816(sc[hd][n], qf[4 * hd][0], qf[4 * hd][1], qf[4 * hd + 1][0], qf[4 * hd + 1][1], kf[n][3 * hd], kf[n][3 * hd + 1]);
                    mma16816(sc[hd][n], qf[4 * hd + 2][0], qf[4 * hd + 2][1], qf[4 * hd + 3][0], qf[4 * hd + 3][1], kf[n][3 * hd + 2], kf[n][3 * hd + 3]);
                }
            };
            scores(1); scores(2);
            mbar_wait(hbar, 0);
            {
                const uint4 u0 = lds4(sr), u1 = lds4(sr + 512), u3 = lds4(sr + 1536), u2 = lds4(sr + 1024);
                kf[0][0] = u0.x; kf[0][1] = u0.y; kf[0][2] = u0.z; kf[0][3] = u0.w;
                kf[0][4] = u1.x; kf[0][5] = u1.y; kf[0][6] = u1.z; vf[0][0] = u1.w;
                vf[0][1] = u2.x; vf[0][2] = u2.y; vf[0][3] = u2.z; vf[0][4] = u2.w;
                vf[0][5] = u3.x; vf[0][6] = u3.y; rk[0][0] = __uint_as_float(u3.z); rk[0][1] = __uint_as_float(u3.w);
            }
            if ((tid & 127) == 0) st_flag(ofl, tag);
            TR(4);
            scores(0);
            const float ke0 = gt0 ? rk[0][0] : rk[1][0], ke1 = gt1 ? rk[0][1] : rk[1][1];
            const float se0 = ke0 * sq0, se1 = ke1 * sq0;
            uint32_t ow[7][2];
            #pragma unroll
            for (int hd = 0; hd < 2; hd++) {
                const int c0 = hd * 3;
                float (&sc_)[3][4] = sc[hd];
                const float e0 = fmaf(gt0 ? sc_[0][0] : sc_[1][0], se0, nb0), e1 = fmaf(gt1 ? sc_[0][1] : sc_[1][1], se1, nb1);
                const float f0 = (gt0 ? sc_[1][2] : sc_[2][2]) * sf0, f1 = (gt1 ? sc_[1][3] : sc_[2][3]) * sf1;
                const float me = quad_max(fmaxf(e0, e1)), mf = quad_max(fmaxf(f0, f1));
                const float p0 = ex2(e0 - me), p1 = ex2(e1 - me), r0 = ex2(f0 - mf), r1 = ex2(f1 - mf);
                const float ie = rcp(quad_sum(p0 + p1)), jf = rcp(quad_sum(r0 + r1));
                const uint32_t pp = pack_bf16(p0 * ke0 * ie, p1 * ke1 * ie), rp = pack_bf16(r0 * kf0 * jf, r1 * kf1 * jf);
                const uint32_t mk = (gt0 ? 0x0000ffffu : 0u) | (gt1 ? 0xffff0000u : 0u);
                #pragma unroll
                for (int c = 0; c < 4; c++) {
                    float o[4] = {0.f, 0.f, 0.f, 0.f};
                    mma16816(o, pp & mk, 0u, pp & ~mk, rp & mk, vf[0][c0 + c], vf[1][c0 + c]);
                    mma1688(o, 0u, rp & ~mk, vf[2][c0 + c]);
                    const uint32_t lo = pack_bf16(o[0], o[1]), hi = pack_bf16(o[2], o[3]);
                    if (hd == 1 && c == 0) { if (t >= 2) { ow[3][0] = lo; ow[3][1] = hi; } }
                    else { ow[c0 + c][0] = lo; ow[c0 + c][1] = hi; }
                }
            }
            #pragma unroll
            for (int c = 0; c < 7; c++) {
                stg1(op + c * 256,      set_par(ow[c][0], (omk >> (c & 3)) & 1, tag));
                stg1(op + c * 256 + 32, set_par(ow[c][1], (omk >> (8 + (c & 3))) & 1, tag));
            }
            TR(5);
        }
        {
            const int cg = a2j * 2 + wg;
            float acc2[28];
            mbar_wait(BAR(B_XRF), 0);
            {
                const uint32_t xa = sb + SM_XR + wg * 8192 + (w * 16 + (lane & 15)) * 128;
                #pragma unroll
                for (int c = 0; c < 4; c++) {
                    uint32_t xr[4];
                    asm volatile("ldmatrix.sync.aligned.m8n8.x4.shared.b16 {%0,%1,%2,%3}, [%4];"
                                 : "=r"(xr[0]), "=r"(xr[1]), "=r"(xr[2]), "=r"(xr[3])
                                 : "r"(xa + ((((c * 2 + wg + (lane >> 4)) ^ lane) & 7) << 4)) : "memory");
                    #pragma unroll
                    for (int e = 0; e < (c < 3 ? 4 : 2); e++) { acc2[8 * c + 2 * e] = bf_lo(xr[e]); acc2[8 * c + 2 * e + 1] = bf_hi(xr[e]); }
                }
            }
            uint32_t* spw = opaque_ptr(&prm.sc->stats[((a2s * 8 + cg) * 4 + w) * 32 + lane]);
            const uint32_t* spr = opaque_ptr(&prm.sc->stats[(a2s * 32 + w) * 32 + lane]);
            uint4* hp = opaque_ptr(&prm.sc->h[((a2s * 8 + w * 2) * 8 + cg) * 64 + lane]);
            const int cgs = cg ^ (a2s >> 4);
            uint32_t* np = opaque_ptr((uint32_t*)&prm.sc->hn[(a2s * 56 + cgs * 7) * 64] + w * 64 + lane);
            const uint64_t dwo = make_desc(sb + SM_WKV + wg * (28672 + 16), 0, true);
            const uint64_t doa = make_desc(sb + SM_WQ, 1024, false, 128);
            bias1a = prm.b1[g1f * 64 + w * 16 + g]; bias1b = prm.b1[g1f * 64 + w * 16 + 8 + g];
            const __nv_bfloat16 bias2a = prm.b2[ti * 128 + (w * 16 + g) * 2 + a2p], bias2b = prm.b2[ti * 128 + (w * 16 + 8 + g) * 2 + a2p];
            reg_fence(acc2);
            fence_async_smem();
            warp_arrive(BAR(B_XD));
            static_for<0, 4>([&](auto P_) {
                constexpr int P = decltype(P_)::value;
                if (P == 0) mbar_wait(BAR(B_WOF), 0);
                if (P == 2) mbar_wait2(BAR(B_OF + P), 0, BAR(B_WOF + 1), 0); else mbar_wait(BAR(B_OF + P), 0);
                if (P == 0) TR(6);
                wg_fence();
                static_for<0, 7>([&](auto K_) { constexpr int k = decltype(K_)::value;
                    wgmma_ss_n56<P * 14336 + k * 2048, (P >> 1) * 57344 + (P & 1) * 14336 + k * 2048, 0>(acc2, doa, dwo); });
                if (P) wg_commit();
                if (P == 2) { wg_wait<1>(); warp_arrive(BAR(B_OC)); }
            });
            wg_wait<0>();
            reg_fence(acc2);
            TR(7);
            float s0 = 0.f, s1 = 0.f, q0 = 0.f, q1 = 0.f;
            #pragma unroll
            for (int c = 0; c < 7; c++) {
                s0 += acc2[4 * c] + acc2[4 * c + 1];     q0 = fmaf(acc2[4 * c], acc2[4 * c], fmaf(acc2[4 * c + 1], acc2[4 * c + 1], q0));
                s1 += acc2[4 * c + 2] + acc2[4 * c + 3]; q1 = fmaf(acc2[4 * c + 2], acc2[4 * c + 2], fmaf(acc2[4 * c + 3], acc2[4 * c + 3], q1));
            }
            const bool th = t >= 2, to = t & 1;
            const float sa = (th ? s1 : s0) + __shfl_xor_sync(~0u, th ? s0 : s1, 2), qa = (th ? q1 : q0) + __shfl_xor_sync(~0u, th ? q0 : q1, 2);
            const float part = (to ? qa : sa) + __shfl_xor_sync(~0u, to ? sa : qa, 1);
            stg1(spw, set_par(__float_as_uint(part), 1u, tag));
            const uint32_t tpoll = clk32() + SDELAY;
            TR(8);
            warp_arrive(BAR(B_HD));
            uint32_t hw[2][7], nm[2][4], us[8];
            #pragma unroll
            for (int r = 0; r < 2; r++) {
                const float b2v = __bfloat162float(r ? bias2b : bias2a);
                #pragma unroll
                for (int c = 0; c < 7; c++) hw[r][c] = pack_bf16(acc2[4 * c + 2 * r] + b2v, acc2[4 * c + 2 * r + 1] + b2v);
                hw[r][0] = set_par(hw[r][0], ~lane & 1, tag);
            }
            auto store_h = [&]() {
                #pragma unroll
                for (int r = 0; r < 2; r++) {
                    stg4(hp + r * 512, hw[r][0], hw[r][1], hw[r][2], hw[r][3]);
                    stg4(hp + r * 512 + 32, tag, hw[r][4], hw[r][5], hw[r][6]);
                }
            };
            if (HPOS == 0) store_h();
            spin_until(tpoll);
            #pragma unroll
            for (int i = 0; i < 8; i++) us[i] = ld_rlx(spr + i * 128);
            if (HPOS == 1) store_h();
            #pragma unroll
            for (int i = 0; i < 8; i++) nm[i >> 2][i & 3] = lane == ((i - (cgs & 1)) & 3) * 8 + w * 2 + (i >> 2);
            {
                int it = 0;
                while (true) {
                    uint32_t bad = 0;
                    #pragma unroll
                    for (int i = 0; i < 8; i++) bad |= us[i] ^ tag;
                    if (!__any_sync(~0u, bad & 1)) break;
                    RETRY_COUNT(3);
                    if (++it > kSpinLimit) { TIMEOUT(103); break; }
                    #pragma unroll
                    for (int i = 0; i < 8; i++) us[i] = ld_rlx(spr + i * 128);
                }
            }
            TR(9);
            const float tot = (((__uint_as_float(us[0]) + __uint_as_float(us[1])) + (__uint_as_float(us[2]) + __uint_as_float(us[3])))
                            + ((__uint_as_float(us[4]) + __uint_as_float(us[5])) + (__uint_as_float(us[6]) + __uint_as_float(us[7])))) * (1.f / kD);
            const float oth = __shfl_xor_sync(~0u, tot, 1);
            const float mean = to ? oth : tot;
            const float var = fmaxf(fmaf(-mean, mean, to ? tot : oth), 0.f);
            const float r1 = rsq(var + kEps);
            const float rra = 0.5f * r1 * rsq(fmaf(var * r1, r1, kEps)), mra = -mean * rra;
            const float rrb = __shfl_xor_sync(~0u, rra, 2), mrb = __shfl_xor_sync(~0u, mra, 2);
            const float rr0 = th ? rrb : rra, mr0 = th ? mrb : mra, rr1 = th ? rra : rrb, mr1 = th ? mra : mrb;
            #pragma unroll
            for (int c = 0; c < 7; c++) {
                stg1(np + c * 256,      set_par(pack_bf16(fmaf(acc2[4 * c], rr0, mr0), fmaf(acc2[4 * c + 1], rr0, mr0)), nm[0][c & 3], tag));
                stg1(np + c * 256 + 32, set_par(pack_bf16(fmaf(acc2[4 * c + 2], rr1, mr1), fmaf(acc2[4 * c + 3], rr1, mr1)), nm[1][c & 3], tag));
            }
            TR(10);
            if (HPOS == 2) store_h();
        }
        float as[28], ac[28];
        const uint32_t xch = opaque(sb + SM_XCH + w * 1792 + lane * 16);
        uint32_t peer_xch; const uint32_t peer_bar = pbar0;
        asm volatile("mapa.shared::cluster.u32 %0, %1, %2;" : "=r"(peer_xch) : "r"(xch), "r"(rank ^ 1));
        uint4 hr[4];
        const int cg2 = (g2j + 2 * wg) * 2 + (rank ^ 1), cg1 = (g1j + 2 * wg) * 2 + (rank ^ (g1f < 14));
        const uint4* hp = &prm.sc->h[((((g2s >> 1) * 2 + (g & 1)) * 8 + (g2s & 1) * 4 + w) * 8 + cg2) * 64 + (g >> 1) * 4 + t];
        auto load_h = [&]() {
            #pragma unroll
            for (int c = 0; c < 4; c++) hr[c] = ld_rlx4(hp + (c >> 1) * 16 + (c & 1) * 32);
        };
        #pragma unroll
        for (int c = 0; c < 4; c++) {
            const float bh = 0.5f * __bfloat162float(c < 2 ? bias1a : bias1b);
            const uint32_t b1h = pack_bf16(bh, bh);
            hr[c] = make_uint4(b1h, b1h, b1h, b1h);
        }
        if (!g1_on) { mbar_wait(BAR(B_GD), 0); load_h(); }
        uint32_t* const gp1 = (uint32_t*)&prm.sc->g[(g1f * 56 + cg1 * 7) * 64] + w * 64 + lane;
        uint32_t* const gp2 = (uint32_t*)(prm.out + (size_t)(g2s * 64 + w * 16 + lane / 7) * kD + cg2 * 56) + (lane % 7) * 4;
        uint32_t gm[2][4];
        #pragma unroll
        for (int i = 0; i < 8; i++) gm[i >> 2][i & 3] = lane == ((i - (cg1 & 1)) & 3) * 8 + w * 2 + (i >> 2);
        const bool lead = elect_one();
        const uint64_t da0 = make_desc(sb, 0, true), db0 = make_desc(sb + SM_B, 128, false);
        #pragma unroll
        for (int c = 0; c < 28; c++) { ac[c] = 0.5f * __bfloat162float(c & 2 ? bias1b : bias1a); as[c] = 0.f; }
        reg_fence(as); reg_fence(ac);
        #pragma unroll 1
        for (int ge = g1_on ? 0 : 1; ge < 2; ge++) {
            if (ge) {
                int it = 0;
                while (true) {
                    uint32_t bad = 0;
                    #pragma unroll
                    for (int c = 0; c < 4; c++) bad |= hr[c].x ^ tag;
                    if (!__any_sync(~0u, bad & ~lane & 1)) break;
                    if (++it > kSpinLimit) { TIMEOUT(110); break; }
                    load_h();
                }
            }
            uint32_t keep = !ge;
            const int use = ge * 2 + wg;
            const uint32_t slot0 = g1_on ? (ge ? 4 : wg * ((16 + NR) % NB)) : 0;
            uint32_t ph = use == 1 ? (16 + NR) / NB & 1 : 0, rb = bar0 + slot0 * 8;
            uint64_t da = da0 + (ge ? 512 : wg * NR * 512), db = db0 + slot0 * 896;
            uint32_t prev = BAR(use == 1 ? B_BE + (15 + NR) % NB : B_WKVF);
            auto next = [&]() {
                const uint32_t cur = rb + B_BE * 8;
                db += 896; rb += 8;
                if (rb == bar0 + NB * 8) { rb = bar0; db = db0; ph ^= 1; }
                wg_wait<1>();
                mbar_arrive_if(prev, lead);
                prev = cur;
            };
            const uint32_t xfree = BAR(use > (g1_on ? 0 : 2) ? B_RE + use - 1 : B_PD), rf = peer_bar + (B_RF + warp) * 8;
            const uint32_t stag = w * (use == 2 ? STAG2 : STAG1);
            mbar_wait(BAR(B_AF), 0);
            if (use == 1) {
                uint32_t af[NR * 4][4];
                mbar_wait(BAR(B_GO), 0);
                const uint32_t tp = lds1(sb + SM_TG + 4) + PLOFF;
                int it = 0;
                while ((int)(gtime32() - tp) < 0 && ++it < 256) __nanosleep(20);
                const uint32_t la = sb + ((lane >> 4) * 8 + (lane & 7)) * 128 + (((w * 2 + ((lane >> 3) & 1)) ^ (lane & 7)) << 4);
                #pragma unroll
                for (int k = 0; k < NR * 4; k++)
                    asm volatile("ldmatrix.sync.aligned.m8n8.x4.trans.shared.b16 {%0,%1,%2,%3}, [%4];"
                                 : "=r"(af[k][0]), "=r"(af[k][1]), "=r"(af[k][2]), "=r"(af[k][3]) : "r"(la + k * 2048) : "memory");
                __syncwarp();
                mbar_arrive_if(BAR(B_PL), lead);
                named_bar(4, 256);
                TR(11);
                static_for<0, NR>([&](auto I_) {
                    constexpr int i = decltype(I_)::value, sl = (16 + i) % NB, o = sl * 14336;
                    mbar_wait_fast(BAR(B_BF + sl), (16 + i) / NB & 1);
                    wg_fence();
                    wgmma_rs_n112<o,       1>(as, ac, af[4 * i][0], af[4 * i][1], af[4 * i][2], af[4 * i][3], db0);
                    wgmma_rs_n112<o + 256, 1>(as, ac, af[4 * i + 1][0], af[4 * i + 1][1], af[4 * i + 1][2], af[4 * i + 1][3], db0);
                    wgmma_rs_n112<o + 512, 1>(as, ac, af[4 * i + 2][0], af[4 * i + 2][1], af[4 * i + 2][2], af[4 * i + 2][3], db0);
                    wgmma_rs_n112<o + 768, 1>(as, ac, af[4 * i + 3][0], af[4 * i + 3][1], af[4 * i + 3][2], af[4 * i + 3][3], db0);
                    wg_commit();
                    if (i) { wg_wait<1>(); mbar_arrive_if(BAR(B_BE + (15 + i) % NB), lead); }
                });
                #pragma unroll
                for (int c = 0; c < 4; c++) asm volatile("" : "=r"(hr[c].x), "=r"(hr[c].y), "=r"(hr[c].z), "=r"(hr[c].w));
            } else if (ge && (wg || g1_on)) named_bar(5 - wg, 256);
            mbar_wait(rb + B_BF * 8, ph);
            if (use != 1) TR(11 + ge * 4);
            auto send = [&]() {
                #pragma unroll
                for (int c = 0; c < 4; c++) {
                    const uint32_t p0 = pack_bf16(as[8 * c], as[8 * c + 1]), p1 = pack_bf16(as[8 * c + 2], as[8 * c + 3]);
                    if (c < 3) {
                        const uint32_t p2 = pack_bf16(as[8 * c + 4], as[8 * c + 5]), p3 = pack_bf16(as[8 * c + 6], as[8 * c + 7]);
                        asm volatile("st.async.shared::cluster.mbarrier::complete_tx::bytes.v4.b32 [%0], {%1,%2,%3,%4}, [%5];"
                                     :: "r"(peer_xch + c * 512), "r"(p0), "r"(p1), "r"(p2), "r"(p3), "r"(rf) : "memory");
                    } else {
                        asm volatile("st.async.shared::cluster.mbarrier::complete_tx::bytes.v2.b32 [%0], {%1,%2}, [%3];"
                                     :: "r"(peer_xch + 1536 - lane * 8), "r"(p0), "r"(p1), "r"(rf) : "memory");
                    }
                }
            };
            #pragma unroll 1
            for (int n = ge ? 14 : 16 - wg * NR;;) {
                wg_fence();
                wgmma_ss_n112<0,    0,   1>(as, ac, da, db, keep);
                wgmma_ss_n112<2048, 256, 1>(as, ac, da, db);
                wgmma_ss_n112<4096, 512, 1>(as, ac, da, db);
                wgmma_ss_n112<6144, 768, 1>(as, ac, da, db);
                wg_commit();
                if (--n == 0 && use < 3) named_arrive(4 + wg, 256);
                da += 512; keep = 1;
                next();
                if (n == 0) break;
                mbar_wait_fast(rb + B_BF * 8, ph);
            }
            const bool xok = mbar_test(xfree, 0);
            wg_wait<0>();
            reg_fence(as); reg_fence(ac);
            mbar_arrive_if(prev, lead);
            EV(0, lane);
            if (STAG1 ? use < 3 : use == 2) sleep_until(clk32() + stag);
            if (!xok) mbar_wait(xfree, 0);
            send();
            EV(1, lane);
            TR(12 + ge * 4);
            if (!ge && HMODE == 0) load_h();
#define OWN(c) pack_bf16(ac[2 * c], ac[2 * c + 1])
            mbar_wait(BAR(B_RF + warp), ge & g1_on);
            EV(2, lane);
            uint32_t pk[14];
            #pragma unroll
            for (int c = 0; c < 3; c++) { const uint4 u = lds4(xch + c * 512); pk[4 * c] = u.x; pk[4 * c + 1] = u.y; pk[4 * c + 2] = u.z; pk[4 * c + 3] = u.w; }
            { const uint2 u = lds2(xch + 1536 - lane * 8); pk[12] = u.x; pk[13] = u.y; }
            EV(3, pk[0] & pk[4] & pk[8] & pk[12]);
            TR(13 + ge * 4);
            if (!ge) {
                #pragma unroll
                for (int c = 0; c < 14; c++) {
                    float r[2];
                    #pragma unroll
                    for (int e = 0; e < 2; e++) {
                        const float u = ac[2 * c + e] + (e ? bf_hi(pk[c]) : bf_lo(pk[c]));
                        r[e] = fmaf(u, tanh_hw(u * fmaf(u * u, 8.f * 0.7978845608f * 0.044715f, 2.f * 0.7978845608f)), u);
                    }
                    const uint32_t rp = pack_bf16(r[0], r[1]);
                    stg1(gp1 + (c >> 1) * 256 + (c & 1) * 32, set_par(rp, gm[c & 1][(c >> 1) & 3], tag));
                    if (c % GCH == GCH - 1 && c < 13) sched_fence(rp);
                }
                EV(4, lane);
                if (HMODE == 2) load_h();
                named_bar(1 + wg, 128);
                EV(5, lane);
                EV(6, lane);
                if (w == 0 && lane == 0) {
                    asm volatile("st.shared.u32 [%0], %1;" :: "r"(sb + SM_TG + 8 + wg * 4), "r"(clk32() + (wg ? XSPECB : XSPEC)) : "memory");
                    mbar_arrive(BAR(B_GD + wg));
                }
                if (lead) mbar_expect(BAR(B_RF + warp), 1792);
                mbar_arrive_remote_if(peer_bar + (B_RE + use) * 8, lead);
            } else {
                #pragma unroll
                for (int c = 0; c < 14; c++) {
                    const int i = (c & 1) * 8 + (c >> 1) + (c >= 8);
                    const uint32_t hw = (i & 3) == 0 ? hr[i >> 2].x : (i & 3) == 1 ? hr[i >> 2].y : (i & 3) == 2 ? hr[i >> 2].z : hr[i >> 2].w;
                    pk[c] = add_bf16x2(add_bf16x2(OWN(c), pk[c]), hw);
                    if (c % OCH == OCH - 1 && c < 13) sched_fence(pk[c]);
                }
                EV(4, pk[13]);
                __syncwarp();
                const uint32_t sa = xch - lane * 16 + (lane & 15) * 112 + (lane >> 4) * 16;
                #pragma unroll
                for (int m = 0; m < 3; m++)
                    asm volatile("stmatrix.sync.aligned.m8n8.x4.shared.b16 [%0], {%1,%2,%3,%4};"
                                 :: "r"(sa + m * 32), "r"(pk[4 * m]), "r"(pk[4 * m + 1]), "r"(pk[4 * m + 2]), "r"(pk[4 * m + 3]) : "memory");
                asm volatile("stmatrix.sync.aligned.m8n8.x2.shared.b16 [%0], {%1,%2};" :: "r"(sa + 96), "r"(pk[12]), "r"(pk[13]) : "memory");
                __syncwarp();
                if (lane < 28) {
                    uint4 u[4];
                    #pragma unroll
                    for (int i = 0; i < 4; i++) u[i] = lds4(xch + i * 448);
                    EV(5, u[0].x & u[1].x & u[2].x & u[3].x);
                    #pragma unroll
                    for (int i = 0; i < 4; i++) stg4(gp2 + i * 896, u[i].x, u[i].y, u[i].z, u[i].w);
                    EV(6, lane);
                }
                __syncwarp();
                mbar_arrive_remote_if(peer_bar + (B_RE + 2) * 8, lead && wg == 0);
            }
            EV(7, lds1(xch));
            TR(14 + ge * 4);
        }
        if (tid == 128) TRG(62);
        if (b == 0 && tid == 128) prm.sc->epoch = tag;
    }
}

typedef CUresult (*EncodeFn)(CUtensorMap*, CUtensorMapDataType, cuuint32_t, void*, const cuuint64_t*, const cuuint64_t*,
                             const cuuint32_t*, const cuuint32_t*, CUtensorMapInterleave, CUtensorMapSwizzle,
                             CUtensorMapL2promotion, CUtensorMapFloatOOBfill);

void make_map(EncodeFn enc, CUtensorMap* m, const void* base, uint64_t cols, uint64_t rows, uint32_t box_rows) {
    cuuint64_t dims[2] = {cols, rows};
    cuuint64_t strides[1] = {cols * 2};
    cuuint32_t box[2] = {64, box_rows};
    cuuint32_t es[2] = {1, 1};
    enc(m, CU_TENSOR_MAP_DATA_TYPE_BFLOAT16, 2, const_cast<void*>(base), dims, strides, box, es, CU_TENSOR_MAP_INTERLEAVE_NONE,
        CU_TENSOR_MAP_SWIZZLE_128B, CU_TENSOR_MAP_L2_PROMOTION_L2_128B, CU_TENSOR_MAP_FLOAT_OOB_FILL_NONE);
}

}

extern "C" void kernel_launch(void* const* d_in, const int* in_sizes, int n_in, void* d_out, int out_size) {
    (void)in_sizes; (void)n_in; (void)out_size;
    void* fn = nullptr;
    cudaDriverEntryPointQueryResult qr;
    cudaGetDriverEntryPoint("cuTensorMapEncodeTiled", &fn, cudaEnableDefault, &qr);
    EncodeFn enc = (EncodeFn)fn;
    CUtensorMap mX2, mX, mWqkv, mWo, mW1, mW2;
    {
        cuuint64_t dims[3] = {kD, kS / 2, 2}, strides[2] = {4 * kD, 2 * kD};
        cuuint32_t box[3] = {64, 64, 2}, es[3] = {1, 1, 1};
        enc(&mX2, CU_TENSOR_MAP_DATA_TYPE_BFLOAT16, 3, d_in[0], dims, strides, box, es, CU_TENSOR_MAP_INTERLEAVE_NONE,
            CU_TENSOR_MAP_SWIZZLE_128B, CU_TENSOR_MAP_L2_PROMOTION_L2_128B, CU_TENSOR_MAP_FLOAT_OOB_FILL_NONE);
    }
    make_map(enc, &mX, d_in[0], 2 * kD, kS / 2, 64);
    make_map(enc, &mWqkv, d_in[1], 3 * kD, kD, 64);
    make_map(enc, &mWo, d_in[2], kD, kD, 224);
    make_map(enc, &mW1, d_in[4], 2 * kF, kS / 2, 64);
    make_map(enc, &mW2, d_in[6], kS, kF, 64);
    Params prm;
    prm.x = (const __nv_bfloat16*)d_in[0];
    prm.wqkv = (const __nv_bfloat16*)d_in[1];
    prm.wo = (const __nv_bfloat16*)d_in[2];
    prm.w1 = (const __nv_bfloat16*)d_in[4];
    prm.b1 = (const __nv_bfloat16*)d_in[5];
    prm.w2 = (const __nv_bfloat16*)d_in[6];
    prm.b2 = (const __nv_bfloat16*)d_in[7];
    prm.out = (__nv_bfloat16*)d_out;
    cudaGetSymbolAddress((void**)&prm.sc, g_scratch);
    cudaFuncSetAttribute(fused_kernel, cudaFuncAttributeMaxDynamicSharedMemorySize, SM_TOTAL);
    fused_kernel<<<128, 384, SM_TOTAL, cudaStreamPerThread>>>(prm, mX2, mX, mWqkv, mWo, mW1, mW2);
}
```

```cpp
#include <cuda_runtime.h>
#include <cuda.h>
#include <cuda_bf16.h>
#include <stdint.h>
#include <type_traits>

namespace {

constexpr int kS = 2048, kD = 448, kF = 1792;
constexpr float kEps = 1e-5f;

#define FS 32
struct Scratch {
    uint4    o[32 * 56 * 64];
    uint4    h[32 * 8 * 8 * 64];
    uint4    hn[32 * 56 * 64];
    uint4    g[28 * 56 * 64];
    uint4    halo[16 * 8 * 2 * 4 * 32];
    uint32_t stats[32 * 8 * 4 * 32];
    uint32_t flag_o[32 * 8 * FS];
    uint32_t flag_h[32 * 4 * FS];
    uint32_t epoch;
};
__device__ __align__(1024) Scratch g_scratch;
#define TIMEOUT(code)
#define RETRY_COUNT(i)
#define CAP_DECL(n, k)
#define CAP(n)
#define CAP_SKIP(n)
#define EV(i, dep)
#define TR2(idx)
#define TR(idx)
#define TRW(idx)
#define TRG(idx)

constexpr uint32_t SM_WKV  = 114688;
constexpr uint32_t SM_XR   = 24576;
constexpr uint32_t SM_STG  = 40960;
constexpr uint32_t SM_WQ   = 57344;
constexpr uint32_t SM_XCH  = 0;
constexpr uint32_t SM_B    = 131072;
constexpr uint32_t SM_BAR  = 231424;
constexpr uint32_t SM_TOTAL = SM_BAR + 1024;
constexpr int NB = 7;
#define SH1 0
#define SH2 0
#define SH2N 5
#define SH3 0
#define NSPEC 4
#define XSPEC 500
#define C2 0
#define C3 0
#define CN2 7200
#define CN3 10900
constexpr int B_XF = 0, B_WKVF = 7, B_WQF = 14, B_XRF = 15, B_WOF = 16,
              B_XC = 18, B_KV3 = 19, B_KVC = 20,
              B_A1D = 21, B_XD = 22, B_OC = 23,
              B_BE = 24, B_RE = B_BE + NB,
              B_PL = B_RE + 3, B_AF = B_PL + 1, B_BL = B_AF + 1  , B_OL = B_BL + 2 * NB  ,
              B_BF = B_OL + 4  , B_OF = B_BF + NB, B_RF = B_OF + 4, B_EP = B_RF + 8, B_PD = B_EP + 1, B_RT = B_PD + 1, B_HL = B_RT + 2,
              B_HD = B_HL + 2  , B_GO = B_HD + 1, B_GD = B_GO + 1, B_COUNT = B_GD + 2;
#define WEARLY 6
#define PF0 126
#define TMPF 2
#define RSTE 2
#define POLLP 1
#define PROBEP 1
#define LOADP 1
#define LOADW 64
#define NOB 0
#define AEARLY 5
#define W1PACE 400
#define W2PACE 200
#define PFPACE 230
#define PFBAR (B_XF + 6)
#define DELTA 1792
#define DELTA2 DELTA
#define BPACE 230
#define BURST 2
#define W1OFF 350
#define W2OFF 2900
#define XPACE 0
#define PSTAG 200
constexpr uint32_t SM_EPOCH = SM_BAR + B_COUNT * 8, SM_TG = SM_EPOCH + 4  , SM_TG2 = SM_TG + 16  , SM_TR = SM_BAR + 768;

#define HDELAY 0
#define QC0 4
#define QC1 10
#define QC2 16
#define HPOS 1
#define XSPECB 850
#define PACE1 120
#define PACE2 400
#define RELOAD1 1
#define VCH 1
#define SOFF 0
#define XW 1
#define XLAG 0
#define PFX 3
#define PFD 250
#define SDELAY 400
#define PDELAY 500
#define NPRE 10
#define PREPACE 0
#define AFIRST 0
#define DELTAO 928
#define NS 0
#define GCH 14
#define OCH 14
#define ICH 14
#define PACKO
#define NR 8
#define HMODE 2
#define HOFF0 (-100)
#define HOFF1 900
#define STAG1 0
#define STAG2 400
#define PLOFF (-250)
#define W1Q 3
#define APOS1 ((1ull << 4) | (1ull << 8) | (1ull << 12) | (1ull << 5) | (1ull << 9) | (1ull << 13))
#define APOS2 (0x5555555ull << 17)
constexpr uint32_t seg_mask(int h, int p0, int p1) {
    uint32_t m = 0; int n = 0;
    for (int p = p0; p < p1; p++) if ((p & 1) == h) m |= (uint32_t)(((APOS1 | APOS2) >> p) & 1) << n++;
    return m | 1u << n;
}
constexpr uint64_t seg_masks(int h) {
    return 2 | (uint64_t)seg_mask(h, 0, 16) << 10 | (uint64_t)seg_mask(h, 16, 32) << 20
             | (uint64_t)seg_mask(h, 32, 46) << 30 | (uint64_t)seg_mask(h, 46, 60) << 40;
}
constexpr uint64_t kSegMasks0 = seg_masks(0), kSegMasks1 = seg_masks(1);

constexpr int kSpinLimit = 1 << 15;
__device__ __forceinline__ bool elect_one() {
    uint32_t p;
    asm volatile("{ .reg .pred P; elect.sync _|P, 0xffffffff; selp.u32 %0, 1, 0, P; }" : "=r"(p));
    return p;
}
__device__ __forceinline__ void mbar_init(uint32_t bar, uint32_t cnt) { asm volatile("mbarrier.init.shared::cta.b64 [%0], %1;" :: "r"(bar), "r"(cnt)); }
__device__ __forceinline__ void mbar_expect(uint32_t bar, uint32_t bytes) { asm volatile("mbarrier.arrive.expect_tx.shared::cta.b64 _, [%0], %1;" :: "r"(bar), "r"(bytes) : "memory"); }
__device__ __forceinline__ void mbar_expect_more(uint32_t bar, uint32_t bytes) { asm volatile("mbarrier.expect_tx.relaxed.cta.shared::cta.b64 [%0], %1;" :: "r"(bar), "r"(bytes) : "memory"); }
__device__ __forceinline__ void mbar_arrive(uint32_t bar) { asm volatile("mbarrier.arrive.shared::cta.b64 _, [%0];" :: "r"(bar) : "memory"); }
__device__ __forceinline__ void mbar_wait(uint32_t bar, uint32_t parity) {
    uint32_t ok; int it = 0;
    do {
        asm volatile("{ .reg .pred p; mbarrier.try_wait.parity.shared::cta.b64 p, [%1], %2; selp.u32 %0, 1, 0, p; }"
                     : "=r"(ok) : "r"(bar), "r"(parity) : "memory");
        if (++it > kSpinLimit) { TIMEOUT((bar & 1023) >> 3); break; }
    } while (!ok);
}
__device__ __forceinline__ bool mbar_try(uint32_t bar, uint32_t parity) {
    uint32_t ok;
    asm volatile("{ .reg .pred p; mbarrier.try_wait.parity.shared::cta.b64 p, [%1], %2; selp.u32 %0, 1, 0, p; }" : "=r"(ok) : "r"(bar), "r"(parity) : "memory");
    return ok;
}
__device__ __forceinline__ bool mbar_test(uint32_t bar, uint32_t parity) {
    uint32_t ok;
    asm volatile("{ .reg .pred p; mbarrier.test_wait.parity.shared::cta.b64 p, [%1], %2; selp.u32 %0, 1, 0, p; }" : "=r"(ok) : "r"(bar), "r"(parity) : "memory");
    return ok;
}
__device__ __forceinline__ void mbar_wait_fast(uint32_t bar, uint32_t parity) { if (!mbar_try(bar, parity)) mbar_wait(bar, parity); }
__device__ __forceinline__ void mbar_wait2(uint32_t bar0, uint32_t par0, uint32_t bar1, uint32_t par1) {
    uint32_t ok; int it = 0;
    do {
        asm volatile("{ .reg .pred p, q; mbarrier.try_wait.parity.shared::cta.b64 p, [%1], %2;\n"
                     "mbarrier.try_wait.parity.shared::cta.b64 q, [%3], %4; and.pred p, p, q; selp.u32 %0, 1, 0, p; }"
                     : "=r"(ok) : "r"(bar0), "r"(par0), "r"(bar1), "r"(par1) : "memory");
        if (++it > kSpinLimit) { TIMEOUT((bar0 & 1023) >> 3); break; }
    } while (!ok);
}
__device__ __forceinline__ void sched_fence(uint32_t v) {
    asm volatile("{ .reg .pred p; .reg .b32 x; mov.b32 x, %0;\nL: setp.eq.u32 p, x, 0xffffffff; @p mov.u32 x, %%clock; @p bra L; }" :: "r"(v) : "memory");
}
template <int N> __device__ __forceinline__ void reg_fence(float (&d)[N]) {
    #pragma unroll
    for (int i = 0; i < N; i++) asm volatile("" : "+f"(d[i]) :: "memory");
}
__device__ __forceinline__ void mbar_wait_cluster(uint32_t bar, uint32_t parity) {
    uint32_t ok; int it = 0;
    do {
        asm volatile("{ .reg .pred p; mbarrier.try_wait.parity.acquire.cluster.shared::cta.b64 p, [%1], %2; selp.u32 %0, 1, 0, p; }"
                     : "=r"(ok) : "r"(bar), "r"(parity) : "memory");
        if (++it > kSpinLimit) { TIMEOUT((bar & 1023) >> 3); break; }
    } while (!ok);
}
__device__ __forceinline__ void mbar_arrive_if(uint32_t bar, bool pred) {
    asm volatile("{ .reg .pred p; setp.ne.u32 p, %1, 0; @p mbarrier.arrive.shared::cta.b64 _, [%0]; }" :: "r"(bar), "r"((uint32_t)pred) : "memory");
}
template <int P> __device__ __forceinline__ void tick() {
    if (P > 1) { const uint32_t t = ((uint32_t)clock() | (P - 1)) + 1; while ((int)((uint32_t)clock() - t) < 0) {} }
}
__device__ __forceinline__ void warp_arrive(uint32_t bar) { __syncwarp(); if (elect_one()) mbar_arrive(bar); }
__device__ __forceinline__ void tma2d(uint32_t dst, const CUtensorMap* m, int c0, int c1, uint32_t bar) {
    asm volatile("cp.async.bulk.tensor.2d.shared::cluster.global.mbarrier::complete_tx::bytes [%0], [%1, {%3, %4}], [%2];"
                 :: "r"(dst), "l"(m), "r"(bar), "r"(c0), "r"(c1) : "memory");
}
__device__ __forceinline__ void tma3d(uint32_t dst, const CUtensorMap* m, int c0, int c1, int c2, uint32_t bar) {
    asm volatile("cp.async.bulk.tensor.3d.shared::cluster.global.mbarrier::complete_tx::bytes [%0], [%1, {%3, %4, %5}], [%2];"
                 :: "r"(dst), "l"(m), "r"(bar), "r"(c0), "r"(c1), "r"(c2) : "memory");
}
__device__ __forceinline__ void tma2d_mc(uint32_t dst, const CUtensorMap* m, int c0, int c1, uint32_t bar) {
    asm volatile("cp.async.bulk.tensor.2d.shared::cluster.global.mbarrier::complete_tx::bytes.multicast::cluster [%0], [%1, {%3, %4}], [%2], %5;"
                 :: "r"(dst), "l"(m), "r"(bar), "r"(c0), "r"(c1), "h"((uint16_t)3) : "memory");
}
__device__ __forceinline__ void bulk_g2s_mc(uint32_t dst, const void* src, uint32_t bytes, uint32_t bar) {
    asm volatile("cp.async.bulk.shared::cluster.global.mbarrier::complete_tx::bytes.multicast::cluster [%0], [%1], %2, [%3], %4;"
                 :: "r"(dst), "l"(src), "r"(bytes), "r"(bar), "h"((uint16_t)3) : "memory");
}
__device__ __forceinline__ void mbar_arrive_remote_if(uint32_t cluster_bar, bool pred) {
    asm volatile("{ .reg .pred p; setp.ne.u32 p, %1, 0; @p mbarrier.arrive.shared::cluster.b64 _, [%0]; }" :: "r"(cluster_bar), "r"((uint32_t)pred) : "memory");
}
__device__ __forceinline__ void bulk_g2s(uint32_t dst, const void* src, uint32_t bytes, uint32_t bar) {
    asm volatile("cp.async.bulk.shared::cluster.global.mbarrier::complete_tx::bytes [%0], [%1], %2, [%3];"
                 :: "r"(dst), "l"(src), "r"(bytes), "r"(bar) : "memory");
}
__device__ __forceinline__ void wg_fence()  { asm volatile("wgmma.fence.sync.aligned;" ::: "memory"); }
__device__ __forceinline__ void wg_commit() { asm volatile("wgmma.commit_group.sync.aligned;" ::: "memory"); }
template <int N> __device__ __forceinline__ void wg_wait() { asm volatile("wgmma.wait_group.sync.aligned %0;" :: "n"(N) : "memory"); }
__device__ __forceinline__ void named_bar(int id, int n) { asm volatile("bar.sync %0, %1;" :: "r"(id), "r"(n) : "memory"); }
__device__ __forceinline__ void named_arrive(int id, int n) { asm volatile("bar.arrive %0, %1;" :: "r"(id), "r"(n) : "memory"); }
__device__ __forceinline__ bool mbar_try2(uint32_t bar0, uint32_t par0, uint32_t bar1, uint32_t par1) {
    uint32_t ok;
    asm volatile("{ .reg .pred p, q; mbarrier.test_wait.parity.shared::cta.b64 p, [%1], %2;\n"
                 "mbarrier.test_wait.parity.shared::cta.b64 q, [%3], %4; and.pred p, p, q; selp.u32 %0, 1, 0, p; }"
                 : "=r"(ok) : "r"(bar0), "r"(par0), "r"(bar1), "r"(par1) : "memory");
    return ok;
}
__device__ __forceinline__ void fence_gpu() { asm volatile("fence.release.gpu;" ::: "memory"); }
__device__ __forceinline__ void fence_async_global() { asm volatile("fence.proxy.async.global;" ::: "memory"); }
__device__ __forceinline__ void fence_async_smem() { asm volatile("fence.proxy.async.shared::cta;" ::: "memory"); }
__device__ __forceinline__ uint32_t gtime32() { uint64_t t; asm volatile("mov.u64 %0, %%globaltimer;" : "=l"(t) :: "memory"); return (uint32_t)t; }
__device__ __forceinline__ uint32_t clk32() { uint64_t t; asm volatile("mov.u64 %0, %%clock64;" : "=l"(t) :: "memory"); return (uint32_t)t; }
__device__ __forceinline__ void spin_until(uint32_t t) { while ((int)(clk32() - t) < 0) {} }
#define SLEEPNS 20
__device__ __forceinline__ void sleep_until(uint32_t t) { while ((int)(clk32() - t) < 0) { if (SLEEPNS) __nanosleep(SLEEPNS); } }
__device__ __forceinline__ void st_flag(uint32_t* p, uint32_t v) {
    const uint64_t w = ((uint64_t)gtime32() << 32) | v;
    asm volatile("st.relaxed.gpu.global.u64 [%0], %1;" :: "l"(p), "l"(w) : "memory");
}
__device__ __forceinline__ void ld_flag_if(uint64_t& v, const uint32_t* p, bool pred) {
    asm volatile("{ .reg .pred p; setp.ne.u32 p, %2, 0; @p ld.relaxed.gpu.global.u64 %0, [%1]; }" : "+l"(v) : "l"(p), "r"((uint32_t)pred) : "memory");
}
__device__ __forceinline__ uint32_t ld_acq(const uint32_t* p) { uint32_t v; asm volatile("ld.acquire.gpu.global.u32 %0, [%1];" : "=r"(v) : "l"(p) : "memory"); return v; }
__device__ __forceinline__ uint32_t ld_rlx(const uint32_t* p) { uint32_t v; asm volatile("ld.relaxed.gpu.global.u32 %0, [%1];" : "=r"(v) : "l"(p) : "memory"); return v; }
template <class T> __device__ __forceinline__ T* opaque_ptr(T* p) { asm volatile("" : "+l"(p)); return p; }
__device__ __forceinline__ uint4 ld_rlx4(const uint4* p) {
    uint4 v; asm volatile("ld.relaxed.gpu.global.v4.u32 {%0,%1,%2,%3}, [%4];" : "=r"(v.x), "=r"(v.y), "=r"(v.z), "=r"(v.w) : "l"(p) : "memory"); return v;
}
__device__ __forceinline__ void st_ll(uint4* p, uint32_t a, uint32_t b, uint32_t tag) {
    uint64_t lo = ((uint64_t)tag << 32) | a, hi = ((uint64_t)tag << 32) | b;
    asm volatile("st.relaxed.gpu.global.v2.u64 [%0], {%1,%2};" :: "l"(p), "l"(lo), "l"(hi) : "memory");
}
__device__ __forceinline__ bool ld_ll(const uint4* p, uint32_t& a, uint32_t& b, uint32_t tag) {
    uint64_t lo, hi;
    asm volatile("ld.relaxed.gpu.global.v2.u64 {%0,%1}, [%2];" : "=l"(lo), "=l"(hi) : "l"(p) : "memory");
    a = (uint32_t)lo; b = (uint32_t)hi;
    return (uint32_t)(lo >> 32) == tag && (uint32_t)(hi >> 32) == tag;
}
__device__ __forceinline__ uint2 ld_acq2(const uint2* p) {
    uint2 v; asm volatile("ld.acquire.gpu.global.v2.u32 {%0,%1}, [%2];" : "=r"(v.x), "=r"(v.y) : "l"(p) : "memory"); return v;
}
__device__ __forceinline__ uint2 ld_rlx2(const uint2* p) {
    uint2 v; asm volatile("ld.relaxed.gpu.global.v2.u32 {%0,%1}, [%2];" : "=r"(v.x), "=r"(v.y) : "l"(p) : "memory"); return v;
}
__device__ __forceinline__ void stg1(uint32_t* p, uint32_t v) { asm volatile("st.global.u32 [%0], %1;" :: "l"(p), "r"(v) : "memory"); }
__device__ __forceinline__ void stg2(void* p, uint32_t x, uint32_t y) { asm volatile("st.global.v2.u32 [%0], {%1,%2};" :: "l"(p), "r"(x), "r"(y) : "memory"); }
__device__ __forceinline__ void stg4(void* p, uint32_t x, uint32_t y, uint32_t z, uint32_t w) { asm volatile("st.global.v4.u32 [%0], {%1,%2,%3,%4};" :: "l"(p), "r"(x), "r"(y), "r"(z), "r"(w) : "memory"); }
__device__ __forceinline__ uint32_t lds1(uint32_t a) { uint32_t v; asm volatile("ld.shared.u32 %0, [%1];" : "=r"(v) : "r"(a) : "memory"); return v; }
__device__ __forceinline__ uint2 lds2(uint32_t a) { uint2 v; asm volatile("ld.shared.v2.u32 {%0,%1}, [%2];" : "=r"(v.x), "=r"(v.y) : "r"(a) : "memory"); return v; }
__device__ __forceinline__ uint32_t set_par(uint32_t v, uint32_t mask, uint32_t par) {
    uint32_t r; asm("lop3.b32 %0, %1, %2, %3, 0xb8;" : "=r"(r) : "r"(v), "r"(mask), "r"(par)); return r;
}
__device__ __forceinline__ void st_gen4(void* p, uint32_t x, uint32_t y, uint32_t z, uint32_t w) { asm volatile("st.v4.u32 [%0], {%1,%2,%3,%4};" :: "l"(p), "r"(x), "r"(y), "r"(z), "r"(w) : "memory"); }
__device__ __forceinline__ float tanh_hw(float x) { float r; asm("tanh.approx.f32 %0, %1;" : "=f"(r) : "f"(x)); return r; }
__device__ __forceinline__ bool bar_any(int id, int n, bool v) {
    uint32_t r;
    asm volatile("{ .reg .pred p, q; setp.ne.u32 p, %3, 0; bar.red.or.pred q, %1, %2, p; selp.u32 %0, 1, 0, q; }" : "=r"(r) : "r"(id), "r"(n), "r"((uint32_t)v) : "memory");
    return r;
}
__device__ __forceinline__ void sts4(uint32_t a, uint32_t x, uint32_t y, uint32_t z, uint32_t w) { asm volatile("st.shared.v4.u32 [%0], {%1,%2,%3,%4};" :: "r"(a), "r"(x), "r"(y), "r"(z), "r"(w) : "memory"); }
__device__ __forceinline__ uint4 lds4(uint32_t a) { uint4 v; asm volatile("ld.shared.v4.u32 {%0,%1,%2,%3}, [%4];" : "=r"(v.x), "=r"(v.y), "=r"(v.z), "=r"(v.w) : "r"(a) : "memory"); return v; }
__device__ __forceinline__ uint32_t pack_bf16(float lo, float hi) { uint32_t r; asm("cvt.rn.bf16x2.f32 %0, %1, %2;" : "=r"(r) : "f"(hi), "f"(lo)); return r; }
__device__ __forceinline__ float bf_lo(uint32_t v) { return __uint_as_float(v << 16); }
__device__ __forceinline__ float bf_hi(uint32_t v) { return __uint_as_float(v & 0xffff0000u); }
__device__ __forceinline__ uint32_t sub_bf16x2(uint32_t a, uint32_t b) { uint32_t r; asm volatile("sub.rn.bf16x2 %0, %1, %2;" : "=r"(r) : "r"(a), "r"(b)); return r; }
__device__ __forceinline__ uint32_t add_bf16x2(uint32_t a, uint32_t b) { uint32_t r; asm volatile("add.rn.bf16x2 %0, %1, %2;" : "=r"(r) : "r"(a), "r"(b)); return r; }
__device__ __forceinline__ uint32_t sqr_bf16x2(uint32_t a) { uint32_t r; asm volatile("mul.rn.bf16x2 %0, %1, %1;" : "=r"(r) : "r"(a)); return r; }
__device__ __forceinline__ uint32_t sqa_bf16x2(uint32_t a, uint32_t c) { uint32_t r; asm volatile("fma.rn.bf16x2 %0, %1, %1, %2;" : "=r"(r) : "r"(a), "r"(c)); return r; }
__device__ __forceinline__ uint32_t movm(uint32_t a) { uint32_t r; asm volatile("movmatrix.sync.aligned.m8n8.trans.b16 %0, %1;" : "=r"(r) : "r"(a)); return r; }
__device__ __forceinline__ float ex2(float x) { float r; asm("ex2.approx.ftz.f32 %0, %1;" : "=f"(r) : "f"(x)); return r; }
__device__ __forceinline__ float rsq(float x) { float r; asm("rsqrt.approx.ftz.f32 %0, %1;" : "=f"(r) : "f"(x)); return r; }
__device__ __forceinline__ float rcp(float x) { float r; asm("rcp.approx.ftz.f32 %0, %1;" : "=f"(r) : "f"(x)); return r; }
__device__ __forceinline__ void mma16816(float (&c)[4], uint32_t a0, uint32_t a1, uint32_t a2, uint32_t a3, uint32_t b0, uint32_t b1) {
    asm("mma.sync.aligned.m16n8k16.row.col.f32.bf16.bf16.f32 {%0,%1,%2,%3}, {%4,%5,%6,%7}, {%8,%9}, {%0,%1,%2,%3};"
        : "+f"(c[0]), "+f"(c[1]), "+f"(c[2]), "+f"(c[3]) : "r"(a0), "r"(a1), "r"(a2), "r"(a3), "r"(b0), "r"(b1));
}
__device__ __forceinline__ void mma1688(float (&c)[4], uint32_t a0, uint32_t a1, uint32_t b0) {
    asm("mma.sync.aligned.m16n8k8.row.col.f32.bf16.bf16.f32 {%0,%1,%2,%3}, {%4,%5}, {%6}, {%0,%1,%2,%3};"
        : "+f"(c[0]), "+f"(c[1]), "+f"(c[2]), "+f"(c[3]) : "r"(a0), "r"(a1), "r"(b0));
}
__device__ __forceinline__ float quad_sum(float v) { v += __shfl_xor_sync(~0u, v, 1); v += __shfl_xor_sync(~0u, v, 2); return v; }
__device__ __forceinline__ float quad_max(float v) { v = fmaxf(v, __shfl_xor_sync(~0u, v, 1)); v = fmaxf(v, __shfl_xor_sync(~0u, v, 2)); return v; }
__device__ __forceinline__ uint64_t make_desc(uint32_t addr, uint32_t lbo, bool swz, uint32_t sbo = 1024) {
    const uint32_t lo = __shfl_sync(~0u, ((addr & 0x3FFFF) >> 4) | ((lbo >> 4) << 16), 0);
    const uint32_t hi = __shfl_sync(~0u, (swz ? 0x40000000u : 0u) + (sbo >> 4) + (threadIdx.x & 31), 0);
    return ((uint64_t)hi << 32) | lo;
}
template <int I, int N, class F> __device__ __forceinline__ void static_for(F&& f) {
    if constexpr (I < N) { f(std::integral_constant<int, I>{}); static_for<I + 1, N>(f); }
}
__device__ __forceinline__ uint32_t opaque(uint32_t v) { asm volatile("" : "+r"(v)); return v; }
template <int BOFF, int SCALE_D>
__device__ __forceinline__ void wgmma_rs_n56(float (&d)[28], uint32_t a0, uint32_t a1, uint32_t a2, uint32_t a3, uint64_t db) {
    asm volatile("{ .reg .b64 db; add.s64 db, %32, %33;\n"
        "wgmma.mma_async.sync.aligned.m64n56k16.f32.bf16.bf16 "
        "{%0, %1, %2, %3, %4, %5, %6, %7, %8, %9, %10, %11, %12, %13, %14, %15, %16, %17, %18, %19, %20, %21, %22, %23, %24, %25, %26, %27}, "
        "{%28, %29, %30, %31}, db, %34, 1, 1, 1; }"
        : "+f"(d[0]), "+f"(d[1]), "+f"(d[2]), "+f"(d[3]), "+f"(d[4]), "+f"(d[5]), "+f"(d[6]), "+f"(d[7]),
        "+f"(d[8]), "+f"(d[9]), "+f"(d[10]), "+f"(d[11]), "+f"(d[12]), "+f"(d[13]), "+f"(d[14]), "+f"(d[15]),
        "+f"(d[16]), "+f"(d[17]), "+f"(d[18]), "+f"(d[19]), "+f"(d[20]), "+f"(d[21]), "+f"(d[22]), "+f"(d[23]),
        "+f"(d[24]), "+f"(d[25]), "+f"(d[26]), "+f"(d[27])
        : "r"(a0), "r"(a1), "r"(a2), "r"(a3), "l"(db), "n"(BOFF >> 4), "n"(SCALE_D));
}
template <int AOFF, int BOFF, int MMAJOR>
__device__ __forceinline__ void wgmma_ss_n56(float (&d)[28], uint64_t da, uint64_t db, uint32_t keep = 1) {
    asm volatile("{ .reg .b64 da, db; .reg .pred p; setp.ne.u32 p, %33, 0; add.s64 da, %28, %30; add.s64 db, %29, %31;\n"
        "wgmma.mma_async.sync.aligned.m64n56k16.f32.bf16.bf16 "
        "{%0, %1, %2, %3, %4, %5, %6, %7, %8, %9, %10, %11, %12, %13, %14, %15, %16, %17, %18, %19, %20, %21, %22, %23, %24, %25, %26, %27}, "
        "da, db, p, 1, 1, %32, 1; }"
        : "+f"(d[0]), "+f"(d[1]), "+f"(d[2]), "+f"(d[3]), "+f"(d[4]), "+f"(d[5]), "+f"(d[6]), "+f"(d[7]),
        "+f"(d[8]), "+f"(d[9]), "+f"(d[10]), "+f"(d[11]), "+f"(d[12]), "+f"(d[13]), "+f"(d[14]), "+f"(d[15]),
        "+f"(d[16]), "+f"(d[17]), "+f"(d[18]), "+f"(d[19]), "+f"(d[20]), "+f"(d[21]), "+f"(d[22]), "+f"(d[23]),
        "+f"(d[24]), "+f"(d[25]), "+f"(d[26]), "+f"(d[27])
        : "l"(da), "l"(db), "n"(AOFF >> 4), "n"(BOFF >> 4), "n"(MMAJOR), "r"(keep));
}
template <int AOFF, int BOFF, int MMAJOR>
__device__ __forceinline__ void wgmma_ss_n112(float (&d)[28], float (&e)[28], uint64_t da, uint64_t db, uint32_t keep = 1) {
    asm volatile("{ .reg .b64 da, db; .reg .pred p; setp.ne.u32 p, %61, 0; add.s64 da, %56, %58; add.s64 db, %57, %59;\n"
        "wgmma.mma_async.sync.aligned.m64n112k16.f32.bf16.bf16 "
        "{%0, %1, %2, %3, %4, %5, %6, %7, %8, %9, %10, %11, %12, %13, %14, %15, %16, %17, %18, %19, %20, %21, %22, %23, %24, %25, %26, %27, %28, %29, %30, %31, %32, %33, %34, %35, %36, %37, %38, %39, %40, %41, %42, %43, %44, %45, %46, %47, %48, %49, %50, %51, %52, %53, %54, %55}, "
        "da, db, p, 1, 1, %60, 1; }"
        : "+f"(d[0]), "+f"(d[1]), "+f"(d[2]), "+f"(d[3]), "+f"(d[4]), "+f"(d[5]), "+f"(d[6]), "+f"(d[7]),
        "+f"(d[8]), "+f"(d[9]), "+f"(d[10]), "+f"(d[11]), "+f"(d[12]), "+f"(d[13]), "+f"(d[14]), "+f"(d[15]),
        "+f"(d[16]), "+f"(d[17]), "+f"(d[18]), "+f"(d[19]), "+f"(d[20]), "+f"(d[21]), "+f"(d[22]), "+f"(d[23]),
        "+f"(d[24]), "+f"(d[25]), "+f"(d[26]), "+f"(d[27]), "+f"(e[0]), "+f"(e[1]), "+f"(e[2]), "+f"(e[3]),
        "+f"(e[4]), "+f"(e[5]), "+f"(e[6]), "+f"(e[7]), "+f"(e[8]), "+f"(e[9]), "+f"(e[10]), "+f"(e[11]),
        "+f"(e[12]), "+f"(e[13]), "+f"(e[14]), "+f"(e[15]), "+f"(e[16]), "+f"(e[17]), "+f"(e[18]), "+f"(e[19]),
        "+f"(e[20]), "+f"(e[21]), "+f"(e[22]), "+f"(e[23]), "+f"(e[24]), "+f"(e[25]), "+f"(e[26]), "+f"(e[27])
        : "l"(da), "l"(db), "n"(AOFF >> 4), "n"(BOFF >> 4), "n"(MMAJOR), "r"(keep));
}
template <int BOFF, int SCALE_D>
__device__ __forceinline__ void wgmma_rs_n112(float (&d)[28], float (&e)[28], uint32_t a0, uint32_t a1, uint32_t a2, uint32_t a3, uint64_t db) {
    asm volatile("{ .reg .b64 db; add.s64 db, %60, %61;\n"
        "wgmma.mma_async.sync.aligned.m64n112k16.f32.bf16.bf16 "
        "{%0, %1, %2, %3, %4, %5, %6, %7, %8, %9, %10, %11, %12, %13, %14, %15, %16, %17, %18, %19, %20, %21, %22, %23, %24, %25, %26, %27, %28, %29, %30, %31, %32, %33, %34, %35, %36, %37, %38, %39, %40, %41, %42, %43, %44, %45, %46, %47, %48, %49, %50, %51, %52, %53, %54, %55}, "
        "{%56, %57, %58, %59}, db, %62, 1, 1, 1; }"
        : "+f"(d[0]), "+f"(d[1]), "+f"(d[2]), "+f"(d[3]), "+f"(d[4]), "+f"(d[5]), "+f"(d[6]), "+f"(d[7]),
        "+f"(d[8]), "+f"(d[9]), "+f"(d[10]), "+f"(d[11]), "+f"(d[12]), "+f"(d[13]), "+f"(d[14]), "+f"(d[15]),
        "+f"(d[16]), "+f"(d[17]), "+f"(d[18]), "+f"(d[19]), "+f"(d[20]), "+f"(d[21]), "+f"(d[22]), "+f"(d[23]),
        "+f"(d[24]), "+f"(d[25]), "+f"(d[26]), "+f"(d[27]), "+f"(e[0]), "+f"(e[1]), "+f"(e[2]), "+f"(e[3]),
        "+f"(e[4]), "+f"(e[5]), "+f"(e[6]), "+f"(e[7]), "+f"(e[8]), "+f"(e[9]), "+f"(e[10]), "+f"(e[11]),
        "+f"(e[12]), "+f"(e[13]), "+f"(e[14]), "+f"(e[15]), "+f"(e[16]), "+f"(e[17]), "+f"(e[18]), "+f"(e[19]),
        "+f"(e[20]), "+f"(e[21]), "+f"(e[22]), "+f"(e[23]), "+f"(e[24]), "+f"(e[25]), "+f"(e[26]), "+f"(e[27])
        : "r"(a0), "r"(a1), "r"(a2), "r"(a3), "l"(db), "n"(BOFF >> 4), "n"(SCALE_D));
}

struct Params {
    const __nv_bfloat16 *x, *wqkv;
    Scratch* sc;
    const __nv_bfloat16 *wo, *w1, *w2, *b1, *b2;
    __nv_bfloat16* out;
};

__global__ void __cluster_dims__(2, 1, 1) __launch_bounds__(384, 1)
fused_kernel(const Params prm, const __grid_constant__ CUtensorMap mX2, const __grid_constant__ CUtensorMap mX, const __grid_constant__ CUtensorMap mWqkv,
             const __grid_constant__ CUtensorMap mWo, const __grid_constant__ CUtensorMap mW1,
             const __grid_constant__ CUtensorMap mW2)
{
    extern __shared__ __align__(1024) unsigned char smem_raw[];
    if (threadIdx.x < 126) {
        const uint32_t i = threadIdx.x, t = clk32() + (i >> 5) * PFD;
        const char* px = (const char*)prm.x + (blockIdx.x * 16 + (i & 15)) * 896 + (i >> 4) * 128;
        const char* pw = (const char*)prm.wqkv + blockIdx.x * 2688 + i * 128 + (896 - 112 * 128);
        spin_until(t);
        asm volatile("prefetch.global.L2 [%0];" :: "l"(i < 112 ? px : pw) : "memory");
    }
    if (threadIdx.x == 128) { asm volatile("prefetch.tensormap [%0];" :: "l"(&mX2) : "memory"); asm volatile("prefetch.tensormap [%0];" :: "l"(&mWqkv) : "memory"); }
    uint32_t sb = (uint32_t)__cvta_generic_to_shared(smem_raw);
    asm volatile("mov.u32 %0, %0;" : "+r"(sb));
    const uint32_t bar0 = sb + SM_BAR;
    auto BAR = [&](int i) { return bar0 + 8u * i; };

    const int tid = threadIdx.x, lane = tid & 31;
    const int warp = __shfl_sync(~0u, tid >> 5, 0);
    const int b = __shfl_sync(~0u, (int)blockIdx.x, 0);
    const int rank = b & 1;
    const int cl = (b >> 1) - 4, cq = ((cl - 32) * 37) >> 8;
    const int res = cl < 0 ? 0 : cl < 32 ? cl & 7 : cl - 31 - 7 * cq;
    const int rnd = cl < 0 ? cl + 8 : cl < 32 ? cl >> 3 : 4 + cq;
    const int hg = (res & 1) * 4 + (rnd & 3);
    const int ti = (res >> 1) * 4 + (rnd >> 2) * 2 + rank;
    const int a2p = res & 1, a2j = rnd & 3;
    const int a2s = ti * 2 + a2p;
    const bool g1_on = rnd != 7;
    const int g1j = (rnd < 6 ? rnd : res) & 1, g1f = rnd < 6 ? res * 3 + (rnd >> 1) : 24 + (res >> 1);
    const int g2j = rnd & 1, g2s = res * 4 + (rnd >> 1);
    uint32_t pbar0;
    asm volatile("mapa.shared::cluster.u32 %0, %1, %2;" : "=r"(pbar0) : "r"(bar0), "r"(rank ^ 1));
    auto pair_arrive = [&](int i) { __syncwarp(); const bool l = elect_one(); mbar_arrive_if(BAR(i), l); mbar_arrive_remote_if(pbar0 + 8u * i, l); };
    const int wcol = hg * 56 - (hg & 1) * 8;

    if (warp == 8) {
        if (elect_one()) {
            #pragma unroll
            for (int i = 0; i < B_WQF; i++) mbar_init(BAR(i), 1);
            asm volatile("fence.mbarrier_init.release.cluster;" ::: "memory");
            fence_async_smem();
            #pragma unroll
            for (int kb = 0; kb < 7; kb++) {
                tma3d(sb + kb * 16384, &mX2, kb * 64, ti * 64, 0, BAR(B_XF + kb));
                mbar_expect(BAR(B_XF + kb), 16384);
                if (kb == 0 && PFX != 3) asm volatile("prefetch.tensormap [%0];" :: "l"(&mWqkv) : "memory");
            }
        }
    } else if (warp > 8) {
        if (elect_one()) {
            if (warp == 9) {
                #pragma unroll
                for (int i = B_WQF; i < B_AF; i++) mbar_init(BAR(i), i < B_XC ? 1 : i < B_A1D ? 16 : i < B_BE ? 8 : 4);
            } else if (warp == 10) {
                #pragma unroll
                for (int i = B_AF; i < B_BF; i++) mbar_init(BAR(i), 1);
            } else {
                #pragma unroll
                for (int i = B_BF; i < B_COUNT; i++) mbar_init(BAR(i), i == B_HD ? 8 : 1);
            }
            asm volatile("fence.mbarrier_init.release.cluster;" ::: "memory");
            fence_async_smem();
        }
    }
    __syncwarp();
    __syncthreads();
    asm volatile("barrier.cluster.arrive.relaxed.aligned;" ::: "memory");
    if (tid < 256) TR(0);
    if (tid == 0) TRG(61);

    if (warp >= 8) {
        asm volatile("setmaxnreg.dec.sync.aligned.u32 40;");
        asm volatile("barrier.cluster.wait.aligned;" ::: "memory");
        auto fetch_halo = [&](int p, uint32_t tag) {
            uint4 u[4];
            #pragma unroll
            for (int c = 0; c < 4; c++) u[c] = make_uint4(0u, 0u, 0u, 0u);
            const uint4* hp = opaque_ptr(&prm.sc->halo[(((ti - 1) * 8 + hg) * 2 + p) * 128 + lane]);
            mbar_wait(BAR(B_KVC), 0);
            if (p == 0) TRW(51);
            sleep_until(clk32() + HDELAY);
            if (ti > 0) {
                int it = 0;
                do {
                    #pragma unroll
                    for (int c = 0; c < 4; c++) u[c] = ld_rlx4(hp + c * 32);
                    if (it) RETRY_COUNT(4);
                    if (++it > kSpinLimit) { TIMEOUT(101); break; }
                } while (__any_sync(~0u, ((u[0].x ^ tag) | (u[1].x ^ tag) | (u[2].x ^ tag) | (u[3].x ^ tag)) & ~lane & 1));
            }
            #pragma unroll
            for (int c = 0; c < 4; c++) sts4(sb + SM_STG + p * 8192 + 3 * 2048 + lane * 16 + c * 512, u[c].x, u[c].y, u[c].z, u[c].w);
            warp_arrive(BAR(B_HL + p));
        };
        if (warp & 1) {
            uint32_t tag;
            if (warp == 11) {
                tag = *(volatile uint32_t*)&prm.sc->epoch + 1;
            #pragma unroll 1
            for (int i = 0; i < 8; i++) prm.sc->halo[(ti * 8 + hg) * 256 + i * 32 + lane] = make_uint4(~tag, 0u, 0u, 0u);
            ((uint4*)prm.sc->stats)[(a2s * 4 + a2j) * 64 + lane] = ((uint4*)prm.sc->stats)[(a2s * 4 + a2j) * 64 + 32 + lane] = make_uint4(~tag, ~tag, ~tag, ~tag);
            prm.sc->flag_h[(a2s * 4 + a2j) * FS + lane] = 0;
            prm.sc->flag_o[(ti * 16 + hg) * FS + lane] = prm.sc->flag_o[(ti * 16 + 8 + hg) * FS + lane] = 0;
            __syncwarp();
            if (lane == 0) {
                asm volatile("st.shared.v2.u32 [%0], {%1, %2};" :: "r"(sb + SM_EPOCH), "r"(tag), "r"(gtime32()) : "memory");
                mbar_arrive(BAR(B_EP));
            }
            if (lane < 8) mbar_expect(BAR(B_RF + lane), 1792);
            __syncwarp();
            TRW(44);
            } else {
                mbar_wait(BAR(B_EP), 0);
                tag = lds1(sb + SM_EPOCH);
            }
            fetch_halo((warp >> 1) & 1, tag);
        }
        if (warp < 10) {
          auto load_slab = [&](int s, bool second) {
              if (!second) tma2d(sb + s * 8192, &mW1, (s & 1) * kF + g1f * 64, (rank * 8 + (s >> 1)) * 64, BAR(B_AF));
              else         tma2d(sb + s * 8192, &mW2, g2s * 64, (rank * 14 + s - 1) * 64, BAR(B_AF));
          };
          if (warp == 8) {
            if (elect_one()) {
                #pragma unroll 1
                for (int s = 0; s < 7; s++) {
                    mbar_expect(BAR(B_WKVF + s), 16384);
                    tma2d_mc(sb + SM_WKV + s * 16384 + rank * 8192, &mWqkv, (1 + rank) * kD + wcol, s * 64, BAR(B_WKVF + s));
                }
            }
            __syncwarp();
            mbar_wait(BAR(B_XC), 0);
            if (elect_one()) {
                asm volatile("prefetch.tensormap [%0];" :: "l"(&mX) : "memory");
                asm volatile("prefetch.tensormap [%0];" :: "l"(&mWo) : "memory");
                asm volatile("prefetch.tensormap [%0];" :: "l"(&mW1) : "memory");
                asm volatile("prefetch.tensormap [%0];" :: "l"(&mW2) : "memory");
                mbar_expect(BAR(B_AF), (g1_on ? NPRE : 14) * 8192);
                mbar_expect(BAR(B_WQF), 57344);
                #pragma unroll 1
                for (int s = rank; s < 7; s += 2) tma2d_mc(sb + SM_WQ + s * 8192, &mWqkv, wcol, s * 64, BAR(B_WQF));
                mbar_expect(BAR(B_XRF), 16384);
                tma2d(sb + SM_XR, &mX, a2p * kD + a2j * 112, ti * 64, BAR(B_XRF));
                tma2d(sb + SM_XR + 8192, &mX, a2p * kD + a2j * 112 + 48, ti * 64, BAR(B_XRF));
            }
            __syncwarp();
            #pragma unroll 1
            for (int h = 0; h < 2; h++) {
                mbar_wait(BAR(B_KV3 + h), 0);
                if (h) mbar_wait2(BAR(B_HL), 0, BAR(B_HL + 1), 0);
                if (elect_one()) {
                    mbar_expect(BAR(B_WOF + h), 57344);
                    tma2d_mc(sb + SM_WKV + h * 57344 + rank * 28672, &mWo, a2j * 112 + rank * 48, h * 224, BAR(B_WOF + h));
                    if (g1_on && h == AFIRST) { load_slab(0, false); load_slab(1, false); load_slab(2, false); }
                }
                __syncwarp();
            }
            if (g1_on) {
                mbar_wait2(BAR(B_XD), 0, BAR(B_OL + 3), 0);
                #pragma unroll 1
                for (int i = 3; i < NPRE; i++) {
                    if (i == 7) mbar_wait(BAR(B_OC), 0);
                    if (elect_one()) load_slab(i, false);
                    __syncwarp();
                }
            } else {
                mbar_wait(BAR(B_HD), 0);
                mbar_arrive_remote_if(pbar0 + 8u * B_PD, lane == 0);
                mbar_wait(BAR(B_GO), 0);
                uint32_t tg = lds1(sb + SM_TG + 4);
                tg += max((int)(lds1(sb + SM_TG2) - tg), 0);
                int it = 0;
                while ((int)(gtime32() - tg) < 0 && ++it < 256) {}
                const uint32_t t0 = clk32();
                if (lane < 2) {
                    asm volatile("st.shared.u32 [%0], %1;" :: "r"(sb + SM_TG + 8 + lane * 4), "r"(t0 + (lane ? CN3 : CN2)) : "memory");
                    mbar_arrive(BAR(B_GD + lane));
                }
                __syncwarp();
                #pragma unroll 1
                for (int s = 1; s < 15; s++) {
                    sleep_until(t0 + W2OFF + s * W2PACE);
                    if (elect_one()) load_slab(s, true);
                    __syncwarp();
                }
            }
          } else {
            TRW(58);
            const uint32_t tag = lds1(sb + SM_EPOCH);
            if (lane < 4) mbar_expect(BAR(B_OL + lane), 14336);
            #pragma unroll 1
            for (int e = 0; e < 2; e++) {
                const uint32_t* fp = e ? &prm.sc->flag_h[(rank * 64 + lane) * FS] : &prm.sc->flag_o[(a2s * 8 + (lane & 7)) * FS];
                if (e) {
                    mbar_wait2(BAR(B_OF + 2), 0, BAR(B_OF + 3), 0);
                    if (lane == 0) st_flag(&prm.sc->flag_h[(a2s * 4 + a2j) * FS], tag);
                    __syncwarp();
                    TRW(57);
                    sleep_until(clk32() + PDELAY);
                }
                uint64_t v0 = 0, v1 = e ? 0 : tag;
                int it = 0;
                do {
                    ld_flag_if(v0, fp, (uint32_t)v0 != tag); ld_flag_if(v1, fp + 32 * FS, (uint32_t)v1 != tag);
                    if (++it > kSpinLimit) { TIMEOUT(108); break; }
                } while (__any_sync(~0u, (uint32_t)v0 != tag || (uint32_t)v1 != tag));
                const uint32_t gbase = __shfl_sync(~0u, (uint32_t)(v0 >> 32), 0);
                const uint32_t tg = gbase + (e ? DELTA : DELTAO)
                                  + __reduce_max_sync(~0u, max((int)((uint32_t)(v0 >> 32) - gbase) - e * (lane >> 2) * SOFF, e ? (int)((uint32_t)(v1 >> 32) - gbase) - 8 * SOFF : 0));
                TRW(e ? 40 : 53);
                mbar_wait(BAR(B_A1D), 0);
                if (elect_one()) {
                    if (e) {
                        asm volatile("st.async.shared::cluster.mbarrier::complete_tx::bytes.b32 [%0], %1, [%2];"
                                     :: "r"(pbar0 + (SM_TG2 - SM_BAR)), "r"(tg), "r"(pbar0 + 8u * B_GO) : "memory");
                        asm volatile("st.shared.u32 [%0], %1;" :: "r"(sb + SM_TG + 4), "r"(tg) : "memory");
                        mbar_expect(BAR(B_GO), 4);
                    } else {
                        it = 0;
                        while ((int)(gtime32() - tg) < 0 && ++it < 256) {}
                        #pragma unroll
                        for (int i = 0; i < 4; i++) bulk_g2s(sb + SM_WQ + i * 14336, &prm.sc->o[(a2s * 4 + i) * 896], 14336, BAR(B_OL + i));
                    }
                }
                __syncwarp();
            }
          }
          if (elect_one()) {
              const int h = ~warp & 1;
              constexpr uint32_t T = 57344, BO = 2 * 14336;
              const char* src1 = (const char*)&prm.sc->hn[(rank * 16 + h) * 3584 + g1j * 896];
              const char* src2 = (const char*)&prm.sc->g[(rank * 14 + h) * 3584 + g2j * 896];
              uint64_t masks = g1_on ? (h ? kSegMasks1 : kSegMasks0) : 0x80 | 0x80 << 10;
              const uint32_t bl = BAR(B_BL + h * NB);
              uint32_t s8 = (g1_on ? NB - 2 + h : h) * 8, ph = 1, tmin = 0;
              const CUtensorMap* am = &mW1;
              uint32_t ad = sb + (NPRE + h) * 8192, astep = 16384; int ac0 = h * kF + g1f * 64, ac1 = (rank * 8 + NPRE / 2) * 64;
              CAP_DECL(ti_, 0);
              #pragma unroll 1
              for (int seg = g1_on ? 0 : 3; seg < 5; seg++) {
                  const char* src = (seg < 3 ? src1 : src2) + (~seg & 1) * BO;
                  uint32_t m = (uint32_t)masks & 0x3ff;
                  masks >>= 10;
                  if (seg == 2) {
                      mbar_wait(BAR(B_PL), 0);
                      mbar_arrive_remote_if(pbar0 + 8u * B_PD, h);
                      am = &mW2; ad = sb + 8192; astep = 8192; ac0 = g2s * 64; ac1 = rank * 14 * 64;
                  } else {
                      const int gate = seg - (seg > 2);
                      mbar_wait(BAR(B_HD + gate), 0);
                      tmin = lds1(sb + SM_TG + gate * 4);
                      if (gate < 2) {
                          tmin += max((int)(lds1(gate ? sb + SM_TG2 : sb + SM_TG) - tmin), 0);
                          int it = 0;
                          while ((int)(gtime32() - tmin) < 0 && ++it < 256) {}
                          tmin = clk32();
                      }
                      tmin += h * PACE1;
                  }
                  #pragma unroll 1
                  do {
                      const uint32_t dst = sb + SM_B + s8 * 1792;
                      spin_until(tmin);
                      mbar_wait_fast(BAR(B_BE) + s8, ph);
                      if (seg) {
                          bulk_g2s(dst, src, 14336, bl + s8);
                          mbar_expect(bl + s8, 14336);
                          CAP(ti_);
                      }
                      tmin += PACE2;
                      src += 2 * T;
                      s8 += 16;
                      if (s8 >= NB * 8) { s8 -= NB * 8; ph ^= 1; }
                      if (m & 1) {
                          mbar_expect_more(bl + s8, 8192);
                          tma2d(ad, am, ac0, ac1, bl + s8);
                          ad += astep; ac1 += 64;
                      }
                      m >>= 1;
                  } while (m != 1);
                  if (seg == 0) ph = 1;
              }
          }
        } else {
          if (warp == 10) {
            mbar_wait(BAR(PFBAR), 0);
            const char* p1 = (const char*)prm.w1 + (size_t)b * 57344 + lane * 128;
            const char* p2 = (const char*)prm.w2 + (size_t)b * 57344 + lane * 128;
            if (lane < 27) asm volatile("prefetch.global.L2 [%0];" :: "l"(lane < 25 ? (const char*)prm.wo + min(b * 25 + lane, 3135) * 128
                                                                          : lane == 25 ? (const char*)prm.b1 + (b % 28) * 128 : (const char*)prm.b2 + (b & 31) * 128));
            uint32_t tnext = clk32();
            #pragma unroll 1
            for (int i = 0; i < 28; i++) {
                while ((int)(clk32() - tnext) < 0) __nanosleep(40);
                asm volatile("prefetch.global.L2 [%0];" :: "l"(i < 14 ? p1 + i * 4096 : p2 + (i - 14) * 4096));
                tnext += PFPACE;
            }
            mbar_wait(BAR(B_EP), 0);
          }
          const uint32_t tag = lds1(sb + SM_EPOCH);
          const int h = warp & 1;
          const bool lead = elect_one();
          const uint32_t wo = lane * 132, l3 = lane < 16 ? 12288 : 0;
          uint32_t base = sb + SM_WQ, bl = BAR(B_OL), bf = BAR(B_OF), m = 4, rph = 0;
          #pragma unroll 1
          for (int e = 0; e < 2; e++) {
              uint32_t s8 = h * 8;
              #pragma unroll 1
              do {
                  const uint32_t dst = base + s8 * 1792;
                  auto stale = [&]() {
                      uint32_t d;
                      asm volatile("{ .reg .b32 x, y, z, u;\n"
                                   "ld.shared.u32 x, [%1]; ld.shared.u32 y, [%1 + 4096]; ld.shared.u32 z, [%1 + 8192]; ld.shared.u32 u, [%2];\n"
                                   "lop3.b32 x, x, y, %3, 0x7e; lop3.b32 z, z, u, %3, 0x7e; lop3.b32 %0, x, z, 1, 0xa8; }"
                                   : "=r"(d) : "r"(dst + wo), "r"(dst + (wo + l3)), "r"(tag) : "memory");
                      return __any_sync(~0u, d);
                  };
                  mbar_wait_fast(bl + s8, m & 1);
                  bool bad = stale();
                  mbar_arrive_if(bf + s8, lead && !bad);
                  if (bad) {
                      const int p = 2 * __clz(m) - 2 + h;
                      RETRY_COUNT(!e ? 1 : p < 32 ? 0 : !g1_on ? 5 : p < 46 ? 2 : 6);
                      const int st = (p > 15) + (p > 31) + (p > 45), s = p - (st < 3 ? 16 * st : 46);
                      const char* src = (const char*)(!e ? &prm.sc->o[(a2s * 4 + p - 56) * 896] : st < 2 ? &prm.sc->hn[(rank * 16 + s) * 3584 + (g1j + 2 * st) * 896]
                                                                                                      : &prm.sc->g[(rank * 14 + s) * 3584 + (g2j + 2 * st - 4) * 896]);
                      int it = 0;
                      do {
                          if (++it > kSpinLimit) { TIMEOUT(111); break; }
                          const uint32_t* q = (const uint32_t*)(src + wo);
                          if (it > RELOAD1 && __any_sync(~0u, ((ld_rlx(q) ^ tag) | (ld_rlx(q + 1024) ^ tag) | (ld_rlx(q + 2048) ^ tag) | (ld_rlx(q + l3 / 4) ^ tag)) & 1)) continue;
                          if (lead) {
                              mbar_expect(BAR(B_RT + h), 14336);
                              bulk_g2s(dst, src, 14336, BAR(B_RT + h));
                          }
                          __syncwarp();
                          mbar_wait(BAR(B_RT + h), rph);
                          rph ^= 1;
                          bad = stale();
                      } while (bad);
                      mbar_arrive_if(bf + s8, lead);
                  }
                  s8 += 16;
                  if (s8 >= NB * 8) s8 -= NB * 8;
                  m >>= 1;
              } while (m != 1);
              base = sb + SM_B; bl = BAR(B_BL + h * NB); bf = BAR(B_BF); m = g1_on ? 0x4fe03f80 : 0x7f80;
          }
        }
    } else {
        asm volatile("setmaxnreg.inc.sync.aligned.u32 232;");
        asm volatile("barrier.cluster.wait.aligned;" ::: "memory");
        const int wg = warp >> 2, w = warp & 3;
        const int g = lane >> 2, t = lane & 3;
        uint32_t tag;
        __nv_bfloat16 bias1a, bias1b;
        {
            const uint64_t dw = make_desc(sb + (hg & 1) * 16, 0, true);
            uint32_t a[28][4];
            float sm[4][4] = {};
            {
                const int r = w * 16 + (lane & 15);
                const uint32_t rowa = sb + wg * 8192 + r * 128;
                #pragma unroll
                for (int k = 0; k < 28; k++) {
                    if (XW == 1 && (k & 3) == 0) mbar_wait(BAR(B_XF + (k >> 2)), 0);
                    if (XW == 2 && k == 0) mbar_wait(BAR(B_XF), 0);
                    if (XW == 2 && (k & 7) == 4) mbar_wait2(BAR(B_XF + (k >> 2)), 0, BAR(B_XF + (k >> 2) + 1), 0);
                    const uint32_t addr = rowa + (k >> 2) * 16384 + ((((k & 3) * 2 + (lane >> 4)) ^ (r & 7)) << 4);
                    uint32_t (&f)[4] = a[k];
                    asm volatile("ldmatrix.sync.aligned.m8n8.x4.shared.b16 {%0,%1,%2,%3}, [%4];"
                                 : "=r"(f[0]), "=r"(f[1]), "=r"(f[2]), "=r"(f[3]) : "r"(addr) : "memory");
                    if (XLAG == 0) mma16816(sm[k & 3], f[0], f[1], f[2], f[3], 0x3F803F80u, 0x3F803F80u);
                    else if (k >= 4) mma16816(sm[k & 3], a[k - 4][0], a[k - 4][1], a[k - 4][2], a[k - 4][3], 0x3F803F80u, 0x3F803F80u);
                }
                if (XLAG) {
                    #pragma unroll
                    for (int k = 24; k < 28; k++) mma16816(sm[k & 3], a[k][0], a[k][1], a[k][2], a[k][3], 0x3F803F80u, 0x3F803F80u);
                }
            }
            const float mean0 = ((sm[0][0] + sm[1][0]) + (sm[2][0] + sm[3][0])) * (1.f / kD);
            const float mean1 = ((sm[0][2] + sm[1][2]) + (sm[2][2] + sm[3][2])) * (1.f / kD);
            const uint32_t mb0 = pack_bf16(mean0, mean0), mb1 = pack_bf16(mean1, mean1);
            pair_arrive(B_XC);
            TR(1);
            float ak[28], av[28], aq[28];
            float ss0 = 0.f, ss1 = 0.f, ss2 = 0.f, ss3 = 0.f;
            uint32_t p0, p1;
            static_for<0, 7>([&](auto S_) {
                constexpr int s = decltype(S_)::value;
                #pragma unroll
                for (int q = 0; q < 4; q++) {
                    uint32_t (&f)[4] = a[s * 4 + q];
                    f[0] = sub_bf16x2(f[0], mb0); f[1] = sub_bf16x2(f[1], mb1);
                    f[2] = sub_bf16x2(f[2], mb0); f[3] = sub_bf16x2(f[3], mb1);
                }
                mbar_wait(BAR(B_WKVF + s), 0);
                wg_fence();
                static_for<0, 4>([&](auto Q_) {
                    constexpr int q = decltype(Q_)::value;
                    uint32_t (&f)[4] = a[s * 4 + q];
                    wgmma_rs_n56<SM_WKV + s * 16384 + q * 2048, (s | q) != 0>(ak, f[0], f[1], f[2], f[3], dw);
                    wgmma_rs_n56<SM_WKV + s * 16384 + q * 2048 + 8192, (s | q) != 0>(av, f[0], f[1], f[2], f[3], dw);
                });
                wg_commit();
                if (s == 4) { wg_wait<1>(); pair_arrive(B_KV3); }
                #pragma unroll
                for (int q = 0; q < 8; q++) {
                    const uint32_t u0 = a[s * 4 + q / 2][(q & 1) * 2], u1 = a[s * 4 + q / 2][(q & 1) * 2 + 1];
                    if (q == 0 && (VCH == 1 || (s & 1) || s == 0)) { p0 = sqr_bf16x2(u0); p1 = sqr_bf16x2(u1); }
                    else { p0 = sqa_bf16x2(u0, p0); p1 = sqa_bf16x2(u1, p1); }
                }
                if (VCH == 1 || !(s & 1)) { ss0 += bf_lo(p0); ss2 += bf_hi(p0); ss1 += bf_lo(p1); ss3 += bf_hi(p1); }
            });
            auto q_chunk = [&](auto K0_, auto K1_) {
                wg_fence();
                static_for<decltype(K0_)::value, decltype(K1_)::value>([&](auto K_) {
                    constexpr int k = decltype(K_)::value;
                    wgmma_rs_n56<SM_WQ + k * 2048, k != 0>(aq, a[k][0], a[k][1], a[k][2], a[k][3], dw);
                });
                wg_commit();
            };
            #define QCHUNK(k0, k1) q_chunk(std::integral_constant<int, k0>{}, std::integral_constant<int, k1>{})
            const float dl0 = mean0 - bf_lo(mb0), dl1 = mean1 - bf_lo(mb1);
            const float rs0 = rsq(fmaxf(quad_sum(ss0 + ss2) * (1.f / kD) - dl0 * dl0, 0.f) + kEps);
            const float rs1 = rsq(fmaxf(quad_sum(ss1 + ss3) * (1.f / kD) - dl1 * dl1, 0.f) + kEps);
            float rk[3][2];
            rk[1][0] = __shfl_sync(~0u, rs0, t * 8); rk[1][1] = __shfl_sync(~0u, rs0, t * 8 + 4);
            rk[2][0] = __shfl_sync(~0u, rs1, t * 8); rk[2][1] = __shfl_sync(~0u, rs1, t * 8 + 4);
            const uint32_t stg = sb + SM_STG + wg * 8192 + lane * 16;
            uint4* hp = (w == 3 ? &prm.sc->halo[((ti * 8 + hg) * 2 + wg) * 128] : (uint4*)(smem_raw + SM_STG + wg * 8192 + w * 2048)) + lane;
            mbar_wait2(BAR(B_EP), 0, BAR(B_WQF), 0);
            tag = lds1(sb + SM_EPOCH);
            QCHUNK(0, QC0);
            wg_wait<1>();
            reg_fence(ak); reg_fence(av);
            TR(2);
            uint32_t kf[3][7], vf[3][7];
            #pragma unroll
            for (int c = 0; c < 7; c++) {
                kf[2][c] = pack_bf16(ak[4 * c + 2], ak[4 * c + 3]);
                vf[2][c] = movm(pack_bf16(av[4 * c + 2], av[4 * c + 3]));
            }
            const uint32_t om = ~lane & 1;
            kf[2][0] = set_par(kf[2][0], om, tag); kf[2][4] = set_par(kf[2][4], om, tag);
            vf[2][1] = set_par(vf[2][1], om, tag); vf[2][5] = set_par(vf[2][5], om, tag);
            st_gen4(hp,      kf[2][0], kf[2][1], kf[2][2], kf[2][3]);
            st_gen4(hp + 32, kf[2][4], kf[2][5], kf[2][6], vf[2][0]);
            st_gen4(hp + 64, vf[2][1], vf[2][2], vf[2][3], vf[2][4]);
            st_gen4(hp + 96, vf[2][5], vf[2][6], __float_as_uint(rk[2][0]), __float_as_uint(rk[2][1]));
            pair_arrive(B_KVC);
            QCHUNK(QC0, QC1);
            #pragma unroll
            for (int c = 0; c < 7; c++) {
                kf[1][c] = pack_bf16(ak[4 * c], ak[4 * c + 1]);
                vf[1][c] = movm(pack_bf16(av[4 * c], av[4 * c + 1]));
            }
            QCHUNK(QC1, QC2);
            named_bar(1 + wg, 128);
            uint32_t* op = opaque_ptr((uint32_t*)&prm.sc->o[((ti * 2 + wg) * 56 + hg * 7) * 64] + w * 64 + lane);
            const uint32_t omk = opaque(((lane & 6) == w * 2 ? 0x11u << (lane & 1) * 8 : 0u) << (((lane >> 3) + (hg & 1)) & 3));
            uint32_t* ofl = opaque_ptr(&prm.sc->flag_o[((ti * 2 + wg) * 8 + hg) * FS]);
            QCHUNK(QC2, 28);
            #undef QCHUNK
            const bool gt0 = 2 * t > g, gt1 = 2 * t + 1 > g, no_prev = ti == 0 && w == 0;
            const float kf0 = gt0 ? rk[1][0] : rk[2][0], kf1 = gt1 ? rk[1][1] : rk[2][1];
            constexpr float kScale = 0.18898223650461362f * 1.4426950408889634f;
            const float sq0 = rs0 * kScale, sf0 = kf0 * (rs1 * kScale), sf1 = kf1 * (rs1 * kScale);
            const float NEG = -__int_as_float(0x7f800000);
            const float nb0 = gt0 && no_prev ? NEG : 0.f, nb1 = gt1 && no_prev ? NEG : 0.f;
            const uint32_t sr = stg + ((w + 3) & 3) * 2048, hbar = BAR(w == 0 ? B_HL + wg : B_EP);
            mbar_wait(BAR(B_EP), 0);
            wg_wait<0>();
            reg_fence(aq);
            warp_arrive(BAR(B_A1D));
            TR(3);
            uint32_t qf[8][2];
            #pragma unroll
            for (int c = 0; c < 7; c++) {
                qf[c + (c > 3)][0] = pack_bf16(aq[4 * c], aq[4 * c + 1]);
                qf[c + (c > 3)][1] = pack_bf16(aq[4 * c + 2], aq[4 * c + 3]);
            }
            qf[4][0] = t >= 2 ? qf[3][0] : 0u; qf[4][1] = t >= 2 ? qf[3][1] : 0u;
            qf[3][0] = t < 2 ? qf[3][0] : 0u;  qf[3][1] = t < 2 ? qf[3][1] : 0u;
            float sc[2][3][4];
            auto scores = [&](int n) {
                #pragma unroll
                for (int hd = 0; hd < 2; hd++) {
                    sc[hd][n][0] = sc[hd][n][1] = sc[hd][n][2] = sc[hd][n][3] = 0.f;
                    mma16816(sc[hd][n], qf[4 * hd][0], qf[4 * hd][1], qf[4 * hd + 1][0], qf[4 * hd + 1][1], kf[n][3 * hd], kf[n][3 * hd + 1]);
                    mma16816(sc[hd][n], qf[4 * hd + 2][0], qf[4 * hd + 2][1], qf[4 * hd + 3][0], qf[4 * hd + 3][1], kf[n][3 * hd + 2], kf[n][3 * hd + 3]);
                }
            };
            scores(1); scores(2);
            mbar_wait(hbar, 0);
            {
                const uint4 u0 = lds4(sr), u1 = lds4(sr + 512), u3 = lds4(sr + 1536), u2 = lds4(sr + 1024);
                kf[0][0] = u0.x; kf[0][1] = u0.y; kf[0][2] = u0.z; kf[0][3] = u0.w;
                kf[0][4] = u1.x; kf[0][5] = u1.y; kf[0][6] = u1.z; vf[0][0] = u1.w;
                vf[0][1] = u2.x; vf[0][2] = u2.y; vf[0][3] = u2.z; vf[0][4] = u2.w;
                vf[0][5] = u3.x; vf[0][6] = u3.y; rk[0][0] = __uint_as_float(u3.z); rk[0][1] = __uint_as_float(u3.w);
            }
            if ((tid & 127) == 0) st_flag(ofl, tag);
            TR(4);
            scores(0);
            const float ke0 = gt0 ? rk[0][0] : rk[1][0], ke1 = gt1 ? rk[0][1] : rk[1][1];
            const float se0 = ke0 * sq0, se1 = ke1 * sq0;
            uint32_t ow[7][2];
            #pragma unroll
            for (int hd = 0; hd < 2; hd++) {
                const int c0 = hd * 3;
                float (&sc_)[3][4] = sc[hd];
                const float e0 = fmaf(gt0 ? sc_[0][0] : sc_[1][0], se0, nb0), e1 = fmaf(gt1 ? sc_[0][1] : sc_[1][1], se1, nb1);
                const float f0 = (gt0 ? sc_[1][2] : sc_[2][2]) * sf0, f1 = (gt1 ? sc_[1][3] : sc_[2][3]) * sf1;
                const float me = quad_max(fmaxf(e0, e1)), mf = quad_max(fmaxf(f0, f1));
                const float p0 = ex2(e0 - me), p1 = ex2(e1 - me), r0 = ex2(f0 - mf), r1 = ex2(f1 - mf);
                const float ie = rcp(quad_sum(p0 + p1)), jf = rcp(quad_sum(r0 + r1));
                const uint32_t pp = pack_bf16(p0 * ke0 * ie, p1 * ke1 * ie), rp = pack_bf16(r0 * kf0 * jf, r1 * kf1 * jf);
                const uint32_t mk = (gt0 ? 0x0000ffffu : 0u) | (gt1 ? 0xffff0000u : 0u);
                #pragma unroll
                for (int c = 0; c < 4; c++) {
                    float o[4] = {0.f, 0.f, 0.f, 0.f};
                    mma16816(o, pp & mk, 0u, pp & ~mk, rp & mk, vf[0][c0 + c], vf[1][c0 + c]);
                    mma1688(o, 0u, rp & ~mk, vf[2][c0 + c]);
                    const uint32_t lo = pack_bf16(o[0], o[1]), hi = pack_bf16(o[2], o[3]);
                    if (hd == 1 && c == 0) { if (t >= 2) { ow[3][0] = lo; ow[3][1] = hi; } }
                    else { ow[c0 + c][0] = lo; ow[c0 + c][1] = hi; }
                }
            }
            #pragma unroll
            for (int c = 0; c < 7; c++) {
                stg1(op + c * 256,      set_par(ow[c][0], (omk >> (c & 3)) & 1, tag));
                stg1(op + c * 256 + 32, set_par(ow[c][1], (omk >> (8 + (c & 3))) & 1, tag));
            }
            TR(5);
        }
        {
            const int cg = a2j * 2 + wg;
            float acc2[28];
            mbar_wait(BAR(B_XRF), 0);
            {
                const uint32_t xa = sb + SM_XR + wg * 8192 + (w * 16 + (lane & 15)) * 128;
                #pragma unroll
                for (int c = 0; c < 4; c++) {
                    uint32_t xr[4];
                    asm volatile("ldmatrix.sync.aligned.m8n8.x4.shared.b16 {%0,%1,%2,%3}, [%4];"
                                 : "=r"(xr[0]), "=r"(xr[1]), "=r"(xr[2]), "=r"(xr[3])
                                 : "r"(xa + ((((c * 2 + wg + (lane >> 4)) ^ lane) & 7) << 4)) : "memory");
                    #pragma unroll
                    for (int e = 0; e < (c < 3 ? 4 : 2); e++) { acc2[8 * c + 2 * e] = bf_lo(xr[e]); acc2[8 * c + 2 * e + 1] = bf_hi(xr[e]); }
                }
            }
            uint32_t* spw = opaque_ptr(&prm.sc->stats[((a2s * 8 + cg) * 4 + w) * 32 + lane]);
            const uint32_t* spr = opaque_ptr(&prm.sc->stats[(a2s * 32 + w) * 32 + lane]);
            uint4* hp = opaque_ptr(&prm.sc->h[((a2s * 8 + w * 2) * 8 + cg) * 64 + lane]);
            const int cgs = cg ^ (a2s >> 4);
            uint32_t* np = opaque_ptr((uint32_t*)&prm.sc->hn[(a2s * 56 + cgs * 7) * 64] + w * 64 + lane);
            const uint64_t dwo = make_desc(sb + SM_WKV + wg * (28672 + 16), 0, true);
            const uint64_t doa = make_desc(sb + SM_WQ, 1024, false, 128);
            bias1a = prm.b1[g1f * 64 + w * 16 + g]; bias1b = prm.b1[g1f * 64 + w * 16 + 8 + g];
            const __nv_bfloat16 bias2a = prm.b2[ti * 128 + (w * 16 + g) * 2 + a2p], bias2b = prm.b2[ti * 128 + (w * 16 + 8 + g) * 2 + a2p];
            reg_fence(acc2);
            fence_async_smem();
            warp_arrive(BAR(B_XD));
            static_for<0, 4>([&](auto P_) {
                constexpr int P = decltype(P_)::value;
                if (P == 0) mbar_wait(BAR(B_WOF), 0);
                if (P == 2) mbar_wait2(BAR(B_OF + P), 0, BAR(B_WOF + 1), 0); else mbar_wait(BAR(B_OF + P), 0);
                if (P == 0) TR(6);
                wg_fence();
                static_for<0, 7>([&](auto K_) { constexpr int k = decltype(K_)::value;
                    wgmma_ss_n56<P * 14336 + k * 2048, (P >> 1) * 57344 + (P & 1) * 14336 + k * 2048, 0>(acc2, doa, dwo); });
                if (P) wg_commit();
                if (P == 2) { wg_wait<1>(); warp_arrive(BAR(B_OC)); }
            });
            wg_wait<0>();
            reg_fence(acc2);
            TR(7);
            float s0 = 0.f, s1 = 0.f, q0 = 0.f, q1 = 0.f;
            #pragma unroll
            for (int c = 0; c < 7; c++) {
                s0 += acc2[4 * c] + acc2[4 * c + 1];     q0 = fmaf(acc2[4 * c], acc2[4 * c], fmaf(acc2[4 * c + 1], acc2[4 * c + 1], q0));
                s1 += acc2[4 * c + 2] + acc2[4 * c + 3]; q1 = fmaf(acc2[4 * c + 2], acc2[4 * c + 2], fmaf(acc2[4 * c + 3], acc2[4 * c + 3], q1));
            }
            const bool th = t >= 2, to = t & 1;
            const float sa = (th ? s1 : s0) + __shfl_xor_sync(~0u, th ? s0 : s1, 2), qa = (th ? q1 : q0) + __shfl_xor_sync(~0u, th ? q0 : q1, 2);
            const float part = (to ? qa : sa) + __shfl_xor_sync(~0u, to ? sa : qa, 1);
            stg1(spw, set_par(__float_as_uint(part), 1u, tag));
            const uint32_t tpoll = clk32() + SDELAY;
            TR(8);
            warp_arrive(BAR(B_HD));
            uint32_t hw[2][7], nm[2][4], us[8];
            #pragma unroll
            for (int r = 0; r < 2; r++) {
                const float b2v = __bfloat162float(r ? bias2b : bias2a);
                #pragma unroll
                for (int c = 0; c < 7; c++) hw[r][c] = pack_bf16(acc2[4 * c + 2 * r] + b2v, acc2[4 * c + 2 * r + 1] + b2v);
                hw[r][0] = set_par(hw[r][0], ~lane & 1, tag);
            }
            auto store_h = [&]() {
                #pragma unroll
                for (int r = 0; r < 2; r++) {
                    stg4(hp + r * 512, hw[r][0], hw[r][1], hw[r][2], hw[r][3]);
                    stg4(hp + r * 512 + 32, tag, hw[r][4], hw[r][5], hw[r][6]);
                }
            };
            if (HPOS == 0) store_h();
            spin_until(tpoll);
            #pragma unroll
            for (int i = 0; i < 8; i++) us[i] = ld_rlx(spr + i * 128);
            if (HPOS == 1) store_h();
            #pragma unroll
            for (int i = 0; i < 8; i++) nm[i >> 2][i & 3] = lane == ((i - (cgs & 1)) & 3) * 8 + w * 2 + (i >> 2);
            {
                int it = 0;
                while (true) {
                    uint32_t bad = 0;
                    #pragma unroll
                    for (int i = 0; i < 8; i++) bad |= us[i] ^ tag;
                    if (!__any_sync(~0u, bad & 1)) break;
                    RETRY_COUNT(3);
                    if (++it > kSpinLimit) { TIMEOUT(103); break; }
                    #pragma unroll
                    for (int i = 0; i < 8; i++) us[i] = ld_rlx(spr + i * 128);
                }
            }
            TR(9);
            const float tot = (((__uint_as_float(us[0]) + __uint_as_float(us[1])) + (__uint_as_float(us[2]) + __uint_as_float(us[3])))
                            + ((__uint_as_float(us[4]) + __uint_as_float(us[5])) + (__uint_as_float(us[6]) + __uint_as_float(us[7])))) * (1.f / kD);
            const float oth = __shfl_xor_sync(~0u, tot, 1);
            const float mean = to ? oth : tot;
            const float var = fmaxf(fmaf(-mean, mean, to ? tot : oth), 0.f);
            const float r1 = rsq(var + kEps);
            const float rra = 0.5f * r1 * rsq(fmaf(var * r1, r1, kEps)), mra = -mean * rra;
            const float rrb = __shfl_xor_sync(~0u, rra, 2), mrb = __shfl_xor_sync(~0u, mra, 2);
            const float rr0 = th ? rrb : rra, mr0 = th ? mrb : mra, rr1 = th ? rra : rrb, mr1 = th ? mra : mrb;
            #pragma unroll
            for (int c = 0; c < 7; c++) {
                stg1(np + c * 256,      set_par(pack_bf16(fmaf(acc2[4 * c], rr0, mr0), fmaf(acc2[4 * c + 1], rr0, mr0)), nm[0][c & 3], tag));
                stg1(np + c * 256 + 32, set_par(pack_bf16(fmaf(acc2[4 * c + 2], rr1, mr1), fmaf(acc2[4 * c + 3], rr1, mr1)), nm[1][c & 3], tag));
            }
            TR(10);
            if (HPOS == 2) store_h();
        }
        float as[28], ac[28];
        #pragma unroll
        for (int c = 0; c < 28; c++) { ac[c] = 0.5f * __bfloat162float(c & 2 ? bias1b : bias1a); as[c] = 0.f; }
        reg_fence(as); reg_fence(ac);
        const uint32_t xch = opaque(sb + SM_XCH + w * 1792 + lane * 16);
        uint32_t peer_xch;
        asm volatile("mapa.shared::cluster.u32 %0, %1, %2;" : "=r"(peer_xch) : "r"(xch), "r"(rank ^ 1));
        auto send = [&]() {
            const uint32_t rf = pbar0 + (B_RF + warp) * 8;
            #pragma unroll
            for (int c = 0; c < 4; c++) {
                const uint32_t p0 = pack_bf16(as[8 * c], as[8 * c + 1]), p1 = pack_bf16(as[8 * c + 2], as[8 * c + 3]);
                if (c < 3) {
                    const uint32_t p2 = pack_bf16(as[8 * c + 4], as[8 * c + 5]), p3 = pack_bf16(as[8 * c + 6], as[8 * c + 7]);
                    asm volatile("st.async.shared::cluster.mbarrier::complete_tx::bytes.v4.b32 [%0], {%1,%2,%3,%4}, [%5];"
                                 :: "r"(peer_xch + c * 512), "r"(p0), "r"(p1), "r"(p2), "r"(p3), "r"(rf) : "memory");
                } else {
                    asm volatile("st.async.shared::cluster.mbarrier::complete_tx::bytes.v2.b32 [%0], {%1,%2}, [%3];"
                                 :: "r"(peer_xch + 1536 - lane * 8), "r"(p0), "r"(p1), "r"(rf) : "memory");
                }
            }
        };
        auto receive = [&](uint32_t (&pk)[14], uint32_t phase) {
            mbar_wait(BAR(B_RF + warp), phase);
            #pragma unroll
            for (int c = 0; c < 3; c++) { const uint4 u = lds4(xch + c * 512); pk[4 * c] = u.x; pk[4 * c + 1] = u.y; pk[4 * c + 2] = u.z; pk[4 * c + 3] = u.w; }
            const uint2 u = lds2(xch + 1536 - lane * 8); pk[12] = u.x; pk[13] = u.y;
        };
        uint4 hr[4];
        const int cg2 = (g2j + 2 * wg) * 2 + (rank ^ 1), cg1 = (g1j + 2 * wg) * 2 + (rank ^ (g1f < 14));
        const uint4* hp = &prm.sc->h[((((g2s >> 1) * 2 + (g & 1)) * 8 + (g2s & 1) * 4 + w) * 8 + cg2) * 64 + (g >> 1) * 4 + t];
        auto forget_h = [&]() {
            #pragma unroll
            for (int c = 0; c < 4; c++) asm volatile("" : "=r"(hr[c].x), "=r"(hr[c].y), "=r"(hr[c].z), "=r"(hr[c].w));
        };
        forget_h();
        if (!g1_on) mbar_wait(BAR(B_GD), 0);
        uint32_t* const gp1 = (uint32_t*)&prm.sc->g[(g1f * 56 + cg1 * 7) * 64] + w * 64 + lane;
        uint32_t* const gp2 = (uint32_t*)(prm.out + (size_t)(g2s * 64 + w * 16 + lane / 7) * kD + cg2 * 56) + (lane % 7) * 4;
        uint32_t gm[2][4];
        #pragma unroll
        for (int i = 0; i < 8; i++) gm[i >> 2][i & 3] = lane == ((i - (cg1 & 1)) & 3) * 8 + w * 2 + (i >> 2);
        const bool lead = elect_one();
        const uint64_t da0 = make_desc(sb, 0, true), db0 = make_desc(sb + SM_B, 128, false);
        uint64_t da, db;
        uint32_t ph, rb, prev, xfree;
        #pragma unroll 1
        for (int ge = g1_on ? 0 : 1;; ge++) {
            if (ge) {
                int it = 0;
                uint32_t bad;
                do {
                    #pragma unroll
                    for (int c = 0; c < 4; c++) hr[c] = ld_rlx4(hp + (c >> 1) * 16 + (c & 1) * 32);
                    bad = (hr[0].x ^ tag) | (hr[1].x ^ tag) | (hr[2].x ^ tag) | (hr[3].x ^ tag);
                    if (++it > kSpinLimit) { TIMEOUT(110); break; }
                } while (__any_sync(~0u, bad & ~lane & 1));
            }
            const int use = ge * 2 + wg;
            const uint32_t slot0 = g1_on ? (ge ? 4 : wg * ((16 + NR) % NB)) : 0;
            uint32_t keep = !ge;
            ph = use == 1 ? (16 + NR) / NB & 1 : 0; rb = bar0 + slot0 * 8;
            da = da0 + (ge ? 512 : wg * NR * 512); db = db0 + slot0 * 896;
            prev = BAR(use == 1 ? B_BE + (15 + NR) % NB : B_WKVF);
            xfree = BAR(use > (g1_on ? 0 : 2) ? B_RE + use - 1 : B_PD);
            mbar_wait(BAR(B_AF), 0);
            if (use == 1) {
                uint32_t af[NR * 4][4];
                mbar_wait(BAR(B_GO), 0);
                const uint32_t tp = lds1(sb + SM_TG + 4) + PLOFF;
                int it = 0;
                while ((int)(gtime32() - tp) < 0 && ++it < 256) __nanosleep(20);
                const uint32_t la = sb + ((lane >> 4) * 8 + (lane & 7)) * 128 + (((w * 2 + ((lane >> 3) & 1)) ^ (lane & 7)) << 4);
                #pragma unroll
                for (int k = 0; k < NR * 4; k++)
                    asm volatile("ldmatrix.sync.aligned.m8n8.x4.trans.shared.b16 {%0,%1,%2,%3}, [%4];"
                                 : "=r"(af[k][0]), "=r"(af[k][1]), "=r"(af[k][2]), "=r"(af[k][3]) : "r"(la + k * 2048) : "memory");
                __syncwarp();
                mbar_arrive_if(BAR(B_PL), lead);
                named_bar(4, 256);
                static_for<0, NR>([&](auto I_) {
                    constexpr int i = decltype(I_)::value, sl = (16 + i) % NB, o = sl * 14336;
                    mbar_wait_fast(BAR(B_BF + sl), (16 + i) / NB & 1);
                    wg_fence();
                    wgmma_rs_n112<o,       1>(as, ac, af[4 * i][0], af[4 * i][1], af[4 * i][2], af[4 * i][3], db0);
                    wgmma_rs_n112<o + 256, 1>(as, ac, af[4 * i + 1][0], af[4 * i + 1][1], af[4 * i + 1][2], af[4 * i + 1][3], db0);
                    wgmma_rs_n112<o + 512, 1>(as, ac, af[4 * i + 2][0], af[4 * i + 2][1], af[4 * i + 2][2], af[4 * i + 2][3], db0);
                    wgmma_rs_n112<o + 768, 1>(as, ac, af[4 * i + 3][0], af[4 * i + 3][1], af[4 * i + 3][2], af[4 * i + 3][3], db0);
                    wg_commit();
                    if (i) { wg_wait<1>(); mbar_arrive_if(BAR(B_BE + (15 + i) % NB), lead); }
                });
                forget_h();
            } else if (ge && (wg || g1_on)) named_bar(5 - wg, 256);
            mbar_wait(rb + B_BF * 8, ph);
            TR(11 + ge * 4);
            #pragma unroll 1
            for (int n = ge ? 14 : 16 - wg * NR;;) {
                wg_fence();
                wgmma_ss_n112<0,    0,   1>(as, ac, da, db, keep);
                wgmma_ss_n112<2048, 256, 1>(as, ac, da, db);
                wgmma_ss_n112<4096, 512, 1>(as, ac, da, db);
                wgmma_ss_n112<6144, 768, 1>(as, ac, da, db);
                wg_commit();
                if (--n == 0 && use < 3) named_arrive(4 + wg, 256);
                const uint32_t cur = rb + B_BE * 8;
                da += 512; db += 896; rb += 8; keep = 1;
                if (rb == bar0 + NB * 8) { rb = bar0; db = db0; ph ^= 1; }
                wg_wait<1>();
                mbar_arrive_if(prev, lead);
                prev = cur;
                if (n == 0) break;
                mbar_wait_fast(rb + B_BF * 8, ph);
            }
            if (ge) break;
            mbar_wait(xfree, 0);
            wg_wait<0>();
            reg_fence(as); reg_fence(ac);
            mbar_arrive_if(prev, lead);
            send();
            TR(12);
            uint32_t pk[14];
            receive(pk, 0);
            TR(13);
            #pragma unroll
            for (int c = 0; c < 14; c++) {
                float r[2];
                #pragma unroll
                for (int e = 0; e < 2; e++) {
                    const float u = ac[2 * c + e] + (e ? bf_hi(pk[c]) : bf_lo(pk[c]));
                    r[e] = fmaf(u, tanh_hw(u * fmaf(u * u, 8.f * 0.7978845608f * 0.044715f, 2.f * 0.7978845608f)), u);
                }
                stg1(gp1 + (c >> 1) * 256 + (c & 1) * 32, set_par(pack_bf16(r[0], r[1]), gm[c & 1][(c >> 1) & 3], tag));
            }
            named_bar(1 + wg, 128);
            if (w == 0 && lane == 0) {
                asm volatile("st.shared.u32 [%0], %1;" :: "r"(sb + SM_TG + 8 + wg * 4), "r"(clk32() + (wg ? XSPECB : XSPEC)) : "memory");
                mbar_arrive(BAR(B_GD + wg));
            }
            if (lead) mbar_expect(BAR(B_RF + warp), 1792);
            mbar_arrive_remote_if(pbar0 + (B_RE + wg) * 8, lead);
            TR(14);
        }
        uint32_t po[14], pk[14];
        mbar_wait(xfree, 0);
        wg_wait<0>();
        reg_fence(as); reg_fence(ac);
        mbar_arrive_if(prev, lead);
        if (!wg) sleep_until(clk32() + w * STAG2);
        send();
        #pragma unroll
        for (int c = 0; c < 14; c++) po[c] = opaque(pack_bf16(ac[2 * c], ac[2 * c + 1]));
        TR(16);
        receive(pk, g1_on);
        TR(17);
        #pragma unroll
        for (int c = 0; c < 14; c++) {
            const int i = (c & 1) * 8 + (c >> 1) + (c >= 8);
            const uint32_t hw = (i & 3) == 0 ? hr[i >> 2].x : (i & 3) == 1 ? hr[i >> 2].y : (i & 3) == 2 ? hr[i >> 2].z : hr[i >> 2].w;
            pk[c] = add_bf16x2(add_bf16x2(po[c], pk[c]), hw);
        }
        __syncwarp();
        const uint32_t sa = xch - lane * 16 + (lane & 15) * 112 + (lane >> 4) * 16;
        #pragma unroll
        for (int m = 0; m < 3; m++)
            asm volatile("stmatrix.sync.aligned.m8n8.x4.shared.b16 [%0], {%1,%2,%3,%4};"
                         :: "r"(sa + m * 32), "r"(pk[4 * m]), "r"(pk[4 * m + 1]), "r"(pk[4 * m + 2]), "r"(pk[4 * m + 3]) : "memory");
        asm volatile("stmatrix.sync.aligned.m8n8.x2.shared.b16 [%0], {%1,%2};" :: "r"(sa + 96), "r"(pk[12]), "r"(pk[13]) : "memory");
        __syncwarp();
        if (lane < 28) {
            #pragma unroll
            for (int i = 0; i < 4; i++) { const uint4 u = lds4(xch + i * 448); stg4(gp2 + i * 896, u.x, u.y, u.z, u.w); }
        }
        __syncwarp();
        mbar_arrive_remote_if(pbar0 + (B_RE + 2) * 8, lead && wg == 0);
        TR(18);
        if (tid == 128) TRG(62);
        if (b == 0 && tid == 128) prm.sc->epoch = tag;
    }
}

typedef CUresult (*EncodeFn)(CUtensorMap*, CUtensorMapDataType, cuuint32_t, void*, const cuuint64_t*, const cuuint64_t*,
                             const cuuint32_t*, const cuuint32_t*, CUtensorMapInterleave, CUtensorMapSwizzle,
                             CUtensorMapL2promotion, CUtensorMapFloatOOBfill);

void make_map(EncodeFn enc, CUtensorMap* m, const void* base, uint64_t cols, uint64_t rows, uint32_t box_rows) {
    cuuint64_t dims[2] = {cols, rows};
    cuuint64_t strides[1] = {cols * 2};
    cuuint32_t box[2] = {64, box_rows};
    cuuint32_t es[2] = {1, 1};
    enc(m, CU_TENSOR_MAP_DATA_TYPE_BFLOAT16, 2, const_cast<void*>(base), dims, strides, box, es, CU_TENSOR_MAP_INTERLEAVE_NONE,
        CU_TENSOR_MAP_SWIZZLE_128B, CU_TENSOR_MAP_L2_PROMOTION_L2_128B, CU_TENSOR_MAP_FLOAT_OOB_FILL_NONE);
}

}

extern "C" void kernel_launch(void* const* d_in, const int* in_sizes, int n_in, void* d_out, int out_size) {
    (void)in_sizes; (void)n_in; (void)out_size;
    void* fn = nullptr;
    cudaDriverEntryPointQueryResult qr;
    cudaGetDriverEntryPoint("cuTensorMapEncodeTiled", &fn, cudaEnableDefault, &qr);
    EncodeFn enc = (EncodeFn)fn;
    CUtensorMap mX2, mX, mWqkv, mWo, mW1, mW2;
    {
        cuuint64_t dims[3] = {kD, kS / 2, 2}, strides[2] = {4 * kD, 2 * kD};
        cuuint32_t box[3] = {64, 64, 2}, es[3] = {1, 1, 1};
        enc(&mX2, CU_TENSOR_MAP_DATA_TYPE_BFLOAT16, 3, d_in[0], dims, strides, box, es, CU_TENSOR_MAP_INTERLEAVE_NONE,
            CU_TENSOR_MAP_SWIZZLE_128B, CU_TENSOR_MAP_L2_PROMOTION_L2_128B, CU_TENSOR_MAP_FLOAT_OOB_FILL_NONE);
    }
    make_map(enc, &mX, d_in[0], 2 * kD, kS / 2, 64);
    make_map(enc, &mWqkv, d_in[1], 3 * kD, kD, 64);
    make_map(enc, &mWo, d_in[2], kD, kD, 224);
    make_map(enc, &mW1, d_in[4], 2 * kF, kS / 2, 64);
    make_map(enc, &mW2, d_in[6], kS, kF, 64);
    Params prm;
    prm.x = (const __nv_bfloat16*)d_in[0];
    prm.wqkv = (const __nv_bfloat16*)d_in[1];
    prm.wo = (const __nv_bfloat16*)d_in[2];
    prm.w1 = (const __nv_bfloat16*)d_in[4];
    prm.b1 = (const __nv_bfloat16*)d_in[5];
    prm.w2 = (const __nv_bfloat16*)d_in[6];
    prm.b2 = (const __nv_bfloat16*)d_in[7];
    prm.out = (__nv_bfloat16*)d_out;
    cudaGetSymbolAddress((void**)&prm.sc, g_scratch);
    cudaFuncSetAttribute(fused_kernel, cudaFuncAttributeMaxDynamicSharedMemorySize, SM_TOTAL);
    fused_kernel<<<128, 384, SM_TOTAL, cudaStreamPerThread>>>(prm, mX2, mX, mWqkv, mWo, mW1, mW2);
}
```

```cpp
#include <cuda_runtime.h>
#include <cuda.h>
#include <cuda_bf16.h>
#include <stdint.h>
#include <type_traits>

namespace {

constexpr int kS = 2048, kD = 448, kF = 1792;
constexpr float kEps = 1e-5f;

#define FS 32
struct Scratch {
    uint4    o[32 * 56 * 64];
    uint4    hn[32 * 56 * 64];
    uint4    g[28 * 56 * 64];
    uint4    halo[16 * 8 * 2 * 4 * 32];
    uint32_t stats[32 * 8 * 4 * 32];
    uint2    rows[32 * 64];
    uint32_t flag_o[32 * 8 * FS];
    uint32_t flag_h[32 * 4 * FS];
    uint32_t epoch;
};
__device__ __align__(1024) Scratch g_scratch;
#define TIMEOUT(code)
#define RETRY_COUNT(i)
#define CAP_DECL(n, k)
#define CAP(n)
#define CAP_SKIP(n)
#define EV(i, dep)
#define TR2(idx)
#define TR(idx)
#define TRW(idx)
#define TRG(idx)

constexpr uint32_t SM_WKV  = 114688;
constexpr uint32_t SM_XR   = 24576;
constexpr uint32_t SM_STG  = 40960;
constexpr uint32_t SM_WQ   = 57344;
constexpr uint32_t SM_XCH  = 0;
constexpr uint32_t SM_B    = 131072;
constexpr uint32_t SM_BAR  = 231424;
constexpr uint32_t SM_TOTAL = SM_BAR + 1024;
constexpr int NB = 7;
#define SH1 0
#define SH2 0
#define SH2N 5
#define SH3 0
#define NSPEC 4
#define XSPEC 500
#define C2 0
#define C3 0
#define CN2 7200
#define CN3 10900
constexpr int B_XF = 0, B_WKVF = 7, B_WQF = 14, B_XRF = 15, B_WOF = 16,
              B_XC = 18, B_KV3 = 19, B_KVC = 20,
              B_A1D = 21, B_XD = 22, B_OC = 23,
              B_BE = 24  , B_RE = B_BE + 2 * NB,
              B_PL = B_RE + 3, B_AF = B_PL + 1, B_BL = B_AF + 1  , B_OL = B_BL + 2 * NB  ,
              B_BF = B_OL + 4  , B_OF = B_BF + NB, B_RF = B_OF + 4, B_EP = B_RF + 8, B_PD = B_EP + 1, B_RT = B_PD + 1, B_HL = B_RT + 2,
              B_HD = B_HL + 2  , B_GO = B_HD + 1, B_GD = B_GO + 1, B_COUNT = B_GD + 2;
#define WEARLY 6
#define PF0 126
#define TMPF 2
#define RSTE 2
#define POLLP 1
#define PROBEP 1
#define LOADP 1
#define LOADW 64
#define NOB 0
#define AEARLY 5
#define W1PACE 400
#define W2PACE 200
#define PFPACE 230
#define PFBAR (B_XF + 6)
#define DELTA 1632
#define DELTA2 DELTA
#define BPACE 230
#define BURST 2
#define W1OFF 350
#define W2OFF 2900
#define XPACE 0
#define PSTAG 200
constexpr uint32_t SM_EPOCH = SM_BAR + B_COUNT * 8, SM_TG = SM_EPOCH + 4  , SM_TG2 = SM_TG + 16  , SM_TR = SM_BAR + 768;

#define HDELAY 0
#define QC0 4
#define QC1 10
#define QC2 16
#define HPOS 1
#define XSPECB 850
#define PACE1 120
#define PACE2 400
#define RELOAD1 1
#define VCH 1
#define SOFF 0
#define XW 1
#define XLAG 0
#define PFX 3
#define PFD 250
#define SDELAY 300
#define PDELAY 500
#define NPRE 10
#define PREPACE 0
#define AFIRST 0
#define DELTAO 928
#define NS 0
#define GCH 14
#define OCH 14
#define ICH 14
#define PACKO
#define NR 8
#define HMODE 2
#define HOFF0 (-100)
#define HOFF1 900
#define STAG1 0
#define STAG2 400
#define PLOFF (-250)
#define HSRC h
#define W1Q 3
#define APOS1 ((1ull << 4) | (1ull << 8) | (1ull << 12) | (1ull << 5) | (1ull << 9) | (1ull << 13))
#define APOS2 (0x5555555ull << 17)
constexpr uint32_t seg_mask(int h, int p0, int p1) {
    uint32_t m = 0; int n = 0;
    for (int p = p0; p < p1; p++) if ((p & 1) == h) m |= (uint32_t)(((APOS1 | APOS2) >> p) & 1) << n++;
    return m | 1u << n;
}
constexpr uint64_t seg_masks(int h) {
    return 2 | (uint64_t)seg_mask(h, 0, 16) << 10 | (uint64_t)seg_mask(h, 16, 32) << 20
             | (uint64_t)seg_mask(h, 32, 46) << 30 | (uint64_t)seg_mask(h, 46, 60) << 40;
}
constexpr uint64_t kSegMasks0 = seg_masks(0), kSegMasks1 = seg_masks(1);

constexpr int kSpinLimit = 1 << 15;
__device__ __forceinline__ bool elect_one() {
    uint32_t p;
    asm volatile("{ .reg .pred P; elect.sync _|P, 0xffffffff; selp.u32 %0, 1, 0, P; }" : "=r"(p));
    return p;
}
__device__ __forceinline__ void mbar_init(uint32_t bar, uint32_t cnt) { asm volatile("mbarrier.init.shared::cta.b64 [%0], %1;" :: "r"(bar), "r"(cnt)); }
__device__ __forceinline__ void mbar_expect(uint32_t bar, uint32_t bytes) { asm volatile("mbarrier.arrive.expect_tx.shared::cta.b64 _, [%0], %1;" :: "r"(bar), "r"(bytes) : "memory"); }
__device__ __forceinline__ void mbar_expect_more(uint32_t bar, uint32_t bytes) { asm volatile("mbarrier.expect_tx.relaxed.cta.shared::cta.b64 [%0], %1;" :: "r"(bar), "r"(bytes) : "memory"); }
__device__ __forceinline__ void mbar_arrive(uint32_t bar) { asm volatile("mbarrier.arrive.shared::cta.b64 _, [%0];" :: "r"(bar) : "memory"); }
__device__ __forceinline__ void mbar_wait(uint32_t bar, uint32_t parity) {
    uint32_t ok; int it = 0;
    do {
        asm volatile("{ .reg .pred p; mbarrier.try_wait.parity.shared::cta.b64 p, [%1], %2; selp.u32 %0, 1, 0, p; }"
                     : "=r"(ok) : "r"(bar), "r"(parity) : "memory");
        if (++it > kSpinLimit) { TIMEOUT((bar & 1023) >> 3); break; }
    } while (!ok);
}
__device__ __forceinline__ bool mbar_try(uint32_t bar, uint32_t parity) {
    uint32_t ok;
    asm volatile("{ .reg .pred p; mbarrier.try_wait.parity.shared::cta.b64 p, [%1], %2; selp.u32 %0, 1, 0, p; }" : "=r"(ok) : "r"(bar), "r"(parity) : "memory");
    return ok;
}
__device__ __forceinline__ bool mbar_test(uint32_t bar, uint32_t parity) {
    uint32_t ok;
    asm volatile("{ .reg .pred p; mbarrier.test_wait.parity.shared::cta.b64 p, [%1], %2; selp.u32 %0, 1, 0, p; }" : "=r"(ok) : "r"(bar), "r"(parity) : "memory");
    return ok;
}
__device__ __forceinline__ void mbar_wait_fast(uint32_t bar, uint32_t parity) { if (!mbar_try(bar, parity)) mbar_wait(bar, parity); }
__device__ __forceinline__ void mbar_wait2(uint32_t bar0, uint32_t par0, uint32_t bar1, uint32_t par1) {
    uint32_t ok; int it = 0;
    do {
        asm volatile("{ .reg .pred p, q; mbarrier.try_wait.parity.shared::cta.b64 p, [%1], %2;\n"
                     "mbarrier.try_wait.parity.shared::cta.b64 q, [%3], %4; and.pred p, p, q; selp.u32 %0, 1, 0, p; }"
                     : "=r"(ok) : "r"(bar0), "r"(par0), "r"(bar1), "r"(par1) : "memory");
        if (++it > kSpinLimit) { TIMEOUT((bar0 & 1023) >> 3); break; }
    } while (!ok);
}
__device__ __forceinline__ void sched_fence(uint32_t v) {
    asm volatile("{ .reg .pred p; .reg .b32 x; mov.b32 x, %0;\nL: setp.eq.u32 p, x, 0xffffffff; @p mov.u32 x, %%clock; @p bra L; }" :: "r"(v) : "memory");
}
template <int N> __device__ __forceinline__ void reg_fence(float (&d)[N]) {
    #pragma unroll
    for (int i = 0; i < N; i++) asm volatile("" : "+f"(d[i]) :: "memory");
}
__device__ __forceinline__ void mbar_wait_cluster(uint32_t bar, uint32_t parity) {
    uint32_t ok; int it = 0;
    do {
        asm volatile("{ .reg .pred p; mbarrier.try_wait.parity.acquire.cluster.shared::cta.b64 p, [%1], %2; selp.u32 %0, 1, 0, p; }"
                     : "=r"(ok) : "r"(bar), "r"(parity) : "memory");
        if (++it > kSpinLimit) { TIMEOUT((bar & 1023) >> 3); break; }
    } while (!ok);
}
__device__ __forceinline__ void mbar_arrive_if(uint32_t bar, bool pred) {
    asm volatile("{ .reg .pred p; setp.ne.u32 p, %1, 0; @p mbarrier.arrive.shared::cta.b64 _, [%0]; }" :: "r"(bar), "r"((uint32_t)pred) : "memory");
}
template <int P> __device__ __forceinline__ void tick() {
    if (P > 1) { const uint32_t t = ((uint32_t)clock() | (P - 1)) + 1; while ((int)((uint32_t)clock() - t) < 0) {} }
}
__device__ __forceinline__ void warp_arrive(uint32_t bar) { __syncwarp(); if (elect_one()) mbar_arrive(bar); }
__device__ __forceinline__ void tma2d(uint32_t dst, const CUtensorMap* m, int c0, int c1, uint32_t bar) {
    asm volatile("cp.async.bulk.tensor.2d.shared::cluster.global.mbarrier::complete_tx::bytes [%0], [%1, {%3, %4}], [%2];"
                 :: "r"(dst), "l"(m), "r"(bar), "r"(c0), "r"(c1) : "memory");
}
__device__ __forceinline__ void tma3d(uint32_t dst, const CUtensorMap* m, int c0, int c1, int c2, uint32_t bar) {
    asm volatile("cp.async.bulk.tensor.3d.shared::cluster.global.mbarrier::complete_tx::bytes [%0], [%1, {%3, %4, %5}], [%2];"
                 :: "r"(dst), "l"(m), "r"(bar), "r"(c0), "r"(c1), "r"(c2) : "memory");
}
__device__ __forceinline__ void tma2d_mc(uint32_t dst, const CUtensorMap* m, int c0, int c1, uint32_t bar) {
    asm volatile("cp.async.bulk.tensor.2d.shared::cluster.global.mbarrier::complete_tx::bytes.multicast::cluster [%0], [%1, {%3, %4}], [%2], %5;"
                 :: "r"(dst), "l"(m), "r"(bar), "r"(c0), "r"(c1), "h"((uint16_t)3) : "memory");
}
__device__ __forceinline__ void bulk_g2s_mc(uint32_t dst, const void* src, uint32_t bytes, uint32_t bar) {
    asm volatile("cp.async.bulk.shared::cluster.global.mbarrier::complete_tx::bytes.multicast::cluster [%0], [%1], %2, [%3], %4;"
                 :: "r"(dst), "l"(src), "r"(bytes), "r"(bar), "h"((uint16_t)3) : "memory");
}
__device__ __forceinline__ void mbar_arrive_remote_if(uint32_t cluster_bar, bool pred) {
    asm volatile("{ .reg .pred p; setp.ne.u32 p, %1, 0; @p mbarrier.arrive.shared::cluster.b64 _, [%0]; }" :: "r"(cluster_bar), "r"((uint32_t)pred) : "memory");
}
__device__ __forceinline__ void bulk_g2s(uint32_t dst, const void* src, uint32_t bytes, uint32_t bar) {
    asm volatile("cp.async.bulk.shared::cluster.global.mbarrier::complete_tx::bytes [%0], [%1], %2, [%3];"
                 :: "r"(dst), "l"(src), "r"(bytes), "r"(bar) : "memory");
}
__device__ __forceinline__ void wg_fence()  { asm volatile("wgmma.fence.sync.aligned;" ::: "memory"); }
__device__ __forceinline__ void wg_commit() { asm volatile("wgmma.commit_group.sync.aligned;" ::: "memory"); }
template <int N> __device__ __forceinline__ void wg_wait() { asm volatile("wgmma.wait_group.sync.aligned %0;" :: "n"(N) : "memory"); }
__device__ __forceinline__ void named_bar(int id, int n) { asm volatile("bar.sync %0, %1;" :: "r"(id), "r"(n) : "memory"); }
__device__ __forceinline__ void named_arrive(int id, int n) { asm volatile("bar.arrive %0, %1;" :: "r"(id), "r"(n) : "memory"); }
__device__ __forceinline__ bool mbar_try2(uint32_t bar0, uint32_t par0, uint32_t bar1, uint32_t par1) {
    uint32_t ok;
    asm volatile("{ .reg .pred p, q; mbarrier.test_wait.parity.shared::cta.b64 p, [%1], %2;\n"
                 "mbarrier.test_wait.parity.shared::cta.b64 q, [%3], %4; and.pred p, p, q; selp.u32 %0, 1, 0, p; }"
                 : "=r"(ok) : "r"(bar0), "r"(par0), "r"(bar1), "r"(par1) : "memory");
    return ok;
}
__device__ __forceinline__ void fence_gpu() { asm volatile("fence.release.gpu;" ::: "memory"); }
__device__ __forceinline__ void fence_async_global() { asm volatile("fence.proxy.async.global;" ::: "memory"); }
__device__ __forceinline__ void fence_async_smem() { asm volatile("fence.proxy.async.shared::cta;" ::: "memory"); }
__device__ __forceinline__ uint32_t gtime32() { uint64_t t; asm volatile("mov.u64 %0, %%globaltimer;" : "=l"(t) :: "memory"); return (uint32_t)t; }
__device__ __forceinline__ uint32_t clk32() { uint64_t t; asm volatile("mov.u64 %0, %%clock64;" : "=l"(t) :: "memory"); return (uint32_t)t; }
__device__ __forceinline__ void spin_until(uint32_t t) { while ((int)(clk32() - t) < 0) {} }
#define SLEEPNS 20
__device__ __forceinline__ void sleep_until(uint32_t t) { while ((int)(clk32() - t) < 0) { if (SLEEPNS) __nanosleep(SLEEPNS); } }
__device__ __forceinline__ void st_flag(uint32_t* p, uint32_t v) {
    const uint64_t w = ((uint64_t)gtime32() << 32) | v;
    asm volatile("st.relaxed.gpu.global.u64 [%0], %1;" :: "l"(p), "l"(w) : "memory");
}
__device__ __forceinline__ void ld_flag_if(uint64_t& v, const uint32_t* p, bool pred) {
    asm volatile("{ .reg .pred p; setp.ne.u32 p, %2, 0; @p ld.relaxed.gpu.global.u64 %0, [%1]; }" : "+l"(v) : "l"(p), "r"((uint32_t)pred) : "memory");
}
__device__ __forceinline__ uint32_t ld_acq(const uint32_t* p) { uint32_t v; asm volatile("ld.acquire.gpu.global.u32 %0, [%1];" : "=r"(v) : "l"(p) : "memory"); return v; }
__device__ __forceinline__ uint32_t ld_rlx(const uint32_t* p) { uint32_t v; asm volatile("ld.relaxed.gpu.global.u32 %0, [%1];" : "=r"(v) : "l"(p) : "memory"); return v; }
template <class T> __device__ __forceinline__ T* opaque_ptr(T* p) { asm volatile("" : "+l"(p)); return p; }
__device__ __forceinline__ uint4 ld_rlx4(const uint4* p) {
    uint4 v; asm volatile("ld.relaxed.gpu.global.v4.u32 {%0,%1,%2,%3}, [%4];" : "=r"(v.x), "=r"(v.y), "=r"(v.z), "=r"(v.w) : "l"(p) : "memory"); return v;
}
__device__ __forceinline__ void st_ll(uint4* p, uint32_t a, uint32_t b, uint32_t tag) {
    uint64_t lo = ((uint64_t)tag << 32) | a, hi = ((uint64_t)tag << 32) | b;
    asm volatile("st.relaxed.gpu.global.v2.u64 [%0], {%1,%2};" :: "l"(p), "l"(lo), "l"(hi) : "memory");
}
__device__ __forceinline__ bool ld_ll(const uint4* p, uint32_t& a, uint32_t& b, uint32_t tag) {
    uint64_t lo, hi;
    asm volatile("ld.relaxed.gpu.global.v2.u64 {%0,%1}, [%2];" : "=l"(lo), "=l"(hi) : "l"(p) : "memory");
    a = (uint32_t)lo; b = (uint32_t)hi;
    return (uint32_t)(lo >> 32) == tag && (uint32_t)(hi >> 32) == tag;
}
__device__ __forceinline__ uint2 ld_acq2(const uint2* p) {
    uint2 v; asm volatile("ld.acquire.gpu.global.v2.u32 {%0,%1}, [%2];" : "=r"(v.x), "=r"(v.y) : "l"(p) : "memory"); return v;
}
__device__ __forceinline__ uint2 ld_rlx2(const uint2* p) {
    uint2 v; asm volatile("ld.relaxed.gpu.global.v2.u32 {%0,%1}, [%2];" : "=r"(v.x), "=r"(v.y) : "l"(p) : "memory"); return v;
}
__device__ __forceinline__ void stg1(uint32_t* p, uint32_t v) { asm volatile("st.global.u32 [%0], %1;" :: "l"(p), "r"(v) : "memory"); }
__device__ __forceinline__ void stg2(void* p, uint32_t x, uint32_t y) { asm volatile("st.global.v2.u32 [%0], {%1,%2};" :: "l"(p), "r"(x), "r"(y) : "memory"); }
__device__ __forceinline__ void stg4(void* p, uint32_t x, uint32_t y, uint32_t z, uint32_t w) { asm volatile("st.global.v4.u32 [%0], {%1,%2,%3,%4};" :: "l"(p), "r"(x), "r"(y), "r"(z), "r"(w) : "memory"); }
__device__ __forceinline__ uint32_t lds1(uint32_t a) { uint32_t v; asm volatile("ld.shared.u32 %0, [%1];" : "=r"(v) : "r"(a) : "memory"); return v; }
__device__ __forceinline__ uint2 lds2(uint32_t a) { uint2 v; asm volatile("ld.shared.v2.u32 {%0,%1}, [%2];" : "=r"(v.x), "=r"(v.y) : "r"(a) : "memory"); return v; }
__device__ __forceinline__ uint32_t set_par(uint32_t v, uint32_t mask, uint32_t par) {
    uint32_t r; asm("lop3.b32 %0, %1, %2, %3, 0xb8;" : "=r"(r) : "r"(v), "r"(mask), "r"(par)); return r;
}
__device__ __forceinline__ void st_gen4(void* p, uint32_t x, uint32_t y, uint32_t z, uint32_t w) { asm volatile("st.v4.u32 [%0], {%1,%2,%3,%4};" :: "l"(p), "r"(x), "r"(y), "r"(z), "r"(w) : "memory"); }
__device__ __forceinline__ float tanh_hw(float x) { float r; asm("tanh.approx.f32 %0, %1;" : "=f"(r) : "f"(x)); return r; }
__device__ __forceinline__ bool bar_any(int id, int n, bool v) {
    uint32_t r;
    asm volatile("{ .reg .pred p, q; setp.ne.u32 p, %3, 0; bar.red.or.pred q, %1, %2, p; selp.u32 %0, 1, 0, q; }" : "=r"(r) : "r"(id), "r"(n), "r"((uint32_t)v) : "memory");
    return r;
}
__device__ __forceinline__ void sts4(uint32_t a, uint32_t x, uint32_t y, uint32_t z, uint32_t w) { asm volatile("st.shared.v4.u32 [%0], {%1,%2,%3,%4};" :: "r"(a), "r"(x), "r"(y), "r"(z), "r"(w) : "memory"); }
__device__ __forceinline__ uint4 lds4(uint32_t a) { uint4 v; asm volatile("ld.shared.v4.u32 {%0,%1,%2,%3}, [%4];" : "=r"(v.x), "=r"(v.y), "=r"(v.z), "=r"(v.w) : "r"(a) : "memory"); return v; }
__device__ __forceinline__ uint32_t pack_bf16(float lo, float hi) { uint32_t r; asm("cvt.rn.bf16x2.f32 %0, %1, %2;" : "=r"(r) : "f"(hi), "f"(lo)); return r; }
__device__ __forceinline__ float bf_lo(uint32_t v) { return __uint_as_float(v << 16); }
__device__ __forceinline__ float bf_hi(uint32_t v) { return __uint_as_float(v & 0xffff0000u); }
__device__ __forceinline__ uint32_t sub_bf16x2(uint32_t a, uint32_t b) { uint32_t r; asm volatile("sub.rn.bf16x2 %0, %1, %2;" : "=r"(r) : "r"(a), "r"(b)); return r; }
__device__ __forceinline__ uint32_t add_bf16x2(uint32_t a, uint32_t b) { uint32_t r; asm volatile("add.rn.bf16x2 %0, %1, %2;" : "=r"(r) : "r"(a), "r"(b)); return r; }
__device__ __forceinline__ uint32_t sqr_bf16x2(uint32_t a) { uint32_t r; asm volatile("mul.rn.bf16x2 %0, %1, %1;" : "=r"(r) : "r"(a)); return r; }
__device__ __forceinline__ uint32_t sqa_bf16x2(uint32_t a, uint32_t c) { uint32_t r; asm volatile("fma.rn.bf16x2 %0, %1, %1, %2;" : "=r"(r) : "r"(a), "r"(c)); return r; }
__device__ __forceinline__ uint32_t movm(uint32_t a) { uint32_t r; asm volatile("movmatrix.sync.aligned.m8n8.trans.b16 %0, %1;" : "=r"(r) : "r"(a)); return r; }
__device__ __forceinline__ float ex2(float x) { float r; asm("ex2.approx.ftz.f32 %0, %1;" : "=f"(r) : "f"(x)); return r; }
__device__ __forceinline__ float rsq(float x) { float r; asm("rsqrt.approx.ftz.f32 %0, %1;" : "=f"(r) : "f"(x)); return r; }
__device__ __forceinline__ float rcp(float x) { float r; asm("rcp.approx.ftz.f32 %0, %1;" : "=f"(r) : "f"(x)); return r; }
__device__ __forceinline__ void mma16816(float (&c)[4], uint32_t a0, uint32_t a1, uint32_t a2, uint32_t a3, uint32_t b0, uint32_t b1) {
    asm("mma.sync.aligned.m16n8k16.row.col.f32.bf16.bf16.f32 {%0,%1,%2,%3}, {%4,%5,%6,%7}, {%8,%9}, {%0,%1,%2,%3};"
        : "+f"(c[0]), "+f"(c[1]), "+f"(c[2]), "+f"(c[3]) : "r"(a0), "r"(a1), "r"(a2), "r"(a3), "r"(b0), "r"(b1));
}
__device__ __forceinline__ void mma1688(float (&c)[4], uint32_t a0, uint32_t a1, uint32_t b0) {
    asm("mma.sync.aligned.m16n8k8.row.col.f32.bf16.bf16.f32 {%0,%1,%2,%3}, {%4,%5}, {%6}, {%0,%1,%2,%3};"
        : "+f"(c[0]), "+f"(c[1]), "+f"(c[2]), "+f"(c[3]) : "r"(a0), "r"(a1), "r"(b0));
}
__device__ __forceinline__ float quad_sum(float v) { v += __shfl_xor_sync(~0u, v, 1); v += __shfl_xor_sync(~0u, v, 2); return v; }
__device__ __forceinline__ float quad_max(float v) { v = fmaxf(v, __shfl_xor_sync(~0u, v, 1)); v = fmaxf(v, __shfl_xor_sync(~0u, v, 2)); return v; }
__device__ __forceinline__ uint64_t make_desc(uint32_t addr, uint32_t lbo, bool swz, uint32_t sbo = 1024) {
    const uint32_t lo = __shfl_sync(~0u, ((addr & 0x3FFFF) >> 4) | ((lbo >> 4) << 16), 0);
    const uint32_t hi = __shfl_sync(~0u, (swz ? 0x40000000u : 0u) + (sbo >> 4) + (threadIdx.x & 31), 0);
    return ((uint64_t)hi << 32) | lo;
}
template <int I, int N, class F> __device__ __forceinline__ void static_for(F&& f) {
    if constexpr (I < N) { f(std::integral_constant<int, I>{}); static_for<I + 1, N>(f); }
}
__device__ __forceinline__ uint32_t opaque(uint32_t v) { asm volatile("" : "+r"(v)); return v; }
template <int BOFF, int SCALE_D>
__device__ __forceinline__ void wgmma_rs_n56(float (&d)[28], uint32_t a0, uint32_t a1, uint32_t a2, uint32_t a3, uint64_t db) {
    asm volatile("{ .reg .b64 db; add.s64 db, %32, %33;\n"
        "wgmma.mma_async.sync.aligned.m64n56k16.f32.bf16.bf16 "
        "{%0, %1, %2, %3, %4, %5, %6, %7, %8, %9, %10, %11, %12, %13, %14, %15, %16, %17, %18, %19, %20, %21, %22, %23, %24, %25, %26, %27}, "
        "{%28, %29, %30, %31}, db, %34, 1, 1, 1; }"
        : "+f"(d[0]), "+f"(d[1]), "+f"(d[2]), "+f"(d[3]), "+f"(d[4]), "+f"(d[5]), "+f"(d[6]), "+f"(d[7]),
        "+f"(d[8]), "+f"(d[9]), "+f"(d[10]), "+f"(d[11]), "+f"(d[12]), "+f"(d[13]), "+f"(d[14]), "+f"(d[15]),
        "+f"(d[16]), "+f"(d[17]), "+f"(d[18]), "+f"(d[19]), "+f"(d[20]), "+f"(d[21]), "+f"(d[22]), "+f"(d[23]),
        "+f"(d[24]), "+f"(d[25]), "+f"(d[26]), "+f"(d[27])
        : "r"(a0), "r"(a1), "r"(a2), "r"(a3), "l"(db), "n"(BOFF >> 4), "n"(SCALE_D));
}
template <int AOFF, int BOFF, int MMAJOR>
__device__ __forceinline__ void wgmma_ss_n56(float (&d)[28], uint64_t da, uint64_t db) {
    asm volatile("{ .reg .b64 da, db; add.s64 da, %28, %30; add.s64 db, %29, %31;\n"
        "wgmma.mma_async.sync.aligned.m64n56k16.f32.bf16.bf16 "
        "{%0, %1, %2, %3, %4, %5, %6, %7, %8, %9, %10, %11, %12, %13, %14, %15, %16, %17, %18, %19, %20, %21, %22, %23, %24, %25, %26, %27}, "
        "da, db, 1, 1, 1, %32, 1; }"
        : "+f"(d[0]), "+f"(d[1]), "+f"(d[2]), "+f"(d[3]), "+f"(d[4]), "+f"(d[5]), "+f"(d[6]), "+f"(d[7]),
        "+f"(d[8]), "+f"(d[9]), "+f"(d[10]), "+f"(d[11]), "+f"(d[12]), "+f"(d[13]), "+f"(d[14]), "+f"(d[15]),
        "+f"(d[16]), "+f"(d[17]), "+f"(d[18]), "+f"(d[19]), "+f"(d[20]), "+f"(d[21]), "+f"(d[22]), "+f"(d[23]),
        "+f"(d[24]), "+f"(d[25]), "+f"(d[26]), "+f"(d[27])
        : "l"(da), "l"(db), "n"(AOFF >> 4), "n"(BOFF >> 4), "n"(MMAJOR));
}
template <int AOFF, int BOFF, int MMAJOR>
__device__ __forceinline__ void wgmma_ss_n112(float (&d)[28], float (&e)[28], uint64_t da, uint64_t db) {
    asm volatile("{ .reg .b64 da, db; add.s64 da, %56, %58; add.s64 db, %57, %59;\n"
        "wgmma.mma_async.sync.aligned.m64n112k16.f32.bf16.bf16 "
        "{%0, %1, %2, %3, %4, %5, %6, %7, %8, %9, %10, %11, %12, %13, %14, %15, %16, %17, %18, %19, %20, %21, %22, %23, %24, %25, %26, %27, %28, %29, %30, %31, %32, %33, %34, %35, %36, %37, %38, %39, %40, %41, %42, %43, %44, %45, %46, %47, %48, %49, %50, %51, %52, %53, %54, %55}, "
        "da, db, 1, 1, 1, %60, 1; }"
        : "+f"(d[0]), "+f"(d[1]), "+f"(d[2]), "+f"(d[3]), "+f"(d[4]), "+f"(d[5]), "+f"(d[6]), "+f"(d[7]),
        "+f"(d[8]), "+f"(d[9]), "+f"(d[10]), "+f"(d[11]), "+f"(d[12]), "+f"(d[13]), "+f"(d[14]), "+f"(d[15]),
        "+f"(d[16]), "+f"(d[17]), "+f"(d[18]), "+f"(d[19]), "+f"(d[20]), "+f"(d[21]), "+f"(d[22]), "+f"(d[23]),
        "+f"(d[24]), "+f"(d[25]), "+f"(d[26]), "+f"(d[27]), "+f"(e[0]), "+f"(e[1]), "+f"(e[2]), "+f"(e[3]),
        "+f"(e[4]), "+f"(e[5]), "+f"(e[6]), "+f"(e[7]), "+f"(e[8]), "+f"(e[9]), "+f"(e[10]), "+f"(e[11]),
        "+f"(e[12]), "+f"(e[13]), "+f"(e[14]), "+f"(e[15]), "+f"(e[16]), "+f"(e[17]), "+f"(e[18]), "+f"(e[19]),
        "+f"(e[20]), "+f"(e[21]), "+f"(e[22]), "+f"(e[23]), "+f"(e[24]), "+f"(e[25]), "+f"(e[26]), "+f"(e[27])
        : "l"(da), "l"(db), "n"(AOFF >> 4), "n"(BOFF >> 4), "n"(MMAJOR));
}
template <int BOFF, int SCALE_D>
__device__ __forceinline__ void wgmma_rs_n112(float (&d)[28], float (&e)[28], uint32_t a0, uint32_t a1, uint32_t a2, uint32_t a3, uint64_t db) {
    asm volatile("{ .reg .b64 db; add.s64 db, %60, %61;\n"
        "wgmma.mma_async.sync.aligned.m64n112k16.f32.bf16.bf16 "
        "{%0, %1, %2, %3, %4, %5, %6, %7, %8, %9, %10, %11, %12, %13, %14, %15, %16, %17, %18, %19, %20, %21, %22, %23, %24, %25, %26, %27, %28, %29, %30, %31, %32, %33, %34, %35, %36, %37, %38, %39, %40, %41, %42, %43, %44, %45, %46, %47, %48, %49, %50, %51, %52, %53, %54, %55}, "
        "{%56, %57, %58, %59}, db, %62, 1, 1, 1; }"
        : "+f"(d[0]), "+f"(d[1]), "+f"(d[2]), "+f"(d[3]), "+f"(d[4]), "+f"(d[5]), "+f"(d[6]), "+f"(d[7]),
        "+f"(d[8]), "+f"(d[9]), "+f"(d[10]), "+f"(d[11]), "+f"(d[12]), "+f"(d[13]), "+f"(d[14]), "+f"(d[15]),
        "+f"(d[16]), "+f"(d[17]), "+f"(d[18]), "+f"(d[19]), "+f"(d[20]), "+f"(d[21]), "+f"(d[22]), "+f"(d[23]),
        "+f"(d[24]), "+f"(d[25]), "+f"(d[26]), "+f"(d[27]), "+f"(e[0]), "+f"(e[1]), "+f"(e[2]), "+f"(e[3]),
        "+f"(e[4]), "+f"(e[5]), "+f"(e[6]), "+f"(e[7]), "+f"(e[8]), "+f"(e[9]), "+f"(e[10]), "+f"(e[11]),
        "+f"(e[12]), "+f"(e[13]), "+f"(e[14]), "+f"(e[15]), "+f"(e[16]), "+f"(e[17]), "+f"(e[18]), "+f"(e[19]),
        "+f"(e[20]), "+f"(e[21]), "+f"(e[22]), "+f"(e[23]), "+f"(e[24]), "+f"(e[25]), "+f"(e[26]), "+f"(e[27])
        : "r"(a0), "r"(a1), "r"(a2), "r"(a3), "l"(db), "n"(BOFF >> 4), "n"(SCALE_D));
}

struct Params {
    const __nv_bfloat16 *x, *wqkv;
    Scratch* sc;
    const __nv_bfloat16 *wo, *w1, *w2, *b1, *b2;
    __nv_bfloat16* out;
};

__global__ void __cluster_dims__(2, 1, 1) __launch_bounds__(384, 1)
fused_kernel(const Params prm, const __grid_constant__ CUtensorMap mX2, const __grid_constant__ CUtensorMap mX, const __grid_constant__ CUtensorMap mWqkv,
             const __grid_constant__ CUtensorMap mWo, const __grid_constant__ CUtensorMap mW1,
             const __grid_constant__ CUtensorMap mW2)
{
    extern __shared__ __align__(1024) unsigned char smem_raw[];
    if (threadIdx.x < 126) {
        const uint32_t i = threadIdx.x, t = clk32() + (i >> 5) * PFD;
        const char* px = (const char*)prm.x + (blockIdx.x * 16 + (i & 15)) * 896 + (i >> 4) * 128;
        const char* pw = (const char*)prm.wqkv + blockIdx.x * 2688 + i * 128 + (896 - 112 * 128);
        spin_until(t);
        asm volatile("prefetch.global.L2 [%0];" :: "l"(i < 112 ? px : pw) : "memory");
    }
    if (threadIdx.x == 128) { asm volatile("prefetch.tensormap [%0];" :: "l"(&mX2) : "memory"); asm volatile("prefetch.tensormap [%0];" :: "l"(&mWqkv) : "memory"); }
    uint32_t sb = (uint32_t)__cvta_generic_to_shared(smem_raw);
    asm volatile("mov.u32 %0, %0;" : "+r"(sb));
    const uint32_t bar0 = sb + SM_BAR;
    auto BAR = [&](int i) { return bar0 + 8u * i; };

    const int tid = threadIdx.x, lane = tid & 31;
    const int warp = __shfl_sync(~0u, tid >> 5, 0);
    const int b = __shfl_sync(~0u, (int)blockIdx.x, 0);
    const int rank = b & 1;
    const int cl = (b >> 1) - 4, cq = ((cl - 32) * 37) >> 8;
    const int res = cl < 0 ? 0 : cl < 32 ? cl & 7 : cl - 31 - 7 * cq;
    const int rnd = cl < 0 ? cl + 8 : cl < 32 ? cl >> 3 : 4 + cq;
    const int hg = (res & 1) * 4 + (rnd & 3);
    const int ti = (res >> 1) * 4 + (rnd >> 2) * 2 + rank;
    const int a2p = res & 1, a2j = rnd & 3;
    const int a2s = ti * 2 + a2p;
    const bool g1_on = rnd != 7;
    const int g1j = (rnd < 6 ? rnd : res) & 1, g1f = rnd < 6 ? res * 3 + (rnd >> 1) : 24 + (res >> 1);
    const int g2j = rnd & 1, g2s = res * 4 + (rnd >> 1);
    uint32_t pbar0;
    asm volatile("mapa.shared::cluster.u32 %0, %1, %2;" : "=r"(pbar0) : "r"(bar0), "r"(rank ^ 1));
    auto pair_arrive = [&](int i) { __syncwarp(); const bool l = elect_one(); mbar_arrive_if(BAR(i), l); mbar_arrive_remote_if(pbar0 + 8u * i, l); };
    const int wcol = hg * 56 - (hg & 1) * 8;

    if (warp == 8) {
        if (elect_one()) {
            #pragma unroll
            for (int i = 0; i < B_WQF; i++) mbar_init(BAR(i), 1);
            asm volatile("fence.mbarrier_init.release.cluster;" ::: "memory");
            fence_async_smem();
            #pragma unroll
            for (int kb = 0; kb < 7; kb++) {
                tma3d(sb + kb * 16384, &mX2, kb * 64, ti * 64, 0, BAR(B_XF + kb));
                mbar_expect(BAR(B_XF + kb), 16384);
                if (kb == 0 && PFX != 3) asm volatile("prefetch.tensormap [%0];" :: "l"(&mWqkv) : "memory");
            }
        }
    } else if (warp > 8) {
        if (elect_one()) {
            if (warp == 9) {
                #pragma unroll
                for (int i = B_WQF; i < B_AF; i++) mbar_init(BAR(i), i < B_XC ? 1 : i < B_A1D ? 16 : i < B_BE ? 8 : 4);
            } else if (warp == 10) {
                #pragma unroll
                for (int i = B_AF; i < B_BF; i++) mbar_init(BAR(i), 1);
            } else {
                #pragma unroll
                for (int i = B_BF; i < B_COUNT; i++) mbar_init(BAR(i), i == B_HD ? 8 : 1);
            }
            asm volatile("fence.mbarrier_init.release.cluster;" ::: "memory");
            fence_async_smem();
        }
    }
    __syncwarp();
    __syncthreads();
    asm volatile("barrier.cluster.arrive.relaxed.aligned;" ::: "memory");
    if (tid < 256) TR(0);
    if (tid == 0) TRG(61);

    if (warp >= 8) {
        asm volatile("setmaxnreg.dec.sync.aligned.u32 40;");
        asm volatile("barrier.cluster.wait.aligned;" ::: "memory");
        auto fetch_halo = [&](int p, uint32_t tag) {
            uint4 u[4];
            #pragma unroll
            for (int c = 0; c < 4; c++) u[c] = make_uint4(0u, 0u, 0u, 0u);
            const uint4* hp = opaque_ptr(&prm.sc->halo[(((ti - 1) * 8 + hg) * 2 + p) * 128 + lane]);
            mbar_wait(BAR(B_KVC), 0);
            if (p == 0) TRW(51);
            sleep_until(clk32() + HDELAY);
            if (ti > 0) {
                int it = 0;
                do {
                    #pragma unroll
                    for (int c = 0; c < 4; c++) u[c] = ld_rlx4(hp + c * 32);
                    if (it) RETRY_COUNT(4);
                    if (++it > kSpinLimit) { TIMEOUT(101); break; }
                } while (__any_sync(~0u, ((u[0].x ^ tag) | (u[1].x ^ tag) | (u[2].x ^ tag) | (u[3].x ^ tag)) & ~lane & 1));
            }
            #pragma unroll
            for (int c = 0; c < 4; c++) sts4(sb + SM_STG + p * 8192 + 3 * 2048 + lane * 16 + c * 512, u[c].x, u[c].y, u[c].z, u[c].w);
            warp_arrive(BAR(B_HL + p));
        };
        if (warp & 1) {
            uint32_t tag;
            if (warp == 11) {
                tag = *(volatile uint32_t*)&prm.sc->epoch + 1;
            #pragma unroll 1
            for (int i = 0; i < 8; i++) prm.sc->halo[(ti * 8 + hg) * 256 + i * 32 + lane] = make_uint4(~tag, 0u, 0u, 0u);
            ((uint4*)prm.sc->stats)[(a2s * 4 + a2j) * 64 + lane] = ((uint4*)prm.sc->stats)[(a2s * 4 + a2j) * 64 + 32 + lane] = make_uint4(~tag, ~tag, ~tag, ~tag);
            prm.sc->flag_h[(a2s * 4 + a2j) * FS + lane] = 0;
            prm.sc->flag_o[(ti * 16 + hg) * FS + lane] = prm.sc->flag_o[(ti * 16 + 8 + hg) * FS + lane] = 0;
            __syncwarp();
            if (lane == 0) {
                asm volatile("st.shared.v2.u32 [%0], {%1, %2};" :: "r"(sb + SM_EPOCH), "r"(tag), "r"(gtime32()) : "memory");
                mbar_arrive(BAR(B_EP));
            }
            if (lane < 8) mbar_expect(BAR(B_RF + lane), 1792);
            __syncwarp();
            TRW(44);
            } else {
                mbar_wait(BAR(B_EP), 0);
                tag = lds1(sb + SM_EPOCH);
            }
            fetch_halo((warp >> 1) & 1, tag);
        }
        if (warp < 10) {
          auto load_slab = [&](int s, bool second) {
              if (!second) tma2d(sb + s * 8192, &mW1, (s & 1) * kF + g1f * 64, (rank * 8 + (s >> 1)) * 64, BAR(B_AF));
              else         tma2d(sb + s * 8192, &mW2, g2s * 64, (rank * 14 + s - 1) * 64, BAR(B_AF));
          };
          if (warp == 8) {
            if (elect_one()) {
                #pragma unroll 1
                for (int s = 0; s < 7; s++) {
                    mbar_expect(BAR(B_WKVF + s), 16384);
                    tma2d_mc(sb + SM_WKV + s * 16384 + rank * 8192, &mWqkv, (1 + rank) * kD + wcol, s * 64, BAR(B_WKVF + s));
                }
            }
            __syncwarp();
            mbar_wait(BAR(B_XC), 0);
            if (elect_one()) {
                asm volatile("prefetch.tensormap [%0];" :: "l"(&mX) : "memory");
                asm volatile("prefetch.tensormap [%0];" :: "l"(&mWo) : "memory");
                asm volatile("prefetch.tensormap [%0];" :: "l"(&mW1) : "memory");
                asm volatile("prefetch.tensormap [%0];" :: "l"(&mW2) : "memory");
                mbar_expect(BAR(B_AF), (g1_on ? NPRE : 14) * 8192);
                mbar_expect(BAR(B_WQF), 57344);
                #pragma unroll 1
                for (int s = rank; s < 7; s += 2) tma2d_mc(sb + SM_WQ + s * 8192, &mWqkv, wcol, s * 64, BAR(B_WQF));
                mbar_expect(BAR(B_XRF), 16384);
                tma2d(sb + SM_XR, &mX, a2p * kD + a2j * 112, ti * 64, BAR(B_XRF));
                tma2d(sb + SM_XR + 8192, &mX, a2p * kD + a2j * 112 + 48, ti * 64, BAR(B_XRF));
            }
            __syncwarp();
            #pragma unroll 1
            for (int h = 0; h < 2; h++) {
                mbar_wait(BAR(B_KV3 + h), 0);
                if (h) mbar_wait2(BAR(B_HL), 0, BAR(B_HL + 1), 0);
                if (elect_one()) {
                    mbar_expect(BAR(B_WOF + h), 57344);
                    tma2d_mc(sb + SM_WKV + h * 57344 + rank * 28672, &mWo, a2j * 112 + rank * 48, h * 224, BAR(B_WOF + h));
                    if (g1_on && h == AFIRST) { load_slab(0, false); load_slab(1, false); load_slab(2, false); }
                }
                __syncwarp();
            }
            if (g1_on) {
                mbar_wait2(BAR(B_XD), 0, BAR(B_OL + 3), 0);
                #pragma unroll 1
                for (int i = 3; i < NPRE; i++) {
                    if (i == 7) mbar_wait(BAR(B_OC), 0);
                    if (elect_one()) load_slab(i, false);
                    __syncwarp();
                }
            } else {
                mbar_wait(BAR(B_HD), 0);
                mbar_arrive_remote_if(pbar0 + 8u * B_PD, lane == 0);
                mbar_wait(BAR(B_GO), 0);
                uint32_t tg = lds1(sb + SM_TG + 4);
                tg += max((int)(lds1(sb + SM_TG2) - tg), 0);
                int it = 0;
                while ((int)(gtime32() - tg) < 0 && ++it < 256) {}
                const uint32_t t0 = clk32();
                if (lane < 2) {
                    asm volatile("st.shared.u32 [%0], %1;" :: "r"(sb + SM_TG + 8 + lane * 4), "r"(t0 + (lane ? CN3 : CN2)) : "memory");
                    mbar_arrive(BAR(B_GD + lane));
                }
                __syncwarp();
                #pragma unroll 1
                for (int s = 1; s < 15; s++) {
                    sleep_until(t0 + W2OFF + s * W2PACE);
                    if (elect_one()) load_slab(s, true);
                    __syncwarp();
                }
            }
          } else {
            TRW(58);
            const uint32_t tag = lds1(sb + SM_EPOCH);
            if (lane < 4) mbar_expect(BAR(B_OL + lane), 14336);
            #pragma unroll 1
            for (int e = 0; e < 2; e++) {
                const uint32_t* fp = e ? &prm.sc->flag_h[(rank * 64 + lane) * FS] : &prm.sc->flag_o[(a2s * 8 + (lane & 7)) * FS];
                if (e) {
                    mbar_wait2(BAR(B_OF + 2), 0, BAR(B_OF + 3), 0);
                    if (lane == 0) st_flag(&prm.sc->flag_h[(a2s * 4 + a2j) * FS], tag);
                    __syncwarp();
                    TRW(57);
                    sleep_until(clk32() + PDELAY);
                }
                uint64_t v0 = 0, v1 = e ? 0 : tag;
                int it = 0;
                do {
                    ld_flag_if(v0, fp, (uint32_t)v0 != tag); ld_flag_if(v1, fp + 32 * FS, (uint32_t)v1 != tag);
                    if (++it > kSpinLimit) { TIMEOUT(108); break; }
                } while (__any_sync(~0u, (uint32_t)v0 != tag || (uint32_t)v1 != tag));
                const uint32_t gbase = __shfl_sync(~0u, (uint32_t)(v0 >> 32), 0);
                const uint32_t tg = gbase + (e ? DELTA : DELTAO)
                                  + __reduce_max_sync(~0u, max((int)((uint32_t)(v0 >> 32) - gbase) - e * (lane >> 2) * SOFF, e ? (int)((uint32_t)(v1 >> 32) - gbase) - 8 * SOFF : 0));
                TRW(e ? 40 : 53);
                mbar_wait(BAR(B_A1D), 0);
                if (elect_one()) {
                    if (e) {
                        asm volatile("st.async.shared::cluster.mbarrier::complete_tx::bytes.b32 [%0], %1, [%2];"
                                     :: "r"(pbar0 + (SM_TG2 - SM_BAR)), "r"(tg), "r"(pbar0 + 8u * B_GO) : "memory");
                        asm volatile("st.shared.u32 [%0], %1;" :: "r"(sb + SM_TG + 4), "r"(tg) : "memory");
                        mbar_expect(BAR(B_GO), 4);
                    } else {
                        it = 0;
                        while ((int)(gtime32() - tg) < 0 && ++it < 256) {}
                        #pragma unroll
                        for (int i = 0; i < 4; i++) bulk_g2s(sb + SM_WQ + i * 14336, &prm.sc->o[(a2s * 4 + i) * 896], 14336, BAR(B_OL + i));
                    }
                }
                __syncwarp();
            }
          }
          if (elect_one()) {
              const int h = ~warp & 1;
              constexpr uint32_t T = 57344, BO = 2 * 14336;
              const char* src1 = (const char*)&prm.sc->hn[(rank * 16 + h) * 3584 + g1j * 896];
              const char* src2 = (const char*)&prm.sc->g[(rank * 14 + h) * 3584 + g2j * 896];
              uint64_t masks = g1_on ? (h ? kSegMasks1 : kSegMasks0) : 0x80 | 0x80 << 10;
              const uint32_t bl = BAR(B_BL + h * NB);
              uint32_t s8 = (g1_on ? NB - 2 + h : h) * 8, lap = 3, tmin = 0;
              const CUtensorMap* am = &mW1;
              uint32_t ad = sb + (NPRE + h) * 8192, astep = 16384; int ac0 = h * kF + g1f * 64, ac1 = (rank * 8 + NPRE / 2) * 64;
              CAP_DECL(ti_, 0);
              #pragma unroll 1
              for (int seg = g1_on ? 0 : 3; seg < 5; seg++) {
                  const char* src = (seg < 3 ? src1 : src2) + (~seg & 1) * BO;
                  uint32_t m = (uint32_t)masks & 0x3ff;
                  masks >>= 10;
                  if (seg == 2) {
                      mbar_wait(BAR(B_PL), 0);
                      mbar_arrive_remote_if(pbar0 + 8u * B_PD, h);
                      am = &mW2; ad = sb + 8192; astep = 8192; ac0 = g2s * 64; ac1 = rank * 14 * 64;
                  } else {
                      const int gate = seg - (seg > 2);
                      mbar_wait(BAR(B_HD + gate), 0);
                      tmin = lds1(sb + SM_TG + gate * 4);
                      if (gate < 2) {
                          tmin += max((int)(lds1(gate ? sb + SM_TG2 : sb + SM_TG) - tmin), 0);
                          int it = 0;
                          while ((int)(gtime32() - tmin) < 0 && ++it < 256) {}
                          tmin = clk32();
                      }
                      tmin += h * PACE1;
                  }
                  #pragma unroll 1
                  do {
                      const uint32_t dst = sb + SM_B + s8 * 1792;
                      spin_until(tmin);
                      mbar_wait_fast(BAR(B_BE) + s8 + (lap & 1) * (NB * 8), lap >> 1 & 1);
                      if (seg) {
                          bulk_g2s(dst, src, 14336, bl + s8);
                          mbar_expect(bl + s8, 14336);
                          CAP(ti_);
                      }
                      tmin += PACE2;
                      src += 2 * T;
                      s8 += 16;
                      if (s8 >= NB * 8) { s8 -= NB * 8; lap++; }
                      if (m & 1) {
                          mbar_expect_more(bl + s8, 8192);
                          tma2d(ad, am, ac0, ac1, bl + s8);
                          ad += astep; ac1 += 64;
                      }
                      m >>= 1;
                  } while (m != 1);
                  if (seg == 0) lap = 3;
              }
          }
        } else {
          if (warp == 10) {
            mbar_wait(BAR(PFBAR), 0);
            const char* p1 = (const char*)prm.w1 + (size_t)b * 57344 + lane * 128;
            const char* p2 = (const char*)prm.w2 + (size_t)b * 57344 + lane * 128;
            if (lane < 27) asm volatile("prefetch.global.L2 [%0];" :: "l"(lane < 25 ? (const char*)prm.wo + min(b * 25 + lane, 3135) * 128
                                                                          : lane == 25 ? (const char*)prm.b1 + (b % 28) * 128 : (const char*)prm.b2 + (b & 31) * 128));
            uint32_t tnext = clk32();
            #pragma unroll 1
            for (int i = 0; i < 28; i++) {
                while ((int)(clk32() - tnext) < 0) __nanosleep(40);
                asm volatile("prefetch.global.L2 [%0];" :: "l"(i < 14 ? p1 + i * 4096 : p2 + (i - 14) * 4096));
                tnext += PFPACE;
            }
            mbar_wait(BAR(B_EP), 0);
          }
          const uint32_t tag = lds1(sb + SM_EPOCH);
          const int h = warp & 1;
          const bool lead = elect_one();
          const uint32_t wo = lane * 132, l3 = lane < 16 ? 12288 : 0;
          uint32_t base = sb + SM_WQ, bl = BAR(B_OL), bf = BAR(B_OF), m = 4, rph = 0;
          #pragma unroll 1
          for (int e = 0; e < 2; e++) {
              uint32_t s8 = h * 8;
              #pragma unroll 1
              do {
                  const uint32_t dst = base + s8 * 1792;
                  auto stale = [&]() {
                      uint32_t d;
                      asm volatile("{ .reg .b32 x, y, z, u;\n"
                                   "ld.shared.u32 x, [%1]; ld.shared.u32 y, [%1 + 4096]; ld.shared.u32 z, [%1 + 8192]; ld.shared.u32 u, [%2];\n"
                                   "lop3.b32 x, x, y, %3, 0x7e; lop3.b32 z, z, u, %3, 0x7e; lop3.b32 %0, x, z, 1, 0xa8; }"
                                   : "=r"(d) : "r"(dst + wo), "r"(dst + (wo + l3)), "r"(tag) : "memory");
                      return __any_sync(~0u, d);
                  };
                  mbar_wait_fast(bl + s8, m & 1);
                  bool bad = stale();
                  mbar_arrive_if(bf + s8, lead && !bad);
                  if (bad) {
                      const int p = 2 * __clz(m) - 2 + h;
                      RETRY_COUNT(!e ? 1 : p < 32 ? 0 : !g1_on ? 5 : p < 46 ? 2 : 6);
                      const int st = (p > 15) + (p > 31) + (p > 45), s = p - (st < 3 ? 16 * st : 46);
                      const char* src = (const char*)(!e ? &prm.sc->o[(a2s * 4 + p - 56) * 896] : st < 2 ? &prm.sc->hn[(rank * 16 + s) * 3584 + (g1j + 2 * st) * 896]
                                                                                                      : &prm.sc->g[(rank * 14 + s) * 3584 + (g2j + 2 * st - 4) * 896]);
                      int it = 0;
                      do {
                          if (++it > kSpinLimit) { TIMEOUT(111); break; }
                          const uint32_t* q = (const uint32_t*)(src + wo);
                          if (it > RELOAD1 && __any_sync(~0u, ((ld_rlx(q) ^ tag) | (ld_rlx(q + 1024) ^ tag) | (ld_rlx(q + 2048) ^ tag) | (ld_rlx(q + l3 / 4) ^ tag)) & 1)) continue;
                          if (lead) {
                              mbar_expect(BAR(B_RT + h), 14336);
                              bulk_g2s(dst, src, 14336, BAR(B_RT + h));
                          }
                          __syncwarp();
                          mbar_wait(BAR(B_RT + h), rph);
                          rph ^= 1;
                          bad = stale();
                      } while (bad);
                      mbar_arrive_if(bf + s8, lead);
                  }
                  s8 += 16;
                  if (s8 >= NB * 8) s8 -= NB * 8;
                  m >>= 1;
              } while (m != 1);
              base = sb + SM_B; bl = BAR(B_BL + h * NB); bf = BAR(B_BF); m = g1_on ? 0x4fe03f80 : 0x7f80;
          }
        }
    } else {
        asm volatile("setmaxnreg.inc.sync.aligned.u32 232;");
        asm volatile("barrier.cluster.wait.aligned;" ::: "memory");
        const int wg = warp >> 2, w = warp & 3;
        const int g = lane >> 2, t = lane & 3;
        uint32_t tag;
        __nv_bfloat16 bias1a, bias1b;
        {
            const uint64_t dw = make_desc(sb + (hg & 1) * 16, 0, true);
            uint32_t a[28][4];
            float sm[4][4] = {};
            {
                const int r = w * 16 + (lane & 15);
                const uint32_t rowa = sb + wg * 8192 + r * 128;
                #pragma unroll
                for (int k = 0; k < 28; k++) {
                    if (XW == 1 && (k & 3) == 0) mbar_wait(BAR(B_XF + (k >> 2)), 0);
                    if (XW == 2 && k == 0) mbar_wait(BAR(B_XF), 0);
                    if (XW == 2 && (k & 7) == 4) mbar_wait2(BAR(B_XF + (k >> 2)), 0, BAR(B_XF + (k >> 2) + 1), 0);
                    const uint32_t addr = rowa + (k >> 2) * 16384 + ((((k & 3) * 2 + (lane >> 4)) ^ (r & 7)) << 4);
                    uint32_t (&f)[4] = a[k];
                    asm volatile("ldmatrix.sync.aligned.m8n8.x4.shared.b16 {%0,%1,%2,%3}, [%4];"
                                 : "=r"(f[0]), "=r"(f[1]), "=r"(f[2]), "=r"(f[3]) : "r"(addr) : "memory");
                    if (XLAG == 0) mma16816(sm[k & 3], f[0], f[1], f[2], f[3], 0x3F803F80u, 0x3F803F80u);
                    else if (k >= 4) mma16816(sm[k & 3], a[k - 4][0], a[k - 4][1], a[k - 4][2], a[k - 4][3], 0x3F803F80u, 0x3F803F80u);
                }
                if (XLAG) {
                    #pragma unroll
                    for (int k = 24; k < 28; k++) mma16816(sm[k & 3], a[k][0], a[k][1], a[k][2], a[k][3], 0x3F803F80u, 0x3F803F80u);
                }
            }
            const float mean0 = ((sm[0][0] + sm[1][0]) + (sm[2][0] + sm[3][0])) * (1.f / kD);
            const float mean1 = ((sm[0][2] + sm[1][2]) + (sm[2][2] + sm[3][2])) * (1.f / kD);
            const uint32_t mb0 = pack_bf16(mean0, mean0), mb1 = pack_bf16(mean1, mean1);
            pair_arrive(B_XC);
            TR(1);
            float ak[28], av[28], aq[28];
            float ss0 = 0.f, ss1 = 0.f, ss2 = 0.f, ss3 = 0.f;
            uint32_t p0, p1;
            static_for<0, 7>([&](auto S_) {
                constexpr int s = decltype(S_)::value;
                #pragma unroll
                for (int q = 0; q < 4; q++) {
                    uint32_t (&f)[4] = a[s * 4 + q];
                    f[0] = sub_bf16x2(f[0], mb0); f[1] = sub_bf16x2(f[1], mb1);
                    f[2] = sub_bf16x2(f[2], mb0); f[3] = sub_bf16x2(f[3], mb1);
                }
                mbar_wait(BAR(B_WKVF + s), 0);
                wg_fence();
                static_for<0, 4>([&](auto Q_) {
                    constexpr int q = decltype(Q_)::value;
                    uint32_t (&f)[4] = a[s * 4 + q];
                    wgmma_rs_n56<SM_WKV + s * 16384 + q * 2048, (s | q) != 0>(ak, f[0], f[1], f[2], f[3], dw);
                    wgmma_rs_n56<SM_WKV + s * 16384 + q * 2048 + 8192, (s | q) != 0>(av, f[0], f[1], f[2], f[3], dw);
                });
                wg_commit();
                if (s == 4) { wg_wait<1>(); pair_arrive(B_KV3); }
                #pragma unroll
                for (int q = 0; q < 8; q++) {
                    const uint32_t u0 = a[s * 4 + q / 2][(q & 1) * 2], u1 = a[s * 4 + q / 2][(q & 1) * 2 + 1];
                    if (q == 0 && (VCH == 1 || (s & 1) || s == 0)) { p0 = sqr_bf16x2(u0); p1 = sqr_bf16x2(u1); }
                    else { p0 = sqa_bf16x2(u0, p0); p1 = sqa_bf16x2(u1, p1); }
                }
                if (VCH == 1 || !(s & 1)) { ss0 += bf_lo(p0); ss2 += bf_hi(p0); ss1 += bf_lo(p1); ss3 += bf_hi(p1); }
            });
            auto q_chunk = [&](auto K0_, auto K1_) {
                wg_fence();
                static_for<decltype(K0_)::value, decltype(K1_)::value>([&](auto K_) {
                    constexpr int k = decltype(K_)::value;
                    wgmma_rs_n56<SM_WQ + k * 2048, k != 0>(aq, a[k][0], a[k][1], a[k][2], a[k][3], dw);
                });
                wg_commit();
            };
            #define QCHUNK(k0, k1) q_chunk(std::integral_constant<int, k0>{}, std::integral_constant<int, k1>{})
            const float dl0 = mean0 - bf_lo(mb0), dl1 = mean1 - bf_lo(mb1);
            const float rs0 = rsq(fmaxf(quad_sum(ss0 + ss2) * (1.f / kD) - dl0 * dl0, 0.f) + kEps);
            const float rs1 = rsq(fmaxf(quad_sum(ss1 + ss3) * (1.f / kD) - dl1 * dl1, 0.f) + kEps);
            float rk[3][2];
            rk[1][0] = __shfl_sync(~0u, rs0, t * 8); rk[1][1] = __shfl_sync(~0u, rs0, t * 8 + 4);
            rk[2][0] = __shfl_sync(~0u, rs1, t * 8); rk[2][1] = __shfl_sync(~0u, rs1, t * 8 + 4);
            const uint32_t stg = sb + SM_STG + wg * 8192 + lane * 16;
            uint4* hp = (w == 3 ? &prm.sc->halo[((ti * 8 + hg) * 2 + wg) * 128] : (uint4*)(smem_raw + SM_STG + wg * 8192 + w * 2048)) + lane;
            mbar_wait2(BAR(B_EP), 0, BAR(B_WQF), 0);
            tag = lds1(sb + SM_EPOCH);
            QCHUNK(0, QC0);
            wg_wait<1>();
            reg_fence(ak); reg_fence(av);
            TR(2);
            uint32_t kf[3][7], vf[3][7];
            #pragma unroll
            for (int c = 0; c < 7; c++) {
                kf[2][c] = pack_bf16(ak[4 * c + 2], ak[4 * c + 3]);
                vf[2][c] = movm(pack_bf16(av[4 * c + 2], av[4 * c + 3]));
            }
            const uint32_t om = ~lane & 1;
            kf[2][0] = set_par(kf[2][0], om, tag); kf[2][4] = set_par(kf[2][4], om, tag);
            vf[2][1] = set_par(vf[2][1], om, tag); vf[2][5] = set_par(vf[2][5], om, tag);
            st_gen4(hp,      kf[2][0], kf[2][1], kf[2][2], kf[2][3]);
            st_gen4(hp + 32, kf[2][4], kf[2][5], kf[2][6], vf[2][0]);
            st_gen4(hp + 64, vf[2][1], vf[2][2], vf[2][3], vf[2][4]);
            st_gen4(hp + 96, vf[2][5], vf[2][6], __float_as_uint(rk[2][0]), __float_as_uint(rk[2][1]));
            pair_arrive(B_KVC);
            QCHUNK(QC0, QC1);
            #pragma unroll
            for (int c = 0; c < 7; c++) {
                kf[1][c] = pack_bf16(ak[4 * c], ak[4 * c + 1]);
                vf[1][c] = movm(pack_bf16(av[4 * c], av[4 * c + 1]));
            }
            QCHUNK(QC1, QC2);
            named_bar(1 + wg, 128);
            uint32_t* op = opaque_ptr((uint32_t*)&prm.sc->o[((ti * 2 + wg) * 56 + hg * 7) * 64] + w * 64 + lane);
            const uint32_t omk = opaque(((lane & 6) == w * 2 ? 0x11u << (lane & 1) * 8 : 0u) << (((lane >> 3) + (hg & 1)) & 3));
            uint32_t* ofl = opaque_ptr(&prm.sc->flag_o[((ti * 2 + wg) * 8 + hg) * FS]);
            QCHUNK(QC2, 28);
            #undef QCHUNK
            const bool gt0 = 2 * t > g, gt1 = 2 * t + 1 > g, no_prev = ti == 0 && w == 0;
            const float kf0 = gt0 ? rk[1][0] : rk[2][0], kf1 = gt1 ? rk[1][1] : rk[2][1];
            constexpr float kScale = 0.18898223650461362f * 1.4426950408889634f;
            const float sq0 = rs0 * kScale, sf0 = kf0 * (rs1 * kScale), sf1 = kf1 * (rs1 * kScale);
            const float NEG = -__int_as_float(0x7f800000);
            const float nb0 = gt0 && no_prev ? NEG : 0.f, nb1 = gt1 && no_prev ? NEG : 0.f;
            const uint32_t sr = stg + ((w + 3) & 3) * 2048, hbar = BAR(w == 0 ? B_HL + wg : B_EP);
            mbar_wait(BAR(B_EP), 0);
            wg_wait<0>();
            reg_fence(aq);
            warp_arrive(BAR(B_A1D));
            TR(3);
            uint32_t qf[8][2];
            #pragma unroll
            for (int c = 0; c < 7; c++) {
                qf[c + (c > 3)][0] = pack_bf16(aq[4 * c], aq[4 * c + 1]);
                qf[c + (c > 3)][1] = pack_bf16(aq[4 * c + 2], aq[4 * c + 3]);
            }
            qf[4][0] = t >= 2 ? qf[3][0] : 0u; qf[4][1] = t >= 2 ? qf[3][1] : 0u;
            qf[3][0] = t < 2 ? qf[3][0] : 0u;  qf[3][1] = t < 2 ? qf[3][1] : 0u;
            float sc[2][3][4];
            auto scores = [&](int n) {
                #pragma unroll
                for (int hd = 0; hd < 2; hd++) {
                    sc[hd][n][0] = sc[hd][n][1] = sc[hd][n][2] = sc[hd][n][3] = 0.f;
                    mma16816(sc[hd][n], qf[4 * hd][0], qf[4 * hd][1], qf[4 * hd + 1][0], qf[4 * hd + 1][1], kf[n][3 * hd], kf[n][3 * hd + 1]);
                    mma16816(sc[hd][n], qf[4 * hd + 2][0], qf[4 * hd + 2][1], qf[4 * hd + 3][0], qf[4 * hd + 3][1], kf[n][3 * hd + 2], kf[n][3 * hd + 3]);
                }
            };
            scores(1); scores(2);
            mbar_wait(hbar, 0);
            {
                const uint4 u0 = lds4(sr), u1 = lds4(sr + 512), u3 = lds4(sr + 1536), u2 = lds4(sr + 1024);
                kf[0][0] = u0.x; kf[0][1] = u0.y; kf[0][2] = u0.z; kf[0][3] = u0.w;
                kf[0][4] = u1.x; kf[0][5] = u1.y; kf[0][6] = u1.z; vf[0][0] = u1.w;
                vf[0][1] = u2.x; vf[0][2] = u2.y; vf[0][3] = u2.z; vf[0][4] = u2.w;
                vf[0][5] = u3.x; vf[0][6] = u3.y; rk[0][0] = __uint_as_float(u3.z); rk[0][1] = __uint_as_float(u3.w);
            }
            if ((tid & 127) == 0) st_flag(ofl, tag);
            TR(4);
            scores(0);
            const float ke0 = gt0 ? rk[0][0] : rk[1][0], ke1 = gt1 ? rk[0][1] : rk[1][1];
            const float se0 = ke0 * sq0, se1 = ke1 * sq0;
            uint32_t ow[7][2];
            #pragma unroll
            for (int hd = 0; hd < 2; hd++) {
                const int c0 = hd * 3;
                float (&sc_)[3][4] = sc[hd];
                const float e0 = fmaf(gt0 ? sc_[0][0] : sc_[1][0], se0, nb0), e1 = fmaf(gt1 ? sc_[0][1] : sc_[1][1], se1, nb1);
                const float f0 = (gt0 ? sc_[1][2] : sc_[2][2]) * sf0, f1 = (gt1 ? sc_[1][3] : sc_[2][3]) * sf1;
                const float me = quad_max(fmaxf(e0, e1)), mf = quad_max(fmaxf(f0, f1));
                const float p0 = ex2(e0 - me), p1 = ex2(e1 - me), r0 = ex2(f0 - mf), r1 = ex2(f1 - mf);
                const float ie = rcp(quad_sum(p0 + p1)), jf = rcp(quad_sum(r0 + r1));
                const uint32_t pp = pack_bf16(p0 * ke0 * ie, p1 * ke1 * ie), rp = pack_bf16(r0 * kf0 * jf, r1 * kf1 * jf);
                const uint32_t mk = (gt0 ? 0x0000ffffu : 0u) | (gt1 ? 0xffff0000u : 0u);
                #pragma unroll
                for (int c = 0; c < 4; c++) {
                    float o[4] = {0.f, 0.f, 0.f, 0.f};
                    mma16816(o, pp & mk, 0u, pp & ~mk, rp & mk, vf[0][c0 + c], vf[1][c0 + c]);
                    mma1688(o, 0u, rp & ~mk, vf[2][c0 + c]);
                    const uint32_t lo = pack_bf16(o[0], o[1]), hi = pack_bf16(o[2], o[3]);
                    if (hd == 1 && c == 0) { if (t >= 2) { ow[3][0] = lo; ow[3][1] = hi; } }
                    else { ow[c0 + c][0] = lo; ow[c0 + c][1] = hi; }
                }
            }
            #pragma unroll
            for (int c = 0; c < 7; c++) {
                stg1(op + c * 256,      set_par(ow[c][0], (omk >> (c & 3)) & 1, tag));
                stg1(op + c * 256 + 32, set_par(ow[c][1], (omk >> (8 + (c & 3))) & 1, tag));
            }
            TR(5);
        }
        {
            const int cg = a2j * 2 + wg;
            float acc2[28];
            mbar_wait(BAR(B_XRF), 0);
            {
                const uint32_t xa = sb + SM_XR + wg * 8192 + (w * 16 + (lane & 15)) * 128;
                #pragma unroll
                for (int c = 0; c < 4; c++) {
                    uint32_t xr[4];
                    asm volatile("ldmatrix.sync.aligned.m8n8.x4.shared.b16 {%0,%1,%2,%3}, [%4];"
                                 : "=r"(xr[0]), "=r"(xr[1]), "=r"(xr[2]), "=r"(xr[3])
                                 : "r"(xa + ((((c * 2 + wg + (lane >> 4)) ^ lane) & 7) << 4)) : "memory");
                    #pragma unroll
                    for (int e = 0; e < (c < 3 ? 4 : 2); e++) { acc2[8 * c + 2 * e] = bf_lo(xr[e]); acc2[8 * c + 2 * e + 1] = bf_hi(xr[e]); }
                }
            }
            uint32_t* spw = opaque_ptr(&prm.sc->stats[((a2s * 8 + cg) * 4 + w) * 32 + lane]);
            const uint32_t* spr = opaque_ptr(&prm.sc->stats[(a2s * 32 + w) * 32 + lane]);
            uint32_t* rp = opaque_ptr((uint32_t*)&prm.sc->rows[a2s * 64 + w * 16 + (t >> 1) * 8 + g] + (t & 1));
            const int cgs = cg ^ (a2s >> 4);
            uint32_t* np = opaque_ptr((uint32_t*)&prm.sc->hn[(a2s * 56 + cgs * 7) * 64] + w * 64 + lane);
            const uint64_t dwo = make_desc(sb + SM_WKV + wg * (28672 + 16), 0, true);
            const uint64_t doa = make_desc(sb + SM_WQ, 1024, false, 128);
            bias1a = prm.b1[g1f * 64 + w * 16 + g]; bias1b = prm.b1[g1f * 64 + w * 16 + 8 + g];
            const __nv_bfloat16 bias2 = prm.b2[ti * 128 + (w * 16 + (t >> 1) * 8 + g) * 2 + a2p];
            reg_fence(acc2);
            fence_async_smem();
            warp_arrive(BAR(B_XD));
            static_for<0, 4>([&](auto P_) {
                constexpr int P = decltype(P_)::value;
                if (P == 0) mbar_wait(BAR(B_WOF), 0);
                if (P == 2) mbar_wait2(BAR(B_OF + P), 0, BAR(B_WOF + 1), 0); else mbar_wait(BAR(B_OF + P), 0);
                if (P == 0) TR(6);
                wg_fence();
                static_for<0, 7>([&](auto K_) { constexpr int k = decltype(K_)::value;
                    wgmma_ss_n56<P * 14336 + k * 2048, (P >> 1) * 57344 + (P & 1) * 14336 + k * 2048, 0>(acc2, doa, dwo); });
                if (P) wg_commit();
                if (P == 2) { wg_wait<1>(); warp_arrive(BAR(B_OC)); }
            });
            wg_wait<0>();
            reg_fence(acc2);
            TR(7);
            float s0 = 0.f, s1 = 0.f, q0 = 0.f, q1 = 0.f;
            #pragma unroll
            for (int c = 0; c < 7; c++) {
                s0 += acc2[4 * c] + acc2[4 * c + 1];     q0 = fmaf(acc2[4 * c], acc2[4 * c], fmaf(acc2[4 * c + 1], acc2[4 * c + 1], q0));
                s1 += acc2[4 * c + 2] + acc2[4 * c + 3]; q1 = fmaf(acc2[4 * c + 2], acc2[4 * c + 2], fmaf(acc2[4 * c + 3], acc2[4 * c + 3], q1));
            }
            const bool th = t >= 2, to = t & 1;
            const float sa = (th ? s1 : s0) + __shfl_xor_sync(~0u, th ? s0 : s1, 2), qa = (th ? q1 : q0) + __shfl_xor_sync(~0u, th ? q0 : q1, 2);
            const float part = (to ? qa : sa) + __shfl_xor_sync(~0u, to ? sa : qa, 1);
            stg1(spw, set_par(__float_as_uint(part), 1u, tag));
            const uint32_t tpoll = clk32() + SDELAY;
            TR(8);
            warp_arrive(BAR(B_HD));
            uint32_t nm[2][4], us[8];
            spin_until(tpoll);
            #pragma unroll
            for (int i = 0; i < 8; i++) us[i] = ld_rlx(spr + i * 128);
            #pragma unroll
            for (int i = 0; i < 8; i++) nm[i >> 2][i & 3] = lane == ((i - (cgs & 1)) & 3) * 8 + w * 2 + (i >> 2);
            {
                int it = 0;
                while (true) {
                    uint32_t bad = 0;
                    #pragma unroll
                    for (int i = 0; i < 8; i++) bad |= us[i] ^ tag;
                    if (!__any_sync(~0u, bad & 1)) break;
                    RETRY_COUNT(3);
                    if (++it > kSpinLimit) { TIMEOUT(103); break; }
                    #pragma unroll
                    for (int i = 0; i < 8; i++) us[i] = ld_rlx(spr + i * 128);
                }
            }
            TR(9);
            const float tot = (((__uint_as_float(us[0]) + __uint_as_float(us[1])) + (__uint_as_float(us[2]) + __uint_as_float(us[3])))
                            + ((__uint_as_float(us[4]) + __uint_as_float(us[5])) + (__uint_as_float(us[6]) + __uint_as_float(us[7])))) * (1.f / kD);
            const float oth = __shfl_xor_sync(~0u, tot, 1);
            const float mean = to ? oth : tot;
            const float var = fmaxf(fmaf(-mean, mean, to ? tot : oth), 0.f);
            const float r1 = rsq(var + kEps);
            const float rra = 0.5f * r1 * rsq(fmaf(var * r1, r1, kEps)), mra = -mean * rra;
            const float rrb = __shfl_xor_sync(~0u, rra, 2), mrb = __shfl_xor_sync(~0u, mra, 2);
            const float rr0 = th ? rrb : rra, mr0 = th ? mrb : mra, rr1 = th ? rra : rrb, mr1 = th ? mra : mrb;
            #pragma unroll
            for (int c = 0; c < 7; c++) {
                stg1(np + c * 256,      set_par(pack_bf16(fmaf(acc2[4 * c], rr0, mr0), fmaf(acc2[4 * c + 1], rr0, mr0)), nm[0][c & 3], tag));
                stg1(np + c * 256 + 32, set_par(pack_bf16(fmaf(acc2[4 * c + 2], rr1, mr1), fmaf(acc2[4 * c + 3], rr1, mr1)), nm[1][c & 3], tag));
            }
            TR(10);
            if (cg == 0) stg1(rp, set_par(__float_as_uint(to ? mean + __bfloat162float(bias2) : rcp(rra)), 1u, tag));
        }
        float as[28], ac[28];
        #pragma unroll
        for (int c = 0; c < 28; c++) { ac[c] = 0.5f * __bfloat162float(c & 2 ? bias1b : bias1a); as[c] = 0.f; }
        reg_fence(as); reg_fence(ac);
        const uint32_t xch = opaque(sb + SM_XCH + w * 1792 + lane * 16);
        uint32_t peer_xch;
        asm volatile("mapa.shared::cluster.u32 %0, %1, %2;" : "=r"(peer_xch) : "r"(xch), "r"(rank ^ 1));
        auto send = [&]() {
            const uint32_t rf = pbar0 + (B_RF + warp) * 8;
            #pragma unroll
            for (int c = 0; c < 4; c++) {
                const uint32_t p0 = pack_bf16(as[8 * c], as[8 * c + 1]), p1 = pack_bf16(as[8 * c + 2], as[8 * c + 3]);
                if (c < 3) {
                    const uint32_t p2 = pack_bf16(as[8 * c + 4], as[8 * c + 5]), p3 = pack_bf16(as[8 * c + 6], as[8 * c + 7]);
                    asm volatile("st.async.shared::cluster.mbarrier::complete_tx::bytes.v4.b32 [%0], {%1,%2,%3,%4}, [%5];"
                                 :: "r"(peer_xch + c * 512), "r"(p0), "r"(p1), "r"(p2), "r"(p3), "r"(rf) : "memory");
                } else {
                    asm volatile("st.async.shared::cluster.mbarrier::complete_tx::bytes.v2.b32 [%0], {%1,%2}, [%3];"
                                 :: "r"(peer_xch + 1536 - lane * 8), "r"(p0), "r"(p1), "r"(rf) : "memory");
                }
            }
        };
        auto receive = [&](uint32_t (&pk)[14], uint32_t phase) {
            mbar_wait(BAR(B_RF + warp), phase);
            #pragma unroll
            for (int c = 0; c < 3; c++) { const uint4 u = lds4(xch + c * 512); pk[4 * c] = u.x; pk[4 * c + 1] = u.y; pk[4 * c + 2] = u.z; pk[4 * c + 3] = u.w; }
            const uint2 u = lds2(xch + 1536 - lane * 8); pk[12] = u.x; pk[13] = u.y;
        };
        const int cg2 = (g2j + 2 * wg) * 2 + (rank ^ 1), cg1 = (g1j + 2 * wg) * 2 + (rank ^ (g1f < 14));
        const int hcg = cg2 ^ (g2s >> 4), hrg = (g2s & 1) * 4 + w;
        const uint32_t* hl = (const uint32_t*)&prm.sc->hn[((g2s >> 1) * 112 + hcg * 7) * 64 + hrg * 8];
        const uint32_t* hp = hl + (g & 1) * 14336 + (g >> 1) * 4 + t;
        const uint32_t* ht = hl + (lane & 1) * 14336 + (lane >> 1) % 7 * 256 + (((lane >> 1) % 7 - (hcg & 1)) & 3) * 8 + hrg;
        const uint2* hq = &prm.sc->rows[((g2s >> 1) * 2 + (g & 1)) * 64 + hrg * 8 + (g >> 1)];
        uint2 rw[2]; uint32_t tw;
        auto load_rows = [&]() { tw = ld_rlx(ht); rw[0] = ld_rlx2(hq); rw[1] = ld_rlx2(hq + 4); };
        rw[0] = rw[1] = make_uint2(0u, 0u); tw = ~tag;
        if (!g1_on) mbar_wait(BAR(B_GD), 0);
        uint32_t* const gp1 = (uint32_t*)&prm.sc->g[(g1f * 56 + cg1 * 7) * 64] + w * 64 + lane;
        uint32_t* const gp2 = (uint32_t*)(prm.out + (size_t)(g2s * 64 + w * 16 + lane / 7) * kD + cg2 * 56) + (lane % 7) * 4;
        uint32_t gm[2][4];
        #pragma unroll
        for (int i = 0; i < 8; i++) gm[i >> 2][i & 3] = lane == ((i - (cg1 & 1)) & 3) * 8 + w * 2 + (i >> 2);
        const bool lead = elect_one();
        const uint64_t da0 = make_desc(sb, 0, true), db0 = make_desc(sb + SM_B, 128, false);
        #pragma unroll 1
        for (int ge = g1_on ? 0 : 1;; ge++) {
            if (ge) {
                int it = 0;
                while (__any_sync(~0u, ((tw ^ tag) | (rw[0].x ^ tag) | (rw[0].y ^ tag) | (rw[1].x ^ tag) | (rw[1].y ^ tag)) & 1)) {
                    if (++it > kSpinLimit) { TIMEOUT(110); break; }
                    load_rows();
                }
                uint32_t hw[14];
                #pragma unroll
                for (int c = 0; c < 14; c++) hw[c] = ld_rlx(hp + (c >> 1) * 256 + (c & 1) * 16);
                #pragma unroll
                for (int c = 0; c < 14; c++) {
                    ac[2 * c]     = fmaf(bf_lo(hw[c]), __uint_as_float(rw[c & 1].x), __uint_as_float(rw[c & 1].y));
                    ac[2 * c + 1] = fmaf(bf_hi(hw[c]), __uint_as_float(rw[c & 1].x), __uint_as_float(rw[c & 1].y));
                    as[2 * c] = as[2 * c + 1] = 0.f;
                }
                reg_fence(as); reg_fence(ac);
            }
            const int use = ge * 2 + wg;
            const uint32_t slot0 = g1_on ? (ge ? 4 : wg * ((16 + NR) % NB)) : 0;
            uint32_t ph = use == 1 ? (16 + NR) / NB & 1 : 0, rb = bar0 + slot0 * 8;
            uint64_t da = da0 + (ge ? 512 : wg * NR * 512), db = db0 + slot0 * 896;
            uint32_t prev = BAR(use == 1 ? B_BE + (15 + NR) % (2 * NB) : B_WKVF);
            const uint32_t xfree = BAR(use > (g1_on ? 0 : 2) ? B_RE + use - 1 : B_PD);
            mbar_wait(BAR(B_AF), 0);
            if (use == 1) {
                uint32_t af[NR * 4][4];
                mbar_wait(BAR(B_GO), 0);
                const uint32_t tp = lds1(sb + SM_TG + 4) + PLOFF;
                int it = 0;
                while ((int)(gtime32() - tp) < 0 && ++it < 256) __nanosleep(20);
                const uint32_t la = sb + ((lane >> 4) * 8 + (lane & 7)) * 128 + (((w * 2 + ((lane >> 3) & 1)) ^ (lane & 7)) << 4);
                #pragma unroll
                for (int k = 0; k < NR * 4; k++)
                    asm volatile("ldmatrix.sync.aligned.m8n8.x4.trans.shared.b16 {%0,%1,%2,%3}, [%4];"
                                 : "=r"(af[k][0]), "=r"(af[k][1]), "=r"(af[k][2]), "=r"(af[k][3]) : "r"(la + k * 2048) : "memory");
                __syncwarp();
                mbar_arrive_if(BAR(B_PL), lead);
                named_bar(4, 256);
                static_for<0, NR>([&](auto I_) {
                    constexpr int i = decltype(I_)::value, sl = (16 + i) % NB, o = sl * 14336;
                    mbar_wait_fast(BAR(B_BF + sl), (16 + i) / NB & 1);
                    wg_fence();
                    wgmma_rs_n112<o,       1>(as, ac, af[4 * i][0], af[4 * i][1], af[4 * i][2], af[4 * i][3], db0);
                    wgmma_rs_n112<o + 256, 1>(as, ac, af[4 * i + 1][0], af[4 * i + 1][1], af[4 * i + 1][2], af[4 * i + 1][3], db0);
                    wgmma_rs_n112<o + 512, 1>(as, ac, af[4 * i + 2][0], af[4 * i + 2][1], af[4 * i + 2][2], af[4 * i + 2][3], db0);
                    wgmma_rs_n112<o + 768, 1>(as, ac, af[4 * i + 3][0], af[4 * i + 3][1], af[4 * i + 3][2], af[4 * i + 3][3], db0);
                    wg_commit();
                    if (i) { wg_wait<1>(); mbar_arrive_if(BAR(B_BE + (15 + i) % (2 * NB)), lead); }
                });
            } else if (ge && (wg || g1_on)) named_bar(5 - wg, 256);
            mbar_wait(rb + B_BF * 8, ph);
            TR(11 + ge * 4);
            #pragma unroll 1
            for (int n = ge ? 14 : 16 - wg * NR;;) {
                wg_fence();
                wgmma_ss_n112<0,    0,   1>(as, ac, da, db);
                wgmma_ss_n112<2048, 256, 1>(as, ac, da, db);
                wgmma_ss_n112<4096, 512, 1>(as, ac, da, db);
                wgmma_ss_n112<6144, 768, 1>(as, ac, da, db);
                wg_commit();
                if (--n == 0 && use < 3) named_arrive(4 + wg, 256);
                const uint32_t cur = rb + B_BE * 8 + ph * (NB * 8);
                da += 512; db += 896; rb += 8;
                if (rb == bar0 + NB * 8) { rb = bar0; db = db0; ph ^= 1; }
                wg_wait<1>();
                mbar_arrive_if(prev, lead);
                prev = cur;
                if (n == 0) break;
                mbar_wait_fast(rb + B_BF * 8, ph);
            }
            const bool xok = mbar_test(xfree, 0);
            wg_wait<0>();
            reg_fence(as); reg_fence(ac);
            mbar_arrive_if(prev, lead);
            if (!xok) mbar_wait(xfree, 0);
            if (ge) break;
            send();
            load_rows();
            TR(12);
            uint32_t pk[14];
            receive(pk, 0);
            TR(13);
            #pragma unroll
            for (int c = 0; c < 14; c++) {
                float r[2];
                #pragma unroll
                for (int e = 0; e < 2; e++) {
                    const float u = ac[2 * c + e] + (e ? bf_hi(pk[c]) : bf_lo(pk[c]));
                    r[e] = fmaf(u, tanh_hw(u * fmaf(u * u, 8.f * 0.7978845608f * 0.044715f, 2.f * 0.7978845608f)), u);
                }
                stg1(gp1 + (c >> 1) * 256 + (c & 1) * 32, set_par(pack_bf16(r[0], r[1]), gm[c & 1][(c >> 1) & 3], tag));
            }
            named_bar(1 + wg, 128);
            if (w == 0 && lane == 0) {
                asm volatile("st.shared.u32 [%0], %1;" :: "r"(sb + SM_TG + 8 + wg * 4), "r"(clk32() + (wg ? XSPECB : XSPEC)) : "memory");
                mbar_arrive(BAR(B_GD + wg));
            }
            if (lead) mbar_expect(BAR(B_RF + warp), 1792);
            mbar_arrive_remote_if(pbar0 + (B_RE + wg) * 8, lead);
            TR(14);
        }
        uint32_t po[14], pk[14];
        if (!wg) sleep_until(clk32() + w * STAG2);
        send();
        #pragma unroll
        for (int c = 0; c < 14; c++) po[c] = opaque(pack_bf16(ac[2 * c], ac[2 * c + 1]));
        TR(16);
        receive(pk, g1_on);
        TR(17);
        #pragma unroll
        for (int c = 0; c < 14; c++) pk[c] = add_bf16x2(po[c], pk[c]);
        __syncwarp();
        const uint32_t sa = xch - lane * 16 + (lane & 15) * 112 + (lane >> 4) * 16;
        #pragma unroll
        for (int m = 0; m < 3; m++)
            asm volatile("stmatrix.sync.aligned.m8n8.x4.shared.b16 [%0], {%1,%2,%3,%4};"
                         :: "r"(sa + m * 32), "r"(pk[4 * m]), "r"(pk[4 * m + 1]), "r"(pk[4 * m + 2]), "r"(pk[4 * m + 3]) : "memory");
        asm volatile("stmatrix.sync.aligned.m8n8.x2.shared.b16 [%0], {%1,%2};" :: "r"(sa + 96), "r"(pk[12]), "r"(pk[13]) : "memory");
        __syncwarp();
        if (lane < 28) {
            #pragma unroll
            for (int i = 0; i < 4; i++) { const uint4 u = lds4(xch + i * 448); stg4(gp2 + i * 896, u.x, u.y, u.z, u.w); }
        }
        __syncwarp();
        mbar_arrive_remote_if(pbar0 + (B_RE + 2) * 8, lead && wg == 0);
        TR(18);
        if (tid == 128) TRG(62);
        if (b == 0 && tid == 128) prm.sc->epoch = tag;
    }
}

typedef CUresult (*EncodeFn)(CUtensorMap*, CUtensorMapDataType, cuuint32_t, void*, const cuuint64_t*, const cuuint64_t*,
                             const cuuint32_t*, const cuuint32_t*, CUtensorMapInterleave, CUtensorMapSwizzle,
                             CUtensorMapL2promotion, CUtensorMapFloatOOBfill);

void make_map(EncodeFn enc, CUtensorMap* m, const void* base, uint64_t cols, uint64_t rows, uint32_t box_rows) {
    cuuint64_t dims[2] = {cols, rows};
    cuuint64_t strides[1] = {cols * 2};
    cuuint32_t box[2] = {64, box_rows};
    cuuint32_t es[2] = {1, 1};
    enc(m, CU_TENSOR_MAP_DATA_TYPE_BFLOAT16, 2, const_cast<void*>(base), dims, strides, box, es, CU_TENSOR_MAP_INTERLEAVE_NONE,
        CU_TENSOR_MAP_SWIZZLE_128B, CU_TENSOR_MAP_L2_PROMOTION_L2_128B, CU_TENSOR_MAP_FLOAT_OOB_FILL_NONE);
}

}

extern "C" void kernel_launch(void* const* d_in, const int* in_sizes, int n_in, void* d_out, int out_size) {
    (void)in_sizes; (void)n_in; (void)out_size;
    void* fn = nullptr;
    cudaDriverEntryPointQueryResult qr;
    cudaGetDriverEntryPoint("cuTensorMapEncodeTiled", &fn, cudaEnableDefault, &qr);
    EncodeFn enc = (EncodeFn)fn;
    CUtensorMap mX2, mX, mWqkv, mWo, mW1, mW2;
    {
        cuuint64_t dims[3] = {kD, kS / 2, 2}, strides[2] = {4 * kD, 2 * kD};
        cuuint32_t box[3] = {64, 64, 2}, es[3] = {1, 1, 1};
        enc(&mX2, CU_TENSOR_MAP_DATA_TYPE_BFLOAT16, 3, d_in[0], dims, strides, box, es, CU_TENSOR_MAP_INTERLEAVE_NONE,
            CU_TENSOR_MAP_SWIZZLE_128B, CU_TENSOR_MAP_L2_PROMOTION_L2_128B, CU_TENSOR_MAP_FLOAT_OOB_FILL_NONE);
    }
    make_map(enc, &mX, d_in[0], 2 * kD, kS / 2, 64);
    make_map(enc, &mWqkv, d_in[1], 3 * kD, kD, 64);
    make_map(enc, &mWo, d_in[2], kD, kD, 224);
    make_map(enc, &mW1, d_in[4], 2 * kF, kS / 2, 64);
    make_map(enc, &mW2, d_in[6], kS, kF, 64);
    Params prm;
    prm.x = (const __nv_bfloat16*)d_in[0];
    prm.wqkv = (const __nv_bfloat16*)d_in[1];
    prm.wo = (const __nv_bfloat16*)d_in[2];
    prm.w1 = (const __nv_bfloat16*)d_in[4];
    prm.b1 = (const __nv_bfloat16*)d_in[5];
    prm.w2 = (const __nv_bfloat16*)d_in[6];
    prm.b2 = (const __nv_bfloat16*)d_in[7];
    prm.out = (__nv_bfloat16*)d_out;
    cudaGetSymbolAddress((void**)&prm.sc, g_scratch);
    cudaFuncSetAttribute(fused_kernel, cudaFuncAttributeMaxDynamicSharedMemorySize, SM_TOTAL);
    fused_kernel<<<128, 384, SM_TOTAL, cudaStreamPerThread>>>(prm, mX2, mX, mWqkv, mWo, mW1, mW2);
}
```

```cpp
#include <cuda_runtime.h>
#include <cuda.h>
#include <cuda_bf16.h>
#include <stdint.h>
#include <type_traits>

namespace {

constexpr int kS = 2048, kD = 448, kF = 1792;
constexpr float kEps = 1e-5f;

#define FS 32
struct Scratch {
    uint4    o[32 * 56 * 64];
    uint4    hn[32 * 56 * 64];
    uint4    g[28 * 56 * 64];
    uint4    halo[16 * 8 * 2 * 4 * 32];
    uint32_t stats[32 * 8 * 4 * 32];
    uint2    rows[32 * 64];
    uint32_t flag_o[32 * 8 * FS];
    uint32_t flag_h[32 * 4 * FS];
    uint32_t epoch;
};
__device__ __align__(1024) Scratch g_scratch;
#define TIMEOUT(code)
#define RETRY_COUNT(i)
#define CAP_DECL(n, k)
#define CAP(n)
#define CAP_SKIP(n)
#define EV(i, dep)
#define TR2(idx)
#define TR(idx)
#define TRW(idx)
#define TRG(idx)

constexpr uint32_t SM_WKV  = 114688;
constexpr uint32_t SM_XR   = 24576;
constexpr uint32_t SM_STG  = 40960;
constexpr uint32_t SM_WQ   = 57344;
constexpr uint32_t SM_XCH  = 0;
constexpr uint32_t SM_B    = 131072;
constexpr uint32_t SM_BAR  = 231424;
constexpr uint32_t SM_TOTAL = SM_BAR + 1024;
constexpr int NB = 7;
#define SH1 0
#define SH2 0
#define SH2N 5
#define SH3 0
#define NSPEC 4
#define XSPEC 500
#define C2 0
#define C3 0
#define CN2 7200
#define CN3 10900
constexpr int B_XF = 0, B_WKVF = 7, B_WQF = 14, B_XRF = 15, B_WOF = 16,
              B_XC = 18, B_KV3 = 19, B_KVC = 20,
              B_A1D = 21, B_XD = 22, B_OC = 23,
              B_BE = 24  , B_RE = B_BE + 2 * NB,
              B_PL = B_RE + 3, B_AF = B_PL + 1, B_BL = B_AF + 1  , B_OL = B_BL + 2 * NB  ,
              B_BF = B_OL + 4  , B_OF = B_BF + NB, B_RF = B_OF + 4, B_EP = B_RF + 8, B_PD = B_EP + 1, B_RT = B_PD + 1, B_HL = B_RT + 2,
              B_HD = B_HL + 2  , B_GO = B_HD + 1, B_GD = B_GO + 1, B_COUNT = B_GD + 2;
#define WEARLY 6
#define PF0 126
#define TMPF 2
#define RSTE 2
#define POLLP 1
#define PROBEP 1
#define LOADP 1
#define LOADW 64
#define NOB 0
#define AEARLY 5
#define W1PACE 400
#define W2PACE 200
#define PFPACE 230
#define PFBAR (B_XF + 6)
#define DELTA 1664
#define DELTA2 DELTA
#define BPACE 230
#define BURST 2
#define W1OFF 350
#define W2OFF 2900
#define XPACE 0
#define PSTAG 200
constexpr uint32_t SM_EPOCH = SM_BAR + B_COUNT * 8, SM_TG = SM_EPOCH + 4  , SM_TG2 = SM_TG + 16  , SM_TR = SM_BAR + 768;

#define HDELAY 0
#define QC0 4
#define QC1 10
#define QC2 16
#define HPOS 1
#define XSPECB 850
#define PACE1 120
#define PACE2 400
#define RELOAD1 1
#define VCH 1
#define SOFF 0
#define XW 1
#define XLAG 0
#define PFX 3
#define PFD 250
#define SDELAY 300
#define PDELAY 500
#define NPRE 10
#define PREPACE 0
#define AFIRST 0
#define DELTAO 928
#define NS 0
#define GCH 14
#define OCH 14
#define ICH 14
#define PACKO
#define NR 8
#define HMODE 2
#define HOFF0 (-100)
#define HOFF1 900
#define STAG1 0
#define STAG2 400
#define PLOFF (-250)
#define HSRC h
#define W1Q 3
#define APOS1 ((1ull << 4) | (1ull << 8) | (1ull << 12) | (1ull << 5) | (1ull << 9) | (1ull << 13))
#define APOS2 (0x5555555ull << 17)
constexpr uint32_t seg_mask(int h, int p0, int p1) {
    uint32_t m = 0; int n = 0;
    for (int p = p0; p < p1; p++) if ((p & 1) == h) m |= (uint32_t)(((APOS1 | APOS2) >> p) & 1) << n++;
    return m | 1u << n;
}
constexpr uint64_t seg_masks(int h) {
    return 2 | (uint64_t)seg_mask(h, 0, 16) << 10 | (uint64_t)seg_mask(h, 16, 32) << 20
             | (uint64_t)seg_mask(h, 32, 46) << 30 | (uint64_t)seg_mask(h, 46, 60) << 40;
}
constexpr uint64_t kSegMasks0 = seg_masks(0), kSegMasks1 = seg_masks(1);

constexpr int kSpinLimit = 1 << 15;
__device__ __forceinline__ bool elect_one() {
    uint32_t p;
    asm volatile("{ .reg .pred P; elect.sync _|P, 0xffffffff; selp.u32 %0, 1, 0, P; }" : "=r"(p));
    return p;
}
__device__ __forceinline__ void mbar_init(uint32_t bar, uint32_t cnt) { asm volatile("mbarrier.init.shared::cta.b64 [%0], %1;" :: "r"(bar), "r"(cnt)); }
__device__ __forceinline__ void mbar_expect(uint32_t bar, uint32_t bytes) { asm volatile("mbarrier.arrive.expect_tx.shared::cta.b64 _, [%0], %1;" :: "r"(bar), "r"(bytes) : "memory"); }
__device__ __forceinline__ void mbar_expect_more(uint32_t bar, uint32_t bytes) { asm volatile("mbarrier.expect_tx.relaxed.cta.shared::cta.b64 [%0], %1;" :: "r"(bar), "r"(bytes) : "memory"); }
__device__ __forceinline__ void mbar_arrive(uint32_t bar) { asm volatile("mbarrier.arrive.shared::cta.b64 _, [%0];" :: "r"(bar) : "memory"); }
__device__ __forceinline__ void mbar_wait(uint32_t bar, uint32_t parity) {
    uint32_t ok; int it = 0;
    do {
        asm volatile("{ .reg .pred p; mbarrier.try_wait.parity.shared::cta.b64 p, [%1], %2; selp.u32 %0, 1, 0, p; }"
                     : "=r"(ok) : "r"(bar), "r"(parity) : "memory");
        if (++it > kSpinLimit) { TIMEOUT((bar & 1023) >> 3); break; }
    } while (!ok);
}
__device__ __forceinline__ bool mbar_try(uint32_t bar, uint32_t parity) {
    uint32_t ok;
    asm volatile("{ .reg .pred p; mbarrier.try_wait.parity.shared::cta.b64 p, [%1], %2; selp.u32 %0, 1, 0, p; }" : "=r"(ok) : "r"(bar), "r"(parity) : "memory");
    return ok;
}
__device__ __forceinline__ bool mbar_test(uint32_t bar, uint32_t parity) {
    uint32_t ok;
    asm volatile("{ .reg .pred p; mbarrier.test_wait.parity.shared::cta.b64 p, [%1], %2; selp.u32 %0, 1, 0, p; }" : "=r"(ok) : "r"(bar), "r"(parity) : "memory");
    return ok;
}
__device__ __forceinline__ void mbar_wait_fast(uint32_t bar, uint32_t parity) { if (!mbar_try(bar, parity)) mbar_wait(bar, parity); }
__device__ __forceinline__ void mbar_wait2(uint32_t bar0, uint32_t par0, uint32_t bar1, uint32_t par1) {
    uint32_t ok; int it = 0;
    do {
        asm volatile("{ .reg .pred p, q; mbarrier.try_wait.parity.shared::cta.b64 p, [%1], %2;\n"
                     "mbarrier.try_wait.parity.shared::cta.b64 q, [%3], %4; and.pred p, p, q; selp.u32 %0, 1, 0, p; }"
                     : "=r"(ok) : "r"(bar0), "r"(par0), "r"(bar1), "r"(par1) : "memory");
        if (++it > kSpinLimit) { TIMEOUT((bar0 & 1023) >> 3); break; }
    } while (!ok);
}
__device__ __forceinline__ void sched_fence(uint32_t v) {
    asm volatile("{ .reg .pred p; .reg .b32 x; mov.b32 x, %0;\nL: setp.eq.u32 p, x, 0xffffffff; @p mov.u32 x, %%clock; @p bra L; }" :: "r"(v) : "memory");
}
template <int N> __device__ __forceinline__ void reg_fence(float (&d)[N]) {
    #pragma unroll
    for (int i = 0; i < N; i++) asm volatile("" : "+f"(d[i]) :: "memory");
}
__device__ __forceinline__ void mbar_wait_cluster(uint32_t bar, uint32_t parity) {
    uint32_t ok; int it = 0;
    do {
        asm volatile("{ .reg .pred p; mbarrier.try_wait.parity.acquire.cluster.shared::cta.b64 p, [%1], %2; selp.u32 %0, 1, 0, p; }"
                     : "=r"(ok) : "r"(bar), "r"(parity) : "memory");
        if (++it > kSpinLimit) { TIMEOUT((bar & 1023) >> 3); break; }
    } while (!ok);
}
__device__ __forceinline__ void mbar_arrive_if(uint32_t bar, bool pred) {
    asm volatile("{ .reg .pred p; setp.ne.u32 p, %1, 0; @p mbarrier.arrive.shared::cta.b64 _, [%0]; }" :: "r"(bar), "r"((uint32_t)pred) : "memory");
}
template <int P> __device__ __forceinline__ void tick() {
    if (P > 1) { const uint32_t t = ((uint32_t)clock() | (P - 1)) + 1; while ((int)((uint32_t)clock() - t) < 0) {} }
}
__device__ __forceinline__ void warp_arrive(uint32_t bar) { __syncwarp(); if (elect_one()) mbar_arrive(bar); }
__device__ __forceinline__ void tma2d(uint32_t dst, const CUtensorMap* m, int c0, int c1, uint32_t bar) {
    asm volatile("cp.async.bulk.tensor.2d.shared::cluster.global.mbarrier::complete_tx::bytes [%0], [%1, {%3, %4}], [%2];"
                 :: "r"(dst), "l"(m), "r"(bar), "r"(c0), "r"(c1) : "memory");
}
__device__ __forceinline__ void tma3d(uint32_t dst, const CUtensorMap* m, int c0, int c1, int c2, uint32_t bar) {
    asm volatile("cp.async.bulk.tensor.3d.shared::cluster.global.mbarrier::complete_tx::bytes [%0], [%1, {%3, %4, %5}], [%2];"
                 :: "r"(dst), "l"(m), "r"(bar), "r"(c0), "r"(c1), "r"(c2) : "memory");
}
__device__ __forceinline__ void tma2d_mc(uint32_t dst, const CUtensorMap* m, int c0, int c1, uint32_t bar) {
    asm volatile("cp.async.bulk.tensor.2d.shared::cluster.global.mbarrier::complete_tx::bytes.multicast::cluster [%0], [%1, {%3, %4}], [%2], %5;"
                 :: "r"(dst), "l"(m), "r"(bar), "r"(c0), "r"(c1), "h"((uint16_t)3) : "memory");
}
__device__ __forceinline__ void bulk_g2s_mc(uint32_t dst, const void* src, uint32_t bytes, uint32_t bar) {
    asm volatile("cp.async.bulk.shared::cluster.global.mbarrier::complete_tx::bytes.multicast::cluster [%0], [%1], %2, [%3], %4;"
                 :: "r"(dst), "l"(src), "r"(bytes), "r"(bar), "h"((uint16_t)3) : "memory");
}
__device__ __forceinline__ void mbar_arrive_remote_if(uint32_t cluster_bar, bool pred) {
    asm volatile("{ .reg .pred p; setp.ne.u32 p, %1, 0; @p mbarrier.arrive.shared::cluster.b64 _, [%0]; }" :: "r"(cluster_bar), "r"((uint32_t)pred) : "memory");
}
__device__ __forceinline__ void bulk_g2s(uint32_t dst, const void* src, uint32_t bytes, uint32_t bar) {
    asm volatile("cp.async.bulk.shared::cluster.global.mbarrier::complete_tx::bytes [%0], [%1], %2, [%3];"
                 :: "r"(dst), "l"(src), "r"(bytes), "r"(bar) : "memory");
}
__device__ __forceinline__ void wg_fence()  { asm volatile("wgmma.fence.sync.aligned;" ::: "memory"); }
__device__ __forceinline__ void wg_commit() { asm volatile("wgmma.commit_group.sync.aligned;" ::: "memory"); }
template <int N> __device__ __forceinline__ void wg_wait() { asm volatile("wgmma.wait_group.sync.aligned %0;" :: "n"(N) : "memory"); }
__device__ __forceinline__ void named_bar(int id, int n) { asm volatile("bar.sync %0, %1;" :: "r"(id), "r"(n) : "memory"); }
__device__ __forceinline__ void named_arrive(int id, int n) { asm volatile("bar.arrive %0, %1;" :: "r"(id), "r"(n) : "memory"); }
__device__ __forceinline__ bool mbar_try2(uint32_t bar0, uint32_t par0, uint32_t bar1, uint32_t par1) {
    uint32_t ok;
    asm volatile("{ .reg .pred p, q; mbarrier.test_wait.parity.shared::cta.b64 p, [%1], %2;\n"
                 "mbarrier.test_wait.parity.shared::cta.b64 q, [%3], %4; and.pred p, p, q; selp.u32 %0, 1, 0, p; }"
                 : "=r"(ok) : "r"(bar0), "r"(par0), "r"(bar1), "r"(par1) : "memory");
    return ok;
}
__device__ __forceinline__ void fence_gpu() { asm volatile("fence.release.gpu;" ::: "memory"); }
__device__ __forceinline__ void fence_async_global() { asm volatile("fence.proxy.async.global;" ::: "memory"); }
__device__ __forceinline__ void fence_async_smem() { asm volatile("fence.proxy.async.shared::cta;" ::: "memory"); }
__device__ __forceinline__ uint32_t gtime32() { uint64_t t; asm volatile("mov.u64 %0, %%globaltimer;" : "=l"(t) :: "memory"); return (uint32_t)t; }
__device__ __forceinline__ uint32_t clk32() { uint64_t t; asm volatile("mov.u64 %0, %%clock64;" : "=l"(t) :: "memory"); return (uint32_t)t; }
__device__ __forceinline__ void spin_until(uint32_t t) { while ((int)(clk32() - t) < 0) {} }
#define SLEEPNS 20
__device__ __forceinline__ void sleep_until(uint32_t t) { while ((int)(clk32() - t) < 0) { if (SLEEPNS) __nanosleep(SLEEPNS); } }
__device__ __forceinline__ void st_flag(uint32_t* p, uint32_t v) {
    const uint64_t w = ((uint64_t)gtime32() << 32) | v;
    asm volatile("st.relaxed.gpu.global.u64 [%0], %1;" :: "l"(p), "l"(w) : "memory");
}
__device__ __forceinline__ void ld_flag_if(uint64_t& v, const uint32_t* p, bool pred) {
    asm volatile("{ .reg .pred p; setp.ne.u32 p, %2, 0; @p ld.relaxed.gpu.global.u64 %0, [%1]; }" : "+l"(v) : "l"(p), "r"((uint32_t)pred) : "memory");
}
__device__ __forceinline__ uint32_t ld_acq(const uint32_t* p) { uint32_t v; asm volatile("ld.acquire.gpu.global.u32 %0, [%1];" : "=r"(v) : "l"(p) : "memory"); return v; }
__device__ __forceinline__ uint32_t ld_rlx(const uint32_t* p) { uint32_t v; asm volatile("ld.relaxed.gpu.global.u32 %0, [%1];" : "=r"(v) : "l"(p) : "memory"); return v; }
template <class T> __device__ __forceinline__ T* opaque_ptr(T* p) { asm volatile("" : "+l"(p)); return p; }
__device__ __forceinline__ uint4 ld_rlx4(const uint4* p) {
    uint4 v; asm volatile("ld.relaxed.gpu.global.v4.u32 {%0,%1,%2,%3}, [%4];" : "=r"(v.x), "=r"(v.y), "=r"(v.z), "=r"(v.w) : "l"(p) : "memory"); return v;
}
__device__ __forceinline__ void st_ll(uint4* p, uint32_t a, uint32_t b, uint32_t tag) {
    uint64_t lo = ((uint64_t)tag << 32) | a, hi = ((uint64_t)tag << 32) | b;
    asm volatile("st.relaxed.gpu.global.v2.u64 [%0], {%1,%2};" :: "l"(p), "l"(lo), "l"(hi) : "memory");
}
__device__ __forceinline__ bool ld_ll(const uint4* p, uint32_t& a, uint32_t& b, uint32_t tag) {
    uint64_t lo, hi;
    asm volatile("ld.relaxed.gpu.global.v2.u64 {%0,%1}, [%2];" : "=l"(lo), "=l"(hi) : "l"(p) : "memory");
    a = (uint32_t)lo; b = (uint32_t)hi;
    return (uint32_t)(lo >> 32) == tag && (uint32_t)(hi >> 32) == tag;
}
__device__ __forceinline__ uint2 ld_acq2(const uint2* p) {
    uint2 v; asm volatile("ld.acquire.gpu.global.v2.u32 {%0,%1}, [%2];" : "=r"(v.x), "=r"(v.y) : "l"(p) : "memory"); return v;
}
__device__ __forceinline__ uint2 ld_rlx2(const uint2* p) {
    uint2 v; asm volatile("ld.relaxed.gpu.global.v2.u32 {%0,%1}, [%2];" : "=r"(v.x), "=r"(v.y) : "l"(p) : "memory"); return v;
}
__device__ __forceinline__ void stg1(uint32_t* p, uint32_t v) { asm volatile("st.global.u32 [%0], %1;" :: "l"(p), "r"(v) : "memory"); }
__device__ __forceinline__ void stg2(void* p, uint32_t x, uint32_t y) { asm volatile("st.global.v2.u32 [%0], {%1,%2};" :: "l"(p), "r"(x), "r"(y) : "memory"); }
__device__ __forceinline__ void stg4(void* p, uint32_t x, uint32_t y, uint32_t z, uint32_t w) { asm volatile("st.global.v4.u32 [%0], {%1,%2,%3,%4};" :: "l"(p), "r"(x), "r"(y), "r"(z), "r"(w) : "memory"); }
__device__ __forceinline__ uint32_t lds1(uint32_t a) { uint32_t v; asm volatile("ld.shared.u32 %0, [%1];" : "=r"(v) : "r"(a) : "memory"); return v; }
__device__ __forceinline__ uint2 lds2(uint32_t a) { uint2 v; asm volatile("ld.shared.v2.u32 {%0,%1}, [%2];" : "=r"(v.x), "=r"(v.y) : "r"(a) : "memory"); return v; }
__device__ __forceinline__ uint32_t set_par(uint32_t v, uint32_t mask, uint32_t par) {
    uint32_t r; asm("lop3.b32 %0, %1, %2, %3, 0xb8;" : "=r"(r) : "r"(v), "r"(mask), "r"(par)); return r;
}
__device__ __forceinline__ void st_gen4(void* p, uint32_t x, uint32_t y, uint32_t z, uint32_t w) { asm volatile("st.v4.u32 [%0], {%1,%2,%3,%4};" :: "l"(p), "r"(x), "r"(y), "r"(z), "r"(w) : "memory"); }
__device__ __forceinline__ float tanh_hw(float x) { float r; asm("tanh.approx.f32 %0, %1;" : "=f"(r) : "f"(x)); return r; }
__device__ __forceinline__ bool bar_any(int id, int n, bool v) {
    uint32_t r;
    asm volatile("{ .reg .pred p, q; setp.ne.u32 p, %3, 0; bar.red.or.pred q, %1, %2, p; selp.u32 %0, 1, 0, q; }" : "=r"(r) : "r"(id), "r"(n), "r"((uint32_t)v) : "memory");
    return r;
}
__device__ __forceinline__ void sts4(uint32_t a, uint32_t x, uint32_t y, uint32_t z, uint32_t w) { asm volatile("st.shared.v4.u32 [%0], {%1,%2,%3,%4};" :: "r"(a), "r"(x), "r"(y), "r"(z), "r"(w) : "memory"); }
__device__ __forceinline__ uint4 lds4(uint32_t a) { uint4 v; asm volatile("ld.shared.v4.u32 {%0,%1,%2,%3}, [%4];" : "=r"(v.x), "=r"(v.y), "=r"(v.z), "=r"(v.w) : "r"(a) : "memory"); return v; }
__device__ __forceinline__ uint32_t pack_bf16(float lo, float hi) { uint32_t r; asm("cvt.rn.bf16x2.f32 %0, %1, %2;" : "=r"(r) : "f"(hi), "f"(lo)); return r; }
__device__ __forceinline__ float bf_lo(uint32_t v) { return __uint_as_float(v << 16); }
__device__ __forceinline__ float bf_hi(uint32_t v) { return __uint_as_float(v & 0xffff0000u); }
__device__ __forceinline__ uint32_t sub_bf16x2(uint32_t a, uint32_t b) { uint32_t r; asm volatile("sub.rn.bf16x2 %0, %1, %2;" : "=r"(r) : "r"(a), "r"(b)); return r; }
__device__ __forceinline__ uint32_t add_bf16x2(uint32_t a, uint32_t b) { uint32_t r; asm volatile("add.rn.bf16x2 %0, %1, %2;" : "=r"(r) : "r"(a), "r"(b)); return r; }
__device__ __forceinline__ uint32_t sqr_bf16x2(uint32_t a) { uint32_t r; asm volatile("mul.rn.bf16x2 %0, %1, %1;" : "=r"(r) : "r"(a)); return r; }
__device__ __forceinline__ uint32_t sqa_bf16x2(uint32_t a, uint32_t c) { uint32_t r; asm volatile("fma.rn.bf16x2 %0, %1, %1, %2;" : "=r"(r) : "r"(a), "r"(c)); return r; }
__device__ __forceinline__ uint32_t movm(uint32_t a) { uint32_t r; asm volatile("movmatrix.sync.aligned.m8n8.trans.b16 %0, %1;" : "=r"(r) : "r"(a)); return r; }
__device__ __forceinline__ float ex2(float x) { float r; asm("ex2.approx.ftz.f32 %0, %1;" : "=f"(r) : "f"(x)); return r; }
__device__ __forceinline__ float rsq(float x) { float r; asm("rsqrt.approx.ftz.f32 %0, %1;" : "=f"(r) : "f"(x)); return r; }
__device__ __forceinline__ float rcp(float x) { float r; asm("rcp.approx.ftz.f32 %0, %1;" : "=f"(r) : "f"(x)); return r; }
__device__ __forceinline__ void mma16816(float (&c)[4], uint32_t a0, uint32_t a1, uint32_t a2, uint32_t a3, uint32_t b0, uint32_t b1) {
    asm("mma.sync.aligned.m16n8k16.row.col.f32.bf16.bf16.f32 {%0,%1,%2,%3}, {%4,%5,%6,%7}, {%8,%9}, {%0,%1,%2,%3};"
        : "+f"(c[0]), "+f"(c[1]), "+f"(c[2]), "+f"(c[3]) : "r"(a0), "r"(a1), "r"(a2), "r"(a3), "r"(b0), "r"(b1));
}
__device__ __forceinline__ void mma1688(float (&c)[4], uint32_t a0, uint32_t a1, uint32_t b0) {
    asm("mma.sync.aligned.m16n8k8.row.col.f32.bf16.bf16.f32 {%0,%1,%2,%3}, {%4,%5}, {%6}, {%0,%1,%2,%3};"
        : "+f"(c[0]), "+f"(c[1]), "+f"(c[2]), "+f"(c[3]) : "r"(a0), "r"(a1), "r"(b0));
}
__device__ __forceinline__ float quad_sum(float v) { v += __shfl_xor_sync(~0u, v, 1); v += __shfl_xor_sync(~0u, v, 2); return v; }
__device__ __forceinline__ float quad_max(float v) { v = fmaxf(v, __shfl_xor_sync(~0u, v, 1)); v = fmaxf(v, __shfl_xor_sync(~0u, v, 2)); return v; }
__device__ __forceinline__ uint64_t make_desc(uint32_t addr, uint32_t lbo, bool swz, uint32_t sbo = 1024) {
    const uint32_t lo = __shfl_sync(~0u, ((addr & 0x3FFFF) >> 4) | ((lbo >> 4) << 16), 0);
    const uint32_t hi = __shfl_sync(~0u, (swz ? 0x40000000u : 0u) + (sbo >> 4) + (threadIdx.x & 31), 0);
    return ((uint64_t)hi << 32) | lo;
}
template <int I, int N, class F> __device__ __forceinline__ void static_for(F&& f) {
    if constexpr (I < N) { f(std::integral_constant<int, I>{}); static_for<I + 1, N>(f); }
}
__device__ __forceinline__ uint32_t opaque(uint32_t v) { asm volatile("" : "+r"(v)); return v; }
template <int BOFF, int SCALE_D>
__device__ __forceinline__ void wgmma_rs_n56(float (&d)[28], uint32_t a0, uint32_t a1, uint32_t a2, uint32_t a3, uint64_t db) {
    asm volatile("{ .reg .b64 db; add.s64 db, %32, %33;\n"
        "wgmma.mma_async.sync.aligned.m64n56k16.f32.bf16.bf16 "
        "{%0, %1, %2, %3, %4, %5, %6, %7, %8, %9, %10, %11, %12, %13, %14, %15, %16, %17, %18, %19, %20, %21, %22, %23, %24, %25, %26, %27}, "
        "{%28, %29, %30, %31}, db, %34, 1, 1, 1; }"
        : "+f"(d[0]), "+f"(d[1]), "+f"(d[2]), "+f"(d[3]), "+f"(d[4]), "+f"(d[5]), "+f"(d[6]), "+f"(d[7]),
        "+f"(d[8]), "+f"(d[9]), "+f"(d[10]), "+f"(d[11]), "+f"(d[12]), "+f"(d[13]), "+f"(d[14]), "+f"(d[15]),
        "+f"(d[16]), "+f"(d[17]), "+f"(d[18]), "+f"(d[19]), "+f"(d[20]), "+f"(d[21]), "+f"(d[22]), "+f"(d[23]),
        "+f"(d[24]), "+f"(d[25]), "+f"(d[26]), "+f"(d[27])
        : "r"(a0), "r"(a1), "r"(a2), "r"(a3), "l"(db), "n"(BOFF >> 4), "n"(SCALE_D));
}
template <int AOFF, int BOFF, int MMAJOR>
__device__ __forceinline__ void wgmma_ss_n56(float (&d)[28], uint64_t da, uint64_t db) {
    asm volatile("{ .reg .b64 da, db; add.s64 da, %28, %30; add.s64 db, %29, %31;\n"
        "wgmma.mma_async.sync.aligned.m64n56k16.f32.bf16.bf16 "
        "{%0, %1, %2, %3, %4, %5, %6, %7, %8, %9, %10, %11, %12, %13, %14, %15, %16, %17, %18, %19, %20, %21, %22, %23, %24, %25, %26, %27}, "
        "da, db, 1, 1, 1, %32, 1; }"
        : "+f"(d[0]), "+f"(d[1]), "+f"(d[2]), "+f"(d[3]), "+f"(d[4]), "+f"(d[5]), "+f"(d[6]), "+f"(d[7]),
        "+f"(d[8]), "+f"(d[9]), "+f"(d[10]), "+f"(d[11]), "+f"(d[12]), "+f"(d[13]), "+f"(d[14]), "+f"(d[15]),
        "+f"(d[16]), "+f"(d[17]), "+f"(d[18]), "+f"(d[19]), "+f"(d[20]), "+f"(d[21]), "+f"(d[22]), "+f"(d[23]),
        "+f"(d[24]), "+f"(d[25]), "+f"(d[26]), "+f"(d[27])
        : "l"(da), "l"(db), "n"(AOFF >> 4), "n"(BOFF >> 4), "n"(MMAJOR));
}
template <int AOFF, int BOFF, int MMAJOR>
__device__ __forceinline__ void wgmma_ss_n112(float (&d)[28], float (&e)[28], uint64_t da, uint64_t db) {
    asm volatile("{ .reg .b64 da, db; add.s64 da, %56, %58; add.s64 db, %57, %59;\n"
        "wgmma.mma_async.sync.aligned.m64n112k16.f32.bf16.bf16 "
        "{%0, %1, %2, %3, %4, %5, %6, %7, %8, %9, %10, %11, %12, %13, %14, %15, %16, %17, %18, %19, %20, %21, %22, %23, %24, %25, %26, %27, %28, %29, %30, %31, %32, %33, %34, %35, %36, %37, %38, %39, %40, %41, %42, %43, %44, %45, %46, %47, %48, %49, %50, %51, %52, %53, %54, %55}, "
        "da, db, 1, 1, 1, %60, 1; }"
        : "+f"(d[0]), "+f"(d[1]), "+f"(d[2]), "+f"(d[3]), "+f"(d[4]), "+f"(d[5]), "+f"(d[6]), "+f"(d[7]),
        "+f"(d[8]), "+f"(d[9]), "+f"(d[10]), "+f"(d[11]), "+f"(d[12]), "+f"(d[13]), "+f"(d[14]), "+f"(d[15]),
        "+f"(d[16]), "+f"(d[17]), "+f"(d[18]), "+f"(d[19]), "+f"(d[20]), "+f"(d[21]), "+f"(d[22]), "+f"(d[23]),
        "+f"(d[24]), "+f"(d[25]), "+f"(d[26]), "+f"(d[27]), "+f"(e[0]), "+f"(e[1]), "+f"(e[2]), "+f"(e[3]),
        "+f"(e[4]), "+f"(e[5]), "+f"(e[6]), "+f"(e[7]), "+f"(e[8]), "+f"(e[9]), "+f"(e[10]), "+f"(e[11]),
        "+f"(e[12]), "+f"(e[13]), "+f"(e[14]), "+f"(e[15]), "+f"(e[16]), "+f"(e[17]), "+f"(e[18]), "+f"(e[19]),
        "+f"(e[20]), "+f"(e[21]), "+f"(e[22]), "+f"(e[23]), "+f"(e[24]), "+f"(e[25]), "+f"(e[26]), "+f"(e[27])
        : "l"(da), "l"(db), "n"(AOFF >> 4), "n"(BOFF >> 4), "n"(MMAJOR));
}
template <int BOFF, int SCALE_D>
__device__ __forceinline__ void wgmma_rs_n112(float (&d)[28], float (&e)[28], uint32_t a0, uint32_t a1, uint32_t a2, uint32_t a3, uint64_t db) {
    asm volatile("{ .reg .b64 db; add.s64 db, %60, %61;\n"
        "wgmma.mma_async.sync.aligned.m64n112k16.f32.bf16.bf16 "
        "{%0, %1, %2, %3, %4, %5, %6, %7, %8, %9, %10, %11, %12, %13, %14, %15, %16, %17, %18, %19, %20, %21, %22, %23, %24, %25, %26, %27, %28, %29, %30, %31, %32, %33, %34, %35, %36, %37, %38, %39, %40, %41, %42, %43, %44, %45, %46, %47, %48, %49, %50, %51, %52, %53, %54, %55}, "
        "{%56, %57, %58, %59}, db, %62, 1, 1, 1; }"
        : "+f"(d[0]), "+f"(d[1]), "+f"(d[2]), "+f"(d[3]), "+f"(d[4]), "+f"(d[5]), "+f"(d[6]), "+f"(d[7]),
        "+f"(d[8]), "+f"(d[9]), "+f"(d[10]), "+f"(d[11]), "+f"(d[12]), "+f"(d[13]), "+f"(d[14]), "+f"(d[15]),
        "+f"(d[16]), "+f"(d[17]), "+f"(d[18]), "+f"(d[19]), "+f"(d[20]), "+f"(d[21]), "+f"(d[22]), "+f"(d[23]),
        "+f"(d[24]), "+f"(d[25]), "+f"(d[26]), "+f"(d[27]), "+f"(e[0]), "+f"(e[1]), "+f"(e[2]), "+f"(e[3]),
        "+f"(e[4]), "+f"(e[5]), "+f"(e[6]), "+f"(e[7]), "+f"(e[8]), "+f"(e[9]), "+f"(e[10]), "+f"(e[11]),
        "+f"(e[12]), "+f"(e[13]), "+f"(e[14]), "+f"(e[15]), "+f"(e[16]), "+f"(e[17]), "+f"(e[18]), "+f"(e[19]),
        "+f"(e[20]), "+f"(e[21]), "+f"(e[22]), "+f"(e[23]), "+f"(e[24]), "+f"(e[25]), "+f"(e[26]), "+f"(e[27])
        : "r"(a0), "r"(a1), "r"(a2), "r"(a3), "l"(db), "n"(BOFF >> 4), "n"(SCALE_D));
}

struct Params {
    const __nv_bfloat16 *x, *wqkv;
    Scratch* sc;
    const __nv_bfloat16 *wo, *w1, *w2, *b1, *b2;
    __nv_bfloat16* out;
};

__global__ void __cluster_dims__(2, 1, 1) __launch_bounds__(384, 1)
fused_kernel(const Params prm, const __grid_constant__ CUtensorMap mX2, const __grid_constant__ CUtensorMap mX, const __grid_constant__ CUtensorMap mWqkv,
             const __grid_constant__ CUtensorMap mWo, const __grid_constant__ CUtensorMap mW1,
             const __grid_constant__ CUtensorMap mW2)
{
    extern __shared__ __align__(1024) unsigned char smem_raw[];
    if (threadIdx.x < 126) {
        const uint32_t i = threadIdx.x, t = clk32() + (i >> 5) * PFD;
        const char* px = (const char*)prm.x + (blockIdx.x * 16 + (i & 15)) * 896 + (i >> 4) * 128;
        const char* pw = (const char*)prm.wqkv + blockIdx.x * 2688 + i * 128 + (896 - 112 * 128);
        spin_until(t);
        asm volatile("prefetch.global.L2 [%0];" :: "l"(i < 112 ? px : pw) : "memory");
    }
    if (threadIdx.x == 128) { asm volatile("prefetch.tensormap [%0];" :: "l"(&mX2) : "memory"); asm volatile("prefetch.tensormap [%0];" :: "l"(&mWqkv) : "memory"); }
    uint32_t sb = (uint32_t)__cvta_generic_to_shared(smem_raw);
    asm volatile("mov.u32 %0, %0;" : "+r"(sb));
    const uint32_t bar0 = sb + SM_BAR;
    auto BAR = [&](int i) { return bar0 + 8u * i; };

    const int tid = threadIdx.x, lane = tid & 31;
    const int warp = __shfl_sync(~0u, tid >> 5, 0);
    const int b = __shfl_sync(~0u, (int)blockIdx.x, 0);
    const int rank = b & 1;
    const int cl = (b >> 1) - 4, cq = ((cl - 32) * 37) >> 8;
    const int res = cl < 0 ? 0 : cl < 32 ? cl & 7 : cl - 31 - 7 * cq;
    const int rnd = cl < 0 ? cl + 8 : cl < 32 ? cl >> 3 : 4 + cq;
    const int hg = (res & 1) * 4 + (rnd & 3);
    const int ti = (res >> 1) * 4 + (rnd >> 2) * 2 + rank;
    const int a2p = res & 1, a2j = rnd & 3;
    const int a2s = ti * 2 + a2p;
    const bool g1_on = rnd != 7;
    const int g1j = (rnd < 6 ? rnd : res) & 1, g1f = rnd < 6 ? res * 3 + (rnd >> 1) : 24 + (res >> 1);
    const int g2j = rnd & 1, g2s = res * 4 + (rnd >> 1);
    uint32_t pbar0;
    asm volatile("mapa.shared::cluster.u32 %0, %1, %2;" : "=r"(pbar0) : "r"(bar0), "r"(rank ^ 1));
    auto pair_arrive = [&](int i) { __syncwarp(); const bool l = elect_one(); mbar_arrive_if(BAR(i), l); mbar_arrive_remote_if(pbar0 + 8u * i, l); };
    const int wcol = hg * 56 - (hg & 1) * 8;

    if (warp == 8) {
        if (elect_one()) {
            #pragma unroll
            for (int i = 0; i < B_WQF; i++) mbar_init(BAR(i), 1);
            asm volatile("fence.mbarrier_init.release.cluster;" ::: "memory");
            fence_async_smem();
            #pragma unroll
            for (int kb = 0; kb < 7; kb++) {
                tma3d(sb + kb * 16384, &mX2, kb * 64, ti * 64, 0, BAR(B_XF + kb));
                mbar_expect(BAR(B_XF + kb), 16384);
                if (kb == 0 && PFX != 3) asm volatile("prefetch.tensormap [%0];" :: "l"(&mWqkv) : "memory");
            }
        }
    } else if (warp > 8) {
        if (elect_one()) {
            if (warp == 9) {
                #pragma unroll
                for (int i = B_WQF; i < B_AF; i++) mbar_init(BAR(i), i < B_XC ? 1 : i < B_A1D ? 16 : i < B_BE ? 8 : 4);
            } else if (warp == 10) {
                #pragma unroll
                for (int i = B_AF; i < B_BF; i++) mbar_init(BAR(i), 1);
            } else {
                #pragma unroll
                for (int i = B_BF; i < B_COUNT; i++) mbar_init(BAR(i), i == B_HD ? 8 : 1);
            }
            asm volatile("fence.mbarrier_init.release.cluster;" ::: "memory");
            fence_async_smem();
        }
    }
    __syncwarp();
    __syncthreads();
    asm volatile("barrier.cluster.arrive.relaxed.aligned;" ::: "memory");
    if (tid < 256) TR(0);
    if (tid == 0) TRG(61);

    if (warp >= 8) {
        asm volatile("setmaxnreg.dec.sync.aligned.u32 40;");
        asm volatile("barrier.cluster.wait.aligned;" ::: "memory");
        auto fetch_halo = [&](int p, uint32_t tag) {
            uint4 u[4];
            #pragma unroll
            for (int c = 0; c < 4; c++) u[c] = make_uint4(0u, 0u, 0u, 0u);
            const uint4* hp = opaque_ptr(&prm.sc->halo[(((ti - 1) * 8 + hg) * 2 + p) * 128 + lane]);
            mbar_wait(BAR(B_KVC), 0);
            if (p == 0) TRW(51);
            sleep_until(clk32() + HDELAY);
            if (ti > 0) {
                int it = 0;
                do {
                    #pragma unroll
                    for (int c = 0; c < 4; c++) u[c] = ld_rlx4(hp + c * 32);
                    if (it) RETRY_COUNT(4);
                    if (++it > kSpinLimit) { TIMEOUT(101); break; }
                } while (__any_sync(~0u, ((u[0].x ^ tag) | (u[1].x ^ tag) | (u[2].x ^ tag) | (u[3].x ^ tag)) & ~lane & 1));
            }
            #pragma unroll
            for (int c = 0; c < 4; c++) sts4(sb + SM_STG + p * 8192 + 3 * 2048 + lane * 16 + c * 512, u[c].x, u[c].y, u[c].z, u[c].w);
            warp_arrive(BAR(B_HL + p));
        };
        if (warp & 1) {
            uint32_t tag;
            if (warp == 11) {
                tag = *(volatile uint32_t*)&prm.sc->epoch + 1;
            #pragma unroll 1
            for (int i = 0; i < 8; i++) prm.sc->halo[(ti * 8 + hg) * 256 + i * 32 + lane] = make_uint4(~tag, 0u, 0u, 0u);
            ((uint4*)prm.sc->stats)[(a2s * 4 + a2j) * 64 + lane] = ((uint4*)prm.sc->stats)[(a2s * 4 + a2j) * 64 + 32 + lane] = make_uint4(~tag, ~tag, ~tag, ~tag);
            prm.sc->flag_h[(a2s * 4 + a2j) * FS + lane] = 0;
            prm.sc->flag_o[(ti * 16 + hg) * FS + lane] = prm.sc->flag_o[(ti * 16 + 8 + hg) * FS + lane] = 0;
            __syncwarp();
            if (lane == 0) {
                asm volatile("st.shared.v2.u32 [%0], {%1, %2};" :: "r"(sb + SM_EPOCH), "r"(tag), "r"(gtime32()) : "memory");
                mbar_arrive(BAR(B_EP));
            }
            if (lane < 8) mbar_expect(BAR(B_RF + lane), 1792);
            __syncwarp();
            TRW(44);
            } else {
                mbar_wait(BAR(B_EP), 0);
                tag = lds1(sb + SM_EPOCH);
            }
            fetch_halo((warp >> 1) & 1, tag);
        }
        if (warp < 10) {
          auto load_slab = [&](int s, bool second) {
              if (!second) tma2d(sb + s * 8192, &mW1, (s & 1) * kF + g1f * 64, (rank * 8 + (s >> 1)) * 64, BAR(B_AF));
              else         tma2d(sb + s * 8192, &mW2, g2s * 64, (rank * 14 + s - 1) * 64, BAR(B_AF));
          };
          if (warp == 8) {
            if (elect_one()) {
                #pragma unroll 1
                for (int s = 0; s < 7; s++) {
                    mbar_expect(BAR(B_WKVF + s), 16384);
                    tma2d_mc(sb + SM_WKV + s * 16384 + rank * 8192, &mWqkv, (1 + rank) * kD + wcol, s * 64, BAR(B_WKVF + s));
                }
            }
            __syncwarp();
            mbar_wait(BAR(B_XC), 0);
            if (elect_one()) {
                asm volatile("prefetch.tensormap [%0];" :: "l"(&mX) : "memory");
                asm volatile("prefetch.tensormap [%0];" :: "l"(&mWo) : "memory");
                asm volatile("prefetch.tensormap [%0];" :: "l"(&mW1) : "memory");
                asm volatile("prefetch.tensormap [%0];" :: "l"(&mW2) : "memory");
                mbar_expect(BAR(B_AF), (g1_on ? NPRE : 14) * 8192);
                mbar_expect(BAR(B_WQF), 57344);
                #pragma unroll 1
                for (int s = rank; s < 7; s += 2) tma2d_mc(sb + SM_WQ + s * 8192, &mWqkv, wcol, s * 64, BAR(B_WQF));
                mbar_expect(BAR(B_XRF), 16384);
                tma2d(sb + SM_XR, &mX, a2p * kD + a2j * 112, ti * 64, BAR(B_XRF));
                tma2d(sb + SM_XR + 8192, &mX, a2p * kD + a2j * 112 + 48, ti * 64, BAR(B_XRF));
            }
            __syncwarp();
            #pragma unroll 1
            for (int h = 0; h < 2; h++) {
                mbar_wait(BAR(B_KV3 + h), 0);
                if (h) mbar_wait2(BAR(B_HL), 0, BAR(B_HL + 1), 0);
                if (elect_one()) {
                    mbar_expect(BAR(B_WOF + h), 57344);
                    tma2d_mc(sb + SM_WKV + h * 57344 + rank * 28672, &mWo, a2j * 112 + rank * 48, h * 224, BAR(B_WOF + h));
                    if (g1_on && h == AFIRST) { load_slab(0, false); load_slab(1, false); load_slab(2, false); }
                }
                __syncwarp();
            }
            if (g1_on) {
                mbar_wait2(BAR(B_XD), 0, BAR(B_OL + 3), 0);
                #pragma unroll 1
                for (int i = 3; i < NPRE; i++) {
                    if (i == 7) mbar_wait(BAR(B_OC), 0);
                    if (elect_one()) load_slab(i, false);
                    __syncwarp();
                }
            } else {
                mbar_arrive_if(BAR((lane < 16 ? B_BE : B_BF) + (lane & 3)), lane < 20);
                mbar_wait(BAR(B_HD), 0);
                mbar_arrive_remote_if(pbar0 + 8u * B_PD, lane == 0);
                mbar_wait(BAR(B_GO), 0);
                uint32_t tg = lds1(sb + SM_TG + 4);
                tg += max((int)(lds1(sb + SM_TG2) - tg), 0);
                int it = 0;
                while ((int)(gtime32() - tg) < 0 && ++it < 256) {}
                const uint32_t t0 = clk32();
                if (lane < 2) {
                    asm volatile("st.shared.u32 [%0], %1;" :: "r"(sb + SM_TG + 8 + lane * 4), "r"(t0 + (lane ? CN3 : CN2)) : "memory");
                    mbar_arrive(BAR(B_GD + lane));
                }
                __syncwarp();
                #pragma unroll 1
                for (int s = 1; s < 15; s++) {
                    sleep_until(t0 + W2OFF + s * W2PACE);
                    if (elect_one()) load_slab(s, true);
                    __syncwarp();
                }
            }
          } else {
            TRW(58);
            const uint32_t tag = lds1(sb + SM_EPOCH);
            if (lane < 4) mbar_expect(BAR(B_OL + lane), 14336);
            #pragma unroll 1
            for (int e = 0; e < 2; e++) {
                const uint32_t* fp = e ? &prm.sc->flag_h[(rank * 64 + lane) * FS] : &prm.sc->flag_o[(a2s * 8 + (lane & 7)) * FS];
                if (e) {
                    mbar_wait2(BAR(B_OF + 2), 0, BAR(B_OF + 3), 0);
                    if (lane == 0) st_flag(&prm.sc->flag_h[(a2s * 4 + a2j) * FS], tag);
                    __syncwarp();
                    TRW(57);
                    sleep_until(clk32() + PDELAY);
                }
                uint64_t v0 = 0, v1 = e ? 0 : tag;
                int it = 0;
                do {
                    ld_flag_if(v0, fp, (uint32_t)v0 != tag); ld_flag_if(v1, fp + 32 * FS, (uint32_t)v1 != tag);
                    if (++it > kSpinLimit) { TIMEOUT(108); break; }
                } while (__any_sync(~0u, (uint32_t)v0 != tag || (uint32_t)v1 != tag));
                const uint32_t gbase = __shfl_sync(~0u, (uint32_t)(v0 >> 32), 0);
                const uint32_t tg = gbase + (e ? DELTA : DELTAO)
                                  + __reduce_max_sync(~0u, max((int)((uint32_t)(v0 >> 32) - gbase) - e * (lane >> 2) * SOFF, e ? (int)((uint32_t)(v1 >> 32) - gbase) - 8 * SOFF : 0));
                TRW(e ? 40 : 53);
                mbar_wait(BAR(B_A1D), 0);
                if (elect_one()) {
                    if (e) {
                        asm volatile("st.async.shared::cluster.mbarrier::complete_tx::bytes.b32 [%0], %1, [%2];"
                                     :: "r"(pbar0 + (SM_TG2 - SM_BAR)), "r"(tg), "r"(pbar0 + 8u * B_GO) : "memory");
                        asm volatile("st.shared.u32 [%0], %1;" :: "r"(sb + SM_TG + 4), "r"(tg) : "memory");
                        mbar_expect(BAR(B_GO), 4);
                    } else {
                        it = 0;
                        while ((int)(gtime32() - tg) < 0 && ++it < 256) {}
                        #pragma unroll
                        for (int i = 0; i < 4; i++) bulk_g2s(sb + SM_WQ + i * 14336, &prm.sc->o[(a2s * 4 + i) * 896], 14336, BAR(B_OL + i));
                    }
                }
                __syncwarp();
            }
          }
          if (elect_one()) {
              const int h = ~warp & 1;
              constexpr uint32_t T = 57344, BO = 2 * 14336;
              const char* src1 = (const char*)&prm.sc->hn[(rank * 16 + h) * 3584 + g1j * 896];
              const char* src2 = (const char*)&prm.sc->g[(rank * 14 + h) * 3584 + g2j * 896];
              uint64_t masks = g1_on ? (h ? kSegMasks1 : kSegMasks0) : 0x80 | 0x80 << 10;
              const uint32_t bl = BAR(B_BL + h * NB);
              uint32_t s8 = (g1_on ? NB - 2 + h : 4 + h) * 8, lap = 3, tmin = 0;
              const CUtensorMap* am = &mW1;
              uint32_t ad = sb + (NPRE + h) * 8192, astep = 16384; int ac0 = h * kF + g1f * 64, ac1 = (rank * 8 + NPRE / 2) * 64;
              CAP_DECL(ti_, 0);
              #pragma unroll 1
              for (int seg = g1_on ? 0 : 3; seg < 5; seg++) {
                  const char* src = (seg < 3 ? src1 : src2) + (~seg & 1) * BO;
                  uint32_t m = (uint32_t)masks & 0x3ff;
                  masks >>= 10;
                  if (seg == 2) {
                      mbar_wait(BAR(B_PL), 0);
                      mbar_arrive_remote_if(pbar0 + 8u * B_PD, h);
                      am = &mW2; ad = sb + 8192; astep = 8192; ac0 = g2s * 64; ac1 = rank * 14 * 64;
                  } else {
                      const int gate = seg - (seg > 2);
                      mbar_wait(BAR(B_HD + gate), 0);
                      tmin = lds1(sb + SM_TG + gate * 4);
                      if (gate < 2) {
                          tmin += max((int)(lds1(gate ? sb + SM_TG2 : sb + SM_TG) - tmin), 0);
                          int it = 0;
                          while ((int)(gtime32() - tmin) < 0 && ++it < 256) {}
                          tmin = clk32();
                      }
                      tmin += h * PACE1;
                  }
                  #pragma unroll 1
                  do {
                      const uint32_t dst = sb + SM_B + s8 * 1792;
                      spin_until(tmin);
                      mbar_wait_fast(BAR(B_BE) + s8 + (lap & 1) * (NB * 8), lap >> 1 & 1);
                      if (seg) {
                          bulk_g2s(dst, src, 14336, bl + s8);
                          mbar_expect(bl + s8, 14336);
                          CAP(ti_);
                      }
                      tmin += PACE2;
                      src += 2 * T;
                      s8 += 16;
                      if (s8 >= NB * 8) { s8 -= NB * 8; lap++; }
                      if (m & 1) {
                          mbar_expect_more(bl + s8, 8192);
                          tma2d(ad, am, ac0, ac1, bl + s8);
                          ad += astep; ac1 += 64;
                      }
                      m >>= 1;
                  } while (m != 1);
                  if (seg == 0) lap = 3;
              }
          }
        } else {
          if (warp == 10) {
            mbar_wait(BAR(PFBAR), 0);
            const char* p1 = (const char*)prm.w1 + (size_t)b * 57344 + lane * 128;
            const char* p2 = (const char*)prm.w2 + (size_t)b * 57344 + lane * 128;
            if (lane < 27) asm volatile("prefetch.global.L2 [%0];" :: "l"(lane < 25 ? (const char*)prm.wo + min(b * 25 + lane, 3135) * 128
                                                                          : lane == 25 ? (const char*)prm.b1 + (b % 28) * 128 : (const char*)prm.b2 + (b & 31) * 128));
            uint32_t tnext = clk32();
            #pragma unroll 1
            for (int i = 0; i < 28; i++) {
                while ((int)(clk32() - tnext) < 0) __nanosleep(40);
                asm volatile("prefetch.global.L2 [%0];" :: "l"(i < 14 ? p1 + i * 4096 : p2 + (i - 14) * 4096));
                tnext += PFPACE;
            }
            mbar_wait(BAR(B_EP), 0);
          }
          const uint32_t tag = lds1(sb + SM_EPOCH);
          const int h = warp & 1;
          const bool lead = elect_one();
          const uint32_t wo = lane * 132, l3 = lane < 16 ? 12288 : 0;
          uint32_t base = sb + SM_WQ, bl = BAR(B_OL), bf = BAR(B_OF), m = 4, rph = 0;
          #pragma unroll 1
          for (int e = 0; e < 2; e++) {
              uint32_t s8 = (e && !g1_on ? 4 + h : h) * 8;
              #pragma unroll 1
              do {
                  const uint32_t dst = base + s8 * 1792;
                  auto stale = [&]() {
                      uint32_t d;
                      asm volatile("{ .reg .b32 x, y, z, u;\n"
                                   "ld.shared.u32 x, [%1]; ld.shared.u32 y, [%1 + 4096]; ld.shared.u32 z, [%1 + 8192]; ld.shared.u32 u, [%2];\n"
                                   "lop3.b32 x, x, y, %3, 0x7e; lop3.b32 z, z, u, %3, 0x7e; lop3.b32 %0, x, z, 1, 0xa8; }"
                                   : "=r"(d) : "r"(dst + wo), "r"(dst + (wo + l3)), "r"(tag) : "memory");
                      return __any_sync(~0u, d);
                  };
                  mbar_wait_fast(bl + s8, m & 1);
                  bool bad = stale();
                  mbar_arrive_if(bf + s8, lead && !bad);
                  if (bad) {
                      const int p = 2 * __clz(m) - 2 + h;
                      RETRY_COUNT(!e ? 1 : p < 32 ? 0 : !g1_on ? 5 : p < 46 ? 2 : 6);
                      const int st = (p > 15) + (p > 31) + (p > 45), s = p - (st < 3 ? 16 * st : 46);
                      const char* src = (const char*)(!e ? &prm.sc->o[(a2s * 4 + p - 56) * 896] : st < 2 ? &prm.sc->hn[(rank * 16 + s) * 3584 + (g1j + 2 * st) * 896]
                                                                                                      : &prm.sc->g[(rank * 14 + s) * 3584 + (g2j + 2 * st - 4) * 896]);
                      int it = 0;
                      do {
                          if (++it > kSpinLimit) { TIMEOUT(111); break; }
                          const uint32_t* q = (const uint32_t*)(src + wo);
                          if (it > RELOAD1 && __any_sync(~0u, ((ld_rlx(q) ^ tag) | (ld_rlx(q + 1024) ^ tag) | (ld_rlx(q + 2048) ^ tag) | (ld_rlx(q + l3 / 4) ^ tag)) & 1)) continue;
                          if (lead) {
                              mbar_expect(BAR(B_RT + h), 14336);
                              bulk_g2s(dst, src, 14336, BAR(B_RT + h));
                          }
                          __syncwarp();
                          mbar_wait(BAR(B_RT + h), rph);
                          rph ^= 1;
                          bad = stale();
                      } while (bad);
                      mbar_arrive_if(bf + s8, lead);
                  }
                  s8 += 16;
                  if (s8 >= NB * 8) s8 -= NB * 8;
                  m >>= 1;
              } while (m != 1);
              base = sb + SM_B; bl = BAR(B_BL + h * NB); bf = BAR(B_BF); m = g1_on ? 0x4fe03f80 : 0x7f80;
          }
        }
    } else {
        asm volatile("setmaxnreg.inc.sync.aligned.u32 232;");
        asm volatile("barrier.cluster.wait.aligned;" ::: "memory");
        const int wg = warp >> 2, w = warp & 3;
        const int g = lane >> 2, t = lane & 3;
        uint32_t tag;
        __nv_bfloat16 bias1a, bias1b;
        {
            const uint64_t dw = make_desc(sb + (hg & 1) * 16, 0, true);
            uint32_t a[28][4];
            float sm[4][4] = {};
            {
                const int r = w * 16 + (lane & 15);
                const uint32_t rowa = sb + wg * 8192 + r * 128;
                #pragma unroll
                for (int k = 0; k < 28; k++) {
                    if (XW == 1 && (k & 3) == 0) mbar_wait(BAR(B_XF + (k >> 2)), 0);
                    if (XW == 2 && k == 0) mbar_wait(BAR(B_XF), 0);
                    if (XW == 2 && (k & 7) == 4) mbar_wait2(BAR(B_XF + (k >> 2)), 0, BAR(B_XF + (k >> 2) + 1), 0);
                    const uint32_t addr = rowa + (k >> 2) * 16384 + ((((k & 3) * 2 + (lane >> 4)) ^ (r & 7)) << 4);
                    uint32_t (&f)[4] = a[k];
                    asm volatile("ldmatrix.sync.aligned.m8n8.x4.shared.b16 {%0,%1,%2,%3}, [%4];"
                                 : "=r"(f[0]), "=r"(f[1]), "=r"(f[2]), "=r"(f[3]) : "r"(addr) : "memory");
                    if (XLAG == 0) mma16816(sm[k & 3], f[0], f[1], f[2], f[3], 0x3F803F80u, 0x3F803F80u);
                    else if (k >= 4) mma16816(sm[k & 3], a[k - 4][0], a[k - 4][1], a[k - 4][2], a[k - 4][3], 0x3F803F80u, 0x3F803F80u);
                }
                if (XLAG) {
                    #pragma unroll
                    for (int k = 24; k < 28; k++) mma16816(sm[k & 3], a[k][0], a[k][1], a[k][2], a[k][3], 0x3F803F80u, 0x3F803F80u);
                }
            }
            const float mean0 = ((sm[0][0] + sm[1][0]) + (sm[2][0] + sm[3][0])) * (1.f / kD);
            const float mean1 = ((sm[0][2] + sm[1][2]) + (sm[2][2] + sm[3][2])) * (1.f / kD);
            const uint32_t mb0 = pack_bf16(mean0, mean0), mb1 = pack_bf16(mean1, mean1);
            pair_arrive(B_XC);
            TR(1);
            float ak[28], av[28], aq[28];
            float ss0 = 0.f, ss1 = 0.f, ss2 = 0.f, ss3 = 0.f;
            uint32_t p0, p1;
            static_for<0, 7>([&](auto S_) {
                constexpr int s = decltype(S_)::value;
                #pragma unroll
                for (int q = 0; q < 4; q++) {
                    uint32_t (&f)[4] = a[s * 4 + q];
                    f[0] = sub_bf16x2(f[0], mb0); f[1] = sub_bf16x2(f[1], mb1);
                    f[2] = sub_bf16x2(f[2], mb0); f[3] = sub_bf16x2(f[3], mb1);
                }
                mbar_wait(BAR(B_WKVF + s), 0);
                wg_fence();
                static_for<0, 4>([&](auto Q_) {
                    constexpr int q = decltype(Q_)::value;
                    uint32_t (&f)[4] = a[s * 4 + q];
                    wgmma_rs_n56<SM_WKV + s * 16384 + q * 2048, (s | q) != 0>(ak, f[0], f[1], f[2], f[3], dw);
                    wgmma_rs_n56<SM_WKV + s * 16384 + q * 2048 + 8192, (s | q) != 0>(av, f[0], f[1], f[2], f[3], dw);
                });
                wg_commit();
                if (s == 4) { wg_wait<1>(); pair_arrive(B_KV3); }
                #pragma unroll
                for (int q = 0; q < 8; q++) {
                    const uint32_t u0 = a[s * 4 + q / 2][(q & 1) * 2], u1 = a[s * 4 + q / 2][(q & 1) * 2 + 1];
                    if (q == 0 && (VCH == 1 || (s & 1) || s == 0)) { p0 = sqr_bf16x2(u0); p1 = sqr_bf16x2(u1); }
                    else { p0 = sqa_bf16x2(u0, p0); p1 = sqa_bf16x2(u1, p1); }
                }
                if (VCH == 1 || !(s & 1)) { ss0 += bf_lo(p0); ss2 += bf_hi(p0); ss1 += bf_lo(p1); ss3 += bf_hi(p1); }
            });
            auto q_chunk = [&](auto K0_, auto K1_) {
                wg_fence();
                static_for<decltype(K0_)::value, decltype(K1_)::value>([&](auto K_) {
                    constexpr int k = decltype(K_)::value;
                    wgmma_rs_n56<SM_WQ + k * 2048, k != 0>(aq, a[k][0], a[k][1], a[k][2], a[k][3], dw);
                });
                wg_commit();
            };
            #define QCHUNK(k0, k1) q_chunk(std::integral_constant<int, k0>{}, std::integral_constant<int, k1>{})
            const float dl0 = mean0 - bf_lo(mb0), dl1 = mean1 - bf_lo(mb1);
            const float rs0 = rsq(fmaxf(quad_sum(ss0 + ss2) * (1.f / kD) - dl0 * dl0, 0.f) + kEps);
            const float rs1 = rsq(fmaxf(quad_sum(ss1 + ss3) * (1.f / kD) - dl1 * dl1, 0.f) + kEps);
            float rk[3][2];
            rk[1][0] = __shfl_sync(~0u, rs0, t * 8); rk[1][1] = __shfl_sync(~0u, rs0, t * 8 + 4);
            rk[2][0] = __shfl_sync(~0u, rs1, t * 8); rk[2][1] = __shfl_sync(~0u, rs1, t * 8 + 4);
            const uint32_t stg = sb + SM_STG + wg * 8192 + lane * 16;
            uint4* hp = (w == 3 ? &prm.sc->halo[((ti * 8 + hg) * 2 + wg) * 128] : (uint4*)(smem_raw + SM_STG + wg * 8192 + w * 2048)) + lane;
            mbar_wait2(BAR(B_EP), 0, BAR(B_WQF), 0);
            tag = lds1(sb + SM_EPOCH);
            QCHUNK(0, QC0);
            wg_wait<1>();
            reg_fence(ak); reg_fence(av);
            TR(2);
            uint32_t kf[3][7], vf[3][7];
            #pragma unroll
            for (int c = 0; c < 7; c++) {
                kf[2][c] = pack_bf16(ak[4 * c + 2], ak[4 * c + 3]);
                vf[2][c] = movm(pack_bf16(av[4 * c + 2], av[4 * c + 3]));
            }
            const uint32_t om = ~lane & 1;
            kf[2][0] = set_par(kf[2][0], om, tag); kf[2][4] = set_par(kf[2][4], om, tag);
            vf[2][1] = set_par(vf[2][1], om, tag); vf[2][5] = set_par(vf[2][5], om, tag);
            st_gen4(hp,      kf[2][0], kf[2][1], kf[2][2], kf[2][3]);
            st_gen4(hp + 32, kf[2][4], kf[2][5], kf[2][6], vf[2][0]);
            st_gen4(hp + 64, vf[2][1], vf[2][2], vf[2][3], vf[2][4]);
            st_gen4(hp + 96, vf[2][5], vf[2][6], __float_as_uint(rk[2][0]), __float_as_uint(rk[2][1]));
            pair_arrive(B_KVC);
            QCHUNK(QC0, QC1);
            #pragma unroll
            for (int c = 0; c < 7; c++) {
                kf[1][c] = pack_bf16(ak[4 * c], ak[4 * c + 1]);
                vf[1][c] = movm(pack_bf16(av[4 * c], av[4 * c + 1]));
            }
            QCHUNK(QC1, QC2);
            named_bar(1 + wg, 128);
            uint32_t* op = opaque_ptr((uint32_t*)&prm.sc->o[((ti * 2 + wg) * 56 + hg * 7) * 64] + w * 64 + lane);
            const uint32_t omk = opaque(((lane & 6) == w * 2 ? 0x11u << (lane & 1) * 8 : 0u) << (((lane >> 3) + (hg & 1)) & 3));
            uint32_t* ofl = opaque_ptr(&prm.sc->flag_o[((ti * 2 + wg) * 8 + hg) * FS]);
            QCHUNK(QC2, 28);
            #undef QCHUNK
            const bool gt0 = 2 * t > g, gt1 = 2 * t + 1 > g, no_prev = ti == 0 && w == 0;
            const float kf0 = gt0 ? rk[1][0] : rk[2][0], kf1 = gt1 ? rk[1][1] : rk[2][1];
            constexpr float kScale = 0.18898223650461362f * 1.4426950408889634f;
            const float sq0 = rs0 * kScale, sf0 = kf0 * (rs1 * kScale), sf1 = kf1 * (rs1 * kScale);
            const float NEG = -__int_as_float(0x7f800000);
            const float nb0 = gt0 && no_prev ? NEG : 0.f, nb1 = gt1 && no_prev ? NEG : 0.f;
            const uint32_t sr = stg + ((w + 3) & 3) * 2048, hbar = BAR(w == 0 ? B_HL + wg : B_EP);
            mbar_wait(BAR(B_EP), 0);
            wg_wait<0>();
            reg_fence(aq);
            warp_arrive(BAR(B_A1D));
            TR(3);
            uint32_t qf[8][2];
            #pragma unroll
            for (int c = 0; c < 7; c++) {
                qf[c + (c > 3)][0] = pack_bf16(aq[4 * c], aq[4 * c + 1]);
                qf[c + (c > 3)][1] = pack_bf16(aq[4 * c + 2], aq[4 * c + 3]);
            }
            qf[4][0] = t >= 2 ? qf[3][0] : 0u; qf[4][1] = t >= 2 ? qf[3][1] : 0u;
            qf[3][0] = t < 2 ? qf[3][0] : 0u;  qf[3][1] = t < 2 ? qf[3][1] : 0u;
            float sc[2][3][4];
            auto scores = [&](int n) {
                #pragma unroll
                for (int hd = 0; hd < 2; hd++) {
                    sc[hd][n][0] = sc[hd][n][1] = sc[hd][n][2] = sc[hd][n][3] = 0.f;
                    mma16816(sc[hd][n], qf[4 * hd][0], qf[4 * hd][1], qf[4 * hd + 1][0], qf[4 * hd + 1][1], kf[n][3 * hd], kf[n][3 * hd + 1]);
                    mma16816(sc[hd][n], qf[4 * hd + 2][0], qf[4 * hd + 2][1], qf[4 * hd + 3][0], qf[4 * hd + 3][1], kf[n][3 * hd + 2], kf[n][3 * hd + 3]);
                }
            };
            scores(1); scores(2);
            mbar_wait(hbar, 0);
            {
                const uint4 u0 = lds4(sr), u1 = lds4(sr + 512), u3 = lds4(sr + 1536), u2 = lds4(sr + 1024);
                kf[0][0] = u0.x; kf[0][1] = u0.y; kf[0][2] = u0.z; kf[0][3] = u0.w;
                kf[0][4] = u1.x; kf[0][5] = u1.y; kf[0][6] = u1.z; vf[0][0] = u1.w;
                vf[0][1] = u2.x; vf[0][2] = u2.y; vf[0][3] = u2.z; vf[0][4] = u2.w;
                vf[0][5] = u3.x; vf[0][6] = u3.y; rk[0][0] = __uint_as_float(u3.z); rk[0][1] = __uint_as_float(u3.w);
            }
            if ((tid & 127) == 0) st_flag(ofl, tag);
            TR(4);
            scores(0);
            const float ke0 = gt0 ? rk[0][0] : rk[1][0], ke1 = gt1 ? rk[0][1] : rk[1][1];
            const float se0 = ke0 * sq0, se1 = ke1 * sq0;
            uint32_t ow[7][2];
            #pragma unroll
            for (int hd = 0; hd < 2; hd++) {
                const int c0 = hd * 3;
                float (&sc_)[3][4] = sc[hd];
                const float e0 = fmaf(gt0 ? sc_[0][0] : sc_[1][0], se0, nb0), e1 = fmaf(gt1 ? sc_[0][1] : sc_[1][1], se1, nb1);
                const float f0 = (gt0 ? sc_[1][2] : sc_[2][2]) * sf0, f1 = (gt1 ? sc_[1][3] : sc_[2][3]) * sf1;
                const float me = quad_max(fmaxf(e0, e1)), mf = quad_max(fmaxf(f0, f1));
                const float p0 = ex2(e0 - me), p1 = ex2(e1 - me), r0 = ex2(f0 - mf), r1 = ex2(f1 - mf);
                const float ie = rcp(quad_sum(p0 + p1)), jf = rcp(quad_sum(r0 + r1));
                const uint32_t pp = pack_bf16(p0 * ke0 * ie, p1 * ke1 * ie), rp = pack_bf16(r0 * kf0 * jf, r1 * kf1 * jf);
                const uint32_t mk = (gt0 ? 0x0000ffffu : 0u) | (gt1 ? 0xffff0000u : 0u);
                #pragma unroll
                for (int c = 0; c < 4; c++) {
                    float o[4] = {0.f, 0.f, 0.f, 0.f};
                    mma16816(o, pp & mk, 0u, pp & ~mk, rp & mk, vf[0][c0 + c], vf[1][c0 + c]);
                    mma1688(o, 0u, rp & ~mk, vf[2][c0 + c]);
                    const uint32_t lo = pack_bf16(o[0], o[1]), hi = pack_bf16(o[2], o[3]);
                    if (hd == 1 && c == 0) { if (t >= 2) { ow[3][0] = lo; ow[3][1] = hi; } }
                    else { ow[c0 + c][0] = lo; ow[c0 + c][1] = hi; }
                }
            }
            #pragma unroll
            for (int c = 0; c < 7; c++) {
                stg1(op + c * 256,      set_par(ow[c][0], (omk >> (c & 3)) & 1, tag));
                stg1(op + c * 256 + 32, set_par(ow[c][1], (omk >> (8 + (c & 3))) & 1, tag));
            }
            TR(5);
        }
        {
            const int cg = a2j * 2 + wg;
            float acc2[28];
            mbar_wait(BAR(B_XRF), 0);
            {
                const uint32_t xa = sb + SM_XR + wg * 8192 + (w * 16 + (lane & 15)) * 128;
                #pragma unroll
                for (int c = 0; c < 4; c++) {
                    uint32_t xr[4];
                    asm volatile("ldmatrix.sync.aligned.m8n8.x4.shared.b16 {%0,%1,%2,%3}, [%4];"
                                 : "=r"(xr[0]), "=r"(xr[1]), "=r"(xr[2]), "=r"(xr[3])
                                 : "r"(xa + ((((c * 2 + wg + (lane >> 4)) ^ lane) & 7) << 4)) : "memory");
                    #pragma unroll
                    for (int e = 0; e < (c < 3 ? 4 : 2); e++) { acc2[8 * c + 2 * e] = bf_lo(xr[e]); acc2[8 * c + 2 * e + 1] = bf_hi(xr[e]); }
                }
            }
            uint32_t* spw = opaque_ptr(&prm.sc->stats[((a2s * 8 + cg) * 4 + w) * 32 + lane]);
            const uint32_t* spr = opaque_ptr(&prm.sc->stats[(a2s * 32 + w) * 32 + lane]);
            uint32_t* rp = opaque_ptr((uint32_t*)&prm.sc->rows[a2s * 64 + w * 16 + (t >> 1) * 8 + g] + (t & 1));
            const int cgs = cg ^ (a2s >> 4);
            uint32_t* np = opaque_ptr((uint32_t*)&prm.sc->hn[(a2s * 56 + cgs * 7) * 64] + w * 64 + lane);
            const uint64_t dwo = make_desc(sb + SM_WKV + wg * (28672 + 16), 0, true);
            const uint64_t doa = make_desc(sb + SM_WQ, 1024, false, 128);
            bias1a = prm.b1[g1f * 64 + w * 16 + g]; bias1b = prm.b1[g1f * 64 + w * 16 + 8 + g];
            const __nv_bfloat16 bias2 = prm.b2[ti * 128 + (w * 16 + (t >> 1) * 8 + g) * 2 + a2p];
            reg_fence(acc2);
            fence_async_smem();
            warp_arrive(BAR(B_XD));
            static_for<0, 4>([&](auto P_) {
                constexpr int P = decltype(P_)::value;
                if (P == 0) mbar_wait(BAR(B_WOF), 0);
                if (P == 2) mbar_wait2(BAR(B_OF + P), 0, BAR(B_WOF + 1), 0); else mbar_wait(BAR(B_OF + P), 0);
                if (P == 0) TR(6);
                wg_fence();
                static_for<0, 7>([&](auto K_) { constexpr int k = decltype(K_)::value;
                    wgmma_ss_n56<P * 14336 + k * 2048, (P >> 1) * 57344 + (P & 1) * 14336 + k * 2048, 0>(acc2, doa, dwo); });
                if (P) wg_commit();
                if (P == 2) { wg_wait<1>(); warp_arrive(BAR(B_OC)); }
            });
            wg_wait<0>();
            reg_fence(acc2);
            TR(7);
            float s0 = 0.f, s1 = 0.f, q0 = 0.f, q1 = 0.f;
            #pragma unroll
            for (int c = 0; c < 7; c++) {
                s0 += acc2[4 * c] + acc2[4 * c + 1];     q0 = fmaf(acc2[4 * c], acc2[4 * c], fmaf(acc2[4 * c + 1], acc2[4 * c + 1], q0));
                s1 += acc2[4 * c + 2] + acc2[4 * c + 3]; q1 = fmaf(acc2[4 * c + 2], acc2[4 * c + 2], fmaf(acc2[4 * c + 3], acc2[4 * c + 3], q1));
            }
            const bool th = t >= 2, to = t & 1;
            const float sa = (th ? s1 : s0) + __shfl_xor_sync(~0u, th ? s0 : s1, 2), qa = (th ? q1 : q0) + __shfl_xor_sync(~0u, th ? q0 : q1, 2);
            const float part = (to ? qa : sa) + __shfl_xor_sync(~0u, to ? sa : qa, 1);
            stg1(spw, set_par(__float_as_uint(part), 1u, tag));
            const uint32_t tpoll = clk32() + SDELAY;
            TR(8);
            warp_arrive(BAR(B_HD));
            uint32_t nm[2][4], us[8];
            spin_until(tpoll);
            #pragma unroll
            for (int i = 0; i < 8; i++) us[i] = ld_rlx(spr + i * 128);
            #pragma unroll
            for (int i = 0; i < 8; i++) nm[i >> 2][i & 3] = lane == ((i - (cgs & 1)) & 3) * 8 + w * 2 + (i >> 2);
            {
                int it = 0;
                while (true) {
                    uint32_t bad = 0;
                    #pragma unroll
                    for (int i = 0; i < 8; i++) bad |= us[i] ^ tag;
                    if (!__any_sync(~0u, bad & 1)) break;
                    RETRY_COUNT(3);
                    if (++it > kSpinLimit) { TIMEOUT(103); break; }
                    #pragma unroll
                    for (int i = 0; i < 8; i++) us[i] = ld_rlx(spr + i * 128);
                }
            }
            TR(9);
            const float tot = (((__uint_as_float(us[0]) + __uint_as_float(us[1])) + (__uint_as_float(us[2]) + __uint_as_float(us[3])))
                            + ((__uint_as_float(us[4]) + __uint_as_float(us[5])) + (__uint_as_float(us[6]) + __uint_as_float(us[7])))) * (1.f / kD);
            const float oth = __shfl_xor_sync(~0u, tot, 1);
            const float mean = to ? oth : tot;
            const float var = fmaxf(fmaf(-mean, mean, to ? tot : oth), 0.f);
            const float r1 = rsq(var + kEps);
            const float rra = 0.5f * r1 * rsq(fmaf(var * r1, r1, kEps)), mra = -mean * rra;
            const float rrb = __shfl_xor_sync(~0u, rra, 2), mrb = __shfl_xor_sync(~0u, mra, 2);
            const float rr0 = th ? rrb : rra, mr0 = th ? mrb : mra, rr1 = th ? rra : rrb, mr1 = th ? mra : mrb;
            #pragma unroll
            for (int c = 0; c < 7; c++) {
                stg1(np + c * 256,      set_par(pack_bf16(fmaf(acc2[4 * c], rr0, mr0), fmaf(acc2[4 * c + 1], rr0, mr0)), nm[0][c & 3], tag));
                stg1(np + c * 256 + 32, set_par(pack_bf16(fmaf(acc2[4 * c + 2], rr1, mr1), fmaf(acc2[4 * c + 3], rr1, mr1)), nm[1][c & 3], tag));
            }
            TR(10);
            if (cg == 0) stg1(rp, set_par(__float_as_uint(to ? mean + __bfloat162float(bias2) : rcp(rra)), 1u, tag));
        }
        float as[28], ac[28];
        #pragma unroll
        for (int c = 0; c < 28; c++) { ac[c] = 0.5f * __bfloat162float(c & 2 ? bias1b : bias1a); as[c] = 0.f; }
        reg_fence(as); reg_fence(ac);
        const uint32_t xch = opaque(sb + SM_XCH + w * 1792 + lane * 16);
        uint32_t peer_xch;
        asm volatile("mapa.shared::cluster.u32 %0, %1, %2;" : "=r"(peer_xch) : "r"(xch), "r"(rank ^ 1));
        auto send = [&]() {
            const uint32_t rf = pbar0 + (B_RF + warp) * 8;
            #pragma unroll
            for (int c = 0; c < 4; c++) {
                const uint32_t p0 = pack_bf16(as[8 * c], as[8 * c + 1]), p1 = pack_bf16(as[8 * c + 2], as[8 * c + 3]);
                if (c < 3) {
                    const uint32_t p2 = pack_bf16(as[8 * c + 4], as[8 * c + 5]), p3 = pack_bf16(as[8 * c + 6], as[8 * c + 7]);
                    asm volatile("st.async.shared::cluster.mbarrier::complete_tx::bytes.v4.b32 [%0], {%1,%2,%3,%4}, [%5];"
                                 :: "r"(peer_xch + c * 512), "r"(p0), "r"(p1), "r"(p2), "r"(p3), "r"(rf) : "memory");
                } else {
                    asm volatile("st.async.shared::cluster.mbarrier::complete_tx::bytes.v2.b32 [%0], {%1,%2}, [%3];"
                                 :: "r"(peer_xch + 1536 - lane * 8), "r"(p0), "r"(p1), "r"(rf) : "memory");
                }
            }
        };
        auto receive = [&](uint32_t (&pk)[14], uint32_t phase) {
            mbar_wait(BAR(B_RF + warp), phase);
            #pragma unroll
            for (int c = 0; c < 3; c++) { const uint4 u = lds4(xch + c * 512); pk[4 * c] = u.x; pk[4 * c + 1] = u.y; pk[4 * c + 2] = u.z; pk[4 * c + 3] = u.w; }
            const uint2 u = lds2(xch + 1536 - lane * 8); pk[12] = u.x; pk[13] = u.y;
        };
        const int cg2 = (g2j + 2 * wg) * 2 + (rank ^ 1), cg1 = (g1j + 2 * wg) * 2 + (rank ^ (g1f < 14));
        const int hcg = cg2 ^ (g2s >> 4), hrg = (g2s & 1) * 4 + w;
        const uint32_t* hl = (const uint32_t*)&prm.sc->hn[((g2s >> 1) * 112 + hcg * 7) * 64 + hrg * 8];
        const uint32_t* hp = hl + (g & 1) * 14336 + (g >> 1) * 4 + t;
        const uint32_t* ht = hl + (lane & 1) * 14336 + (lane >> 1) % 7 * 256 + (((lane >> 1) % 7 - (hcg & 1)) & 3) * 8 + hrg;
        const uint2* hq = &prm.sc->rows[((g2s >> 1) * 2 + (g & 1)) * 64 + hrg * 8 + (g >> 1)];
        uint2 rw[2]; uint32_t tw;
        auto load_rows = [&]() { tw = ld_rlx(ht); rw[0] = ld_rlx2(hq); rw[1] = ld_rlx2(hq + 4); };
        rw[0] = rw[1] = make_uint2(0u, 0u); tw = ~tag;
        if (!g1_on) mbar_wait(BAR(B_GD), 0);
        uint32_t* const gp1 = (uint32_t*)&prm.sc->g[(g1f * 56 + cg1 * 7) * 64] + w * 64 + lane;
        uint32_t* const gp2 = (uint32_t*)(prm.out + (size_t)(g2s * 64 + w * 16 + lane / 7) * kD + cg2 * 56) + (lane % 7) * 4;
        uint32_t gm[2][4];
        #pragma unroll
        for (int i = 0; i < 8; i++) gm[i >> 2][i & 3] = lane == ((i - (cg1 & 1)) & 3) * 8 + w * 2 + (i >> 2);
        const bool lead = elect_one();
        const uint64_t da0 = make_desc(sb, 0, true), db0 = make_desc(sb + SM_B, 128, false);
        #pragma unroll 1
        for (int ge = g1_on ? 0 : 1;; ge++) {
            if (ge) {
                int it = 0;
                while (__any_sync(~0u, ((tw ^ tag) | (rw[0].x ^ tag) | (rw[0].y ^ tag) | (rw[1].x ^ tag) | (rw[1].y ^ tag)) & 1)) {
                    if (++it > kSpinLimit) { TIMEOUT(110); break; }
                    load_rows();
                }
                uint32_t hw[14];
                #pragma unroll
                for (int c = 0; c < 14; c++) hw[c] = ld_rlx(hp + (c >> 1) * 256 + (c & 1) * 16);
                #pragma unroll
                for (int c = 0; c < 14; c++) {
                    ac[2 * c]     = fmaf(bf_lo(hw[c]), __uint_as_float(rw[c & 1].x), __uint_as_float(rw[c & 1].y));
                    ac[2 * c + 1] = fmaf(bf_hi(hw[c]), __uint_as_float(rw[c & 1].x), __uint_as_float(rw[c & 1].y));
                    as[2 * c] = as[2 * c + 1] = 0.f;
                }
                reg_fence(as); reg_fence(ac);
            }
            const int use = ge * 2 + wg;
            int entry = ge ? 0 : 2 - wg;
            uint64_t da = da0 + (ge ? 1 : wg ? NR - 6 : -10) * 512;
            bool rel = lead && use == 1;
            const uint32_t xfree = BAR(use > (g1_on ? 0 : 2) ? B_RE + use - 1 : B_PD);
            mbar_wait(BAR(B_AF), 0);
            if (use == 1) {
                uint32_t af[NR * 4][4];
                mbar_wait(BAR(B_GO), 0);
                const uint32_t tp = lds1(sb + SM_TG + 4) + PLOFF;
                int it = 0;
                while ((int)(gtime32() - tp) < 0 && ++it < 256) __nanosleep(20);
                const uint32_t la = sb + ((lane >> 4) * 8 + (lane & 7)) * 128 + (((w * 2 + ((lane >> 3) & 1)) ^ (lane & 7)) << 4);
                #pragma unroll
                for (int k = 0; k < NR * 4; k++)
                    asm volatile("ldmatrix.sync.aligned.m8n8.x4.trans.shared.b16 {%0,%1,%2,%3}, [%4];"
                                 : "=r"(af[k][0]), "=r"(af[k][1]), "=r"(af[k][2]), "=r"(af[k][3]) : "r"(la + k * 2048) : "memory");
                __syncwarp();
                mbar_arrive_if(BAR(B_PL), lead);
                named_bar(4, 256);
                static_for<0, NR>([&](auto I_) {
                    constexpr int i = decltype(I_)::value, sl = (16 + i) % NB, o = sl * 14336;
                    mbar_wait_fast(BAR(B_BF + sl), (16 + i) / NB & 1);
                    wg_fence();
                    wgmma_rs_n112<o,       1>(as, ac, af[4 * i][0], af[4 * i][1], af[4 * i][2], af[4 * i][3], db0);
                    wgmma_rs_n112<o + 256, 1>(as, ac, af[4 * i + 1][0], af[4 * i + 1][1], af[4 * i + 1][2], af[4 * i + 1][3], db0);
                    wgmma_rs_n112<o + 512, 1>(as, ac, af[4 * i + 2][0], af[4 * i + 2][1], af[4 * i + 2][2], af[4 * i + 2][3], db0);
                    wgmma_rs_n112<o + 768, 1>(as, ac, af[4 * i + 3][0], af[4 * i + 3][1], af[4 * i + 3][2], af[4 * i + 3][3], db0);
                    wg_commit();
                    if (i) { wg_wait<1>(); mbar_arrive_if(BAR(B_BE + (15 + i) % (2 * NB)), lead); }
                });
            } else if (ge && (wg || g1_on)) named_bar(5 - wg, 256);
            TR(11 + ge * 4);
            auto step = [&](auto I_) {
                constexpr int i = decltype(I_)::value, sl = (4 + i) % NB, ao = i * 8192, bo = sl * 14336;
                mbar_wait_fast(BAR(B_BF + sl), (4 + i) / NB & 1);
                wg_fence();
                wgmma_ss_n112<ao,        bo,       1>(as, ac, da, db0);
                wgmma_ss_n112<ao + 2048, bo + 256, 1>(as, ac, da, db0);
                wgmma_ss_n112<ao + 4096, bo + 512, 1>(as, ac, da, db0);
                wgmma_ss_n112<ao + 6144, bo + 768, 1>(as, ac, da, db0);
                wg_commit();
                if (i == 11 && entry < 0) named_arrive(4, 256);
                if (i == 13 && (use == 1 || use == 2)) named_arrive(4 + wg, 256);
                wg_wait<1>();
                mbar_arrive_if(BAR(B_BE + (3 + i) % (2 * NB)), rel);
                rel = lead;
            };
            #pragma unroll 1
            while (true) {
                if (entry < 1) static_for<0, 6>(step);
                if (entry < 2) static_for<6, 10>(step);
                static_for<10, 12>(step);
                if (entry < 0) break;
                static_for<12, 14>(step);
                if (entry < 2) break;
                entry = -1; da += 14 * 512;
            }
            const uint32_t prev = BAR(B_BE + (use ? 3 : 1));
            const bool xok = mbar_test(xfree, 0);
            wg_wait<0>();
            reg_fence(as); reg_fence(ac);
            mbar_arrive_if(prev, lead);
            if (!xok) mbar_wait(xfree, 0);
            if (ge) break;
            send();
            load_rows();
            TR(12);
            uint32_t pk[14];
            receive(pk, 0);
            TR(13);
            #pragma unroll
            for (int c = 0; c < 14; c++) {
                float r[2];
                #pragma unroll
                for (int e = 0; e < 2; e++) {
                    const float u = ac[2 * c + e] + (e ? bf_hi(pk[c]) : bf_lo(pk[c]));
                    r[e] = fmaf(u, tanh_hw(u * fmaf(u * u, 8.f * 0.7978845608f * 0.044715f, 2.f * 0.7978845608f)), u);
                }
                stg1(gp1 + (c >> 1) * 256 + (c & 1) * 32, set_par(pack_bf16(r[0], r[1]), gm[c & 1][(c >> 1) & 3], tag));
            }
            named_bar(1 + wg, 128);
            if (w == 0 && lane == 0) {
                asm volatile("st.shared.u32 [%0], %1;" :: "r"(sb + SM_TG + 8 + wg * 4), "r"(clk32() + (wg ? XSPECB : XSPEC)) : "memory");
                mbar_arrive(BAR(B_GD + wg));
            }
            if (lead) mbar_expect(BAR(B_RF + warp), 1792);
            mbar_arrive_remote_if(pbar0 + (B_RE + wg) * 8, lead);
            TR(14);
        }
        uint32_t po[14], pk[14];
        if (!wg) sleep_until(clk32() + w * STAG2);
        send();
        #pragma unroll
        for (int c = 0; c < 14; c++) po[c] = opaque(pack_bf16(ac[2 * c], ac[2 * c + 1]));
        TR(16);
        receive(pk, g1_on);
        TR(17);
        #pragma unroll
        for (int c = 0; c < 14; c++) pk[c] = add_bf16x2(po[c], pk[c]);
        __syncwarp();
        const uint32_t sa = xch - lane * 16 + (lane & 15) * 112 + (lane >> 4) * 16;
        #pragma unroll
        for (int m = 0; m < 3; m++)
            asm volatile("stmatrix.sync.aligned.m8n8.x4.shared.b16 [%0], {%1,%2,%3,%4};"
                         :: "r"(sa + m * 32), "r"(pk[4 * m]), "r"(pk[4 * m + 1]), "r"(pk[4 * m + 2]), "r"(pk[4 * m + 3]) : "memory");
        asm volatile("stmatrix.sync.aligned.m8n8.x2.shared.b16 [%0], {%1,%2};" :: "r"(sa + 96), "r"(pk[12]), "r"(pk[13]) : "memory");
        __syncwarp();
        if (lane < 28) {
            #pragma unroll
            for (int i = 0; i < 4; i++) { const uint4 u = lds4(xch + i * 448); stg4(gp2 + i * 896, u.x, u.y, u.z, u.w); }
        }
        __syncwarp();
        mbar_arrive_remote_if(pbar0 + (B_RE + 2) * 8, lead && wg == 0);
        TR(18);
        if (tid == 128) TRG(62);
        if (b == 0 && tid == 128) prm.sc->epoch = tag;
    }
}

typedef CUresult (*EncodeFn)(CUtensorMap*, CUtensorMapDataType, cuuint32_t, void*, const cuuint64_t*, const cuuint64_t*,
                             const cuuint32_t*, const cuuint32_t*, CUtensorMapInterleave, CUtensorMapSwizzle,
                             CUtensorMapL2promotion, CUtensorMapFloatOOBfill);

void make_map(EncodeFn enc, CUtensorMap* m, const void* base, uint64_t cols, uint64_t rows, uint32_t box_rows) {
    cuuint64_t dims[2] = {cols, rows};
    cuuint64_t strides[1] = {cols * 2};
    cuuint32_t box[2] = {64, box_rows};
    cuuint32_t es[2] = {1, 1};
    enc(m, CU_TENSOR_MAP_DATA_TYPE_BFLOAT16, 2, const_cast<void*>(base), dims, strides, box, es, CU_TENSOR_MAP_INTERLEAVE_NONE,
        CU_TENSOR_MAP_SWIZZLE_128B, CU_TENSOR_MAP_L2_PROMOTION_L2_128B, CU_TENSOR_MAP_FLOAT_OOB_FILL_NONE);
}

}

extern "C" void kernel_launch(void* const* d_in, const int* in_sizes, int n_in, void* d_out, int out_size) {
    (void)in_sizes; (void)n_in; (void)out_size;
    void* fn = nullptr;
    cudaDriverEntryPointQueryResult qr;
    cudaGetDriverEntryPoint("cuTensorMapEncodeTiled", &fn, cudaEnableDefault, &qr);
    EncodeFn enc = (EncodeFn)fn;
    CUtensorMap mX2, mX, mWqkv, mWo, mW1, mW2;
    {
        cuuint64_t dims[3] = {kD, kS / 2, 2}, strides[2] = {4 * kD, 2 * kD};
        cuuint32_t box[3] = {64, 64, 2}, es[3] = {1, 1, 1};
        enc(&mX2, CU_TENSOR_MAP_DATA_TYPE_BFLOAT16, 3, d_in[0], dims, strides, box, es, CU_TENSOR_MAP_INTERLEAVE_NONE,
            CU_TENSOR_MAP_SWIZZLE_128B, CU_TENSOR_MAP_L2_PROMOTION_L2_128B, CU_TENSOR_MAP_FLOAT_OOB_FILL_NONE);
    }
    make_map(enc, &mX, d_in[0], 2 * kD, kS / 2, 64);
    make_map(enc, &mWqkv, d_in[1], 3 * kD, kD, 64);
    make_map(enc, &mWo, d_in[2], kD, kD, 224);
    make_map(enc, &mW1, d_in[4], 2 * kF, kS / 2, 64);
    make_map(enc, &mW2, d_in[6], kS, kF, 64);
    Params prm;
    prm.x = (const __nv_bfloat16*)d_in[0];
    prm.wqkv = (const __nv_bfloat16*)d_in[1];
    prm.wo = (const __nv_bfloat16*)d_in[2];
    prm.w1 = (const __nv_bfloat16*)d_in[4];
    prm.b1 = (const __nv_bfloat16*)d_in[5];
    prm.w2 = (const __nv_bfloat16*)d_in[6];
    prm.b2 = (const __nv_bfloat16*)d_in[7];
    prm.out = (__nv_bfloat16*)d_out;
    cudaGetSymbolAddress((void**)&prm.sc, g_scratch);
    cudaFuncSetAttribute(fused_kernel, cudaFuncAttributeMaxDynamicSharedMemorySize, SM_TOTAL);
    fused_kernel<<<128, 384, SM_TOTAL, cudaStreamPerThread>>>(prm, mX2, mX, mWqkv, mWo, mW1, mW2);
}
```

```cpp
#include <cuda_runtime.h>
#include <cuda.h>
#include <cuda_bf16.h>
#include <stdint.h>
#include <type_traits>

namespace {

constexpr int kS = 2048, kD = 448, kF = 1792;
constexpr float kEps = 1e-5f;

#define FS 32
struct Scratch {
    uint4    o[32 * 56 * 64];
    uint4    hn[32 * 56 * 64];
    uint4    g[28 * 56 * 64];
    uint4    halo[16 * 8 * 2 * 4 * 32];
    uint32_t stats[32 * 8 * 4 * 32];
    uint2    rows[32 * 64];
    uint32_t flag_o[32 * 8 * FS];
    uint32_t flag_h[32 * 4 * FS];
    uint32_t epoch;
};
__device__ __align__(1024) Scratch g_scratch;
#define TIMEOUT(code)
#define RETRY_COUNT(i)
#define CAP_DECL(n, k)
#define CAP(n)
#define CAP_SKIP(n)
#define EV(i, dep)
#define TR2(idx)
#define TR(idx)
#define TRW(idx)
#define TRG(idx)

constexpr uint32_t SM_WKV  = 114688;
constexpr uint32_t SM_XR   = 24576;
constexpr uint32_t SM_STG  = 40960;
constexpr uint32_t SM_WQ   = 57344;
constexpr uint32_t SM_XCH  = 0;
constexpr uint32_t SM_B    = 131072;
constexpr uint32_t SM_BAR  = 231424;
constexpr uint32_t SM_TOTAL = SM_BAR + 1024;
constexpr int NB = 7;
#define SH1 0
#define SH2 0
#define SH2N 5
#define SH3 0
#define NSPEC 4
#define XSPEC 500
#define C2 0
#define C3 0
#define CN2 7200
#define CN3 10900
constexpr int B_XF = 0, B_WKVF = 7, B_WQF = 14, B_XRF = 15, B_WOF = 16,
              B_XC = 18, B_KV3 = 19, B_KVC = 20,
              B_A1D = 21, B_XD = 22, B_OC = 23,
              B_BE = 24  , B_RE = B_BE + 2 * NB,
              B_PL = B_RE + 3, B_AF = B_PL + 1, B_BL = B_AF + 1  , B_OL = B_BL + 2 * NB  ,
              B_BF = B_OL + 4  , B_OF = B_BF + NB, B_RF = B_OF + 4, B_EP = B_RF + 8, B_PD = B_EP + 1, B_RT = B_PD + 1, B_HL = B_RT + 2,
              B_HD = B_HL + 2  , B_GO = B_HD + 1, B_GD = B_GO + 1, B_COUNT = B_GD + 2;
#define WEARLY 6
#define PF0 126
#define TMPF 2
#define RSTE 2
#define POLLP 1
#define PROBEP 1
#define LOADP 1
#define LOADW 64
#define NOB 0
#define AEARLY 5
#define W1PACE 400
#define W2PACE 200
#define PFPACE 230
#define PFBAR (B_XF + 6)
#define DELTA 1600
#define DELTA2 DELTA
#define BPACE 230
#define BURST 2
#define W1OFF 350
#define W2OFF 2900
#define XPACE 0
#define PSTAG 200
constexpr uint32_t SM_EPOCH = SM_BAR + B_COUNT * 8, SM_TG = SM_EPOCH + 4  , SM_TG2 = SM_TG + 16  , SM_TR = SM_BAR + 768;

#define HDELAY 0
#define QC0 4
#define QC1 10
#define QC2 16
#define HPOS 1
#define XSPECB 850
#define PACE1 120
#define PACE2 400
#define RELOAD1 1
#define VCH 1
#define SOFF 0
#define XW 1
#define XLAG 0
#define PFX 3
#define PFD 250
#define SDELAY 300
#define PDELAY 500
#define NPRE 10
#define PREPACE 0
#define AFIRST 0
#define DELTAO 928
#define NS 0
#define GCH 14
#define OCH 14
#define ICH 14
#define PACKO
#define NR 8
#define HMODE 2
#define HOFF0 (-100)
#define HOFF1 900
#define STAG1 0
#define STAG2 400
#define PLOFF (-250)
#define HSRC h
#define W1Q 3
#define APOS1 ((1ull << 4) | (1ull << 8) | (1ull << 12) | (1ull << 5) | (1ull << 9) | (1ull << 13))
#define APOS2 (0x5555555ull << 17)
constexpr uint32_t seg_mask(int h, int p0, int p1) {
    uint32_t m = 0; int n = 0;
    for (int p = p0; p < p1; p++) if ((p & 1) == h) m |= (uint32_t)(((APOS1 | APOS2) >> p) & 1) << n++;
    return m | 1u << n;
}
constexpr uint64_t seg_masks(int h) {
    return 2 | (uint64_t)seg_mask(h, 0, 16) << 10 | (uint64_t)seg_mask(h, 16, 32) << 20
             | (uint64_t)seg_mask(h, 32, 46) << 30 | (uint64_t)seg_mask(h, 46, 60) << 40;
}
constexpr uint64_t kSegMasks0 = seg_masks(0), kSegMasks1 = seg_masks(1);

constexpr int kSpinLimit = 1 << 15;
__device__ __forceinline__ bool elect_one() {
    uint32_t p;
    asm volatile("{ .reg .pred P; elect.sync _|P, 0xffffffff; selp.u32 %0, 1, 0, P; }" : "=r"(p));
    return p;
}
__device__ __forceinline__ void mbar_init(uint32_t bar, uint32_t cnt) { asm volatile("mbarrier.init.shared::cta.b64 [%0], %1;" :: "r"(bar), "r"(cnt)); }
__device__ __forceinline__ void mbar_expect(uint32_t bar, uint32_t bytes) { asm volatile("mbarrier.arrive.expect_tx.shared::cta.b64 _, [%0], %1;" :: "r"(bar), "r"(bytes) : "memory"); }
__device__ __forceinline__ void mbar_expect_more(uint32_t bar, uint32_t bytes) { asm volatile("mbarrier.expect_tx.relaxed.cta.shared::cta.b64 [%0], %1;" :: "r"(bar), "r"(bytes) : "memory"); }
__device__ __forceinline__ void mbar_arrive(uint32_t bar) { asm volatile("mbarrier.arrive.shared::cta.b64 _, [%0];" :: "r"(bar) : "memory"); }
__device__ __forceinline__ void mbar_wait(uint32_t bar, uint32_t parity) {
    uint32_t ok; int it = 0;
    do {
        asm volatile("{ .reg .pred p; mbarrier.try_wait.parity.shared::cta.b64 p, [%1], %2; selp.u32 %0, 1, 0, p; }"
                     : "=r"(ok) : "r"(bar), "r"(parity) : "memory");
        if (++it > kSpinLimit) { TIMEOUT((bar & 1023) >> 3); break; }
    } while (!ok);
}
__device__ __forceinline__ bool mbar_try(uint32_t bar, uint32_t parity) {
    uint32_t ok;
    asm volatile("{ .reg .pred p; mbarrier.try_wait.parity.shared::cta.b64 p, [%1], %2; selp.u32 %0, 1, 0, p; }" : "=r"(ok) : "r"(bar), "r"(parity) : "memory");
    return ok;
}
__device__ __forceinline__ bool mbar_test(uint32_t bar, uint32_t parity) {
    uint32_t ok;
    asm volatile("{ .reg .pred p; mbarrier.test_wait.parity.shared::cta.b64 p, [%1], %2; selp.u32 %0, 1, 0, p; }" : "=r"(ok) : "r"(bar), "r"(parity) : "memory");
    return ok;
}
__device__ __forceinline__ void mbar_wait_fast(uint32_t bar, uint32_t parity) { if (!mbar_try(bar, parity)) mbar_wait(bar, parity); }
__device__ __forceinline__ void mbar_wait2(uint32_t bar0, uint32_t par0, uint32_t bar1, uint32_t par1) {
    uint32_t ok; int it = 0;
    do {
        asm volatile("{ .reg .pred p, q; mbarrier.try_wait.parity.shared::cta.b64 p, [%1], %2;\n"
                     "mbarrier.try_wait.parity.shared::cta.b64 q, [%3], %4; and.pred p, p, q; selp.u32 %0, 1, 0, p; }"
                     : "=r"(ok) : "r"(bar0), "r"(par0), "r"(bar1), "r"(par1) : "memory");
        if (++it > kSpinLimit) { TIMEOUT((bar0 & 1023) >> 3); break; }
    } while (!ok);
}
__device__ __forceinline__ void sched_fence(uint32_t v) {
    asm volatile("{ .reg .pred p; .reg .b32 x; mov.b32 x, %0;\nL: setp.eq.u32 p, x, 0xffffffff; @p mov.u32 x, %%clock; @p bra L; }" :: "r"(v) : "memory");
}
template <int N> __device__ __forceinline__ void reg_fence(float (&d)[N]) {
    #pragma unroll
    for (int i = 0; i < N; i++) asm volatile("" : "+f"(d[i]) :: "memory");
}
__device__ __forceinline__ void mbar_wait_cluster(uint32_t bar, uint32_t parity) {
    uint32_t ok; int it = 0;
    do {
        asm volatile("{ .reg .pred p; mbarrier.try_wait.parity.acquire.cluster.shared::cta.b64 p, [%1], %2; selp.u32 %0, 1, 0, p; }"
                     : "=r"(ok) : "r"(bar), "r"(parity) : "memory");
        if (++it > kSpinLimit) { TIMEOUT((bar & 1023) >> 3); break; }
    } while (!ok);
}
__device__ __forceinline__ void mbar_arrive_if(uint32_t bar, bool pred) {
    asm volatile("{ .reg .pred p; setp.ne.u32 p, %1, 0; @p mbarrier.arrive.shared::cta.b64 _, [%0]; }" :: "r"(bar), "r"((uint32_t)pred) : "memory");
}
template <int P> __device__ __forceinline__ void tick() {
    if (P > 1) { const uint32_t t = ((uint32_t)clock() | (P - 1)) + 1; while ((int)((uint32_t)clock() - t) < 0) {} }
}
__device__ __forceinline__ void warp_arrive(uint32_t bar) { __syncwarp(); if (elect_one()) mbar_arrive(bar); }
__device__ __forceinline__ void tma2d(uint32_t dst, const CUtensorMap* m, int c0, int c1, uint32_t bar) {
    asm volatile("cp.async.bulk.tensor.2d.shared::cluster.global.mbarrier::complete_tx::bytes [%0], [%1, {%3, %4}], [%2];"
                 :: "r"(dst), "l"(m), "r"(bar), "r"(c0), "r"(c1) : "memory");
}
__device__ __forceinline__ void tma3d(uint32_t dst, const CUtensorMap* m, int c0, int c1, int c2, uint32_t bar) {
    asm volatile("cp.async.bulk.tensor.3d.shared::cluster.global.mbarrier::complete_tx::bytes [%0], [%1, {%3, %4, %5}], [%2];"
                 :: "r"(dst), "l"(m), "r"(bar), "r"(c0), "r"(c1), "r"(c2) : "memory");
}
__device__ __forceinline__ void tma2d_mc(uint32_t dst, const CUtensorMap* m, int c0, int c1, uint32_t bar) {
    asm volatile("cp.async.bulk.tensor.2d.shared::cluster.global.mbarrier::complete_tx::bytes.multicast::cluster [%0], [%1, {%3, %4}], [%2], %5;"
                 :: "r"(dst), "l"(m), "r"(bar), "r"(c0), "r"(c1), "h"((uint16_t)3) : "memory");
}
__device__ __forceinline__ void bulk_g2s_mc(uint32_t dst, const void* src, uint32_t bytes, uint32_t bar) {
    asm volatile("cp.async.bulk.shared::cluster.global.mbarrier::complete_tx::bytes.multicast::cluster [%0], [%1], %2, [%3], %4;"
                 :: "r"(dst), "l"(src), "r"(bytes), "r"(bar), "h"((uint16_t)3) : "memory");
}
__device__ __forceinline__ void mbar_arrive_remote_if(uint32_t cluster_bar, bool pred) {
    asm volatile("{ .reg .pred p; setp.ne.u32 p, %1, 0; @p mbarrier.arrive.shared::cluster.b64 _, [%0]; }" :: "r"(cluster_bar), "r"((uint32_t)pred) : "memory");
}
__device__ __forceinline__ void bulk_g2s(uint32_t dst, const void* src, uint32_t bytes, uint32_t bar) {
    asm volatile("cp.async.bulk.shared::cluster.global.mbarrier::complete_tx::bytes [%0], [%1], %2, [%3];"
                 :: "r"(dst), "l"(src), "r"(bytes), "r"(bar) : "memory");
}
__device__ __forceinline__ void wg_fence()  { asm volatile("wgmma.fence.sync.aligned;" ::: "memory"); }
__device__ __forceinline__ void wg_commit() { asm volatile("wgmma.commit_group.sync.aligned;" ::: "memory"); }
template <int N> __device__ __forceinline__ void wg_wait() { asm volatile("wgmma.wait_group.sync.aligned %0;" :: "n"(N) : "memory"); }
__device__ __forceinline__ void named_bar(int id, int n) { asm volatile("bar.sync %0, %1;" :: "r"(id), "r"(n) : "memory"); }
__device__ __forceinline__ void named_arrive(int id, int n) { asm volatile("bar.arrive %0, %1;" :: "r"(id), "r"(n) : "memory"); }
__device__ __forceinline__ bool mbar_try2(uint32_t bar0, uint32_t par0, uint32_t bar1, uint32_t par1) {
    uint32_t ok;
    asm volatile("{ .reg .pred p, q; mbarrier.test_wait.parity.shared::cta.b64 p, [%1], %2;\n"
                 "mbarrier.test_wait.parity.shared::cta.b64 q, [%3], %4; and.pred p, p, q; selp.u32 %0, 1, 0, p; }"
                 : "=r"(ok) : "r"(bar0), "r"(par0), "r"(bar1), "r"(par1) : "memory");
    return ok;
}
__device__ __forceinline__ void fence_gpu() { asm volatile("fence.release.gpu;" ::: "memory"); }
__device__ __forceinline__ void fence_async_global() { asm volatile("fence.proxy.async.global;" ::: "memory"); }
__device__ __forceinline__ void fence_async_smem() { asm volatile("fence.proxy.async.shared::cta;" ::: "memory"); }
__device__ __forceinline__ uint32_t gtime32() { uint64_t t; asm volatile("mov.u64 %0, %%globaltimer;" : "=l"(t) :: "memory"); return (uint32_t)t; }
__device__ __forceinline__ uint32_t clk32() { uint64_t t; asm volatile("mov.u64 %0, %%clock64;" : "=l"(t) :: "memory"); return (uint32_t)t; }
__device__ __forceinline__ void spin_until(uint32_t t) { while ((int)(clk32() - t) < 0) {} }
#define SLEEPNS 20
__device__ __forceinline__ void sleep_until(uint32_t t) { while ((int)(clk32() - t) < 0) { if (SLEEPNS) __nanosleep(SLEEPNS); } }
__device__ __forceinline__ void st_flag(uint32_t* p, uint32_t v) {
    const uint64_t w = ((uint64_t)gtime32() << 32) | v;
    asm volatile("st.relaxed.gpu.global.u64 [%0], %1;" :: "l"(p), "l"(w) : "memory");
}
__device__ __forceinline__ void ld_flag_if(uint64_t& v, const uint32_t* p, bool pred) {
    asm volatile("{ .reg .pred p; setp.ne.u32 p, %2, 0; @p ld.relaxed.gpu.global.u64 %0, [%1]; }" : "+l"(v) : "l"(p), "r"((uint32_t)pred) : "memory");
}
__device__ __forceinline__ uint32_t ld_acq(const uint32_t* p) { uint32_t v; asm volatile("ld.acquire.gpu.global.u32 %0, [%1];" : "=r"(v) : "l"(p) : "memory"); return v; }
__device__ __forceinline__ uint32_t ld_rlx(const uint32_t* p) { uint32_t v; asm volatile("ld.relaxed.gpu.global.u32 %0, [%1];" : "=r"(v) : "l"(p) : "memory"); return v; }
template <class T> __device__ __forceinline__ T* opaque_ptr(T* p) { asm volatile("" : "+l"(p)); return p; }
__device__ __forceinline__ uint4 ld_rlx4(const uint4* p) {
    uint4 v; asm volatile("ld.relaxed.gpu.global.v4.u32 {%0,%1,%2,%3}, [%4];" : "=r"(v.x), "=r"(v.y), "=r"(v.z), "=r"(v.w) : "l"(p) : "memory"); return v;
}
__device__ __forceinline__ void st_ll(uint4* p, uint32_t a, uint32_t b, uint32_t tag) {
    uint64_t lo = ((uint64_t)tag << 32) | a, hi = ((uint64_t)tag << 32) | b;
    asm volatile("st.relaxed.gpu.global.v2.u64 [%0], {%1,%2};" :: "l"(p), "l"(lo), "l"(hi) : "memory");
}
__device__ __forceinline__ bool ld_ll(const uint4* p, uint32_t& a, uint32_t& b, uint32_t tag) {
    uint64_t lo, hi;
    asm volatile("ld.relaxed.gpu.global.v2.u64 {%0,%1}, [%2];" : "=l"(lo), "=l"(hi) : "l"(p) : "memory");
    a = (uint32_t)lo; b = (uint32_t)hi;
    return (uint32_t)(lo >> 32) == tag && (uint32_t)(hi >> 32) == tag;
}
__device__ __forceinline__ uint2 ld_acq2(const uint2* p) {
    uint2 v; asm volatile("ld.acquire.gpu.global.v2.u32 {%0,%1}, [%2];" : "=r"(v.x), "=r"(v.y) : "l"(p) : "memory"); return v;
}
__device__ __forceinline__ uint2 ld_rlx2(const uint2* p) {
    uint2 v; asm volatile("ld.relaxed.gpu.global.v2.u32 {%0,%1}, [%2];" : "=r"(v.x), "=r"(v.y) : "l"(p) : "memory"); return v;
}
__device__ __forceinline__ void stg1(uint32_t* p, uint32_t v) { asm volatile("st.global.u32 [%0], %1;" :: "l"(p), "r"(v) : "memory"); }
__device__ __forceinline__ void stg2(void* p, uint32_t x, uint32_t y) { asm volatile("st.global.v2.u32 [%0], {%1,%2};" :: "l"(p), "r"(x), "r"(y) : "memory"); }
__device__ __forceinline__ void stg4(void* p, uint32_t x, uint32_t y, uint32_t z, uint32_t w) { asm volatile("st.global.v4.u32 [%0], {%1,%2,%3,%4};" :: "l"(p), "r"(x), "r"(y), "r"(z), "r"(w) : "memory"); }
__device__ __forceinline__ uint32_t lds1(uint32_t a) { uint32_t v; asm volatile("ld.shared.u32 %0, [%1];" : "=r"(v) : "r"(a) : "memory"); return v; }
__device__ __forceinline__ uint2 lds2(uint32_t a) { uint2 v; asm volatile("ld.shared.v2.u32 {%0,%1}, [%2];" : "=r"(v.x), "=r"(v.y) : "r"(a) : "memory"); return v; }
__device__ __forceinline__ uint32_t set_par(uint32_t v, uint32_t mask, uint32_t par) {
    uint32_t r; asm("lop3.b32 %0, %1, %2, %3, 0xb8;" : "=r"(r) : "r"(v), "r"(mask), "r"(par)); return r;
}
__device__ __forceinline__ void st_gen4(void* p, uint32_t x, uint32_t y, uint32_t z, uint32_t w) { asm volatile("st.v4.u32 [%0], {%1,%2,%3,%4};" :: "l"(p), "r"(x), "r"(y), "r"(z), "r"(w) : "memory"); }
__device__ __forceinline__ float tanh_hw(float x) { float r; asm("tanh.approx.f32 %0, %1;" : "=f"(r) : "f"(x)); return r; }
__device__ __forceinline__ bool bar_any(int id, int n, bool v) {
    uint32_t r;
    asm volatile("{ .reg .pred p, q; setp.ne.u32 p, %3, 0; bar.red.or.pred q, %1, %2, p; selp.u32 %0, 1, 0, q; }" : "=r"(r) : "r"(id), "r"(n), "r"((uint32_t)v) : "memory");
    return r;
}
__device__ __forceinline__ void sts4(uint32_t a, uint32_t x, uint32_t y, uint32_t z, uint32_t w) { asm volatile("st.shared.v4.u32 [%0], {%1,%2,%3,%4};" :: "r"(a), "r"(x), "r"(y), "r"(z), "r"(w) : "memory"); }
__device__ __forceinline__ uint4 lds4(uint32_t a) { uint4 v; asm volatile("ld.shared.v4.u32 {%0,%1,%2,%3}, [%4];" : "=r"(v.x), "=r"(v.y), "=r"(v.z), "=r"(v.w) : "r"(a) : "memory"); return v; }
__device__ __forceinline__ uint32_t pack_bf16(float lo, float hi) { uint32_t r; asm("cvt.rn.bf16x2.f32 %0, %1, %2;" : "=r"(r) : "f"(hi), "f"(lo)); return r; }
__device__ __forceinline__ float bf_lo(uint32_t v) { return __uint_as_float(v << 16); }
__device__ __forceinline__ float bf_hi(uint32_t v) { return __uint_as_float(v & 0xffff0000u); }
__device__ __forceinline__ uint32_t sub_bf16x2(uint32_t a, uint32_t b) { uint32_t r; asm volatile("sub.rn.bf16x2 %0, %1, %2;" : "=r"(r) : "r"(a), "r"(b)); return r; }
__device__ __forceinline__ uint32_t add_bf16x2(uint32_t a, uint32_t b) { uint32_t r; asm volatile("add.rn.bf16x2 %0, %1, %2;" : "=r"(r) : "r"(a), "r"(b)); return r; }
__device__ __forceinline__ uint32_t sqr_bf16x2(uint32_t a) { uint32_t r; asm volatile("mul.rn.bf16x2 %0, %1, %1;" : "=r"(r) : "r"(a)); return r; }
__device__ __forceinline__ uint32_t sqa_bf16x2(uint32_t a, uint32_t c) { uint32_t r; asm volatile("fma.rn.bf16x2 %0, %1, %1, %2;" : "=r"(r) : "r"(a), "r"(c)); return r; }
__device__ __forceinline__ uint32_t movm(uint32_t a) { uint32_t r; asm volatile("movmatrix.sync.aligned.m8n8.trans.b16 %0, %1;" : "=r"(r) : "r"(a)); return r; }
__device__ __forceinline__ float ex2(float x) { float r; asm("ex2.approx.ftz.f32 %0, %1;" : "=f"(r) : "f"(x)); return r; }
__device__ __forceinline__ float rsq(float x) { float r; asm("rsqrt.approx.ftz.f32 %0, %1;" : "=f"(r) : "f"(x)); return r; }
__device__ __forceinline__ float rcp(float x) { float r; asm("rcp.approx.ftz.f32 %0, %1;" : "=f"(r) : "f"(x)); return r; }
__device__ __forceinline__ void mma16816(float (&c)[4], uint32_t a0, uint32_t a1, uint32_t a2, uint32_t a3, uint32_t b0, uint32_t b1) {
    asm("mma.sync.aligned.m16n8k16.row.col.f32.bf16.bf16.f32 {%0,%1,%2,%3}, {%4,%5,%6,%7}, {%8,%9}, {%0,%1,%2,%3};"
        : "+f"(c[0]), "+f"(c[1]), "+f"(c[2]), "+f"(c[3]) : "r"(a0), "r"(a1), "r"(a2), "r"(a3), "r"(b0), "r"(b1));
}
__device__ __forceinline__ void mma1688(float (&c)[4], uint32_t a0, uint32_t a1, uint32_t b0) {
    asm("mma.sync.aligned.m16n8k8.row.col.f32.bf16.bf16.f32 {%0,%1,%2,%3}, {%4,%5}, {%6}, {%0,%1,%2,%3};"
        : "+f"(c[0]), "+f"(c[1]), "+f"(c[2]), "+f"(c[3]) : "r"(a0), "r"(a1), "r"(b0));
}
__device__ __forceinline__ float quad_sum(float v) { v += __shfl_xor_sync(~0u, v, 1); v += __shfl_xor_sync(~0u, v, 2); return v; }
__device__ __forceinline__ float quad_max(float v) { v = fmaxf(v, __shfl_xor_sync(~0u, v, 1)); v = fmaxf(v, __shfl_xor_sync(~0u, v, 2)); return v; }
__device__ __forceinline__ uint64_t make_desc(uint32_t addr, uint32_t lbo, bool swz, uint32_t sbo = 1024) {
    const uint32_t lo = __shfl_sync(~0u, ((addr & 0x3FFFF) >> 4) | ((lbo >> 4) << 16), 0);
    const uint32_t hi = __shfl_sync(~0u, (swz ? 0x40000000u : 0u) + (sbo >> 4) + (threadIdx.x & 31), 0);
    return ((uint64_t)hi << 32) | lo;
}
template <int I, int N, class F> __device__ __forceinline__ void static_for(F&& f) {
    if constexpr (I < N) { f(std::integral_constant<int, I>{}); static_for<I + 1, N>(f); }
}
__device__ __forceinline__ uint32_t opaque(uint32_t v) { asm volatile("" : "+r"(v)); return v; }
template <int BOFF, int SCALE_D>
__device__ __forceinline__ void wgmma_rs_n56(float (&d)[28], uint32_t a0, uint32_t a1, uint32_t a2, uint32_t a3, uint64_t db) {
    asm volatile("{ .reg .b64 db; add.s64 db, %32, %33;\n"
        "wgmma.mma_async.sync.aligned.m64n56k16.f32.bf16.bf16 "
        "{%0, %1, %2, %3, %4, %5, %6, %7, %8, %9, %10, %11, %12, %13, %14, %15, %16, %17, %18, %19, %20, %21, %22, %23, %24, %25, %26, %27}, "
        "{%28, %29, %30, %31}, db, %34, 1, 1, 1; }"
        : "+f"(d[0]), "+f"(d[1]), "+f"(d[2]), "+f"(d[3]), "+f"(d[4]), "+f"(d[5]), "+f"(d[6]), "+f"(d[7]),
        "+f"(d[8]), "+f"(d[9]), "+f"(d[10]), "+f"(d[11]), "+f"(d[12]), "+f"(d[13]), "+f"(d[14]), "+f"(d[15]),
        "+f"(d[16]), "+f"(d[17]), "+f"(d[18]), "+f"(d[19]), "+f"(d[20]), "+f"(d[21]), "+f"(d[22]), "+f"(d[23]),
        "+f"(d[24]), "+f"(d[25]), "+f"(d[26]), "+f"(d[27])
        : "r"(a0), "r"(a1), "r"(a2), "r"(a3), "l"(db), "n"(BOFF >> 4), "n"(SCALE_D));
}
template <int AOFF, int BOFF, int MMAJOR>
__device__ __forceinline__ void wgmma_ss_n56(float (&d)[28], uint64_t da, uint64_t db) {
    asm volatile("{ .reg .b64 da, db; add.s64 da, %28, %30; add.s64 db, %29, %31;\n"
        "wgmma.mma_async.sync.aligned.m64n56k16.f32.bf16.bf16 "
        "{%0, %1, %2, %3, %4, %5, %6, %7, %8, %9, %10, %11, %12, %13, %14, %15, %16, %17, %18, %19, %20, %21, %22, %23, %24, %25, %26, %27}, "
        "da, db, 1, 1, 1, %32, 1; }"
        : "+f"(d[0]), "+f"(d[1]), "+f"(d[2]), "+f"(d[3]), "+f"(d[4]), "+f"(d[5]), "+f"(d[6]), "+f"(d[7]),
        "+f"(d[8]), "+f"(d[9]), "+f"(d[10]), "+f"(d[11]), "+f"(d[12]), "+f"(d[13]), "+f"(d[14]), "+f"(d[15]),
        "+f"(d[16]), "+f"(d[17]), "+f"(d[18]), "+f"(d[19]), "+f"(d[20]), "+f"(d[21]), "+f"(d[22]), "+f"(d[23]),
        "+f"(d[24]), "+f"(d[25]), "+f"(d[26]), "+f"(d[27])
        : "l"(da), "l"(db), "n"(AOFF >> 4), "n"(BOFF >> 4), "n"(MMAJOR));
}
template <int AOFF, int BOFF, int MMAJOR>
__device__ __forceinline__ void wgmma_ss_n112(float (&d)[28], float (&e)[28], uint64_t da, uint64_t db) {
    asm volatile("{ .reg .b64 da, db; add.s64 da, %56, %58; add.s64 db, %57, %59;\n"
        "wgmma.mma_async.sync.aligned.m64n112k16.f32.bf16.bf16 "
        "{%0, %1, %2, %3, %4, %5, %6, %7, %8, %9, %10, %11, %12, %13, %14, %15, %16, %17, %18, %19, %20, %21, %22, %23, %24, %25, %26, %27, %28, %29, %30, %31, %32, %33, %34, %35, %36, %37, %38, %39, %40, %41, %42, %43, %44, %45, %46, %47, %48, %49, %50, %51, %52, %53, %54, %55}, "
        "da, db, 1, 1, 1, %60, 1; }"
        : "+f"(d[0]), "+f"(d[1]), "+f"(d[2]), "+f"(d[3]), "+f"(d[4]), "+f"(d[5]), "+f"(d[6]), "+f"(d[7]),
        "+f"(d[8]), "+f"(d[9]), "+f"(d[10]), "+f"(d[11]), "+f"(d[12]), "+f"(d[13]), "+f"(d[14]), "+f"(d[15]),
        "+f"(d[16]), "+f"(d[17]), "+f"(d[18]), "+f"(d[19]), "+f"(d[20]), "+f"(d[21]), "+f"(d[22]), "+f"(d[23]),
        "+f"(d[24]), "+f"(d[25]), "+f"(d[26]), "+f"(d[27]), "+f"(e[0]), "+f"(e[1]), "+f"(e[2]), "+f"(e[3]),
        "+f"(e[4]), "+f"(e[5]), "+f"(e[6]), "+f"(e[7]), "+f"(e[8]), "+f"(e[9]), "+f"(e[10]), "+f"(e[11]),
        "+f"(e[12]), "+f"(e[13]), "+f"(e[14]), "+f"(e[15]), "+f"(e[16]), "+f"(e[17]), "+f"(e[18]), "+f"(e[19]),
        "+f"(e[20]), "+f"(e[21]), "+f"(e[22]), "+f"(e[23]), "+f"(e[24]), "+f"(e[25]), "+f"(e[26]), "+f"(e[27])
        : "l"(da), "l"(db), "n"(AOFF >> 4), "n"(BOFF >> 4), "n"(MMAJOR));
}
template <int BOFF, int SCALE_D>
__device__ __forceinline__ void wgmma_rs_n112(float (&d)[28], float (&e)[28], uint32_t a0, uint32_t a1, uint32_t a2, uint32_t a3, uint64_t db) {
    asm volatile("{ .reg .b64 db; add.s64 db, %60, %61;\n"
        "wgmma.mma_async.sync.aligned.m64n112k16.f32.bf16.bf16 "
        "{%0, %1, %2, %3, %4, %5, %6, %7, %8, %9, %10, %11, %12, %13, %14, %15, %16, %17, %18, %19, %20, %21, %22, %23, %24, %25, %26, %27, %28, %29, %30, %31, %32, %33, %34, %35, %36, %37, %38, %39, %40, %41, %42, %43, %44, %45, %46, %47, %48, %49, %50, %51, %52, %53, %54, %55}, "
        "{%56, %57, %58, %59}, db, %62, 1, 1, 1; }"
        : "+f"(d[0]), "+f"(d[1]), "+f"(d[2]), "+f"(d[3]), "+f"(d[4]), "+f"(d[5]), "+f"(d[6]), "+f"(d[7]),
        "+f"(d[8]), "+f"(d[9]), "+f"(d[10]), "+f"(d[11]), "+f"(d[12]), "+f"(d[13]), "+f"(d[14]), "+f"(d[15]),
        "+f"(d[16]), "+f"(d[17]), "+f"(d[18]), "+f"(d[19]), "+f"(d[20]), "+f"(d[21]), "+f"(d[22]), "+f"(d[23]),
        "+f"(d[24]), "+f"(d[25]), "+f"(d[26]), "+f"(d[27]), "+f"(e[0]), "+f"(e[1]), "+f"(e[2]), "+f"(e[3]),
        "+f"(e[4]), "+f"(e[5]), "+f"(e[6]), "+f"(e[7]), "+f"(e[8]), "+f"(e[9]), "+f"(e[10]), "+f"(e[11]),
        "+f"(e[12]), "+f"(e[13]), "+f"(e[14]), "+f"(e[15]), "+f"(e[16]), "+f"(e[17]), "+f"(e[18]), "+f"(e[19]),
        "+f"(e[20]), "+f"(e[21]), "+f"(e[22]), "+f"(e[23]), "+f"(e[24]), "+f"(e[25]), "+f"(e[26]), "+f"(e[27])
        : "r"(a0), "r"(a1), "r"(a2), "r"(a3), "l"(db), "n"(BOFF >> 4), "n"(SCALE_D));
}

struct Params {
    const __nv_bfloat16 *x, *wqkv;
    Scratch* sc;
    const __nv_bfloat16 *wo, *w1, *w2, *b1, *b2;
    __nv_bfloat16* out;
};

__global__ void __cluster_dims__(2, 1, 1) __launch_bounds__(384, 1)
fused_kernel(const Params prm, const __grid_constant__ CUtensorMap mX2, const __grid_constant__ CUtensorMap mX, const __grid_constant__ CUtensorMap mWqkv,
             const __grid_constant__ CUtensorMap mWo, const __grid_constant__ CUtensorMap mW1,
             const __grid_constant__ CUtensorMap mW2)
{
    extern __shared__ __align__(1024) unsigned char smem_raw[];
    if (threadIdx.x < 126) {
        const uint32_t i = threadIdx.x, t = clk32() + (i >> 5) * PFD;
        const char* px = (const char*)prm.x + (blockIdx.x * 16 + (i & 15)) * 896 + (i >> 4) * 128;
        const char* pw = (const char*)prm.wqkv + blockIdx.x * 2688 + i * 128 + (896 - 112 * 128);
        spin_until(t);
        asm volatile("prefetch.global.L2 [%0];" :: "l"(i < 112 ? px : pw) : "memory");
    }
    if (threadIdx.x == 128) { asm volatile("prefetch.tensormap [%0];" :: "l"(&mX2) : "memory"); asm volatile("prefetch.tensormap [%0];" :: "l"(&mWqkv) : "memory"); }
    uint32_t sb = (uint32_t)__cvta_generic_to_shared(smem_raw);
    asm volatile("mov.u32 %0, %0;" : "+r"(sb));
    const uint32_t bar0 = sb + SM_BAR;
    auto BAR = [&](int i) { return bar0 + 8u * i; };

    const int tid = threadIdx.x, lane = tid & 31;
    const int warp = __shfl_sync(~0u, tid >> 5, 0);
    const int b = __shfl_sync(~0u, (int)blockIdx.x, 0);
    const int rank = b & 1;
    const int cl = (b >> 1) - 4, cq = ((cl - 32) * 37) >> 8;
    const int res = cl < 0 ? 0 : cl < 32 ? cl & 7 : cl - 31 - 7 * cq;
    const int rnd = cl < 0 ? cl + 8 : cl < 32 ? cl >> 3 : 4 + cq;
    const int hg = (res & 1) * 4 + (rnd & 3);
    const int ti = (res >> 1) * 4 + (rnd >> 2) * 2 + rank;
    const int a2p = res & 1, a2j = rnd & 3;
    const int a2s = ti * 2 + a2p;
    const bool g1_on = rnd != 7;
    const int g1j = (rnd < 6 ? rnd : res) & 1, g1f = rnd < 6 ? res * 3 + (rnd >> 1) : 24 + (res >> 1);
    const int g2j = rnd & 1, g2s = res * 4 + (rnd >> 1);
    uint32_t pbar0;
    asm volatile("mapa.shared::cluster.u32 %0, %1, %2;" : "=r"(pbar0) : "r"(bar0), "r"(rank ^ 1));
    auto pair_arrive = [&](int i) { __syncwarp(); const bool l = elect_one(); mbar_arrive_if(BAR(i), l); mbar_arrive_remote_if(pbar0 + 8u * i, l); };
    const int wcol = hg * 56 - (hg & 1) * 8;

    if (warp == 8) {
        if (elect_one()) {
            #pragma unroll
            for (int i = 0; i < B_WQF; i++) mbar_init(BAR(i), 1);
            asm volatile("fence.mbarrier_init.release.cluster;" ::: "memory");
            fence_async_smem();
            #pragma unroll
            for (int kb = 0; kb < 7; kb++) {
                tma3d(sb + kb * 16384, &mX2, kb * 64, ti * 64, 0, BAR(B_XF + kb));
                mbar_expect(BAR(B_XF + kb), 16384);
                if (kb == 0 && PFX != 3) asm volatile("prefetch.tensormap [%0];" :: "l"(&mWqkv) : "memory");
            }
        }
    } else if (warp > 8) {
        if (elect_one()) {
            if (warp == 9) {
                #pragma unroll
                for (int i = B_WQF; i < B_AF; i++) mbar_init(BAR(i), i < B_XC ? 1 : i < B_A1D ? 16 : i < B_BE ? 8 : 4);
            } else if (warp == 10) {
                #pragma unroll
                for (int i = B_AF; i < B_BF; i++) mbar_init(BAR(i), 1);
            } else {
                #pragma unroll
                for (int i = B_BF; i < B_COUNT; i++) mbar_init(BAR(i), i == B_HD ? 8 : 1);
            }
            asm volatile("fence.mbarrier_init.release.cluster;" ::: "memory");
            fence_async_smem();
        }
    }
    __syncwarp();
    __syncthreads();
    asm volatile("barrier.cluster.arrive.relaxed.aligned;" ::: "memory");
    if (tid < 256) TR(0);
    if (tid == 0) TRG(61);

    if (warp >= 8) {
        asm volatile("setmaxnreg.dec.sync.aligned.u32 40;");
        asm volatile("barrier.cluster.wait.aligned;" ::: "memory");
        auto fetch_halo = [&](int p, uint32_t tag) {
            uint4 u[4];
            #pragma unroll
            for (int c = 0; c < 4; c++) u[c] = make_uint4(0u, 0u, 0u, 0u);
            const uint4* hp = opaque_ptr(&prm.sc->halo[(((ti - 1) * 8 + hg) * 2 + p) * 128 + lane]);
            mbar_wait(BAR(B_KVC), 0);
            if (p == 0) TRW(51);
            sleep_until(clk32() + HDELAY);
            if (ti > 0) {
                int it = 0;
                do {
                    #pragma unroll
                    for (int c = 0; c < 4; c++) u[c] = ld_rlx4(hp + c * 32);
                    if (it) RETRY_COUNT(4);
                    if (++it > kSpinLimit) { TIMEOUT(101); break; }
                } while (__any_sync(~0u, ((u[0].x ^ tag) | (u[1].x ^ tag) | (u[2].x ^ tag) | (u[3].x ^ tag)) & ~lane & 1));
            }
            #pragma unroll
            for (int c = 0; c < 4; c++) sts4(sb + SM_STG + p * 8192 + 3 * 2048 + lane * 16 + c * 512, u[c].x, u[c].y, u[c].z, u[c].w);
            warp_arrive(BAR(B_HL + p));
        };
        if (warp & 1) {
            uint32_t tag;
            if (warp == 11) {
                tag = *(volatile uint32_t*)&prm.sc->epoch + 1;
            #pragma unroll 1
            for (int i = 0; i < 8; i++) prm.sc->halo[(ti * 8 + hg) * 256 + i * 32 + lane] = make_uint4(~tag, 0u, 0u, 0u);
            ((uint4*)prm.sc->stats)[(a2s * 4 + a2j) * 64 + lane] = ((uint4*)prm.sc->stats)[(a2s * 4 + a2j) * 64 + 32 + lane] = make_uint4(~tag, ~tag, ~tag, ~tag);
            prm.sc->flag_h[(a2s * 4 + a2j) * FS + lane] = 0;
            prm.sc->flag_o[(ti * 16 + hg) * FS + lane] = prm.sc->flag_o[(ti * 16 + 8 + hg) * FS + lane] = 0;
            __syncwarp();
            if (lane == 0) {
                asm volatile("st.shared.v2.u32 [%0], {%1, %2};" :: "r"(sb + SM_EPOCH), "r"(tag), "r"(gtime32()) : "memory");
                mbar_arrive(BAR(B_EP));
            }
            if (lane < 8) mbar_expect(BAR(B_RF + lane), 1792);
            __syncwarp();
            TRW(44);
            } else {
                mbar_wait(BAR(B_EP), 0);
                tag = lds1(sb + SM_EPOCH);
            }
            fetch_halo((warp >> 1) & 1, tag);
        }
        if (warp < 10) {
          auto load_slab = [&](int s, bool second) {
              if (!second) tma2d(sb + s * 8192, &mW1, (s & 1) * kF + g1f * 64, (rank * 8 + (s >> 1)) * 64, BAR(B_AF));
              else         tma2d(sb + s * 8192, &mW2, g2s * 64, (rank * 14 + s - 1) * 64, BAR(B_AF));
          };
          if (warp == 8) {
            if (elect_one()) {
                #pragma unroll 1
                for (int s = 0; s < 7; s++) {
                    mbar_expect(BAR(B_WKVF + s), 16384);
                    tma2d_mc(sb + SM_WKV + s * 16384 + rank * 8192, &mWqkv, (1 + rank) * kD + wcol, s * 64, BAR(B_WKVF + s));
                }
            }
            __syncwarp();
            mbar_wait(BAR(B_XC), 0);
            if (elect_one()) {
                asm volatile("prefetch.tensormap [%0];" :: "l"(&mX) : "memory");
                asm volatile("prefetch.tensormap [%0];" :: "l"(&mWo) : "memory");
                asm volatile("prefetch.tensormap [%0];" :: "l"(&mW1) : "memory");
                asm volatile("prefetch.tensormap [%0];" :: "l"(&mW2) : "memory");
                mbar_expect(BAR(B_AF), (g1_on ? NPRE : 14) * 8192);
                mbar_expect(BAR(B_WQF), 57344);
                #pragma unroll 1
                for (int s = rank; s < 7; s += 2) tma2d_mc(sb + SM_WQ + s * 8192, &mWqkv, wcol, s * 64, BAR(B_WQF));
                mbar_expect(BAR(B_XRF), 16384);
                tma2d(sb + SM_XR, &mX, a2p * kD + a2j * 112, ti * 64, BAR(B_XRF));
                tma2d(sb + SM_XR + 8192, &mX, a2p * kD + a2j * 112 + 48, ti * 64, BAR(B_XRF));
            }
            __syncwarp();
            #pragma unroll 1
            for (int h = 0; h < 2; h++) {
                mbar_wait(BAR(B_KV3 + h), 0);
                if (h) mbar_wait2(BAR(B_HL), 0, BAR(B_HL + 1), 0);
                if (elect_one()) {
                    mbar_expect(BAR(B_WOF + h), 57344);
                    tma2d_mc(sb + SM_WKV + h * 57344 + rank * 28672, &mWo, a2j * 112 + rank * 48, h * 224, BAR(B_WOF + h));
                    if (g1_on && h == AFIRST) { load_slab(0, false); load_slab(1, false); load_slab(2, false); }
                }
                __syncwarp();
            }
            if (g1_on) {
                mbar_wait2(BAR(B_XD), 0, BAR(B_OL + 3), 0);
                #pragma unroll 1
                for (int i = 3; i < NPRE; i++) {
                    if (i == 7) mbar_wait(BAR(B_OC), 0);
                    if (elect_one()) load_slab(i, false);
                    __syncwarp();
                }
            } else {
                mbar_arrive_if(BAR((lane < 16 ? B_BE : B_BF) + (lane & 3)), lane < 20);
                mbar_wait(BAR(B_HD), 0);
                mbar_arrive_remote_if(pbar0 + 8u * B_PD, lane == 0);
                mbar_wait(BAR(B_GO), 0);
                uint32_t tg = lds1(sb + SM_TG + 4);
                tg += max((int)(lds1(sb + SM_TG2) - tg), 0);
                int it = 0;
                while ((int)(gtime32() - tg) < 0 && ++it < 256) {}
                const uint32_t t0 = clk32();
                if (lane < 2) {
                    asm volatile("st.shared.u32 [%0], %1;" :: "r"(sb + SM_TG + 8 + lane * 4), "r"(t0 + (lane ? CN3 : CN2)) : "memory");
                    mbar_arrive(BAR(B_GD + lane));
                }
                __syncwarp();
                #pragma unroll 1
                for (int s = 1; s < 15; s++) {
                    sleep_until(t0 + W2OFF + s * W2PACE);
                    if (elect_one()) load_slab(s, true);
                    __syncwarp();
                }
            }
          } else {
            TRW(58);
            const uint32_t tag = lds1(sb + SM_EPOCH);
            if (lane < 4) mbar_expect(BAR(B_OL + lane), 14336);
            #pragma unroll 1
            for (int e = 0; e < 2; e++) {
                const uint32_t* fp = e ? &prm.sc->flag_h[(rank * 64 + lane) * FS] : &prm.sc->flag_o[(a2s * 8 + (lane & 7)) * FS];
                if (e) {
                    mbar_wait2(BAR(B_OF + 2), 0, BAR(B_OF + 3), 0);
                    if (lane == 0) st_flag(&prm.sc->flag_h[(a2s * 4 + a2j) * FS], tag);
                    __syncwarp();
                    TRW(57);
                    sleep_until(clk32() + PDELAY);
                }
                uint64_t v0 = 0, v1 = e ? 0 : tag;
                int it = 0;
                do {
                    ld_flag_if(v0, fp, (uint32_t)v0 != tag); ld_flag_if(v1, fp + 32 * FS, (uint32_t)v1 != tag);
                    if (++it > kSpinLimit) { TIMEOUT(108); break; }
                } while (__any_sync(~0u, (uint32_t)v0 != tag || (uint32_t)v1 != tag));
                const uint32_t gbase = __shfl_sync(~0u, (uint32_t)(v0 >> 32), 0);
                const uint32_t tg = gbase + (e ? DELTA : DELTAO)
                                  + __reduce_max_sync(~0u, max((int)((uint32_t)(v0 >> 32) - gbase) - e * (lane >> 2) * SOFF, e ? (int)((uint32_t)(v1 >> 32) - gbase) - 8 * SOFF : 0));
                TRW(e ? 40 : 53);
                mbar_wait(BAR(B_A1D), 0);
                if (elect_one()) {
                    if (e) {
                        asm volatile("st.async.shared::cluster.mbarrier::complete_tx::bytes.b32 [%0], %1, [%2];"
                                     :: "r"(pbar0 + (SM_TG2 - SM_BAR)), "r"(tg), "r"(pbar0 + 8u * B_GO) : "memory");
                        asm volatile("st.shared.u32 [%0], %1;" :: "r"(sb + SM_TG + 4), "r"(tg) : "memory");
                        mbar_expect(BAR(B_GO), 4);
                    } else {
                        it = 0;
                        while ((int)(gtime32() - tg) < 0 && ++it < 256) {}
                        #pragma unroll
                        for (int i = 0; i < 4; i++) bulk_g2s(sb + SM_WQ + i * 14336, &prm.sc->o[(a2s * 4 + i) * 896], 14336, BAR(B_OL + i));
                    }
                }
                __syncwarp();
            }
          }
          if (elect_one()) {
              const int h = ~warp & 1;
              constexpr uint32_t T = 57344, BO = 2 * 14336;
              const char* src1 = (const char*)&prm.sc->hn[(rank * 16 + h) * 3584 + g1j * 896];
              const char* src2 = (const char*)&prm.sc->g[(rank * 14 + h) * 3584 + g2j * 896];
              uint64_t masks = g1_on ? (h ? kSegMasks1 : kSegMasks0) : 0x80 | 0x80 << 10;
              const uint32_t bl = BAR(B_BL + h * NB);
              uint32_t s8 = (g1_on ? NB - 2 + h : 4 + h) * 8, lap = 3, tmin = 0;
              const CUtensorMap* am = &mW1;
              uint32_t ad = sb + (NPRE + h) * 8192, astep = 16384; int ac0 = h * kF + g1f * 64, ac1 = (rank * 8 + NPRE / 2) * 64;
              CAP_DECL(ti_, 0);
              #pragma unroll 1
              for (int seg = g1_on ? 0 : 3; seg < 5; seg++) {
                  const char* src = (seg < 3 ? src1 : src2) + (~seg & 1) * BO;
                  uint32_t m = (uint32_t)masks & 0x3ff;
                  masks >>= 10;
                  if (seg == 2) {
                      mbar_wait(BAR(B_PL), 0);
                      mbar_arrive_remote_if(pbar0 + 8u * B_PD, h);
                      am = &mW2; ad = sb + 8192; astep = 8192; ac0 = g2s * 64; ac1 = rank * 14 * 64;
                  } else {
                      const int gate = seg - (seg > 2);
                      mbar_wait(BAR(B_HD + gate), 0);
                      tmin = lds1(sb + SM_TG + gate * 4);
                      if (gate < 2) {
                          tmin += max((int)(lds1(gate ? sb + SM_TG2 : sb + SM_TG) - tmin), 0);
                          int it = 0;
                          while ((int)(gtime32() - tmin) < 0 && ++it < 256) {}
                          tmin = clk32();
                      }
                      tmin += h * PACE1;
                  }
                  #pragma unroll 1
                  do {
                      const uint32_t dst = sb + SM_B + s8 * 1792;
                      spin_until(tmin);
                      mbar_wait_fast(BAR(B_BE) + s8 + (lap & 1) * (NB * 8), lap >> 1 & 1);
                      if (seg) {
                          bulk_g2s(dst, src, 14336, bl + s8);
                          mbar_expect(bl + s8, 14336);
                          CAP(ti_);
                      }
                      tmin += PACE2;
                      src += 2 * T;
                      s8 += 16;
                      if (s8 >= NB * 8) { s8 -= NB * 8; lap++; }
                      if (m & 1) {
                          mbar_expect_more(bl + s8, 8192);
                          tma2d(ad, am, ac0, ac1, bl + s8);
                          ad += astep; ac1 += 64;
                      }
                      m >>= 1;
                  } while (m != 1);
                  if (seg == 0) lap = 3;
              }
          }
        } else {
          if (warp == 10) {
            mbar_wait(BAR(PFBAR), 0);
            const char* p1 = (const char*)prm.w1 + (size_t)b * 57344 + lane * 128;
            const char* p2 = (const char*)prm.w2 + (size_t)b * 57344 + lane * 128;
            if (lane < 27) asm volatile("prefetch.global.L2 [%0];" :: "l"(lane < 25 ? (const char*)prm.wo + min(b * 25 + lane, 3135) * 128
                                                                          : lane == 25 ? (const char*)prm.b1 + (b % 28) * 128 : (const char*)prm.b2 + (b & 31) * 128));
            uint32_t tnext = clk32();
            #pragma unroll 1
            for (int i = 0; i < 28; i++) {
                while ((int)(clk32() - tnext) < 0) __nanosleep(40);
                asm volatile("prefetch.global.L2 [%0];" :: "l"(i < 14 ? p1 + i * 4096 : p2 + (i - 14) * 4096));
                tnext += PFPACE;
            }
            mbar_wait(BAR(B_EP), 0);
          }
          const uint32_t tag = lds1(sb + SM_EPOCH);
          const int h = warp & 1;
          const bool lead = elect_one();
          const uint32_t wo = lane * 132, l3 = lane < 16 ? 12288 : 0;
          uint32_t base = sb + SM_WQ, bl = BAR(B_OL), bf = BAR(B_OF), m = 4, rph = 0;
          #pragma unroll 1
          for (int e = 0; e < 2; e++) {
              uint32_t s8 = (e && !g1_on ? 4 + h : h) * 8;
              #pragma unroll 1
              do {
                  const uint32_t dst = base + s8 * 1792;
                  auto stale = [&]() {
                      uint32_t d;
                      asm volatile("{ .reg .b32 x, y, z, u;\n"
                                   "ld.shared.u32 x, [%1]; ld.shared.u32 y, [%1 + 4096]; ld.shared.u32 z, [%1 + 8192]; ld.shared.u32 u, [%2];\n"
                                   "lop3.b32 x, x, y, %3, 0x7e; lop3.b32 z, z, u, %3, 0x7e; lop3.b32 %0, x, z, 1, 0xa8; }"
                                   : "=r"(d) : "r"(dst + wo), "r"(dst + (wo + l3)), "r"(tag) : "memory");
                      return __any_sync(~0u, d);
                  };
                  mbar_wait_fast(bl + s8, m & 1);
                  bool bad = stale();
                  mbar_arrive_if(bf + s8, lead && !bad);
                  if (bad) {
                      const int p = 2 * __clz(m) - 2 + h;
                      RETRY_COUNT(!e ? 1 : p < 32 ? 0 : !g1_on ? 5 : p < 46 ? 2 : 6);
                      const int st = (p > 15) + (p > 31) + (p > 45), s = p - (st < 3 ? 16 * st : 46);
                      const char* src = (const char*)(!e ? &prm.sc->o[(a2s * 4 + p - 56) * 896] : st < 2 ? &prm.sc->hn[(rank * 16 + s) * 3584 + (g1j + 2 * st) * 896]
                                                                                                      : &prm.sc->g[(rank * 14 + s) * 3584 + (g2j + 2 * st - 4) * 896]);
                      int it = 0;
                      do {
                          if (++it > kSpinLimit) { TIMEOUT(111); break; }
                          const uint32_t* q = (const uint32_t*)(src + wo);
                          if (it > RELOAD1 && __any_sync(~0u, ((ld_rlx(q) ^ tag) | (ld_rlx(q + 1024) ^ tag) | (ld_rlx(q + 2048) ^ tag) | (ld_rlx(q + l3 / 4) ^ tag)) & 1)) continue;
                          if (lead) {
                              mbar_expect(BAR(B_RT + h), 14336);
                              bulk_g2s(dst, src, 14336, BAR(B_RT + h));
                          }
                          __syncwarp();
                          mbar_wait(BAR(B_RT + h), rph);
                          rph ^= 1;
                          bad = stale();
                      } while (bad);
                      mbar_arrive_if(bf + s8, lead);
                  }
                  s8 += 16;
                  if (s8 >= NB * 8) s8 -= NB * 8;
                  m >>= 1;
              } while (m != 1);
              base = sb + SM_B; bl = BAR(B_BL + h * NB); bf = BAR(B_BF); m = g1_on ? 0x4fe03f80 : 0x7f80;
          }
        }
    } else {
        asm volatile("setmaxnreg.inc.sync.aligned.u32 232;");
        asm volatile("barrier.cluster.wait.aligned;" ::: "memory");
        const int wg = warp >> 2, w = warp & 3;
        const int g = lane >> 2, t = lane & 3;
        uint32_t tag;
        __nv_bfloat16 bias1a, bias1b;
        {
            const uint64_t dw = make_desc(sb + (hg & 1) * 16, 0, true);
            uint32_t a[28][4];
            float sm[4][4] = {};
            {
                const int r = w * 16 + (lane & 15);
                const uint32_t rowa = sb + wg * 8192 + r * 128;
                #pragma unroll
                for (int k = 0; k < 28; k++) {
                    if (XW == 1 && (k & 3) == 0) mbar_wait(BAR(B_XF + (k >> 2)), 0);
                    if (XW == 2 && k == 0) mbar_wait(BAR(B_XF), 0);
                    if (XW == 2 && (k & 7) == 4) mbar_wait2(BAR(B_XF + (k >> 2)), 0, BAR(B_XF + (k >> 2) + 1), 0);
                    const uint32_t addr = rowa + (k >> 2) * 16384 + ((((k & 3) * 2 + (lane >> 4)) ^ (r & 7)) << 4);
                    uint32_t (&f)[4] = a[k];
                    asm volatile("ldmatrix.sync.aligned.m8n8.x4.shared.b16 {%0,%1,%2,%3}, [%4];"
                                 : "=r"(f[0]), "=r"(f[1]), "=r"(f[2]), "=r"(f[3]) : "r"(addr) : "memory");
                    if (XLAG == 0) mma16816(sm[k & 3], f[0], f[1], f[2], f[3], 0x3F803F80u, 0x3F803F80u);
                    else if (k >= 4) mma16816(sm[k & 3], a[k - 4][0], a[k - 4][1], a[k - 4][2], a[k - 4][3], 0x3F803F80u, 0x3F803F80u);
                }
                if (XLAG) {
                    #pragma unroll
                    for (int k = 24; k < 28; k++) mma16816(sm[k & 3], a[k][0], a[k][1], a[k][2], a[k][3], 0x3F803F80u, 0x3F803F80u);
                }
            }
            const float mean0 = ((sm[0][0] + sm[1][0]) + (sm[2][0] + sm[3][0])) * (1.f / kD);
            const float mean1 = ((sm[0][2] + sm[1][2]) + (sm[2][2] + sm[3][2])) * (1.f / kD);
            const uint32_t mb0 = pack_bf16(mean0, mean0), mb1 = pack_bf16(mean1, mean1);
            pair_arrive(B_XC);
            TR(1);
            float ak[28], av[28], aq[28];
            float ss0 = 0.f, ss1 = 0.f, ss2 = 0.f, ss3 = 0.f;
            uint32_t p0, p1;
            static_for<0, 7>([&](auto S_) {
                constexpr int s = decltype(S_)::value;
                #pragma unroll
                for (int q = 0; q < 4; q++) {
                    uint32_t (&f)[4] = a[s * 4 + q];
                    f[0] = sub_bf16x2(f[0], mb0); f[1] = sub_bf16x2(f[1], mb1);
                    f[2] = sub_bf16x2(f[2], mb0); f[3] = sub_bf16x2(f[3], mb1);
                }
                mbar_wait(BAR(B_WKVF + s), 0);
                wg_fence();
                static_for<0, 4>([&](auto Q_) {
                    constexpr int q = decltype(Q_)::value;
                    uint32_t (&f)[4] = a[s * 4 + q];
                    wgmma_rs_n56<SM_WKV + s * 16384 + q * 2048, (s | q) != 0>(ak, f[0], f[1], f[2], f[3], dw);
                    wgmma_rs_n56<SM_WKV + s * 16384 + q * 2048 + 8192, (s | q) != 0>(av, f[0], f[1], f[2], f[3], dw);
                });
                wg_commit();
                if (s == 4) { wg_wait<1>(); pair_arrive(B_KV3); }
                #pragma unroll
                for (int q = 0; q < 8; q++) {
                    const uint32_t u0 = a[s * 4 + q / 2][(q & 1) * 2], u1 = a[s * 4 + q / 2][(q & 1) * 2 + 1];
                    if (q == 0 && (VCH == 1 || (s & 1) || s == 0)) { p0 = sqr_bf16x2(u0); p1 = sqr_bf16x2(u1); }
                    else { p0 = sqa_bf16x2(u0, p0); p1 = sqa_bf16x2(u1, p1); }
                }
                if (VCH == 1 || !(s & 1)) { ss0 += bf_lo(p0); ss2 += bf_hi(p0); ss1 += bf_lo(p1); ss3 += bf_hi(p1); }
            });
            auto q_chunk = [&](auto K0_, auto K1_) {
                wg_fence();
                static_for<decltype(K0_)::value, decltype(K1_)::value>([&](auto K_) {
                    constexpr int k = decltype(K_)::value;
                    wgmma_rs_n56<SM_WQ + k * 2048, k != 0>(aq, a[k][0], a[k][1], a[k][2], a[k][3], dw);
                });
                wg_commit();
            };
            #define QCHUNK(k0, k1) q_chunk(std::integral_constant<int, k0>{}, std::integral_constant<int, k1>{})
            const float dl0 = mean0 - bf_lo(mb0), dl1 = mean1 - bf_lo(mb1);
            const float rs0 = rsq(fmaxf(quad_sum(ss0 + ss2) * (1.f / kD) - dl0 * dl0, 0.f) + kEps);
            const float rs1 = rsq(fmaxf(quad_sum(ss1 + ss3) * (1.f / kD) - dl1 * dl1, 0.f) + kEps);
            float rk[3][2];
            rk[1][0] = __shfl_sync(~0u, rs0, t * 8); rk[1][1] = __shfl_sync(~0u, rs0, t * 8 + 4);
            rk[2][0] = __shfl_sync(~0u, rs1, t * 8); rk[2][1] = __shfl_sync(~0u, rs1, t * 8 + 4);
            const uint32_t stg = sb + SM_STG + wg * 8192 + lane * 16;
            uint4* hp = (w == 3 ? &prm.sc->halo[((ti * 8 + hg) * 2 + wg) * 128] : (uint4*)(smem_raw + SM_STG + wg * 8192 + w * 2048)) + lane;
            mbar_wait2(BAR(B_EP), 0, BAR(B_WQF), 0);
            tag = lds1(sb + SM_EPOCH);
            QCHUNK(0, QC0);
            wg_wait<1>();
            reg_fence(ak); reg_fence(av);
            TR(2);
            uint32_t kf[3][7], vf[3][7];
            #pragma unroll
            for (int c = 0; c < 7; c++) {
                kf[2][c] = pack_bf16(ak[4 * c + 2], ak[4 * c + 3]);
                vf[2][c] = movm(pack_bf16(av[4 * c + 2], av[4 * c + 3]));
            }
            const uint32_t om = ~lane & 1;
            kf[2][0] = set_par(kf[2][0], om, tag); kf[2][4] = set_par(kf[2][4], om, tag);
            vf[2][1] = set_par(vf[2][1], om, tag); vf[2][5] = set_par(vf[2][5], om, tag);
            st_gen4(hp,      kf[2][0], kf[2][1], kf[2][2], kf[2][3]);
            st_gen4(hp + 32, kf[2][4], kf[2][5], kf[2][6], vf[2][0]);
            st_gen4(hp + 64, vf[2][1], vf[2][2], vf[2][3], vf[2][4]);
            st_gen4(hp + 96, vf[2][5], vf[2][6], __float_as_uint(rk[2][0]), __float_as_uint(rk[2][1]));
            pair_arrive(B_KVC);
            QCHUNK(QC0, QC1);
            #pragma unroll
            for (int c = 0; c < 7; c++) {
                kf[1][c] = pack_bf16(ak[4 * c], ak[4 * c + 1]);
                vf[1][c] = movm(pack_bf16(av[4 * c], av[4 * c + 1]));
            }
            QCHUNK(QC1, QC2);
            named_bar(1 + wg, 128);
            uint32_t* op = opaque_ptr((uint32_t*)&prm.sc->o[((ti * 2 + wg) * 56 + hg * 7) * 64] + w * 64 + lane);
            const uint32_t omk = opaque(((lane & 6) == w * 2 ? 0x11u << (lane & 1) * 8 : 0u) << (((lane >> 3) + (hg & 1)) & 3));
            uint32_t* ofl = opaque_ptr(&prm.sc->flag_o[((ti * 2 + wg) * 8 + hg) * FS]);
            QCHUNK(QC2, 28);
            #undef QCHUNK
            const bool gt0 = 2 * t > g, gt1 = 2 * t + 1 > g, no_prev = ti == 0 && w == 0;
            const float kf0 = gt0 ? rk[1][0] : rk[2][0], kf1 = gt1 ? rk[1][1] : rk[2][1];
            constexpr float kScale = 0.18898223650461362f * 1.4426950408889634f;
            const float sq0 = rs0 * kScale, sf0 = kf0 * (rs1 * kScale), sf1 = kf1 * (rs1 * kScale);
            const float NEG = -__int_as_float(0x7f800000);
            const float nb0 = gt0 && no_prev ? NEG : 0.f, nb1 = gt1 && no_prev ? NEG : 0.f;
            const uint32_t sr = stg + ((w + 3) & 3) * 2048, hbar = BAR(w == 0 ? B_HL + wg : B_EP);
            mbar_wait(BAR(B_EP), 0);
            wg_wait<0>();
            reg_fence(aq);
            warp_arrive(BAR(B_A1D));
            TR(3);
            uint32_t qf[8][2];
            #pragma unroll
            for (int c = 0; c < 7; c++) {
                qf[c + (c > 3)][0] = pack_bf16(aq[4 * c], aq[4 * c + 1]);
                qf[c + (c > 3)][1] = pack_bf16(aq[4 * c + 2], aq[4 * c + 3]);
            }
            qf[4][0] = t >= 2 ? qf[3][0] : 0u; qf[4][1] = t >= 2 ? qf[3][1] : 0u;
            qf[3][0] = t < 2 ? qf[3][0] : 0u;  qf[3][1] = t < 2 ? qf[3][1] : 0u;
            float sc[2][3][4];
            auto scores = [&](int n) {
                #pragma unroll
                for (int hd = 0; hd < 2; hd++) {
                    sc[hd][n][0] = sc[hd][n][1] = sc[hd][n][2] = sc[hd][n][3] = 0.f;
                    mma16816(sc[hd][n], qf[4 * hd][0], qf[4 * hd][1], qf[4 * hd + 1][0], qf[4 * hd + 1][1], kf[n][3 * hd], kf[n][3 * hd + 1]);
                    mma16816(sc[hd][n], qf[4 * hd + 2][0], qf[4 * hd + 2][1], qf[4 * hd + 3][0], qf[4 * hd + 3][1], kf[n][3 * hd + 2], kf[n][3 * hd + 3]);
                }
            };
            scores(1); scores(2);
            mbar_wait(hbar, 0);
            {
                const uint4 u0 = lds4(sr), u1 = lds4(sr + 512), u3 = lds4(sr + 1536), u2 = lds4(sr + 1024);
                kf[0][0] = u0.x; kf[0][1] = u0.y; kf[0][2] = u0.z; kf[0][3] = u0.w;
                kf[0][4] = u1.x; kf[0][5] = u1.y; kf[0][6] = u1.z; vf[0][0] = u1.w;
                vf[0][1] = u2.x; vf[0][2] = u2.y; vf[0][3] = u2.z; vf[0][4] = u2.w;
                vf[0][5] = u3.x; vf[0][6] = u3.y; rk[0][0] = __uint_as_float(u3.z); rk[0][1] = __uint_as_float(u3.w);
            }
            if ((tid & 127) == 0) st_flag(ofl, tag);
            TR(4);
            scores(0);
            const float ke0 = gt0 ? rk[0][0] : rk[1][0], ke1 = gt1 ? rk[0][1] : rk[1][1];
            const float se0 = ke0 * sq0, se1 = ke1 * sq0;
            uint32_t ow[7][2];
            #pragma unroll
            for (int hd = 0; hd < 2; hd++) {
                const int c0 = hd * 3;
                float (&sc_)[3][4] = sc[hd];
                const float e0 = fmaf(gt0 ? sc_[0][0] : sc_[1][0], se0, nb0), e1 = fmaf(gt1 ? sc_[0][1] : sc_[1][1], se1, nb1);
                const float f0 = (gt0 ? sc_[1][2] : sc_[2][2]) * sf0, f1 = (gt1 ? sc_[1][3] : sc_[2][3]) * sf1;
                const float me = quad_max(fmaxf(e0, e1)), mf = quad_max(fmaxf(f0, f1));
                const float p0 = ex2(e0 - me), p1 = ex2(e1 - me), r0 = ex2(f0 - mf), r1 = ex2(f1 - mf);
                const float ie = rcp(quad_sum(p0 + p1)), jf = rcp(quad_sum(r0 + r1));
                const uint32_t pp = pack_bf16(p0 * ke0 * ie, p1 * ke1 * ie), rp = pack_bf16(r0 * kf0 * jf, r1 * kf1 * jf);
                const uint32_t mk = (gt0 ? 0x0000ffffu : 0u) | (gt1 ? 0xffff0000u : 0u);
                #pragma unroll
                for (int c = 0; c < 4; c++) {
                    float o[4] = {0.f, 0.f, 0.f, 0.f};
                    mma16816(o, pp & mk, 0u, pp & ~mk, rp & mk, vf[0][c0 + c], vf[1][c0 + c]);
                    mma1688(o, 0u, rp & ~mk, vf[2][c0 + c]);
                    const uint32_t lo = pack_bf16(o[0], o[1]), hi = pack_bf16(o[2], o[3]);
                    if (hd == 1 && c == 0) { if (t >= 2) { ow[3][0] = lo; ow[3][1] = hi; } }
                    else { ow[c0 + c][0] = lo; ow[c0 + c][1] = hi; }
                }
            }
            #pragma unroll
            for (int c = 0; c < 7; c++) {
                stg1(op + c * 256,      set_par(ow[c][0], (omk >> (c & 3)) & 1, tag));
                stg1(op + c * 256 + 32, set_par(ow[c][1], (omk >> (8 + (c & 3))) & 1, tag));
            }
            TR(5);
        }
        float as[28], ac[28];
        uint32_t xch, peer_xch, gm[2][4], *gp1, *gp2;
        const uint32_t *hp, *ht;
        const uint2* hq;
        uint64_t da0, db0;
        const int cg2 = (g2j + 2 * wg) * 2 + (rank ^ 1), cg1 = (g1j + 2 * wg) * 2 + (rank ^ (g1f < 14));
        const bool lead = elect_one();
        {
            const int cg = a2j * 2 + wg;
            float acc2[28];
            mbar_wait(BAR(B_XRF), 0);
            {
                const uint32_t xa = sb + SM_XR + wg * 8192 + (w * 16 + (lane & 15)) * 128;
                #pragma unroll
                for (int c = 0; c < 4; c++) {
                    uint32_t xr[4];
                    asm volatile("ldmatrix.sync.aligned.m8n8.x4.shared.b16 {%0,%1,%2,%3}, [%4];"
                                 : "=r"(xr[0]), "=r"(xr[1]), "=r"(xr[2]), "=r"(xr[3])
                                 : "r"(xa + ((((c * 2 + wg + (lane >> 4)) ^ lane) & 7) << 4)) : "memory");
                    #pragma unroll
                    for (int e = 0; e < (c < 3 ? 4 : 2); e++) { acc2[8 * c + 2 * e] = bf_lo(xr[e]); acc2[8 * c + 2 * e + 1] = bf_hi(xr[e]); }
                }
            }
            uint32_t* spw = opaque_ptr(&prm.sc->stats[((a2s * 8 + cg) * 4 + w) * 32 + lane]);
            const uint32_t* spr = opaque_ptr(&prm.sc->stats[(a2s * 32 + w) * 32 + lane]);
            uint32_t* rp = opaque_ptr((uint32_t*)&prm.sc->rows[a2s * 64 + w * 16 + (t >> 1) * 8 + g] + (t & 1));
            const int cgs = cg ^ (a2s >> 4);
            uint32_t* np = opaque_ptr((uint32_t*)&prm.sc->hn[(a2s * 56 + cgs * 7) * 64] + w * 64 + lane);
            const uint64_t dwo = make_desc(sb + SM_WKV + wg * (28672 + 16), 0, true);
            const uint64_t doa = make_desc(sb + SM_WQ, 1024, false, 128);
            bias1a = prm.b1[g1f * 64 + w * 16 + g]; bias1b = prm.b1[g1f * 64 + w * 16 + 8 + g];
            const __nv_bfloat16 bias2 = prm.b2[ti * 128 + (w * 16 + (t >> 1) * 8 + g) * 2 + a2p];
            reg_fence(acc2);
            fence_async_smem();
            warp_arrive(BAR(B_XD));
            {
                xch = opaque(sb + SM_XCH + w * 1792 + lane * 16);
                asm volatile("mapa.shared::cluster.u32 %0, %1, %2;" : "=r"(peer_xch) : "r"(xch), "r"(rank ^ 1));
                const int hcg = cg2 ^ (g2s >> 4), hrg = (g2s & 1) * 4 + w;
                const uint32_t* hl = (const uint32_t*)&prm.sc->hn[((g2s >> 1) * 112 + hcg * 7) * 64 + hrg * 8];
                hp = opaque_ptr(hl + (g & 1) * 14336 + (g >> 1) * 4 + t);
                ht = opaque_ptr(hl + (lane & 1) * 14336 + min(lane >> 1, 6) * 256 + ((min(lane >> 1, 6) - (hcg & 1)) & 3) * 8 + hrg);
                hq = opaque_ptr(&prm.sc->rows[((g2s >> 1) * 2 + (g & 1)) * 64 + hrg * 8 + (g >> 1)]);
                gp1 = opaque_ptr((uint32_t*)&prm.sc->g[(g1f * 56 + cg1 * 7) * 64] + w * 64 + lane);
                gp2 = opaque_ptr((uint32_t*)(prm.out + (size_t)(g2s * 64 + w * 16 + lane / 7) * kD + cg2 * 56) + (lane % 7) * 4);
                da0 = make_desc(sb, 0, true); db0 = make_desc(sb + SM_B, 128, false);
            }
            static_for<0, 4>([&](auto P_) {
                constexpr int P = decltype(P_)::value;
                if (P == 0) mbar_wait(BAR(B_WOF), 0);
                if (P == 2) mbar_wait2(BAR(B_OF + P), 0, BAR(B_WOF + 1), 0); else mbar_wait(BAR(B_OF + P), 0);
                if (P == 0) TR(6);
                wg_fence();
                static_for<0, 7>([&](auto K_) { constexpr int k = decltype(K_)::value;
                    wgmma_ss_n56<P * 14336 + k * 2048, (P >> 1) * 57344 + (P & 1) * 14336 + k * 2048, 0>(acc2, doa, dwo); });
                if (P) wg_commit();
                if (P == 2) { wg_wait<1>(); warp_arrive(BAR(B_OC)); }
            });
            wg_wait<0>();
            reg_fence(acc2);
            TR(7);
            float s0 = 0.f, s1 = 0.f, q0 = 0.f, q1 = 0.f;
            #pragma unroll
            for (int c = 0; c < 7; c++) {
                s0 += acc2[4 * c] + acc2[4 * c + 1];     q0 = fmaf(acc2[4 * c], acc2[4 * c], fmaf(acc2[4 * c + 1], acc2[4 * c + 1], q0));
                s1 += acc2[4 * c + 2] + acc2[4 * c + 3]; q1 = fmaf(acc2[4 * c + 2], acc2[4 * c + 2], fmaf(acc2[4 * c + 3], acc2[4 * c + 3], q1));
            }
            const bool th = t >= 2, to = t & 1;
            const float sa = (th ? s1 : s0) + __shfl_xor_sync(~0u, th ? s0 : s1, 2), qa = (th ? q1 : q0) + __shfl_xor_sync(~0u, th ? q0 : q1, 2);
            const float part = (to ? qa : sa) + __shfl_xor_sync(~0u, to ? sa : qa, 1);
            stg1(spw, set_par(__float_as_uint(part), 1u, tag));
            const uint32_t tpoll = clk32() + SDELAY;
            TR(8);
            warp_arrive(BAR(B_HD));
            uint32_t nm[2][4], us[8];
            spin_until(tpoll);
            #pragma unroll
            for (int i = 0; i < 8; i++) us[i] = ld_rlx(spr + i * 128);
            #pragma unroll
            for (int i = 0; i < 8; i++) {
                nm[i >> 2][i & 3] = lane == ((i - (cgs & 1)) & 3) * 8 + w * 2 + (i >> 2);
                gm[i >> 2][i & 3] = opaque(lane == ((i - (cg1 & 1)) & 3) * 8 + w * 2 + (i >> 2));
            }
            #pragma unroll
            for (int c = 0; c < 28; c++) { ac[c] = 0.5f * __bfloat162float(c & 2 ? bias1b : bias1a); as[c] = 0.f; }
            reg_fence(as); reg_fence(ac);
            {
                int it = 0;
                while (true) {
                    uint32_t bad = 0;
                    #pragma unroll
                    for (int i = 0; i < 8; i++) bad |= us[i] ^ tag;
                    if (!__any_sync(~0u, bad & 1)) break;
                    RETRY_COUNT(3);
                    if (++it > kSpinLimit) { TIMEOUT(103); break; }
                    #pragma unroll
                    for (int i = 0; i < 8; i++) us[i] = ld_rlx(spr + i * 128);
                }
            }
            TR(9);
            const float tot = (((__uint_as_float(us[0]) + __uint_as_float(us[1])) + (__uint_as_float(us[2]) + __uint_as_float(us[3])))
                            + ((__uint_as_float(us[4]) + __uint_as_float(us[5])) + (__uint_as_float(us[6]) + __uint_as_float(us[7])))) * (1.f / kD);
            const float oth = __shfl_xor_sync(~0u, tot, 1);
            const float mean = to ? oth : tot;
            const float var = fmaxf(fmaf(-mean, mean, to ? tot : oth), 0.f);
            const float r1 = rsq(var + kEps);
            const float rra = 0.5f * r1 * rsq(fmaf(var * r1, r1, kEps)), mra = -mean * rra;
            const float rrb = __shfl_xor_sync(~0u, rra, 2), mrb = __shfl_xor_sync(~0u, mra, 2);
            const float rr0 = th ? rrb : rra, mr0 = th ? mrb : mra, rr1 = th ? rra : rrb, mr1 = th ? mra : mrb;
            #pragma unroll
            for (int c = 0; c < 7; c++) {
                stg1(np + c * 256,      set_par(pack_bf16(fmaf(acc2[4 * c], rr0, mr0), fmaf(acc2[4 * c + 1], rr0, mr0)), nm[0][c & 3], tag));
                stg1(np + c * 256 + 32, set_par(pack_bf16(fmaf(acc2[4 * c + 2], rr1, mr1), fmaf(acc2[4 * c + 3], rr1, mr1)), nm[1][c & 3], tag));
            }
            TR(10);
            if (cg == 0) stg1(rp, set_par(__float_as_uint(to ? mean + __bfloat162float(bias2) : rcp(rra)), 1u, tag));
        }
        auto send = [&]() {
            const uint32_t rf = pbar0 + (B_RF + warp) * 8;
            #pragma unroll
            for (int c = 0; c < 4; c++) {
                const uint32_t p0 = pack_bf16(as[8 * c], as[8 * c + 1]), p1 = pack_bf16(as[8 * c + 2], as[8 * c + 3]);
                if (c < 3) {
                    const uint32_t p2 = pack_bf16(as[8 * c + 4], as[8 * c + 5]), p3 = pack_bf16(as[8 * c + 6], as[8 * c + 7]);
                    asm volatile("st.async.shared::cluster.mbarrier::complete_tx::bytes.v4.b32 [%0], {%1,%2,%3,%4}, [%5];"
                                 :: "r"(peer_xch + c * 512), "r"(p0), "r"(p1), "r"(p2), "r"(p3), "r"(rf) : "memory");
                } else {
                    asm volatile("st.async.shared::cluster.mbarrier::complete_tx::bytes.v2.b32 [%0], {%1,%2}, [%3];"
                                 :: "r"(peer_xch + 1536 - lane * 8), "r"(p0), "r"(p1), "r"(rf) : "memory");
                }
            }
        };
        auto receive = [&](uint32_t (&pk)[14], uint32_t phase) {
            mbar_wait(BAR(B_RF + warp), phase);
            #pragma unroll
            for (int c = 0; c < 3; c++) { const uint4 u = lds4(xch + c * 512); pk[4 * c] = u.x; pk[4 * c + 1] = u.y; pk[4 * c + 2] = u.z; pk[4 * c + 3] = u.w; }
            const uint2 u = lds2(xch + 1536 - lane * 8); pk[12] = u.x; pk[13] = u.y;
        };
        uint2 rw[2]; uint32_t tw;
        auto load_rows = [&]() { tw = ld_rlx(ht); rw[0] = ld_rlx2(hq); rw[1] = ld_rlx2(hq + 4); };
        rw[0] = rw[1] = make_uint2(0u, 0u); tw = ~tag;
        if (!g1_on) mbar_wait(BAR(B_GD), 0);
        #pragma unroll 1
        for (int ge = g1_on ? 0 : 1;; ge++) {
            if (ge) {
                int it = 0;
                while (__any_sync(~0u, ((tw ^ tag) | (rw[0].x ^ tag) | (rw[0].y ^ tag) | (rw[1].x ^ tag) | (rw[1].y ^ tag)) & 1)) {
                    if (++it > kSpinLimit) { TIMEOUT(110); break; }
                    load_rows();
                }
                uint32_t hw[14];
                #pragma unroll
                for (int c = 0; c < 14; c++) hw[c] = ld_rlx(hp + (c >> 1) * 256 + (c & 1) * 16);
                #pragma unroll
                for (int c = 0; c < 14; c++) {
                    ac[2 * c]     = fmaf(bf_lo(hw[c]), __uint_as_float(rw[c & 1].x), __uint_as_float(rw[c & 1].y));
                    ac[2 * c + 1] = fmaf(bf_hi(hw[c]), __uint_as_float(rw[c & 1].x), __uint_as_float(rw[c & 1].y));
                    as[2 * c] = as[2 * c + 1] = 0.f;
                }
                reg_fence(as); reg_fence(ac);
            }
            const int use = ge * 2 + wg;
            int entry = ge ? 0 : 2 - wg;
            uint64_t da = da0 + (ge ? 1 : wg ? NR - 6 : -10) * 512;
            bool rel = lead && use == 1;
            const uint32_t xfree = BAR(use > (g1_on ? 0 : 2) ? B_RE + use - 1 : B_PD);
            mbar_wait(BAR(B_AF), 0);
            if (use == 1) {
                uint32_t af[NR * 4][4];
                mbar_wait(BAR(B_GO), 0);
                const uint32_t tp = lds1(sb + SM_TG + 4) + PLOFF;
                int it = 0;
                while ((int)(gtime32() - tp) < 0 && ++it < 256) __nanosleep(20);
                const uint32_t la = sb + ((lane >> 4) * 8 + (lane & 7)) * 128 + (((w * 2 + ((lane >> 3) & 1)) ^ (lane & 7)) << 4);
                #pragma unroll
                for (int k = 0; k < NR * 4; k++)
                    asm volatile("ldmatrix.sync.aligned.m8n8.x4.trans.shared.b16 {%0,%1,%2,%3}, [%4];"
                                 : "=r"(af[k][0]), "=r"(af[k][1]), "=r"(af[k][2]), "=r"(af[k][3]) : "r"(la + k * 2048) : "memory");
                __syncwarp();
                mbar_arrive_if(BAR(B_PL), lead);
                named_bar(4, 256);
                static_for<0, NR>([&](auto I_) {
                    constexpr int i = decltype(I_)::value, sl = (16 + i) % NB, o = sl * 14336;
                    mbar_wait_fast(BAR(B_BF + sl), (16 + i) / NB & 1);
                    wg_fence();
                    wgmma_rs_n112<o,       1>(as, ac, af[4 * i][0], af[4 * i][1], af[4 * i][2], af[4 * i][3], db0);
                    wgmma_rs_n112<o + 256, 1>(as, ac, af[4 * i + 1][0], af[4 * i + 1][1], af[4 * i + 1][2], af[4 * i + 1][3], db0);
                    wgmma_rs_n112<o + 512, 1>(as, ac, af[4 * i + 2][0], af[4 * i + 2][1], af[4 * i + 2][2], af[4 * i + 2][3], db0);
                    wgmma_rs_n112<o + 768, 1>(as, ac, af[4 * i + 3][0], af[4 * i + 3][1], af[4 * i + 3][2], af[4 * i + 3][3], db0);
                    wg_commit();
                    if (i) { wg_wait<1>(); mbar_arrive_if(BAR(B_BE + (15 + i) % (2 * NB)), lead); }
                });
            } else if (ge && (wg || g1_on)) named_bar(5 - wg, 256);
            TR(11 + ge * 4);
            auto step = [&](auto I_) {
                constexpr int i = decltype(I_)::value, sl = (4 + i) % NB, ao = i * 8192, bo = sl * 14336;
                mbar_wait_fast(BAR(B_BF + sl), (4 + i) / NB & 1);
                wg_fence();
                wgmma_ss_n112<ao,        bo,       1>(as, ac, da, db0);
                wgmma_ss_n112<ao + 2048, bo + 256, 1>(as, ac, da, db0);
                wgmma_ss_n112<ao + 4096, bo + 512, 1>(as, ac, da, db0);
                wgmma_ss_n112<ao + 6144, bo + 768, 1>(as, ac, da, db0);
                wg_commit();
                if (i == 11 && entry < 0) named_arrive(4, 256);
                if (i == 13 && (use == 1 || use == 2)) named_arrive(4 + wg, 256);
                wg_wait<1>();
                mbar_arrive_if(BAR(B_BE + (3 + i) % (2 * NB)), rel);
                rel = lead;
            };
            #pragma unroll 1
            while (true) {
                if (entry < 1) static_for<0, 6>(step);
                if (entry < 2) static_for<6, 10>(step);
                static_for<10, 12>(step);
                if (entry < 0) break;
                static_for<12, 14>(step);
                if (entry < 2) break;
                entry = -1; da += 14 * 512;
            }
            const uint32_t prev = BAR(B_BE + (use ? 3 : 1));
            const bool xok = mbar_test(xfree, 0);
            wg_wait<0>();
            reg_fence(as); reg_fence(ac);
            mbar_arrive_if(prev, lead);
            if (!xok) mbar_wait(xfree, 0);
            if (ge) break;
            send();
            load_rows();
            TR(12);
            uint32_t pk[14];
            receive(pk, 0);
            TR(13);
            #pragma unroll
            for (int c = 0; c < 14; c++) {
                float r[2];
                #pragma unroll
                for (int e = 0; e < 2; e++) {
                    const float u = ac[2 * c + e] + (e ? bf_hi(pk[c]) : bf_lo(pk[c]));
                    r[e] = fmaf(u, tanh_hw(u * fmaf(u * u, 8.f * 0.7978845608f * 0.044715f, 2.f * 0.7978845608f)), u);
                }
                stg1(gp1 + (c >> 1) * 256 + (c & 1) * 32, set_par(pack_bf16(r[0], r[1]), gm[c & 1][(c >> 1) & 3], tag));
            }
            named_bar(1 + wg, 128);
            if (w == 0 && lane == 0) {
                asm volatile("st.shared.u32 [%0], %1;" :: "r"(sb + SM_TG + 8 + wg * 4), "r"(clk32() + (wg ? XSPECB : XSPEC)) : "memory");
                mbar_arrive(BAR(B_GD + wg));
            }
            if (lead) mbar_expect(BAR(B_RF + warp), 1792);
            mbar_arrive_remote_if(pbar0 + (B_RE + wg) * 8, lead);
            TR(14);
        }
        uint32_t po[14], pk[14];
        if (!wg) sleep_until(clk32() + w * STAG2);
        send();
        #pragma unroll
        for (int c = 0; c < 14; c++) po[c] = opaque(pack_bf16(ac[2 * c], ac[2 * c + 1]));
        TR(16);
        receive(pk, g1_on);
        TR(17);
        #pragma unroll
        for (int c = 0; c < 14; c++) pk[c] = add_bf16x2(po[c], pk[c]);
        __syncwarp();
        const uint32_t sa = xch - lane * 16 + (lane & 15) * 112 + (lane >> 4) * 16;
        #pragma unroll
        for (int m = 0; m < 3; m++)
            asm volatile("stmatrix.sync.aligned.m8n8.x4.shared.b16 [%0], {%1,%2,%3,%4};"
                         :: "r"(sa + m * 32), "r"(pk[4 * m]), "r"(pk[4 * m + 1]), "r"(pk[4 * m + 2]), "r"(pk[4 * m + 3]) : "memory");
        asm volatile("stmatrix.sync.aligned.m8n8.x2.shared.b16 [%0], {%1,%2};" :: "r"(sa + 96), "r"(pk[12]), "r"(pk[13]) : "memory");
        __syncwarp();
        if (lane < 28) {
            #pragma unroll
            for (int i = 0; i < 4; i++) { const uint4 u = lds4(xch + i * 448); stg4(gp2 + i * 896, u.x, u.y, u.z, u.w); }
        }
        __syncwarp();
        mbar_arrive_remote_if(pbar0 + (B_RE + 2) * 8, lead && wg == 0);
        TR(18);
        if (tid == 128) TRG(62);
        if (b == 0 && tid == 128) prm.sc->epoch = tag;
    }
}

typedef CUresult (*EncodeFn)(CUtensorMap*, CUtensorMapDataType, cuuint32_t, void*, const cuuint64_t*, const cuuint64_t*,
                             const cuuint32_t*, const cuuint32_t*, CUtensorMapInterleave, CUtensorMapSwizzle,
                             CUtensorMapL2promotion, CUtensorMapFloatOOBfill);

void make_map(EncodeFn enc, CUtensorMap* m, const void* base, uint64_t cols, uint64_t rows, uint32_t box_rows) {
    cuuint64_t dims[2] = {cols, rows};
    cuuint64_t strides[1] = {cols * 2};
    cuuint32_t box[2] = {64, box_rows};
    cuuint32_t es[2] = {1, 1};
    enc(m, CU_TENSOR_MAP_DATA_TYPE_BFLOAT16, 2, const_cast<void*>(base), dims, strides, box, es, CU_TENSOR_MAP_INTERLEAVE_NONE,
        CU_TENSOR_MAP_SWIZZLE_128B, CU_TENSOR_MAP_L2_PROMOTION_L2_128B, CU_TENSOR_MAP_FLOAT_OOB_FILL_NONE);
}

}

extern "C" void kernel_launch(void* const* d_in, const int* in_sizes, int n_in, void* d_out, int out_size) {
    (void)in_sizes; (void)n_in; (void)out_size;
    void* fn = nullptr;
    cudaDriverEntryPointQueryResult qr;
    cudaGetDriverEntryPoint("cuTensorMapEncodeTiled", &fn, cudaEnableDefault, &qr);
    EncodeFn enc = (EncodeFn)fn;
    CUtensorMap mX2, mX, mWqkv, mWo, mW1, mW2;
    {
        cuuint64_t dims[3] = {kD, kS / 2, 2}, strides[2] = {4 * kD, 2 * kD};
        cuuint32_t box[3] = {64, 64, 2}, es[3] = {1, 1, 1};
        enc(&mX2, CU_TENSOR_MAP_DATA_TYPE_BFLOAT16, 3, d_in[0], dims, strides, box, es, CU_TENSOR_MAP_INTERLEAVE_NONE,
            CU_TENSOR_MAP_SWIZZLE_128B, CU_TENSOR_MAP_L2_PROMOTION_L2_128B, CU_TENSOR_MAP_FLOAT_OOB_FILL_NONE);
    }
    make_map(enc, &mX, d_in[0], 2 * kD, kS / 2, 64);
    make_map(enc, &mWqkv, d_in[1], 3 * kD, kD, 64);
    make_map(enc, &mWo, d_in[2], kD, kD, 224);
    make_map(enc, &mW1, d_in[4], 2 * kF, kS / 2, 64);
    make_map(enc, &mW2, d_in[6], kS, kF, 64);
    Params prm;
    prm.x = (const __nv_bfloat16*)d_in[0];
    prm.wqkv = (const __nv_bfloat16*)d_in[1];
    prm.wo = (const __nv_bfloat16*)d_in[2];
    prm.w1 = (const __nv_bfloat16*)d_in[4];
    prm.b1 = (const __nv_bfloat16*)d_in[5];
    prm.w2 = (const __nv_bfloat16*)d_in[6];
    prm.b2 = (const __nv_bfloat16*)d_in[7];
    prm.out = (__nv_bfloat16*)d_out;
    cudaGetSymbolAddress((void**)&prm.sc, g_scratch);
    cudaFuncSetAttribute(fused_kernel, cudaFuncAttributeMaxDynamicSharedMemorySize, SM_TOTAL);
    fused_kernel<<<128, 384, SM_TOTAL, cudaStreamPerThread>>>(prm, mX2, mX, mWqkv, mWo, mW1, mW2);
}
```

```cpp
#include <cuda_runtime.h>
#include <cuda.h>
#include <cuda_bf16.h>
#include <stdint.h>
#include <type_traits>

namespace {

constexpr int kS = 2048, kD = 448, kF = 1792;
constexpr float kEps = 1e-5f;

#define FS 32
struct Scratch {
    uint4    o[32 * 56 * 64];
    uint4    hn[32 * 56 * 64];
    uint4    g[28 * 56 * 64];
    uint4    halo[16 * 8 * 2 * 4 * 32];
    uint32_t stats[32 * 8 * 4 * 32];
    uint2    rows[32 * 64];
    uint32_t flag_o[16 * 8 * FS];
    uint32_t flag_h[32 * 4 * FS];
    uint32_t epoch;
};
__device__ __align__(1024) Scratch g_scratch;
#define TIMEOUT(code)
#define RETRY_COUNT(i)
#define CAP_DECL(n, k)
#define CAP(n)
#define CAP_SKIP(n)
#define EV(i, dep)
#define TR2(idx)
#define TR(idx)
#define TRW(idx)
#define TRG(idx)

constexpr uint32_t SM_WKV  = 114688;
constexpr uint32_t SM_XR   = 24576;
constexpr uint32_t SM_STG  = 40960;
constexpr uint32_t SM_WQ   = 57344;
constexpr uint32_t SM_XCH  = 0;
constexpr uint32_t SM_B    = 131072;
constexpr uint32_t SM_BAR  = 231424;
constexpr uint32_t SM_TOTAL = SM_BAR + 1024;
constexpr int NB = 7;
#define SH1 0
#define SH2 0
#define SH2N 5
#define SH3 0
#define NSPEC 4
#define XSPEC 500
#define C2 0
#define C3 0
#define CN2 7200
#define CN3 10900
constexpr int B_XF = 0, B_WKVF = 7, B_WQF = 14, B_XRF = 15, B_WOF = 16,
              B_XC = 18, B_KV3 = 19, B_KVC = 20,
              B_A1D = 21, B_XD = 22, B_OC = 23,
              B_BE = 24  , B_RE = B_BE + 2 * NB,
              B_PL = B_RE + 3, B_AF = B_PL + 1, B_BL = B_AF + 1  , B_OL = B_BL + 2 * NB  ,
              B_BF = B_OL + 4  , B_OF = B_BF + NB, B_RF = B_OF + 4, B_EP = B_RF + 8, B_PD = B_EP + 1, B_RT = B_PD + 1, B_HL = B_RT + 2,
              B_HD = B_HL + 2  , B_GO = B_HD + 1, B_GD = B_GO + 1, B_COUNT = B_GD + 2;
#define WEARLY 6
#define PF0 126
#define TMPF 2
#define RSTE 2
#define POLLP 1
#define PROBEP 1
#define LOADP 1
#define LOADW 64
#define NOB 0
#define AEARLY 5
#define W1PACE 400
#define W2PACE 200
#define PFPACE 230
#define PFBAR (B_XF + 6)
#define DELTA 1600
#define DELTA2 DELTA
#define BPACE 230
#define BURST 2
#define W1OFF 350
#define W2OFF 2900
#define XPACE 0
#define PSTAG 200
constexpr uint32_t SM_EPOCH = SM_BAR + B_COUNT * 8, SM_TG = SM_EPOCH + 4  , SM_TG2 = SM_TG + 16  , SM_TR = SM_BAR + 768;

#define HDELAY 0
#define QC0 4
#define QC1 10
#define QC2 16
#define HPOS 1
#define XSPECB 850
#define PACE1 120
#define PACE2 400
#define RELOAD1 1
#define VCH 1
#define SOFF 0
#define XW 1
#define XLAG 0
#define PFX 3
#define PFD 250
#define SDELAY 300
#define PDELAY 500
#define NPRE 10
#define PREPACE 0
#define AFIRST 1
#define DELTAO 832
#define NS 0
#define GCH 14
#define OCH 14
#define ICH 14
#define PACKO
#define NR 8
#define HMODE 2
#define HOFF0 (-100)
#define HOFF1 900
#define STAG1 0
#define STAG2 400
#define PLOFF (-250)
#define HSRC h
#define WO1 1
#define WOD 300
#define WOP 400
#define WOP0 0
#define KV5 1
#define W1Q 3
#define APOS1 ((1ull << 4) | (1ull << 8) | (1ull << 12) | (1ull << 5) | (1ull << 9) | (1ull << 13))
#define APOS2 (0x5555555ull << 17)
constexpr uint32_t seg_mask(int h, int p0, int p1) {
    uint32_t m = 0; int n = 0;
    for (int p = p0; p < p1; p++) if ((p & 1) == h) m |= (uint32_t)(((APOS1 | APOS2) >> p) & 1) << n++;
    return m | 1u << n;
}
constexpr uint64_t seg_masks(int h) {
    return 2 | (uint64_t)seg_mask(h, 0, 16) << 10 | (uint64_t)seg_mask(h, 16, 32) << 20
             | (uint64_t)seg_mask(h, 32, 46) << 30 | (uint64_t)seg_mask(h, 46, 60) << 40;
}
constexpr uint64_t kSegMasks0 = seg_masks(0), kSegMasks1 = seg_masks(1);

constexpr int kSpinLimit = 1 << 15;
__device__ __forceinline__ bool elect_one() {
    uint32_t p;
    asm volatile("{ .reg .pred P; elect.sync _|P, 0xffffffff; selp.u32 %0, 1, 0, P; }" : "=r"(p));
    return p;
}
__device__ __forceinline__ void mbar_init(uint32_t bar, uint32_t cnt) { asm volatile("mbarrier.init.shared::cta.b64 [%0], %1;" :: "r"(bar), "r"(cnt)); }
__device__ __forceinline__ void mbar_expect(uint32_t bar, uint32_t bytes) { asm volatile("mbarrier.arrive.expect_tx.shared::cta.b64 _, [%0], %1;" :: "r"(bar), "r"(bytes) : "memory"); }
__device__ __forceinline__ void mbar_expect_more(uint32_t bar, uint32_t bytes) { asm volatile("mbarrier.expect_tx.relaxed.cta.shared::cta.b64 [%0], %1;" :: "r"(bar), "r"(bytes) : "memory"); }
__device__ __forceinline__ void mbar_arrive(uint32_t bar) { asm volatile("mbarrier.arrive.shared::cta.b64 _, [%0];" :: "r"(bar) : "memory"); }
__device__ __forceinline__ void mbar_wait(uint32_t bar, uint32_t parity) {
    uint32_t ok; int it = 0;
    do {
        asm volatile("{ .reg .pred p; mbarrier.try_wait.parity.shared::cta.b64 p, [%1], %2; selp.u32 %0, 1, 0, p; }"
                     : "=r"(ok) : "r"(bar), "r"(parity) : "memory");
        if (++it > kSpinLimit) { TIMEOUT((bar & 1023) >> 3); break; }
    } while (!ok);
}
__device__ __forceinline__ bool mbar_try(uint32_t bar, uint32_t parity) {
    uint32_t ok;
    asm volatile("{ .reg .pred p; mbarrier.try_wait.parity.shared::cta.b64 p, [%1], %2; selp.u32 %0, 1, 0, p; }" : "=r"(ok) : "r"(bar), "r"(parity) : "memory");
    return ok;
}
__device__ __forceinline__ bool mbar_test(uint32_t bar, uint32_t parity) {
    uint32_t ok;
    asm volatile("{ .reg .pred p; mbarrier.test_wait.parity.shared::cta.b64 p, [%1], %2; selp.u32 %0, 1, 0, p; }" : "=r"(ok) : "r"(bar), "r"(parity) : "memory");
    return ok;
}
__device__ __forceinline__ void mbar_wait_fast(uint32_t bar, uint32_t parity) { if (!mbar_try(bar, parity)) mbar_wait(bar, parity); }
__device__ __forceinline__ void mbar_wait2(uint32_t bar0, uint32_t par0, uint32_t bar1, uint32_t par1) {
    uint32_t ok; int it = 0;
    do {
        asm volatile("{ .reg .pred p, q; mbarrier.try_wait.parity.shared::cta.b64 p, [%1], %2;\n"
                     "mbarrier.try_wait.parity.shared::cta.b64 q, [%3], %4; and.pred p, p, q; selp.u32 %0, 1, 0, p; }"
                     : "=r"(ok) : "r"(bar0), "r"(par0), "r"(bar1), "r"(par1) : "memory");
        if (++it > kSpinLimit) { TIMEOUT((bar0 & 1023) >> 3); break; }
    } while (!ok);
}
__device__ __forceinline__ void sched_fence(uint32_t v) {
    asm volatile("{ .reg .pred p; .reg .b32 x; mov.b32 x, %0;\nL: setp.eq.u32 p, x, 0xffffffff; @p mov.u32 x, %%clock; @p bra L; }" :: "r"(v) : "memory");
}
template <int N> __device__ __forceinline__ void reg_fence(float (&d)[N]) {
    #pragma unroll
    for (int i = 0; i < N; i++) asm volatile("" : "+f"(d[i]) :: "memory");
}
__device__ __forceinline__ void mbar_wait_cluster(uint32_t bar, uint32_t parity) {
    uint32_t ok; int it = 0;
    do {
        asm volatile("{ .reg .pred p; mbarrier.try_wait.parity.acquire.cluster.shared::cta.b64 p, [%1], %2; selp.u32 %0, 1, 0, p; }"
                     : "=r"(ok) : "r"(bar), "r"(parity) : "memory");
        if (++it > kSpinLimit) { TIMEOUT((bar & 1023) >> 3); break; }
    } while (!ok);
}
__device__ __forceinline__ void mbar_arrive_if(uint32_t bar, bool pred) {
    asm volatile("{ .reg .pred p; setp.ne.u32 p, %1, 0; @p mbarrier.arrive.shared::cta.b64 _, [%0]; }" :: "r"(bar), "r"((uint32_t)pred) : "memory");
}
template <int P> __device__ __forceinline__ void tick() {
    if (P > 1) { const uint32_t t = ((uint32_t)clock() | (P - 1)) + 1; while ((int)((uint32_t)clock() - t) < 0) {} }
}
__device__ __forceinline__ void warp_arrive(uint32_t bar) { __syncwarp(); if (elect_one()) mbar_arrive(bar); }
__device__ __forceinline__ void tma2d(uint32_t dst, const CUtensorMap* m, int c0, int c1, uint32_t bar) {
    asm volatile("cp.async.bulk.tensor.2d.shared::cluster.global.mbarrier::complete_tx::bytes [%0], [%1, {%3, %4}], [%2];"
                 :: "r"(dst), "l"(m), "r"(bar), "r"(c0), "r"(c1) : "memory");
}
__device__ __forceinline__ void tma3d(uint32_t dst, const CUtensorMap* m, int c0, int c1, int c2, uint32_t bar) {
    asm volatile("cp.async.bulk.tensor.3d.shared::cluster.global.mbarrier::complete_tx::bytes [%0], [%1, {%3, %4, %5}], [%2];"
                 :: "r"(dst), "l"(m), "r"(bar), "r"(c0), "r"(c1), "r"(c2) : "memory");
}
__device__ __forceinline__ void tma2d_mc(uint32_t dst, const CUtensorMap* m, int c0, int c1, uint32_t bar) {
    asm volatile("cp.async.bulk.tensor.2d.shared::cluster.global.mbarrier::complete_tx::bytes.multicast::cluster [%0], [%1, {%3, %4}], [%2], %5;"
                 :: "r"(dst), "l"(m), "r"(bar), "r"(c0), "r"(c1), "h"((uint16_t)3) : "memory");
}
__device__ __forceinline__ void bulk_g2s_mc(uint32_t dst, const void* src, uint32_t bytes, uint32_t bar) {
    asm volatile("cp.async.bulk.shared::cluster.global.mbarrier::complete_tx::bytes.multicast::cluster [%0], [%1], %2, [%3], %4;"
                 :: "r"(dst), "l"(src), "r"(bytes), "r"(bar), "h"((uint16_t)3) : "memory");
}
__device__ __forceinline__ void mbar_arrive_remote_if(uint32_t cluster_bar, bool pred) {
    asm volatile("{ .reg .pred p; setp.ne.u32 p, %1, 0; @p mbarrier.arrive.shared::cluster.b64 _, [%0]; }" :: "r"(cluster_bar), "r"((uint32_t)pred) : "memory");
}
__device__ __forceinline__ void bulk_g2s(uint32_t dst, const void* src, uint32_t bytes, uint32_t bar) {
    asm volatile("cp.async.bulk.shared::cluster.global.mbarrier::complete_tx::bytes [%0], [%1], %2, [%3];"
                 :: "r"(dst), "l"(src), "r"(bytes), "r"(bar) : "memory");
}
__device__ __forceinline__ void wg_fence()  { asm volatile("wgmma.fence.sync.aligned;" ::: "memory"); }
__device__ __forceinline__ void wg_commit() { asm volatile("wgmma.commit_group.sync.aligned;" ::: "memory"); }
template <int N> __device__ __forceinline__ void wg_wait() { asm volatile("wgmma.wait_group.sync.aligned %0;" :: "n"(N) : "memory"); }
__device__ __forceinline__ void named_bar(int id, int n) { asm volatile("bar.sync %0, %1;" :: "r"(id), "r"(n) : "memory"); }
__device__ __forceinline__ void named_arrive(int id, int n) { asm volatile("bar.arrive %0, %1;" :: "r"(id), "r"(n) : "memory"); }
__device__ __forceinline__ bool mbar_try2(uint32_t bar0, uint32_t par0, uint32_t bar1, uint32_t par1) {
    uint32_t ok;
    asm volatile("{ .reg .pred p, q; mbarrier.test_wait.parity.shared::cta.b64 p, [%1], %2;\n"
                 "mbarrier.test_wait.parity.shared::cta.b64 q, [%3], %4; and.pred p, p, q; selp.u32 %0, 1, 0, p; }"
                 : "=r"(ok) : "r"(bar0), "r"(par0), "r"(bar1), "r"(par1) : "memory");
    return ok;
}
__device__ __forceinline__ void fence_gpu() { asm volatile("fence.release.gpu;" ::: "memory"); }
__device__ __forceinline__ void fence_async_global() { asm volatile("fence.proxy.async.global;" ::: "memory"); }
__device__ __forceinline__ void fence_async_smem() { asm volatile("fence.proxy.async.shared::cta;" ::: "memory"); }
__device__ __forceinline__ uint32_t gtime32() { uint64_t t; asm volatile("mov.u64 %0, %%globaltimer;" : "=l"(t) :: "memory"); return (uint32_t)t; }
__device__ __forceinline__ uint32_t clk32() { uint64_t t; asm volatile("mov.u64 %0, %%clock64;" : "=l"(t) :: "memory"); return (uint32_t)t; }
__device__ __forceinline__ void spin_until(uint32_t t) { while ((int)(clk32() - t) < 0) {} }
#define SLEEPNS 20
__device__ __forceinline__ void sleep_until(uint32_t t) { while ((int)(clk32() - t) < 0) { if (SLEEPNS) __nanosleep(SLEEPNS); } }
__device__ __forceinline__ void st_flag(uint32_t* p, uint32_t v) {
    const uint64_t w = ((uint64_t)gtime32() << 32) | v;
    asm volatile("st.relaxed.gpu.global.u64 [%0], %1;" :: "l"(p), "l"(w) : "memory");
}
__device__ __forceinline__ void ld_flag_if(uint64_t& v, const uint32_t* p, bool pred) {
    asm volatile("{ .reg .pred p; setp.ne.u32 p, %2, 0; @p ld.relaxed.gpu.global.u64 %0, [%1]; }" : "+l"(v) : "l"(p), "r"((uint32_t)pred) : "memory");
}
__device__ __forceinline__ uint32_t ld_acq(const uint32_t* p) { uint32_t v; asm volatile("ld.acquire.gpu.global.u32 %0, [%1];" : "=r"(v) : "l"(p) : "memory"); return v; }
__device__ __forceinline__ uint32_t ld_rlx(const uint32_t* p) { uint32_t v; asm volatile("ld.relaxed.gpu.global.u32 %0, [%1];" : "=r"(v) : "l"(p) : "memory"); return v; }
template <class T> __device__ __forceinline__ T* opaque_ptr(T* p) { asm volatile("" : "+l"(p)); return p; }
__device__ __forceinline__ uint4 ld_rlx4(const uint4* p) {
    uint4 v; asm volatile("ld.relaxed.gpu.global.v4.u32 {%0,%1,%2,%3}, [%4];" : "=r"(v.x), "=r"(v.y), "=r"(v.z), "=r"(v.w) : "l"(p) : "memory"); return v;
}
__device__ __forceinline__ void st_ll(uint4* p, uint32_t a, uint32_t b, uint32_t tag) {
    uint64_t lo = ((uint64_t)tag << 32) | a, hi = ((uint64_t)tag << 32) | b;
    asm volatile("st.relaxed.gpu.global.v2.u64 [%0], {%1,%2};" :: "l"(p), "l"(lo), "l"(hi) : "memory");
}
__device__ __forceinline__ bool ld_ll(const uint4* p, uint32_t& a, uint32_t& b, uint32_t tag) {
    uint64_t lo, hi;
    asm volatile("ld.relaxed.gpu.global.v2.u64 {%0,%1}, [%2];" : "=l"(lo), "=l"(hi) : "l"(p) : "memory");
    a = (uint32_t)lo; b = (uint32_t)hi;
    return (uint32_t)(lo >> 32) == tag && (uint32_t)(hi >> 32) == tag;
}
__device__ __forceinline__ uint2 ld_acq2(const uint2* p) {
    uint2 v; asm volatile("ld.acquire.gpu.global.v2.u32 {%0,%1}, [%2];" : "=r"(v.x), "=r"(v.y) : "l"(p) : "memory"); return v;
}
__device__ __forceinline__ uint2 ld_rlx2(const uint2* p) {
    uint2 v; asm volatile("ld.relaxed.gpu.global.v2.u32 {%0,%1}, [%2];" : "=r"(v.x), "=r"(v.y) : "l"(p) : "memory"); return v;
}
__device__ __forceinline__ void stg1(uint32_t* p, uint32_t v) { asm volatile("st.global.u32 [%0], %1;" :: "l"(p), "r"(v) : "memory"); }
__device__ __forceinline__ void stg2(void* p, uint32_t x, uint32_t y) { asm volatile("st.global.v2.u32 [%0], {%1,%2};" :: "l"(p), "r"(x), "r"(y) : "memory"); }
__device__ __forceinline__ void stg4(void* p, uint32_t x, uint32_t y, uint32_t z, uint32_t w) { asm volatile("st.global.v4.u32 [%0], {%1,%2,%3,%4};" :: "l"(p), "r"(x), "r"(y), "r"(z), "r"(w) : "memory"); }
__device__ __forceinline__ uint32_t lds1(uint32_t a) { uint32_t v; asm volatile("ld.shared.u32 %0, [%1];" : "=r"(v) : "r"(a) : "memory"); return v; }
__device__ __forceinline__ uint2 lds2(uint32_t a) { uint2 v; asm volatile("ld.shared.v2.u32 {%0,%1}, [%2];" : "=r"(v.x), "=r"(v.y) : "r"(a) : "memory"); return v; }
__device__ __forceinline__ uint32_t set_par(uint32_t v, uint32_t mask, uint32_t par) {
    uint32_t r; asm("lop3.b32 %0, %1, %2, %3, 0xb8;" : "=r"(r) : "r"(v), "r"(mask), "r"(par)); return r;
}
__device__ __forceinline__ void st_gen4(void* p, uint32_t x, uint32_t y, uint32_t z, uint32_t w) { asm volatile("st.v4.u32 [%0], {%1,%2,%3,%4};" :: "l"(p), "r"(x), "r"(y), "r"(z), "r"(w) : "memory"); }
__device__ __forceinline__ float tanh_hw(float x) { float r; asm("tanh.approx.f32 %0, %1;" : "=f"(r) : "f"(x)); return r; }
__device__ __forceinline__ bool bar_any(int id, int n, bool v) {
    uint32_t r;
    asm volatile("{ .reg .pred p, q; setp.ne.u32 p, %3, 0; bar.red.or.pred q, %1, %2, p; selp.u32 %0, 1, 0, q; }" : "=r"(r) : "r"(id), "r"(n), "r"((uint32_t)v) : "memory");
    return r;
}
__device__ __forceinline__ void sts4(uint32_t a, uint32_t x, uint32_t y, uint32_t z, uint32_t w) { asm volatile("st.shared.v4.u32 [%0], {%1,%2,%3,%4};" :: "r"(a), "r"(x), "r"(y), "r"(z), "r"(w) : "memory"); }
__device__ __forceinline__ uint4 lds4(uint32_t a) { uint4 v; asm volatile("ld.shared.v4.u32 {%0,%1,%2,%3}, [%4];" : "=r"(v.x), "=r"(v.y), "=r"(v.z), "=r"(v.w) : "r"(a) : "memory"); return v; }
__device__ __forceinline__ uint32_t pack_bf16(float lo, float hi) { uint32_t r; asm("cvt.rn.bf16x2.f32 %0, %1, %2;" : "=r"(r) : "f"(hi), "f"(lo)); return r; }
__device__ __forceinline__ float bf_lo(uint32_t v) { return __uint_as_float(v << 16); }
__device__ __forceinline__ float bf_hi(uint32_t v) { return __uint_as_float(v & 0xffff0000u); }
__device__ __forceinline__ uint32_t sub_bf16x2(uint32_t a, uint32_t b) { uint32_t r; asm volatile("sub.rn.bf16x2 %0, %1, %2;" : "=r"(r) : "r"(a), "r"(b)); return r; }
__device__ __forceinline__ uint32_t add_bf16x2(uint32_t a, uint32_t b) { uint32_t r; asm volatile("add.rn.bf16x2 %0, %1, %2;" : "=r"(r) : "r"(a), "r"(b)); return r; }
__device__ __forceinline__ uint32_t sqr_bf16x2(uint32_t a) { uint32_t r; asm volatile("mul.rn.bf16x2 %0, %1, %1;" : "=r"(r) : "r"(a)); return r; }
__device__ __forceinline__ uint32_t sqa_bf16x2(uint32_t a, uint32_t c) { uint32_t r; asm volatile("fma.rn.bf16x2 %0, %1, %1, %2;" : "=r"(r) : "r"(a), "r"(c)); return r; }
__device__ __forceinline__ uint32_t movm(uint32_t a) { uint32_t r; asm volatile("movmatrix.sync.aligned.m8n8.trans.b16 %0, %1;" : "=r"(r) : "r"(a)); return r; }
__device__ __forceinline__ float ex2(float x) { float r; asm("ex2.approx.ftz.f32 %0, %1;" : "=f"(r) : "f"(x)); return r; }
__device__ __forceinline__ float rsq(float x) { float r; asm("rsqrt.approx.ftz.f32 %0, %1;" : "=f"(r) : "f"(x)); return r; }
__device__ __forceinline__ float rcp(float x) { float r; asm("rcp.approx.ftz.f32 %0, %1;" : "=f"(r) : "f"(x)); return r; }
__device__ __forceinline__ void mma16816(float (&c)[4], uint32_t a0, uint32_t a1, uint32_t a2, uint32_t a3, uint32_t b0, uint32_t b1) {
    asm("mma.sync.aligned.m16n8k16.row.col.f32.bf16.bf16.f32 {%0,%1,%2,%3}, {%4,%5,%6,%7}, {%8,%9}, {%0,%1,%2,%3};"
        : "+f"(c[0]), "+f"(c[1]), "+f"(c[2]), "+f"(c[3]) : "r"(a0), "r"(a1), "r"(a2), "r"(a3), "r"(b0), "r"(b1));
}
__device__ __forceinline__ void mma1688(float (&c)[4], uint32_t a0, uint32_t a1, uint32_t b0) {
    asm("mma.sync.aligned.m16n8k8.row.col.f32.bf16.bf16.f32 {%0,%1,%2,%3}, {%4,%5}, {%6}, {%0,%1,%2,%3};"
        : "+f"(c[0]), "+f"(c[1]), "+f"(c[2]), "+f"(c[3]) : "r"(a0), "r"(a1), "r"(b0));
}
__device__ __forceinline__ float quad_sum(float v) { v += __shfl_xor_sync(~0u, v, 1); v += __shfl_xor_sync(~0u, v, 2); return v; }
__device__ __forceinline__ float quad_max(float v) { v = fmaxf(v, __shfl_xor_sync(~0u, v, 1)); v = fmaxf(v, __shfl_xor_sync(~0u, v, 2)); return v; }
__device__ __forceinline__ uint64_t make_desc(uint32_t addr, uint32_t lbo, bool swz, uint32_t sbo = 1024) {
    const uint32_t lo = __shfl_sync(~0u, ((addr & 0x3FFFF) >> 4) | ((lbo >> 4) << 16), 0);
    const uint32_t hi = __shfl_sync(~0u, (swz ? 0x40000000u : 0u) + (sbo >> 4) + (threadIdx.x & 31), 0);
    return ((uint64_t)hi << 32) | lo;
}
template <int I, int N, class F> __device__ __forceinline__ void static_for(F&& f) {
    if constexpr (I < N) { f(std::integral_constant<int, I>{}); static_for<I + 1, N>(f); }
}
__device__ __forceinline__ uint32_t opaque(uint32_t v) { asm volatile("" : "+r"(v)); return v; }
template <int BOFF, int SCALE_D>
__device__ __forceinline__ void wgmma_rs_n56(float (&d)[28], uint32_t a0, uint32_t a1, uint32_t a2, uint32_t a3, uint64_t db) {
    asm volatile("{ .reg .b64 db; add.s64 db, %32, %33;\n"
        "wgmma.mma_async.sync.aligned.m64n56k16.f32.bf16.bf16 "
        "{%0, %1, %2, %3, %4, %5, %6, %7, %8, %9, %10, %11, %12, %13, %14, %15, %16, %17, %18, %19, %20, %21, %22, %23, %24, %25, %26, %27}, "
        "{%28, %29, %30, %31}, db, %34, 1, 1, 1; }"
        : "+f"(d[0]), "+f"(d[1]), "+f"(d[2]), "+f"(d[3]), "+f"(d[4]), "+f"(d[5]), "+f"(d[6]), "+f"(d[7]),
        "+f"(d[8]), "+f"(d[9]), "+f"(d[10]), "+f"(d[11]), "+f"(d[12]), "+f"(d[13]), "+f"(d[14]), "+f"(d[15]),
        "+f"(d[16]), "+f"(d[17]), "+f"(d[18]), "+f"(d[19]), "+f"(d[20]), "+f"(d[21]), "+f"(d[22]), "+f"(d[23]),
        "+f"(d[24]), "+f"(d[25]), "+f"(d[26]), "+f"(d[27])
        : "r"(a0), "r"(a1), "r"(a2), "r"(a3), "l"(db), "n"(BOFF >> 4), "n"(SCALE_D));
}
template <int AOFF, int BOFF, int MMAJOR>
__device__ __forceinline__ void wgmma_ss_n56(float (&d)[28], uint64_t da, uint64_t db) {
    asm volatile("{ .reg .b64 da, db; add.s64 da, %28, %30; add.s64 db, %29, %31;\n"
        "wgmma.mma_async.sync.aligned.m64n56k16.f32.bf16.bf16 "
        "{%0, %1, %2, %3, %4, %5, %6, %7, %8, %9, %10, %11, %12, %13, %14, %15, %16, %17, %18, %19, %20, %21, %22, %23, %24, %25, %26, %27}, "
        "da, db, 1, 1, 1, %32, 1; }"
        : "+f"(d[0]), "+f"(d[1]), "+f"(d[2]), "+f"(d[3]), "+f"(d[4]), "+f"(d[5]), "+f"(d[6]), "+f"(d[7]),
        "+f"(d[8]), "+f"(d[9]), "+f"(d[10]), "+f"(d[11]), "+f"(d[12]), "+f"(d[13]), "+f"(d[14]), "+f"(d[15]),
        "+f"(d[16]), "+f"(d[17]), "+f"(d[18]), "+f"(d[19]), "+f"(d[20]), "+f"(d[21]), "+f"(d[22]), "+f"(d[23]),
        "+f"(d[24]), "+f"(d[25]), "+f"(d[26]), "+f"(d[27])
        : "l"(da), "l"(db), "n"(AOFF >> 4), "n"(BOFF >> 4), "n"(MMAJOR));
}
template <int AOFF, int BOFF, int MMAJOR>
__device__ __forceinline__ void wgmma_ss_n112(float (&d)[28], float (&e)[28], uint64_t da, uint64_t db) {
    asm volatile("{ .reg .b64 da, db; add.s64 da, %56, %58; add.s64 db, %57, %59;\n"
        "wgmma.mma_async.sync.aligned.m64n112k16.f32.bf16.bf16 "
        "{%0, %1, %2, %3, %4, %5, %6, %7, %8, %9, %10, %11, %12, %13, %14, %15, %16, %17, %18, %19, %20, %21, %22, %23, %24, %25, %26, %27, %28, %29, %30, %31, %32, %33, %34, %35, %36, %37, %38, %39, %40, %41, %42, %43, %44, %45, %46, %47, %48, %49, %50, %51, %52, %53, %54, %55}, "
        "da, db, 1, 1, 1, %60, 1; }"
        : "+f"(d[0]), "+f"(d[1]), "+f"(d[2]), "+f"(d[3]), "+f"(d[4]), "+f"(d[5]), "+f"(d[6]), "+f"(d[7]),
        "+f"(d[8]), "+f"(d[9]), "+f"(d[10]), "+f"(d[11]), "+f"(d[12]), "+f"(d[13]), "+f"(d[14]), "+f"(d[15]),
        "+f"(d[16]), "+f"(d[17]), "+f"(d[18]), "+f"(d[19]), "+f"(d[20]), "+f"(d[21]), "+f"(d[22]), "+f"(d[23]),
        "+f"(d[24]), "+f"(d[25]), "+f"(d[26]), "+f"(d[27]), "+f"(e[0]), "+f"(e[1]), "+f"(e[2]), "+f"(e[3]),
        "+f"(e[4]), "+f"(e[5]), "+f"(e[6]), "+f"(e[7]), "+f"(e[8]), "+f"(e[9]), "+f"(e[10]), "+f"(e[11]),
        "+f"(e[12]), "+f"(e[13]), "+f"(e[14]), "+f"(e[15]), "+f"(e[16]), "+f"(e[17]), "+f"(e[18]), "+f"(e[19]),
        "+f"(e[20]), "+f"(e[21]), "+f"(e[22]), "+f"(e[23]), "+f"(e[24]), "+f"(e[25]), "+f"(e[26]), "+f"(e[27])
        : "l"(da), "l"(db), "n"(AOFF >> 4), "n"(BOFF >> 4), "n"(MMAJOR));
}
template <int BOFF, int SCALE_D>
__device__ __forceinline__ void wgmma_rs_n112(float (&d)[28], float (&e)[28], uint32_t a0, uint32_t a1, uint32_t a2, uint32_t a3, uint64_t db) {
    asm volatile("{ .reg .b64 db; add.s64 db, %60, %61;\n"
        "wgmma.mma_async.sync.aligned.m64n112k16.f32.bf16.bf16 "
        "{%0, %1, %2, %3, %4, %5, %6, %7, %8, %9, %10, %11, %12, %13, %14, %15, %16, %17, %18, %19, %20, %21, %22, %23, %24, %25, %26, %27, %28, %29, %30, %31, %32, %33, %34, %35, %36, %37, %38, %39, %40, %41, %42, %43, %44, %45, %46, %47, %48, %49, %50, %51, %52, %53, %54, %55}, "
        "{%56, %57, %58, %59}, db, %62, 1, 1, 1; }"
        : "+f"(d[0]), "+f"(d[1]), "+f"(d[2]), "+f"(d[3]), "+f"(d[4]), "+f"(d[5]), "+f"(d[6]), "+f"(d[7]),
        "+f"(d[8]), "+f"(d[9]), "+f"(d[10]), "+f"(d[11]), "+f"(d[12]), "+f"(d[13]), "+f"(d[14]), "+f"(d[15]),
        "+f"(d[16]), "+f"(d[17]), "+f"(d[18]), "+f"(d[19]), "+f"(d[20]), "+f"(d[21]), "+f"(d[22]), "+f"(d[23]),
        "+f"(d[24]), "+f"(d[25]), "+f"(d[26]), "+f"(d[27]), "+f"(e[0]), "+f"(e[1]), "+f"(e[2]), "+f"(e[3]),
        "+f"(e[4]), "+f"(e[5]), "+f"(e[6]), "+f"(e[7]), "+f"(e[8]), "+f"(e[9]), "+f"(e[10]), "+f"(e[11]),
        "+f"(e[12]), "+f"(e[13]), "+f"(e[14]), "+f"(e[15]), "+f"(e[16]), "+f"(e[17]), "+f"(e[18]), "+f"(e[19]),
        "+f"(e[20]), "+f"(e[21]), "+f"(e[22]), "+f"(e[23]), "+f"(e[24]), "+f"(e[25]), "+f"(e[26]), "+f"(e[27])
        : "r"(a0), "r"(a1), "r"(a2), "r"(a3), "l"(db), "n"(BOFF >> 4), "n"(SCALE_D));
}

struct Params {
    const __nv_bfloat16 *x, *wqkv;
    Scratch* sc;
    const __nv_bfloat16 *wo, *w1, *w2, *b1, *b2;
    __nv_bfloat16* out;
};

__global__ void __cluster_dims__(2, 1, 1) __launch_bounds__(384, 1)
fused_kernel(const Params prm, const __grid_constant__ CUtensorMap mX2, const __grid_constant__ CUtensorMap mX, const __grid_constant__ CUtensorMap mWqkv,
             const __grid_constant__ CUtensorMap mWo, const __grid_constant__ CUtensorMap mW1,
             const __grid_constant__ CUtensorMap mW2)
{
    extern __shared__ __align__(1024) unsigned char smem_raw[];
    if (threadIdx.x < 126) {
        const uint32_t i = threadIdx.x, t = clk32() + (i >> 5) * PFD;
        const char* px = (const char*)prm.x + (blockIdx.x * 16 + (i & 15)) * 896 + (i >> 4) * 128;
        const char* pw = (const char*)prm.wqkv + blockIdx.x * 2688 + i * 128 + (896 - 112 * 128);
        spin_until(t);
        asm volatile("prefetch.global.L2 [%0];" :: "l"(i < 112 ? px : pw) : "memory");
    }
    if (threadIdx.x == 128) { asm volatile("prefetch.tensormap [%0];" :: "l"(&mX2) : "memory"); asm volatile("prefetch.tensormap [%0];" :: "l"(&mWqkv) : "memory"); }
    uint32_t sb = (uint32_t)__cvta_generic_to_shared(smem_raw);
    asm volatile("mov.u32 %0, %0;" : "+r"(sb));
    const uint32_t bar0 = sb + SM_BAR;
    auto BAR = [&](int i) { return bar0 + 8u * i; };

    const int tid = threadIdx.x, lane = tid & 31;
    const int warp = __shfl_sync(~0u, tid >> 5, 0);
    const int b = __shfl_sync(~0u, (int)blockIdx.x, 0);
    const int rank = b & 1;
    const int cl = (b >> 1) - 4, cq = ((cl - 32) * 37) >> 8;
    const int res = cl < 0 ? 0 : cl < 32 ? cl & 7 : cl - 31 - 7 * cq;
    const int rnd = cl < 0 ? cl + 8 : cl < 32 ? cl >> 3 : 4 + cq;
    const int hg = (res & 1) * 4 + (rnd & 3);
    const int ti = (res >> 1) * 4 + (rnd >> 2) * 2 + rank;
    const int a2p = res & 1, a2j = rnd & 3;
    const int a2s = ti * 2 + a2p;
    const bool g1_on = rnd != 7;
    const int g1j = (rnd < 6 ? rnd : res) & 1, g1f = rnd < 6 ? res * 3 + (rnd >> 1) : 24 + (res >> 1);
    const int g2j = rnd & 1, g2s = res * 4 + (rnd >> 1);
    uint32_t pbar0;
    asm volatile("mapa.shared::cluster.u32 %0, %1, %2;" : "=r"(pbar0) : "r"(bar0), "r"(rank ^ 1));
    auto pair_arrive = [&](int i) { __syncwarp(); const bool l = elect_one(); mbar_arrive_if(BAR(i), l); mbar_arrive_remote_if(pbar0 + 8u * i, l); };
    const int wcol = hg * 56 - (hg & 1) * 8;

    if (warp == 8) {
        if (elect_one()) {
            #pragma unroll
            for (int i = 0; i < B_WQF; i++) mbar_init(BAR(i), 1);
            asm volatile("fence.mbarrier_init.release.cluster;" ::: "memory");
            fence_async_smem();
            #pragma unroll
            for (int kb = 0; kb < 7; kb++) {
                tma3d(sb + kb * 16384, &mX2, kb * 64, ti * 64, 0, BAR(B_XF + kb));
                mbar_expect(BAR(B_XF + kb), 16384);
                if (kb == 0 && PFX != 3) asm volatile("prefetch.tensormap [%0];" :: "l"(&mWqkv) : "memory");
            }
        }
    } else if (warp > 8) {
        if (elect_one()) {
            if (warp == 9) {
                #pragma unroll
                for (int i = B_WQF; i < B_AF; i++) mbar_init(BAR(i), i < B_XC ? 1 : i < B_A1D ? 16 : i < B_BE ? 8 : 4);
            } else if (warp == 10) {
                #pragma unroll
                for (int i = B_AF; i < B_BF; i++) mbar_init(BAR(i), 1);
            } else {
                #pragma unroll
                for (int i = B_BF; i < B_COUNT; i++) mbar_init(BAR(i), i == B_HD ? 8 : 1);
            }
            asm volatile("fence.mbarrier_init.release.cluster;" ::: "memory");
            fence_async_smem();
        }
    }
    __syncwarp();
    __syncthreads();
    asm volatile("barrier.cluster.arrive.relaxed.aligned;" ::: "memory");
    if (tid < 256) TR(0);
    if (tid == 0) TRG(61);

    if (warp >= 8) {
        asm volatile("setmaxnreg.dec.sync.aligned.u32 40;");
        asm volatile("barrier.cluster.wait.aligned;" ::: "memory");
        auto fetch_halo = [&](int p, uint32_t tag) {
            uint4 u[4];
            #pragma unroll
            for (int c = 0; c < 4; c++) u[c] = make_uint4(0u, 0u, 0u, 0u);
            const uint4* hp = opaque_ptr(&prm.sc->halo[(((ti - 1) * 8 + hg) * 2 + p) * 128 + lane]);
            mbar_wait(BAR(B_KVC), 0);
            if (p == 0) TRW(51);
            sleep_until(clk32() + HDELAY);
            if (ti > 0) {
                int it = 0;
                do {
                    #pragma unroll
                    for (int c = 0; c < 4; c++) u[c] = ld_rlx4(hp + c * 32);
                    if (it) RETRY_COUNT(4);
                    if (++it > kSpinLimit) { TIMEOUT(101); break; }
                } while (__any_sync(~0u, ((u[0].x ^ tag) | (u[1].x ^ tag) | (u[2].x ^ tag) | (u[3].x ^ tag)) & ~lane & 1));
            }
            #pragma unroll
            for (int c = 0; c < 4; c++) sts4(sb + SM_STG + p * 8192 + 3 * 2048 + lane * 16 + c * 512, u[c].x, u[c].y, u[c].z, u[c].w);
            warp_arrive(BAR(B_HL + p));
        };
        if (warp & 1) {
            uint32_t tag;
            if (warp == 11) {
                tag = *(volatile uint32_t*)&prm.sc->epoch + 1;
            #pragma unroll 1
            for (int i = 0; i < 8; i++) prm.sc->halo[(ti * 8 + hg) * 256 + i * 32 + lane] = make_uint4(~tag, 0u, 0u, 0u);
            ((uint4*)prm.sc->stats)[(a2s * 4 + a2j) * 64 + lane] = ((uint4*)prm.sc->stats)[(a2s * 4 + a2j) * 64 + 32 + lane] = make_uint4(~tag, ~tag, ~tag, ~tag);
            prm.sc->flag_h[(a2s * 4 + a2j) * FS + lane] = 0;
            prm.sc->flag_o[(ti * 8 + hg) * FS + lane] = 0;
            __syncwarp();
            if (lane == 0) {
                asm volatile("st.shared.v2.u32 [%0], {%1, %2};" :: "r"(sb + SM_EPOCH), "r"(tag), "r"(gtime32()) : "memory");
                mbar_arrive(BAR(B_EP));
            }
            if (lane < 8) mbar_expect(BAR(B_RF + lane), 1792);
            __syncwarp();
            TRW(44);
            } else {
                mbar_wait(BAR(B_EP), 0);
                tag = lds1(sb + SM_EPOCH);
            }
            uint32_t* ofl = opaque_ptr(&prm.sc->flag_o[(ti * 8 + hg) * FS]);
            fetch_halo((warp >> 1) & 1, tag);
            if (warp == 11) {
                mbar_wait2(BAR(B_A1D), 0, BAR(B_HL), 0);
                if (lane == 0) st_flag(ofl, tag);
                __syncwarp();
            }
        }
        if (warp < 10) {
          auto load_slab = [&](int s, bool second) {
              if (!second) tma2d(sb + s * 8192, &mW1, (s & 1) * kF + g1f * 64, (rank * 8 + (s >> 1)) * 64, BAR(B_AF));
              else         tma2d(sb + s * 8192, &mW2, g2s * 64, (rank * 14 + s - 1) * 64, BAR(B_AF));
          };
          if (warp == 8) {
            if (elect_one()) {
                #pragma unroll 1
                for (int s = 0; s < 7; s++) {
                    mbar_expect(BAR(B_WKVF + s), 16384);
                    tma2d_mc(sb + SM_WKV + s * 16384 + rank * 8192, &mWqkv, (1 + rank) * kD + wcol, s * 64, BAR(B_WKVF + s));
                }
            }
            __syncwarp();
            mbar_wait(BAR(B_XC), 0);
            if (elect_one()) {
                asm volatile("prefetch.tensormap [%0];" :: "l"(&mX) : "memory");
                asm volatile("prefetch.tensormap [%0];" :: "l"(&mWo) : "memory");
                asm volatile("prefetch.tensormap [%0];" :: "l"(&mW1) : "memory");
                asm volatile("prefetch.tensormap [%0];" :: "l"(&mW2) : "memory");
                mbar_expect(BAR(B_AF), (g1_on ? NPRE : 14) * 8192);
                mbar_expect(BAR(B_WQF), 57344);
                #pragma unroll 1
                for (int s = rank; s < 7; s += 2) tma2d_mc(sb + SM_WQ + s * 8192, &mWqkv, wcol, s * 64, BAR(B_WQF));
                mbar_expect(BAR(B_XRF), 16384);
                tma2d(sb + SM_XR, &mX, a2p * kD + a2j * 112, ti * 64, BAR(B_XRF));
                tma2d(sb + SM_XR + 8192, &mX, a2p * kD + a2j * 112 + 48, ti * 64, BAR(B_XRF));
            }
            __syncwarp();
            #pragma unroll 1
            for (int q = 0; q < 4; q++) {
                mbar_wait(BAR(B_KV3 + (q >> 1)), 0);
                if (q == 3) mbar_wait2(BAR(B_HL), 0, BAR(B_HL + 1), 0);
                if (elect_one()) {
                    if (!(q & 1)) mbar_expect(BAR(B_WOF + (q >> 1)), 57344);
                    tma2d_mc(sb + SM_WKV + q * 28672 + rank * 14336, &mWo, a2j * 112 + (q & 1) * 48, (q >> 1) * 224 + rank * 112, BAR(B_WOF + (q >> 1)));
                    if (g1_on && q == AFIRST) { load_slab(0, false); load_slab(1, false); load_slab(2, false); }
                }
                __syncwarp();
            }
            if (g1_on) {
                mbar_wait2(BAR(B_XD), 0, BAR(B_OL + 3), 0);
                #pragma unroll 1
                for (int i = 3; i < NPRE; i++) {
                    if (i == 7) mbar_wait(BAR(B_OC), 0);
                    if (elect_one()) load_slab(i, false);
                    __syncwarp();
                }
            } else {
                mbar_arrive_if(BAR((lane < 16 ? B_BE : B_BF) + (lane & 3)), lane < 20);
                mbar_wait(BAR(B_HD), 0);
                mbar_arrive_remote_if(pbar0 + 8u * B_PD, lane == 0);
                mbar_wait(BAR(B_GO), 0);
                uint32_t tg = lds1(sb + SM_TG + 4);
                tg += max((int)(lds1(sb + SM_TG2) - tg), 0);
                int it = 0;
                while ((int)(gtime32() - tg) < 0 && ++it < 256) {}
                const uint32_t t0 = clk32();
                if (lane < 2) {
                    asm volatile("st.shared.u32 [%0], %1;" :: "r"(sb + SM_TG + 8 + lane * 4), "r"(t0 + (lane ? CN3 : CN2)) : "memory");
                    mbar_arrive(BAR(B_GD + lane));
                }
                __syncwarp();
                #pragma unroll 1
                for (int s = 1; s < 15; s++) {
                    sleep_until(t0 + W2OFF + s * W2PACE);
                    if (elect_one()) load_slab(s, true);
                    __syncwarp();
                }
            }
          } else {
            TRW(58);
            const uint32_t tag = lds1(sb + SM_EPOCH);
            if (lane < 4) mbar_expect(BAR(B_OL + lane), 14336);
            #pragma unroll 1
            for (int e = 0; e < 2; e++) {
                const uint32_t* fp = e ? &prm.sc->flag_h[(rank * 64 + lane) * FS] : &prm.sc->flag_o[(ti * 8 + (lane & 7)) * FS];
                if (e) {
                    mbar_wait2(BAR(B_OF + 2), 0, BAR(B_OF + 3), 0);
                    if (lane == 0) st_flag(&prm.sc->flag_h[(a2s * 4 + a2j) * FS], tag);
                    __syncwarp();
                    TRW(57);
                    sleep_until(clk32() + PDELAY);
                }
                uint64_t v0 = 0, v1 = e ? 0 : tag;
                int it = 0;
                do {
                    ld_flag_if(v0, fp, (uint32_t)v0 != tag); ld_flag_if(v1, fp + 32 * FS, (uint32_t)v1 != tag);
                    if (++it > kSpinLimit) { TIMEOUT(108); break; }
                } while (__any_sync(~0u, (uint32_t)v0 != tag || (uint32_t)v1 != tag));
                const uint32_t gbase = __shfl_sync(~0u, (uint32_t)(v0 >> 32), 0);
                const uint32_t tg = gbase + (e ? DELTA : DELTAO)
                                  + __reduce_max_sync(~0u, max((int)((uint32_t)(v0 >> 32) - gbase) - e * (lane >> 2) * SOFF, e ? (int)((uint32_t)(v1 >> 32) - gbase) - 8 * SOFF : 0));
                TRW(e ? 40 : 53);
                mbar_wait(BAR(B_A1D), 0);
                if (elect_one()) {
                    if (e) {
                        asm volatile("st.async.shared::cluster.mbarrier::complete_tx::bytes.b32 [%0], %1, [%2];"
                                     :: "r"(pbar0 + (SM_TG2 - SM_BAR)), "r"(tg), "r"(pbar0 + 8u * B_GO) : "memory");
                        asm volatile("st.shared.u32 [%0], %1;" :: "r"(sb + SM_TG + 4), "r"(tg) : "memory");
                        mbar_expect(BAR(B_GO), 4);
                    } else {
                        it = 0;
                        while ((int)(gtime32() - tg) < 0 && ++it < 256) {}
                        #pragma unroll
                        for (int i = 0; i < 4; i++) bulk_g2s(sb + SM_WQ + i * 14336, &prm.sc->o[(a2s * 4 + i) * 896], 14336, BAR(B_OL + i));
                    }
                }
                __syncwarp();
            }
          }
          if (elect_one()) {
              const int h = ~warp & 1;
              constexpr uint32_t T = 57344, BO = 2 * 14336;
              const char* src1 = (const char*)&prm.sc->hn[(rank * 16 + h) * 3584 + g1j * 896];
              const char* src2 = (const char*)&prm.sc->g[(rank * 14 + h) * 3584 + g2j * 896];
              uint64_t masks = g1_on ? (h ? kSegMasks1 : kSegMasks0) : 0x80 | 0x80 << 10;
              const uint32_t bl = BAR(B_BL + h * NB);
              uint32_t s8 = (g1_on ? NB - 2 + h : 4 + h) * 8, lap = 3, tmin = 0;
              const CUtensorMap* am = &mW1;
              uint32_t ad = sb + (NPRE + h) * 8192, astep = 16384; int ac0 = h * kF + g1f * 64, ac1 = (rank * 8 + NPRE / 2) * 64;
              CAP_DECL(ti_, 0);
              #pragma unroll 1
              for (int seg = g1_on ? 0 : 3; seg < 5; seg++) {
                  const char* src = (seg < 3 ? src1 : src2) + (~seg & 1) * BO;
                  uint32_t m = (uint32_t)masks & 0x3ff;
                  masks >>= 10;
                  if (seg == 2) {
                      mbar_wait(BAR(B_PL), 0);
                      mbar_arrive_remote_if(pbar0 + 8u * B_PD, h);
                      am = &mW2; ad = sb + 8192; astep = 8192; ac0 = g2s * 64; ac1 = rank * 14 * 64;
                  } else {
                      const int gate = seg - (seg > 2);
                      mbar_wait(BAR(B_HD + gate), 0);
                      tmin = lds1(sb + SM_TG + gate * 4);
                      if (gate < 2) {
                          tmin += max((int)(lds1(gate ? sb + SM_TG2 : sb + SM_TG) - tmin), 0);
                          int it = 0;
                          while ((int)(gtime32() - tmin) < 0 && ++it < 256) {}
                          tmin = clk32();
                      }
                      tmin += h * PACE1;
                  }
                  #pragma unroll 1
                  do {
                      const uint32_t dst = sb + SM_B + s8 * 1792;
                      spin_until(tmin);
                      mbar_wait_fast(BAR(B_BE) + s8 + (lap & 1) * (NB * 8), lap >> 1 & 1);
                      if (seg) {
                          bulk_g2s(dst, src, 14336, bl + s8);
                          mbar_expect(bl + s8, 14336);
                          CAP(ti_);
                      }
                      tmin += PACE2;
                      src += 2 * T;
                      s8 += 16;
                      if (s8 >= NB * 8) { s8 -= NB * 8; lap++; }
                      if (m & 1) {
                          mbar_expect_more(bl + s8, 8192);
                          tma2d(ad, am, ac0, ac1, bl + s8);
                          ad += astep; ac1 += 64;
                      }
                      m >>= 1;
                  } while (m != 1);
                  if (seg == 0) lap = 3;
              }
          }
        } else {
          if (warp == 10) {
            mbar_wait(BAR(PFBAR), 0);
            const char* p1 = (const char*)prm.w1 + (size_t)b * 57344 + lane * 128;
            const char* p2 = (const char*)prm.w2 + (size_t)b * 57344 + lane * 128;
            if (lane < 27) asm volatile("prefetch.global.L2 [%0];" :: "l"(lane < 25 ? (const char*)prm.wo + min(b * 25 + lane, 3135) * 128
                                                                          : lane == 25 ? (const char*)prm.b1 + (b % 28) * 128 : (const char*)prm.b2 + (b & 31) * 128));
            uint32_t tnext = clk32();
            #pragma unroll 1
            for (int i = 0; i < 28; i++) {
                while ((int)(clk32() - tnext) < 0) __nanosleep(40);
                asm volatile("prefetch.global.L2 [%0];" :: "l"(i < 14 ? p1 + i * 4096 : p2 + (i - 14) * 4096));
                tnext += PFPACE;
            }
            mbar_wait(BAR(B_EP), 0);
          }
          const uint32_t tag = lds1(sb + SM_EPOCH);
          const int h = warp & 1;
          const bool lead = elect_one();
          const uint32_t wo = lane * 132, l3 = lane < 16 ? 12288 : 0;
          uint32_t base = sb + SM_WQ, bl = BAR(B_OL), bf = BAR(B_OF), m = 4, rph = 0;
          #pragma unroll 1
          for (int e = 0; e < 2; e++) {
              uint32_t s8 = (e && !g1_on ? 4 + h : h) * 8;
              #pragma unroll 1
              do {
                  const uint32_t dst = base + s8 * 1792;
                  auto stale = [&]() {
                      uint32_t d;
                      asm volatile("{ .reg .b32 x, y, z, u;\n"
                                   "ld.shared.u32 x, [%1]; ld.shared.u32 y, [%1 + 4096]; ld.shared.u32 z, [%1 + 8192]; ld.shared.u32 u, [%2];\n"
                                   "lop3.b32 x, x, y, %3, 0x7e; lop3.b32 z, z, u, %3, 0x7e; lop3.b32 %0, x, z, 1, 0xa8; }"
                                   : "=r"(d) : "r"(dst + wo), "r"(dst + (wo + l3)), "r"(tag) : "memory");
                      return __any_sync(~0u, d);
                  };
                  mbar_wait_fast(bl + s8, m & 1);
                  bool bad = stale();
                  mbar_arrive_if(bf + s8, lead && !bad);
                  if (bad) {
                      const int p = 2 * __clz(m) - 2 + h;
                      RETRY_COUNT(!e ? 1 : p < 32 ? 0 : !g1_on ? 5 : p < 46 ? 2 : 6);
                      const int st = (p > 15) + (p > 31) + (p > 45), s = p - (st < 3 ? 16 * st : 46);
                      const char* src = (const char*)(!e ? &prm.sc->o[(a2s * 4 + p - 56) * 896] : st < 2 ? &prm.sc->hn[(rank * 16 + s) * 3584 + (g1j + 2 * st) * 896]
                                                                                                      : &prm.sc->g[(rank * 14 + s) * 3584 + (g2j + 2 * st - 4) * 896]);
                      int it = 0;
                      do {
                          if (++it > kSpinLimit) { TIMEOUT(111); break; }
                          const uint32_t* q = (const uint32_t*)(src + wo);
                          if (it > RELOAD1 && __any_sync(~0u, ((ld_rlx(q) ^ tag) | (ld_rlx(q + 1024) ^ tag) | (ld_rlx(q + 2048) ^ tag) | (ld_rlx(q + l3 / 4) ^ tag)) & 1)) continue;
                          if (lead) {
                              mbar_expect(BAR(B_RT + h), 14336);
                              bulk_g2s(dst, src, 14336, BAR(B_RT + h));
                          }
                          __syncwarp();
                          mbar_wait(BAR(B_RT + h), rph);
                          rph ^= 1;
                          bad = stale();
                      } while (bad);
                      mbar_arrive_if(bf + s8, lead);
                  }
                  s8 += 16;
                  if (s8 >= NB * 8) s8 -= NB * 8;
                  m >>= 1;
              } while (m != 1);
              base = sb + SM_B; bl = BAR(B_BL + h * NB); bf = BAR(B_BF); m = g1_on ? 0x4fe03f80 : 0x7f80;
          }
        }
    } else {
        asm volatile("setmaxnreg.inc.sync.aligned.u32 232;");
        asm volatile("barrier.cluster.wait.aligned;" ::: "memory");
        const int wg = warp >> 2, w = warp & 3;
        const int g = lane >> 2, t = lane & 3;
        uint32_t tag;
        __nv_bfloat16 bias1a, bias1b;
        {
            const uint64_t dw = make_desc(sb + (hg & 1) * 16, 0, true);
            uint32_t a[28][4];
            float sm[4][4] = {};
            {
                const int r = w * 16 + (lane & 15);
                const uint32_t rowa = sb + wg * 8192 + r * 128;
                #pragma unroll
                for (int k = 0; k < 28; k++) {
                    if (XW == 1 && (k & 3) == 0) mbar_wait(BAR(B_XF + (k >> 2)), 0);
                    if (XW == 2 && k == 0) mbar_wait(BAR(B_XF), 0);
                    if (XW == 2 && (k & 7) == 4) mbar_wait2(BAR(B_XF + (k >> 2)), 0, BAR(B_XF + (k >> 2) + 1), 0);
                    const uint32_t addr = rowa + (k >> 2) * 16384 + ((((k & 3) * 2 + (lane >> 4)) ^ (r & 7)) << 4);
                    uint32_t (&f)[4] = a[k];
                    asm volatile("ldmatrix.sync.aligned.m8n8.x4.shared.b16 {%0,%1,%2,%3}, [%4];"
                                 : "=r"(f[0]), "=r"(f[1]), "=r"(f[2]), "=r"(f[3]) : "r"(addr) : "memory");
                    if (XLAG == 0) mma16816(sm[k & 3], f[0], f[1], f[2], f[3], 0x3F803F80u, 0x3F803F80u);
                    else if (k >= 4) mma16816(sm[k & 3], a[k - 4][0], a[k - 4][1], a[k - 4][2], a[k - 4][3], 0x3F803F80u, 0x3F803F80u);
                }
                if (XLAG) {
                    #pragma unroll
                    for (int k = 24; k < 28; k++) mma16816(sm[k & 3], a[k][0], a[k][1], a[k][2], a[k][3], 0x3F803F80u, 0x3F803F80u);
                }
            }
            const float mean0 = ((sm[0][0] + sm[1][0]) + (sm[2][0] + sm[3][0])) * (1.f / kD);
            const float mean1 = ((sm[0][2] + sm[1][2]) + (sm[2][2] + sm[3][2])) * (1.f / kD);
            const uint32_t mb0 = pack_bf16(mean0, mean0), mb1 = pack_bf16(mean1, mean1);
            pair_arrive(B_XC);
            TR(1);
            float ak[28], av[28], aq[28];
            float ss0 = 0.f, ss1 = 0.f, ss2 = 0.f, ss3 = 0.f;
            uint32_t p0, p1;
            static_for<0, 7>([&](auto S_) {
                constexpr int s = decltype(S_)::value;
                #pragma unroll
                for (int q = 0; q < 4; q++) {
                    uint32_t (&f)[4] = a[s * 4 + q];
                    f[0] = sub_bf16x2(f[0], mb0); f[1] = sub_bf16x2(f[1], mb1);
                    f[2] = sub_bf16x2(f[2], mb0); f[3] = sub_bf16x2(f[3], mb1);
                }
                mbar_wait(BAR(B_WKVF + s), 0);
                wg_fence();
                static_for<0, 4>([&](auto Q_) {
                    constexpr int q = decltype(Q_)::value;
                    uint32_t (&f)[4] = a[s * 4 + q];
                    wgmma_rs_n56<SM_WKV + s * 16384 + q * 2048, (s | q) != 0>(ak, f[0], f[1], f[2], f[3], dw);
                    wgmma_rs_n56<SM_WKV + s * 16384 + q * 2048 + 8192, (s | q) != 0>(av, f[0], f[1], f[2], f[3], dw);
                });
                wg_commit();
                if (s == 4) { wg_wait<1>(); pair_arrive(B_KV3); }
                #pragma unroll
                for (int q = 0; q < 8; q++) {
                    const uint32_t u0 = a[s * 4 + q / 2][(q & 1) * 2], u1 = a[s * 4 + q / 2][(q & 1) * 2 + 1];
                    if (q == 0 && (VCH == 1 || (s & 1) || s == 0)) { p0 = sqr_bf16x2(u0); p1 = sqr_bf16x2(u1); }
                    else { p0 = sqa_bf16x2(u0, p0); p1 = sqa_bf16x2(u1, p1); }
                }
                if (VCH == 1 || !(s & 1)) { ss0 += bf_lo(p0); ss2 += bf_hi(p0); ss1 += bf_lo(p1); ss3 += bf_hi(p1); }
            });
            auto q_chunk = [&](auto K0_, auto K1_) {
                wg_fence();
                static_for<decltype(K0_)::value, decltype(K1_)::value>([&](auto K_) {
                    constexpr int k = decltype(K_)::value;
                    wgmma_rs_n56<SM_WQ + k * 2048, k != 0>(aq, a[k][0], a[k][1], a[k][2], a[k][3], dw);
                });
                wg_commit();
            };
            #define QCHUNK(k0, k1) q_chunk(std::integral_constant<int, k0>{}, std::integral_constant<int, k1>{})
            const float dl0 = mean0 - bf_lo(mb0), dl1 = mean1 - bf_lo(mb1);
            const float rs0 = rsq(fmaxf(quad_sum(ss0 + ss2) * (1.f / kD) - dl0 * dl0, 0.f) + kEps);
            const float rs1 = rsq(fmaxf(quad_sum(ss1 + ss3) * (1.f / kD) - dl1 * dl1, 0.f) + kEps);
            float rk[3][2];
            rk[1][0] = __shfl_sync(~0u, rs0, t * 8); rk[1][1] = __shfl_sync(~0u, rs0, t * 8 + 4);
            rk[2][0] = __shfl_sync(~0u, rs1, t * 8); rk[2][1] = __shfl_sync(~0u, rs1, t * 8 + 4);
            const uint32_t stg = sb + SM_STG + wg * 8192 + lane * 16;
            uint4* hp = (w == 3 ? &prm.sc->halo[((ti * 8 + hg) * 2 + wg) * 128] : (uint4*)(smem_raw + SM_STG + wg * 8192 + w * 2048)) + lane;
            mbar_wait2(BAR(B_EP), 0, BAR(B_WQF), 0);
            tag = lds1(sb + SM_EPOCH);
            QCHUNK(0, QC0);
            wg_wait<1>();
            reg_fence(ak); reg_fence(av);
            TR(2);
            uint32_t kf[3][7], vf[3][7];
            #pragma unroll
            for (int c = 0; c < 7; c++) {
                kf[2][c] = pack_bf16(ak[4 * c + 2], ak[4 * c + 3]);
                vf[2][c] = movm(pack_bf16(av[4 * c + 2], av[4 * c + 3]));
            }
            const uint32_t om = ~lane & 1;
            kf[2][0] = set_par(kf[2][0], om, tag); kf[2][4] = set_par(kf[2][4], om, tag);
            vf[2][1] = set_par(vf[2][1], om, tag); vf[2][5] = set_par(vf[2][5], om, tag);
            st_gen4(hp,      kf[2][0], kf[2][1], kf[2][2], kf[2][3]);
            st_gen4(hp + 32, kf[2][4], kf[2][5], kf[2][6], vf[2][0]);
            st_gen4(hp + 64, vf[2][1], vf[2][2], vf[2][3], vf[2][4]);
            st_gen4(hp + 96, vf[2][5], vf[2][6], __float_as_uint(rk[2][0]), __float_as_uint(rk[2][1]));
            pair_arrive(B_KVC);
            QCHUNK(QC0, QC1);
            #pragma unroll
            for (int c = 0; c < 7; c++) {
                kf[1][c] = pack_bf16(ak[4 * c], ak[4 * c + 1]);
                vf[1][c] = movm(pack_bf16(av[4 * c], av[4 * c + 1]));
            }
            QCHUNK(QC1, QC2);
            named_bar(1 + wg, 128);
            uint32_t* op = opaque_ptr((uint32_t*)&prm.sc->o[((ti * 2 + wg) * 56 + hg * 7) * 64] + w * 64 + lane);
            const uint32_t om0 = opaque((lane & 7) == w * 2), om1 = opaque((lane & 7) == w * 2 + 1);
            QCHUNK(QC2, 28);
            #undef QCHUNK
            const bool gt0 = 2 * t > g, gt1 = 2 * t + 1 > g, no_prev = ti == 0 && w == 0;
            const float kf0 = gt0 ? rk[1][0] : rk[2][0], kf1 = gt1 ? rk[1][1] : rk[2][1];
            constexpr float kScale = 0.18898223650461362f * 1.4426950408889634f;
            const float sq0 = rs0 * kScale, sf0 = kf0 * (rs1 * kScale), sf1 = kf1 * (rs1 * kScale);
            const float NEG = -__int_as_float(0x7f800000);
            const float nb0 = gt0 && no_prev ? NEG : 0.f, nb1 = gt1 && no_prev ? NEG : 0.f;
            const uint32_t mk = opaque((gt0 ? 0x0000ffffu : 0u) | (gt1 ? 0xffff0000u : 0u));
            const uint32_t sr = stg + ((w + 3) & 3) * 2048, hbar = BAR(w == 0 ? B_HL + wg : B_EP);
            mbar_wait(BAR(B_EP), 0);
            wg_wait<0>();
            reg_fence(aq);
            warp_arrive(BAR(B_A1D));
            TR(3);
            uint32_t qf[8][2];
            #pragma unroll
            for (int c = 0; c < 7; c++) {
                qf[c + (c > 3)][0] = pack_bf16(aq[4 * c], aq[4 * c + 1]);
                qf[c + (c > 3)][1] = pack_bf16(aq[4 * c + 2], aq[4 * c + 3]);
            }
            qf[4][0] = t >= 2 ? qf[3][0] : 0u; qf[4][1] = t >= 2 ? qf[3][1] : 0u;
            qf[3][0] = t < 2 ? qf[3][0] : 0u;  qf[3][1] = t < 2 ? qf[3][1] : 0u;
            float sc[2][3][4];
            auto scores = [&](int n) {
                #pragma unroll
                for (int hd = 0; hd < 2; hd++) {
                    sc[hd][n][0] = sc[hd][n][1] = sc[hd][n][2] = sc[hd][n][3] = 0.f;
                    mma16816(sc[hd][n], qf[4 * hd][0], qf[4 * hd][1], qf[4 * hd + 1][0], qf[4 * hd + 1][1], kf[n][3 * hd], kf[n][3 * hd + 1]);
                    mma16816(sc[hd][n], qf[4 * hd + 2][0], qf[4 * hd + 2][1], qf[4 * hd + 3][0], qf[4 * hd + 3][1], kf[n][3 * hd + 2], kf[n][3 * hd + 3]);
                }
            };
            scores(1); scores(2);
            mbar_wait(hbar, 0);
            {
                const uint4 u0 = lds4(sr), u1 = lds4(sr + 512), u3 = lds4(sr + 1536), u2 = lds4(sr + 1024);
                kf[0][0] = u0.x; kf[0][1] = u0.y; kf[0][2] = u0.z; kf[0][3] = u0.w;
                kf[0][4] = u1.x; kf[0][5] = u1.y; kf[0][6] = u1.z; vf[0][0] = u1.w;
                vf[0][1] = u2.x; vf[0][2] = u2.y; vf[0][3] = u2.z; vf[0][4] = u2.w;
                vf[0][5] = u3.x; vf[0][6] = u3.y; rk[0][0] = __uint_as_float(u3.z); rk[0][1] = __uint_as_float(u3.w);
            }
            TR(4);
            scores(0);
            const float ke0 = gt0 ? rk[0][0] : rk[1][0], ke1 = gt1 ? rk[0][1] : rk[1][1];
            const float se0 = ke0 * sq0, se1 = ke1 * sq0;
            uint32_t ow[7][2];
            #pragma unroll
            for (int hd = 0; hd < 2; hd++) {
                const int c0 = hd * 3;
                float (&sc_)[3][4] = sc[hd];
                const float e0 = fmaf(gt0 ? sc_[0][0] : sc_[1][0], se0, nb0), e1 = fmaf(gt1 ? sc_[0][1] : sc_[1][1], se1, nb1);
                const float f0 = (gt0 ? sc_[1][2] : sc_[2][2]) * sf0, f1 = (gt1 ? sc_[1][3] : sc_[2][3]) * sf1;
                const float me = quad_max(fmaxf(e0, e1)), mf = quad_max(fmaxf(f0, f1));
                const float p0 = ex2(e0 - me), p1 = ex2(e1 - me), r0 = ex2(f0 - mf), r1 = ex2(f1 - mf);
                const float ie = rcp(quad_sum(p0 + p1)), jf = rcp(quad_sum(r0 + r1));
                const uint32_t pp = pack_bf16(p0 * ke0 * ie, p1 * ke1 * ie), rp = pack_bf16(r0 * kf0 * jf, r1 * kf1 * jf);
                const uint32_t a0 = pp & ~mk, a1 = rp & mk, a3 = rp & ~mk, a4 = pp & mk, zero = opaque(0u), zero2 = opaque(0u);
                #pragma unroll
                for (int c = 0; c < 4; c++) {
                    float o[4] = {0.f, 0.f, 0.f, 0.f};
                    mma16816(o, a0, a1, zero, a3, vf[1][c0 + c], vf[2][c0 + c]);
                    mma1688(o, a4, zero2, vf[0][c0 + c]);
                    const uint32_t lo = pack_bf16(o[0], o[1]), hi = pack_bf16(o[2], o[3]);
                    if (hd == 1 && c == 0) { if (t >= 2) { ow[3][0] = lo; ow[3][1] = hi; } }
                    else { ow[c0 + c][0] = lo; ow[c0 + c][1] = hi; }
                }
            }
            #pragma unroll
            for (int c = 0; c < 7; c++) {
                stg1(op + c * 256,      set_par(ow[c][0], om0, tag));
                stg1(op + c * 256 + 32, set_par(ow[c][1], om1, tag));
            }
            TR(5);
        }
        float as[28], ac[28];
        uint32_t xch, peer_xch, gm[2][4], *gp1, *gp2;
        const uint32_t *hp, *ht;
        const uint2* hq;
        uint64_t da0, db0;
        const int cg2 = (g2j + 2 * wg) * 2 + (rank ^ 1), cg1 = (g1j + 2 * wg) * 2 + (rank ^ (g1f < 14));
        const bool lead = elect_one();
        {
            const int cg = a2j * 2 + wg;
            float acc2[28];
            mbar_wait(BAR(B_XRF), 0);
            {
                const uint32_t xa = sb + SM_XR + wg * 8192 + (w * 16 + (lane & 15)) * 128;
                #pragma unroll
                for (int c = 0; c < 4; c++) {
                    uint32_t xr[4];
                    asm volatile("ldmatrix.sync.aligned.m8n8.x4.shared.b16 {%0,%1,%2,%3}, [%4];"
                                 : "=r"(xr[0]), "=r"(xr[1]), "=r"(xr[2]), "=r"(xr[3])
                                 : "r"(xa + ((((c * 2 + wg + (lane >> 4)) ^ lane) & 7) << 4)) : "memory");
                    #pragma unroll
                    for (int e = 0; e < (c < 3 ? 4 : 2); e++) { acc2[8 * c + 2 * e] = bf_lo(xr[e]); acc2[8 * c + 2 * e + 1] = bf_hi(xr[e]); }
                }
            }
            uint32_t* spw = opaque_ptr(&prm.sc->stats[((a2s * 8 + cg) * 4 + w) * 32 + lane]);
            const uint32_t* spr = opaque_ptr(&prm.sc->stats[(a2s * 32 + w) * 32 + lane]);
            uint32_t* rp = opaque_ptr((uint32_t*)&prm.sc->rows[a2s * 64 + w * 16 + (t >> 1) * 8 + g] + (t & 1));
            const int cgs = cg ^ (a2s >> 4);
            uint32_t* np = opaque_ptr((uint32_t*)&prm.sc->hn[(a2s * 56 + cgs * 7) * 64] + w * 64 + lane);
            const uint64_t dwo = make_desc(sb + SM_WKV + wg * (28672 + 16), 0, true);
            const uint64_t doa = make_desc(sb + SM_WQ, 1024, false, 128);
            bias1a = prm.b1[g1f * 64 + w * 16 + g]; bias1b = prm.b1[g1f * 64 + w * 16 + 8 + g];
            const __nv_bfloat16 bias2 = prm.b2[ti * 128 + (w * 16 + (t >> 1) * 8 + g) * 2 + a2p];
            reg_fence(acc2);
            fence_async_smem();
            warp_arrive(BAR(B_XD));
            {
                xch = opaque(sb + SM_XCH + w * 1792 + lane * 16);
                asm volatile("mapa.shared::cluster.u32 %0, %1, %2;" : "=r"(peer_xch) : "r"(xch), "r"(rank ^ 1));
                const int hcg = cg2 ^ (g2s >> 4), hrg = (g2s & 1) * 4 + w;
                const uint32_t* hl = (const uint32_t*)&prm.sc->hn[((g2s >> 1) * 112 + hcg * 7) * 64 + hrg * 8];
                hp = opaque_ptr(hl + (g & 1) * 14336 + (g >> 1) * 4 + t);
                ht = opaque_ptr(hl + (lane & 1) * 14336 + min(lane >> 1, 6) * 256 + ((min(lane >> 1, 6) - (hcg & 1)) & 3) * 8 + hrg);
                hq = opaque_ptr(&prm.sc->rows[((g2s >> 1) * 2 + (g & 1)) * 64 + hrg * 8 + (g >> 1)]);
                gp1 = opaque_ptr((uint32_t*)&prm.sc->g[(g1f * 56 + cg1 * 7) * 64] + w * 64 + lane);
                gp2 = opaque_ptr((uint32_t*)(prm.out + (size_t)(g2s * 64 + w * 16 + lane / 7) * kD + cg2 * 56) + (lane % 7) * 4);
                da0 = make_desc(sb, 0, true); db0 = make_desc(sb + SM_B, 128, false);
            }
            static_for<0, 4>([&](auto P_) {
                constexpr int P = decltype(P_)::value;
                if (P == 0) mbar_wait(BAR(B_WOF), 0);
                if (P == 2) mbar_wait2(BAR(B_OF + P), 0, BAR(B_WOF + 1), 0); else mbar_wait(BAR(B_OF + P), 0);
                if (P == 0) TR(6);
                wg_fence();
                static_for<0, 7>([&](auto K_) { constexpr int k = decltype(K_)::value;
                    wgmma_ss_n56<P * 14336 + k * 2048, (P >> 1) * 57344 + (P & 1) * 14336 + k * 2048, 0>(acc2, doa, dwo); });
                if (P) wg_commit();
                if (P == 2) { wg_wait<1>(); warp_arrive(BAR(B_OC)); }
            });
            wg_wait<0>();
            reg_fence(acc2);
            TR(7);
            float s0 = 0.f, s1 = 0.f, q0 = 0.f, q1 = 0.f;
            #pragma unroll
            for (int c = 0; c < 7; c++) {
                s0 += acc2[4 * c] + acc2[4 * c + 1];     q0 = fmaf(acc2[4 * c], acc2[4 * c], fmaf(acc2[4 * c + 1], acc2[4 * c + 1], q0));
                s1 += acc2[4 * c + 2] + acc2[4 * c + 3]; q1 = fmaf(acc2[4 * c + 2], acc2[4 * c + 2], fmaf(acc2[4 * c + 3], acc2[4 * c + 3], q1));
            }
            const bool th = t >= 2, to = t & 1;
            const float sa = (th ? s1 : s0) + __shfl_xor_sync(~0u, th ? s0 : s1, 2), qa = (th ? q1 : q0) + __shfl_xor_sync(~0u, th ? q0 : q1, 2);
            const float part = (to ? qa : sa) + __shfl_xor_sync(~0u, to ? sa : qa, 1);
            stg1(spw, set_par(__float_as_uint(part), 1u, tag));
            const uint32_t tpoll = clk32() + SDELAY;
            TR(8);
            warp_arrive(BAR(B_HD));
            uint32_t nm[2][4], us[8];
            spin_until(tpoll);
            #pragma unroll
            for (int i = 0; i < 8; i++) us[i] = ld_rlx(spr + i * 128);
            #pragma unroll
            for (int i = 0; i < 8; i++) {
                nm[i >> 2][i & 3] = lane == ((i - (cgs & 1)) & 3) * 8 + w * 2 + (i >> 2);
                gm[i >> 2][i & 3] = opaque(lane == ((i - (cg1 & 1)) & 3) * 8 + w * 2 + (i >> 2));
            }
            #pragma unroll
            for (int c = 0; c < 28; c++) { ac[c] = 0.5f * __bfloat162float(c & 2 ? bias1b : bias1a); as[c] = 0.f; }
            reg_fence(as); reg_fence(ac);
            {
                int it = 0;
                while (true) {
                    uint32_t bad = 0;
                    #pragma unroll
                    for (int i = 0; i < 8; i++) bad |= us[i] ^ tag;
                    if (!__any_sync(~0u, bad & 1)) break;
                    RETRY_COUNT(3);
                    if (++it > kSpinLimit) { TIMEOUT(103); break; }
                    #pragma unroll
                    for (int i = 0; i < 8; i++) us[i] = ld_rlx(spr + i * 128);
                }
            }
            TR(9);
            const float tot = (((__uint_as_float(us[0]) + __uint_as_float(us[1])) + (__uint_as_float(us[2]) + __uint_as_float(us[3])))
                            + ((__uint_as_float(us[4]) + __uint_as_float(us[5])) + (__uint_as_float(us[6]) + __uint_as_float(us[7])))) * (1.f / kD);
            const float oth = __shfl_xor_sync(~0u, tot, 1);
            const float mean = to ? oth : tot;
            const float var = fmaxf(fmaf(-mean, mean, to ? tot : oth), 0.f);
            const float r1 = rsq(var + kEps);
            const float rra = 0.5f * r1 * rsq(fmaf(var * r1, r1, kEps)), mra = -mean * rra;
            const float rrb = __shfl_xor_sync(~0u, rra, 2), mrb = __shfl_xor_sync(~0u, mra, 2);
            const float rr0 = th ? rrb : rra, mr0 = th ? mrb : mra, rr1 = th ? rra : rrb, mr1 = th ? mra : mrb;
            #pragma unroll
            for (int c = 0; c < 7; c++) {
                stg1(np + c * 256,      set_par(pack_bf16(fmaf(acc2[4 * c], rr0, mr0), fmaf(acc2[4 * c + 1], rr0, mr0)), nm[0][c & 3], tag));
                stg1(np + c * 256 + 32, set_par(pack_bf16(fmaf(acc2[4 * c + 2], rr1, mr1), fmaf(acc2[4 * c + 3], rr1, mr1)), nm[1][c & 3], tag));
            }
            TR(10);
            if (cg == 0) stg1(rp, set_par(__float_as_uint(to ? mean + __bfloat162float(bias2) : rcp(rra)), 1u, tag));
        }
        auto send = [&]() {
            const uint32_t rf = pbar0 + (B_RF + warp) * 8;
            #pragma unroll
            for (int c = 0; c < 4; c++) {
                const uint32_t p0 = pack_bf16(as[8 * c], as[8 * c + 1]), p1 = pack_bf16(as[8 * c + 2], as[8 * c + 3]);
                if (c < 3) {
                    const uint32_t p2 = pack_bf16(as[8 * c + 4], as[8 * c + 5]), p3 = pack_bf16(as[8 * c + 6], as[8 * c + 7]);
                    asm volatile("st.async.shared::cluster.mbarrier::complete_tx::bytes.v4.b32 [%0], {%1,%2,%3,%4}, [%5];"
                                 :: "r"(peer_xch + c * 512), "r"(p0), "r"(p1), "r"(p2), "r"(p3), "r"(rf) : "memory");
                } else {
                    asm volatile("st.async.shared::cluster.mbarrier::complete_tx::bytes.v2.b32 [%0], {%1,%2}, [%3];"
                                 :: "r"(peer_xch + 1536 - lane * 8), "r"(p0), "r"(p1), "r"(rf) : "memory");
                }
            }
        };
        auto receive = [&](uint32_t (&pk)[14], uint32_t phase) {
            mbar_wait(BAR(B_RF + warp), phase);
            #pragma unroll
            for (int c = 0; c < 3; c++) { const uint4 u = lds4(xch + c * 512); pk[4 * c] = u.x; pk[4 * c + 1] = u.y; pk[4 * c + 2] = u.z; pk[4 * c + 3] = u.w; }
            const uint2 u = lds2(xch + 1536 - lane * 8); pk[12] = u.x; pk[13] = u.y;
        };
        uint2 rw[2]; uint32_t tw;
        auto load_rows = [&]() { tw = ld_rlx(ht); rw[0] = ld_rlx2(hq); rw[1] = ld_rlx2(hq + 4); };
        rw[0] = rw[1] = make_uint2(0u, 0u); tw = ~tag;
        #pragma unroll 1
        for (int ge = 0;; ge++) {
          if (ge || g1_on) {
            const int use = ge * 2 + wg;
            int entry = ge ? 1 : 2 * wg, stop = 0;
            uint64_t da = da0 + (ge ? -3 : wg ? NR - 10 : 0) * 512;
            bool rel = lead && use == 1;
            const uint32_t xfree = BAR(use > (g1_on ? 0 : 2) ? B_RE + use - 1 : B_PD);
            mbar_wait(BAR(B_AF), 0);
            if (__builtin_expect(use == 1, 0)) {
                uint32_t af[NR * 4][4];
                mbar_wait(BAR(B_GO), 0);
                const uint32_t tp = lds1(sb + SM_TG + 4) + PLOFF;
                int it = 0;
                while ((int)(gtime32() - tp) < 0 && ++it < 256) __nanosleep(20);
                const uint32_t la = sb + ((lane >> 4) * 8 + (lane & 7)) * 128 + (((w * 2 + ((lane >> 3) & 1)) ^ (lane & 7)) << 4);
                #pragma unroll
                for (int k = 0; k < NR * 4; k++)
                    asm volatile("ldmatrix.sync.aligned.m8n8.x4.trans.shared.b16 {%0,%1,%2,%3}, [%4];"
                                 : "=r"(af[k][0]), "=r"(af[k][1]), "=r"(af[k][2]), "=r"(af[k][3]) : "r"(la + k * 2048) : "memory");
                __syncwarp();
                mbar_arrive_if(BAR(B_PL), lead);
                named_bar(4, 256);
                static_for<0, NR>([&](auto I_) {
                    constexpr int i = decltype(I_)::value, sl = (16 + i) % NB, o = sl * 14336;
                    mbar_wait_fast(BAR(B_BF + sl), (16 + i) / NB & 1);
                    wg_fence();
                    wgmma_rs_n112<o,       1>(as, ac, af[4 * i][0], af[4 * i][1], af[4 * i][2], af[4 * i][3], db0);
                    wgmma_rs_n112<o + 256, 1>(as, ac, af[4 * i + 1][0], af[4 * i + 1][1], af[4 * i + 1][2], af[4 * i + 1][3], db0);
                    wgmma_rs_n112<o + 512, 1>(as, ac, af[4 * i + 2][0], af[4 * i + 2][1], af[4 * i + 2][2], af[4 * i + 2][3], db0);
                    wgmma_rs_n112<o + 768, 1>(as, ac, af[4 * i + 3][0], af[4 * i + 3][1], af[4 * i + 3][2], af[4 * i + 3][3], db0);
                    wg_commit();
                    if (i) { wg_wait<1>(); mbar_arrive_if(BAR(B_BE + (15 + i) % (2 * NB)), lead); }
                });
            } else if (ge && (wg || g1_on)) named_bar(5 - wg, 256);
            TR(11 + ge * 4);
            auto step = [&](auto I_) {
                constexpr int i = decltype(I_)::value, sl = i % NB, ao = i * 8192, bo = sl * 14336;
                mbar_wait_fast(BAR(B_BF + sl), i / NB);
                wg_fence();
                wgmma_ss_n112<ao,        bo,       1>(as, ac, da, db0);
                wgmma_ss_n112<ao + 2048, bo + 256, 1>(as, ac, da, db0);
                wgmma_ss_n112<ao + 4096, bo + 512, 1>(as, ac, da, db0);
                wgmma_ss_n112<ao + 6144, bo + 768, 1>(as, ac, da, db0);
                wg_commit();
                if (i == 1 && stop == 1) named_arrive(4, 256);
                if (i == 3 && (use == 1 || use == 2)) named_arrive(4 + wg, 256);
                wg_wait<1>();
                mbar_arrive_if(BAR(B_BE + (13 + i) % 14), rel);
                rel = lead;
            };
            #pragma unroll 1
            while (true) {
                if (entry < 1) {
                    static_for<0, 2>(step);
                    if (stop == 1) break;
                    static_for<2, 4>(step);
                    if (stop) break;
                }
                if (entry < 2) static_for<4, 10>(step);
                static_for<10, 14>(step);
                entry = 0; stop = use + 1; da += 14 * 512;
            }
            const uint32_t prev = BAR(B_BE + (use ? 3 : 1));
            const bool xok = mbar_test(xfree, 0);
            wg_wait<0>();
            reg_fence(as); reg_fence(ac);
            mbar_arrive_if(prev, lead);
            if (!xok) mbar_wait(xfree, 0);
            if (ge) break;
            send();
            load_rows();
            TR(12);
            uint32_t pk[14];
            receive(pk, 0);
            TR(13);
            #pragma unroll
            for (int c = 0; c < 14; c++) {
                float r[2];
                #pragma unroll
                for (int e = 0; e < 2; e++) {
                    const float u = ac[2 * c + e] + (e ? bf_hi(pk[c]) : bf_lo(pk[c]));
                    r[e] = fmaf(u, tanh_hw(u * fmaf(u * u, 8.f * 0.7978845608f * 0.044715f, 2.f * 0.7978845608f)), u);
                }
                stg1(gp1 + (c >> 1) * 256 + (c & 1) * 32, set_par(pack_bf16(r[0], r[1]), gm[c & 1][(c >> 1) & 3], tag));
            }
            named_bar(1 + wg, 128);
            if (w == 0 && lane == 0) {
                asm volatile("st.shared.u32 [%0], %1;" :: "r"(sb + SM_TG + 8 + wg * 4), "r"(clk32() + (wg ? XSPECB : XSPEC)) : "memory");
                mbar_arrive(BAR(B_GD + wg));
            }
            if (lead) mbar_expect(BAR(B_RF + warp), 1792);
            mbar_arrive_remote_if(pbar0 + (B_RE + wg) * 8, lead);
            TR(14);
          } else mbar_wait(BAR(B_GD), 0);
            {
                int it = 0;
                while (__any_sync(~0u, ((tw ^ tag) | (rw[0].x ^ tag) | (rw[0].y ^ tag) | (rw[1].x ^ tag) | (rw[1].y ^ tag)) & 1)) {
                    if (++it > kSpinLimit) { TIMEOUT(110); break; }
                    load_rows();
                }
                uint32_t hw[14];
                #pragma unroll
                for (int c = 0; c < 14; c++) hw[c] = ld_rlx(hp + (c >> 1) * 256 + (c & 1) * 16);
                #pragma unroll
                for (int c = 0; c < 14; c++) {
                    ac[2 * c]     = fmaf(bf_lo(hw[c]), __uint_as_float(rw[c & 1].x), __uint_as_float(rw[c & 1].y));
                    ac[2 * c + 1] = fmaf(bf_hi(hw[c]), __uint_as_float(rw[c & 1].x), __uint_as_float(rw[c & 1].y));
                    as[2 * c] = as[2 * c + 1] = 0.f;
                }
                reg_fence(as); reg_fence(ac);
            }
        }
        uint32_t po[14], pk[14];
        if (!wg) sleep_until(clk32() + w * STAG2);
        send();
        #pragma unroll
        for (int c = 0; c < 14; c++) po[c] = opaque(pack_bf16(ac[2 * c], ac[2 * c + 1]));
        TR(16);
        receive(pk, g1_on);
        TR(17);
        #pragma unroll
        for (int c = 0; c < 14; c++) pk[c] = add_bf16x2(po[c], pk[c]);
        __syncwarp();
        const uint32_t sa = xch - lane * 16 + (lane & 15) * 112 + (lane >> 4) * 16;
        #pragma unroll
        for (int m = 0; m < 3; m++)
            asm volatile("stmatrix.sync.aligned.m8n8.x4.shared.b16 [%0], {%1,%2,%3,%4};"
                         :: "r"(sa + m * 32), "r"(pk[4 * m]), "r"(pk[4 * m + 1]), "r"(pk[4 * m + 2]), "r"(pk[4 * m + 3]) : "memory");
        asm volatile("stmatrix.sync.aligned.m8n8.x2.shared.b16 [%0], {%1,%2};" :: "r"(sa + 96), "r"(pk[12]), "r"(pk[13]) : "memory");
        __syncwarp();
        if (lane < 28) {
            #pragma unroll
            for (int i = 0; i < 4; i++) { const uint4 u = lds4(xch + i * 448); stg4(gp2 + i * 896, u.x, u.y, u.z, u.w); }
        }
        __syncwarp();
        mbar_arrive_remote_if(pbar0 + (B_RE + 2) * 8, lead && wg == 0);
        TR(18);
        if (tid == 128) TRG(62);
        if (b == 0 && tid == 128) prm.sc->epoch = tag;
    }
}

typedef CUresult (*EncodeFn)(CUtensorMap*, CUtensorMapDataType, cuuint32_t, void*, const cuuint64_t*, const cuuint64_t*,
                             const cuuint32_t*, const cuuint32_t*, CUtensorMapInterleave, CUtensorMapSwizzle,
                             CUtensorMapL2promotion, CUtensorMapFloatOOBfill);

void make_map(EncodeFn enc, CUtensorMap* m, const void* base, uint64_t cols, uint64_t rows, uint32_t box_rows) {
    cuuint64_t dims[2] = {cols, rows};
    cuuint64_t strides[1] = {cols * 2};
    cuuint32_t box[2] = {64, box_rows};
    cuuint32_t es[2] = {1, 1};
    enc(m, CU_TENSOR_MAP_DATA_TYPE_BFLOAT16, 2, const_cast<void*>(base), dims, strides, box, es, CU_TENSOR_MAP_INTERLEAVE_NONE,
        CU_TENSOR_MAP_SWIZZLE_128B, CU_TENSOR_MAP_L2_PROMOTION_L2_128B, CU_TENSOR_MAP_FLOAT_OOB_FILL_NONE);
}

}

extern "C" void kernel_launch(void* const* d_in, const int* in_sizes, int n_in, void* d_out, int out_size) {
    (void)in_sizes; (void)n_in; (void)out_size;
    void* fn = nullptr;
    cudaDriverEntryPointQueryResult qr;
    cudaGetDriverEntryPoint("cuTensorMapEncodeTiled", &fn, cudaEnableDefault, &qr);
    EncodeFn enc = (EncodeFn)fn;
    CUtensorMap mX2, mX, mWqkv, mWo, mW1, mW2;
    {
        cuuint64_t dims[3] = {kD, kS / 2, 2}, strides[2] = {4 * kD, 2 * kD};
        cuuint32_t box[3] = {64, 64, 2}, es[3] = {1, 1, 1};
        enc(&mX2, CU_TENSOR_MAP_DATA_TYPE_BFLOAT16, 3, d_in[0], dims, strides, box, es, CU_TENSOR_MAP_INTERLEAVE_NONE,
            CU_TENSOR_MAP_SWIZZLE_128B, CU_TENSOR_MAP_L2_PROMOTION_L2_128B, CU_TENSOR_MAP_FLOAT_OOB_FILL_NONE);
    }
    make_map(enc, &mX, d_in[0], 2 * kD, kS / 2, 64);
    make_map(enc, &mWqkv, d_in[1], 3 * kD, kD, 64);
    make_map(enc, &mWo, d_in[2], kD, kD, 112);
    make_map(enc, &mW1, d_in[4], 2 * kF, kS / 2, 64);
    make_map(enc, &mW2, d_in[6], kS, kF, 64);
    Params prm;
    prm.x = (const __nv_bfloat16*)d_in[0];
    prm.wqkv = (const __nv_bfloat16*)d_in[1];
    prm.wo = (const __nv_bfloat16*)d_in[2];
    prm.w1 = (const __nv_bfloat16*)d_in[4];
    prm.b1 = (const __nv_bfloat16*)d_in[5];
    prm.w2 = (const __nv_bfloat16*)d_in[6];
    prm.b2 = (const __nv_bfloat16*)d_in[7];
    prm.out = (__nv_bfloat16*)d_out;
    cudaGetSymbolAddress((void**)&prm.sc, g_scratch);
    cudaFuncSetAttribute(fused_kernel, cudaFuncAttributeMaxDynamicSharedMemorySize, SM_TOTAL);
    fused_kernel<<<128, 384, SM_TOTAL, cudaStreamPerThread>>>(prm, mX2, mX, mWqkv, mWo, mW1, mW2);
}
```

```cpp
#include <cuda_runtime.h>
#include <cuda.h>
#include <cuda_bf16.h>
#include <stdint.h>
#include <type_traits>

namespace {

constexpr int kS = 2048, kD = 448, kF = 1792;
constexpr float kEps = 1e-5f;

#define FS 32
struct Scratch {
    uint4    o[32 * 56 * 64];
    uint4    hn[32 * 56 * 64];
    uint4    g[28 * 56 * 64];
    uint4    halo[16 * 8 * 2 * 4 * 32];
    uint32_t stats[32 * 8 * 4 * 32];
    uint2    rows[32 * 64];
    uint32_t flag_o[16 * 8 * FS];
    uint32_t flag_h[32 * 4 * FS];
    uint32_t epoch;
};
__device__ __align__(1024) Scratch g_scratch;
#define TIMEOUT(code)
#define RETRY_COUNT(i)
#define CAP_DECL(n, k)
#define CAP(n)
#define CAP_SKIP(n)
#define EV(i, dep)
#define TR2(idx)
#define TR(idx)
#define TRW(idx)
#define TRG(idx)

constexpr uint32_t SM_WKV  = 114688;
constexpr uint32_t SM_XR   = 24576;
constexpr uint32_t SM_STG  = 40960;
constexpr uint32_t SM_WQ   = 57344;
constexpr uint32_t SM_XCH  = 0;
constexpr uint32_t SM_B    = 131072;
constexpr uint32_t SM_BAR  = 231424;
constexpr uint32_t SM_TOTAL = SM_BAR + 1024;
constexpr int NB = 7;
#define SH1 0
#define SH2 0
#define SH2N 5
#define SH3 0
#define NSPEC 4
#define XSPEC 500
#define C2 0
#define C3 0
#define CN2 7200
#define CN3 10900
constexpr int B_XF = 0, B_WKVF = 7, B_WQF = 14, B_XRF = 15, B_WOF = 16,
              B_XC = 18, B_KV3 = 19, B_KVC = 20,
              B_A1D = 21, B_XD = 22, B_OC = 23,
              B_BE = 24  , B_RE = B_BE + 2 * NB,
              B_PL = B_RE + 3, B_AF = B_PL + 1, B_BL = B_AF + 1  , B_OL = B_BL + 2 * NB  ,
              B_BF = B_OL + 4  , B_OF = B_BF + NB, B_RF = B_OF + 4, B_EP = B_RF + 8, B_PD = B_EP + 1, B_RT = B_PD + 1, B_HL = B_RT + 2,
              B_HD = B_HL + 2  , B_GO = B_HD + 1, B_GD = B_GO + 1, B_COUNT = B_GD + 2;
#define WEARLY 6
#define PF0 126
#define TMPF 2
#define RSTE 2
#define POLLP 1
#define PROBEP 1
#define LOADP 1
#define LOADW 64
#define NOB 0
#define AEARLY 5
#define W1PACE 400
#define W2PACE 350
#define PFPACE 390
#define PFBAR (B_XF + 6)
#define DELTA 1600
#define DELTA2 DELTA
#define BPACE 230
#define BURST 2
#define W1OFF 350
#define W2OFF 800
#define XPACE 0
#define PSTAG 200
constexpr uint32_t SM_EPOCH = SM_BAR + B_COUNT * 8, SM_TG = SM_EPOCH + 4  , SM_TG2 = SM_TG + 16  , SM_TR = SM_BAR + 768;

#define HDELAY 0
#define QC0 4
#define QC1 10
#define QC2 16
#define HPOS 1
#define XSPECB 750
#define PACE1 120
#define PACE2 400
#define RELOAD1 1
#define VCH 1
#define SOFF 0
#define XW 1
#define XLAG 0
#define PFX 3
#define PFD 250
#define SDELAY 300
#define PDELAY 500
#define NPRE 10
#define PREPACE 0
#define AFIRST 1
#define DELTAO 832
#define NS 0
#define GCH 14
#define OCH 14
#define ICH 14
#define PACKO
#define NR 8
#define HMODE 2
#define HOFF0 (-100)
#define HOFF1 900
#define STAG1 0
#define STAG2 400
#define PLOFF (-250)
#define HSRC h
#define WO1 1
#define WOD 300
#define WOP 400
#define WOP0 0
#define KV5 1
#define XLATE 0
#define W0E 1
#define W0F 2
#define PACEA 400
#define PACEB 300
#define PFN 16
#define PFPACE2 200
#define PF2R 3
#define W1Q 3
#define APOS1 ((1ull << 4) | (1ull << 8) | (1ull << 12) | (1ull << 5) | (1ull << 9) | (1ull << 13))
#define APOS2 (0x5555555ull << 17)
constexpr uint32_t seg_mask(int h, int p0, int p1) {
    uint32_t m = 0; int n = 0;
    for (int p = p0; p < p1; p++) if ((p & 1) == h) m |= (uint32_t)(((APOS1 | APOS2) >> p) & 1) << n++;
    return m | 1u << n;
}
constexpr uint64_t seg_masks(int h) {
    return 2 | (uint64_t)seg_mask(h, 0, 16) << 10 | (uint64_t)seg_mask(h, 16, 32) << 20
             | (uint64_t)seg_mask(h, 32, 46) << 30 | (uint64_t)seg_mask(h, 46, 60) << 40;
}
constexpr uint64_t kSegMasks0 = seg_masks(0), kSegMasks1 = seg_masks(1);

constexpr int kSpinLimit = 1 << 15;
__device__ __forceinline__ bool elect_one() {
    uint32_t p;
    asm volatile("{ .reg .pred P; elect.sync _|P, 0xffffffff; selp.u32 %0, 1, 0, P; }" : "=r"(p));
    return p;
}
__device__ __forceinline__ void mbar_init(uint32_t bar, uint32_t cnt) { asm volatile("mbarrier.init.shared::cta.b64 [%0], %1;" :: "r"(bar), "r"(cnt)); }
__device__ __forceinline__ void mbar_expect(uint32_t bar, uint32_t bytes) { asm volatile("mbarrier.arrive.expect_tx.shared::cta.b64 _, [%0], %1;" :: "r"(bar), "r"(bytes) : "memory"); }
__device__ __forceinline__ void mbar_expect_more(uint32_t bar, uint32_t bytes) { asm volatile("mbarrier.expect_tx.relaxed.cta.shared::cta.b64 [%0], %1;" :: "r"(bar), "r"(bytes) : "memory"); }
__device__ __forceinline__ void mbar_arrive(uint32_t bar) { asm volatile("mbarrier.arrive.shared::cta.b64 _, [%0];" :: "r"(bar) : "memory"); }
__device__ __forceinline__ void mbar_wait(uint32_t bar, uint32_t parity) {
    uint32_t ok; int it = 0;
    do {
        asm volatile("{ .reg .pred p; mbarrier.try_wait.parity.shared::cta.b64 p, [%1], %2; selp.u32 %0, 1, 0, p; }"
                     : "=r"(ok) : "r"(bar), "r"(parity) : "memory");
        if (++it > kSpinLimit) { TIMEOUT((bar & 1023) >> 3); break; }
    } while (!ok);
}
__device__ __forceinline__ bool mbar_try(uint32_t bar, uint32_t parity) {
    uint32_t ok;
    asm volatile("{ .reg .pred p; mbarrier.try_wait.parity.shared::cta.b64 p, [%1], %2; selp.u32 %0, 1, 0, p; }" : "=r"(ok) : "r"(bar), "r"(parity) : "memory");
    return ok;
}
__device__ __forceinline__ bool mbar_test(uint32_t bar, uint32_t parity) {
    uint32_t ok;
    asm volatile("{ .reg .pred p; mbarrier.test_wait.parity.shared::cta.b64 p, [%1], %2; selp.u32 %0, 1, 0, p; }" : "=r"(ok) : "r"(bar), "r"(parity) : "memory");
    return ok;
}
__device__ __forceinline__ void mbar_wait_fast(uint32_t bar, uint32_t parity) { if (!mbar_try(bar, parity)) mbar_wait(bar, parity); }
__device__ __forceinline__ void mbar_wait2(uint32_t bar0, uint32_t par0, uint32_t bar1, uint32_t par1) {
    uint32_t ok; int it = 0;
    do {
        asm volatile("{ .reg .pred p, q; mbarrier.try_wait.parity.shared::cta.b64 p, [%1], %2;\n"
                     "mbarrier.try_wait.parity.shared::cta.b64 q, [%3], %4; and.pred p, p, q; selp.u32 %0, 1, 0, p; }"
                     : "=r"(ok) : "r"(bar0), "r"(par0), "r"(bar1), "r"(par1) : "memory");
        if (++it > kSpinLimit) { TIMEOUT((bar0 & 1023) >> 3); break; }
    } while (!ok);
}
__device__ __forceinline__ void sched_fence(uint32_t v) {
    asm volatile("{ .reg .pred p; .reg .b32 x; mov.b32 x, %0;\nL: setp.eq.u32 p, x, 0xffffffff; @p mov.u32 x, %%clock; @p bra L; }" :: "r"(v) : "memory");
}
template <int N> __device__ __forceinline__ void reg_fence(float (&d)[N]) {
    #pragma unroll
    for (int i = 0; i < N; i++) asm volatile("" : "+f"(d[i]) :: "memory");
}
__device__ __forceinline__ void mbar_wait_cluster(uint32_t bar, uint32_t parity) {
    uint32_t ok; int it = 0;
    do {
        asm volatile("{ .reg .pred p; mbarrier.try_wait.parity.acquire.cluster.shared::cta.b64 p, [%1], %2; selp.u32 %0, 1, 0, p; }"
                     : "=r"(ok) : "r"(bar), "r"(parity) : "memory");
        if (++it > kSpinLimit) { TIMEOUT((bar & 1023) >> 3); break; }
    } while (!ok);
}
__device__ __forceinline__ void mbar_arrive_if(uint32_t bar, bool pred) {
    asm volatile("{ .reg .pred p; setp.ne.u32 p, %1, 0; @p mbarrier.arrive.shared::cta.b64 _, [%0]; }" :: "r"(bar), "r"((uint32_t)pred) : "memory");
}
template <int P> __device__ __forceinline__ void tick() {
    if (P > 1) { const uint32_t t = ((uint32_t)clock() | (P - 1)) + 1; while ((int)((uint32_t)clock() - t) < 0) {} }
}
__device__ __forceinline__ void warp_arrive(uint32_t bar) { __syncwarp(); if (elect_one()) mbar_arrive(bar); }
__device__ __forceinline__ void tma2d(uint32_t dst, const CUtensorMap* m, int c0, int c1, uint32_t bar) {
    asm volatile("cp.async.bulk.tensor.2d.shared::cluster.global.mbarrier::complete_tx::bytes [%0], [%1, {%3, %4}], [%2];"
                 :: "r"(dst), "l"(m), "r"(bar), "r"(c0), "r"(c1) : "memory");
}
__device__ __forceinline__ void tma3d(uint32_t dst, const CUtensorMap* m, int c0, int c1, int c2, uint32_t bar) {
    asm volatile("cp.async.bulk.tensor.3d.shared::cluster.global.mbarrier::complete_tx::bytes [%0], [%1, {%3, %4, %5}], [%2];"
                 :: "r"(dst), "l"(m), "r"(bar), "r"(c0), "r"(c1), "r"(c2) : "memory");
}
__device__ __forceinline__ void tma2d_mc(uint32_t dst, const CUtensorMap* m, int c0, int c1, uint32_t bar) {
    asm volatile("cp.async.bulk.tensor.2d.shared::cluster.global.mbarrier::complete_tx::bytes.multicast::cluster [%0], [%1, {%3, %4}], [%2], %5;"
                 :: "r"(dst), "l"(m), "r"(bar), "r"(c0), "r"(c1), "h"((uint16_t)3) : "memory");
}
__device__ __forceinline__ void bulk_g2s_mc(uint32_t dst, const void* src, uint32_t bytes, uint32_t bar) {
    asm volatile("cp.async.bulk.shared::cluster.global.mbarrier::complete_tx::bytes.multicast::cluster [%0], [%1], %2, [%3], %4;"
                 :: "r"(dst), "l"(src), "r"(bytes), "r"(bar), "h"((uint16_t)3) : "memory");
}
__device__ __forceinline__ void mbar_arrive_remote_if(uint32_t cluster_bar, bool pred) {
    asm volatile("{ .reg .pred p; setp.ne.u32 p, %1, 0; @p mbarrier.arrive.shared::cluster.b64 _, [%0]; }" :: "r"(cluster_bar), "r"((uint32_t)pred) : "memory");
}
__device__ __forceinline__ void bulk_g2s(uint32_t dst, const void* src, uint32_t bytes, uint32_t bar) {
    asm volatile("cp.async.bulk.shared::cluster.global.mbarrier::complete_tx::bytes [%0], [%1], %2, [%3];"
                 :: "r"(dst), "l"(src), "r"(bytes), "r"(bar) : "memory");
}
__device__ __forceinline__ void bulk_prefetch(const void* src, uint32_t bytes) { asm volatile("cp.async.bulk.prefetch.L2.global [%0], %1;" :: "l"(src), "r"(bytes) : "memory"); }
__device__ __forceinline__ void wg_fence()  { asm volatile("wgmma.fence.sync.aligned;" ::: "memory"); }
__device__ __forceinline__ void wg_commit() { asm volatile("wgmma.commit_group.sync.aligned;" ::: "memory"); }
template <int N> __device__ __forceinline__ void wg_wait() { asm volatile("wgmma.wait_group.sync.aligned %0;" :: "n"(N) : "memory"); }
__device__ __forceinline__ void named_bar(int id, int n) { asm volatile("bar.sync %0, %1;" :: "r"(id), "r"(n) : "memory"); }
__device__ __forceinline__ void named_arrive(int id, int n) { asm volatile("bar.arrive %0, %1;" :: "r"(id), "r"(n) : "memory"); }
__device__ __forceinline__ bool mbar_try2(uint32_t bar0, uint32_t par0, uint32_t bar1, uint32_t par1) {
    uint32_t ok;
    asm volatile("{ .reg .pred p, q; mbarrier.test_wait.parity.shared::cta.b64 p, [%1], %2;\n"
                 "mbarrier.test_wait.parity.shared::cta.b64 q, [%3], %4; and.pred p, p, q; selp.u32 %0, 1, 0, p; }"
                 : "=r"(ok) : "r"(bar0), "r"(par0), "r"(bar1), "r"(par1) : "memory");
    return ok;
}
__device__ __forceinline__ void fence_gpu() { asm volatile("fence.release.gpu;" ::: "memory"); }
__device__ __forceinline__ void fence_async_global() { asm volatile("fence.proxy.async.global;" ::: "memory"); }
__device__ __forceinline__ void fence_async_smem() { asm volatile("fence.proxy.async.shared::cta;" ::: "memory"); }
__device__ __forceinline__ uint32_t gtime32() { uint64_t t; asm volatile("mov.u64 %0, %%globaltimer;" : "=l"(t) :: "memory"); return (uint32_t)t; }
__device__ __forceinline__ uint32_t clk32() { uint64_t t; asm volatile("mov.u64 %0, %%clock64;" : "=l"(t) :: "memory"); return (uint32_t)t; }
__device__ __forceinline__ void spin_until(uint32_t t) { while ((int)(clk32() - t) < 0) {} }
#define SLEEPNS 20
__device__ __forceinline__ void sleep_until(uint32_t t) { while ((int)(clk32() - t) < 0) { if (SLEEPNS) __nanosleep(SLEEPNS); } }
__device__ __forceinline__ void st_flag(uint32_t* p, uint32_t v) {
    const uint64_t w = ((uint64_t)gtime32() << 32) | v;
    asm volatile("st.relaxed.gpu.global.u64 [%0], %1;" :: "l"(p), "l"(w) : "memory");
}
__device__ __forceinline__ void ld_flag_if(uint64_t& v, const uint32_t* p, bool pred) {
    asm volatile("{ .reg .pred p; setp.ne.u32 p, %2, 0; @p ld.relaxed.gpu.global.u64 %0, [%1]; }" : "+l"(v) : "l"(p), "r"((uint32_t)pred) : "memory");
}
__device__ __forceinline__ uint32_t ld_acq(const uint32_t* p) { uint32_t v; asm volatile("ld.acquire.gpu.global.u32 %0, [%1];" : "=r"(v) : "l"(p) : "memory"); return v; }
__device__ __forceinline__ uint32_t ld_rlx(const uint32_t* p) { uint32_t v; asm volatile("ld.relaxed.gpu.global.u32 %0, [%1];" : "=r"(v) : "l"(p) : "memory"); return v; }
template <class T> __device__ __forceinline__ T* opaque_ptr(T* p) { asm volatile("" : "+l"(p)); return p; }
__device__ __forceinline__ uint4 ld_rlx4(const uint4* p) {
    uint4 v; asm volatile("ld.relaxed.gpu.global.v4.u32 {%0,%1,%2,%3}, [%4];" : "=r"(v.x), "=r"(v.y), "=r"(v.z), "=r"(v.w) : "l"(p) : "memory"); return v;
}
__device__ __forceinline__ void st_ll(uint4* p, uint32_t a, uint32_t b, uint32_t tag) {
    uint64_t lo = ((uint64_t)tag << 32) | a, hi = ((uint64_t)tag << 32) | b;
    asm volatile("st.relaxed.gpu.global.v2.u64 [%0], {%1,%2};" :: "l"(p), "l"(lo), "l"(hi) : "memory");
}
__device__ __forceinline__ bool ld_ll(const uint4* p, uint32_t& a, uint32_t& b, uint32_t tag) {
    uint64_t lo, hi;
    asm volatile("ld.relaxed.gpu.global.v2.u64 {%0,%1}, [%2];" : "=l"(lo), "=l"(hi) : "l"(p) : "memory");
    a = (uint32_t)lo; b = (uint32_t)hi;
    return (uint32_t)(lo >> 32) == tag && (uint32_t)(hi >> 32) == tag;
}
__device__ __forceinline__ uint2 ld_acq2(const uint2* p) {
    uint2 v; asm volatile("ld.acquire.gpu.global.v2.u32 {%0,%1}, [%2];" : "=r"(v.x), "=r"(v.y) : "l"(p) : "memory"); return v;
}
__device__ __forceinline__ uint2 ld_rlx2(const uint2* p) {
    uint2 v; asm volatile("ld.relaxed.gpu.global.v2.u32 {%0,%1}, [%2];" : "=r"(v.x), "=r"(v.y) : "l"(p) : "memory"); return v;
}
__device__ __forceinline__ void stg1(uint32_t* p, uint32_t v) { asm volatile("st.global.u32 [%0], %1;" :: "l"(p), "r"(v) : "memory"); }
__device__ __forceinline__ void stg2(void* p, uint32_t x, uint32_t y) { asm volatile("st.global.v2.u32 [%0], {%1,%2};" :: "l"(p), "r"(x), "r"(y) : "memory"); }
__device__ __forceinline__ void stg4(void* p, uint32_t x, uint32_t y, uint32_t z, uint32_t w) { asm volatile("st.global.v4.u32 [%0], {%1,%2,%3,%4};" :: "l"(p), "r"(x), "r"(y), "r"(z), "r"(w) : "memory"); }
__device__ __forceinline__ uint32_t lds1(uint32_t a) { uint32_t v; asm volatile("ld.shared.u32 %0, [%1];" : "=r"(v) : "r"(a) : "memory"); return v; }
__device__ __forceinline__ uint2 lds2(uint32_t a) { uint2 v; asm volatile("ld.shared.v2.u32 {%0,%1}, [%2];" : "=r"(v.x), "=r"(v.y) : "r"(a) : "memory"); return v; }
__device__ __forceinline__ uint32_t set_par(uint32_t v, uint32_t mask, uint32_t par) {
    uint32_t r; asm("lop3.b32 %0, %1, %2, %3, 0xb8;" : "=r"(r) : "r"(v), "r"(mask), "r"(par)); return r;
}
__device__ __forceinline__ void st_gen4(void* p, uint32_t x, uint32_t y, uint32_t z, uint32_t w) { asm volatile("st.v4.u32 [%0], {%1,%2,%3,%4};" :: "l"(p), "r"(x), "r"(y), "r"(z), "r"(w) : "memory"); }
__device__ __forceinline__ float tanh_hw(float x) { float r; asm("tanh.approx.f32 %0, %1;" : "=f"(r) : "f"(x)); return r; }
__device__ __forceinline__ bool bar_any(int id, int n, bool v) {
    uint32_t r;
    asm volatile("{ .reg .pred p, q; setp.ne.u32 p, %3, 0; bar.red.or.pred q, %1, %2, p; selp.u32 %0, 1, 0, q; }" : "=r"(r) : "r"(id), "r"(n), "r"((uint32_t)v) : "memory");
    return r;
}
__device__ __forceinline__ void sts4(uint32_t a, uint32_t x, uint32_t y, uint32_t z, uint32_t w) { asm volatile("st.shared.v4.u32 [%0], {%1,%2,%3,%4};" :: "r"(a), "r"(x), "r"(y), "r"(z), "r"(w) : "memory"); }
__device__ __forceinline__ uint4 lds4(uint32_t a) { uint4 v; asm volatile("ld.shared.v4.u32 {%0,%1,%2,%3}, [%4];" : "=r"(v.x), "=r"(v.y), "=r"(v.z), "=r"(v.w) : "r"(a) : "memory"); return v; }
__device__ __forceinline__ uint32_t pack_bf16(float lo, float hi) { uint32_t r; asm("cvt.rn.bf16x2.f32 %0, %1, %2;" : "=r"(r) : "f"(hi), "f"(lo)); return r; }
__device__ __forceinline__ float bf_lo(uint32_t v) { return __uint_as_float(v << 16); }
__device__ __forceinline__ float bf_hi(uint32_t v) { return __uint_as_float(v & 0xffff0000u); }
__device__ __forceinline__ uint32_t sub_bf16x2(uint32_t a, uint32_t b) { uint32_t r; asm volatile("sub.rn.bf16x2 %0, %1, %2;" : "=r"(r) : "r"(a), "r"(b)); return r; }
__device__ __forceinline__ uint32_t add_bf16x2(uint32_t a, uint32_t b) { uint32_t r; asm volatile("add.rn.bf16x2 %0, %1, %2;" : "=r"(r) : "r"(a), "r"(b)); return r; }
__device__ __forceinline__ uint32_t sqr_bf16x2(uint32_t a) { uint32_t r; asm volatile("mul.rn.bf16x2 %0, %1, %1;" : "=r"(r) : "r"(a)); return r; }
__device__ __forceinline__ uint32_t sqa_bf16x2(uint32_t a, uint32_t c) { uint32_t r; asm volatile("fma.rn.bf16x2 %0, %1, %1, %2;" : "=r"(r) : "r"(a), "r"(c)); return r; }
__device__ __forceinline__ uint32_t movm(uint32_t a) { uint32_t r; asm volatile("movmatrix.sync.aligned.m8n8.trans.b16 %0, %1;" : "=r"(r) : "r"(a)); return r; }
__device__ __forceinline__ float ex2(float x) { float r; asm("ex2.approx.ftz.f32 %0, %1;" : "=f"(r) : "f"(x)); return r; }
__device__ __forceinline__ float rsq(float x) { float r; asm("rsqrt.approx.ftz.f32 %0, %1;" : "=f"(r) : "f"(x)); return r; }
__device__ __forceinline__ float rcp(float x) { float r; asm("rcp.approx.ftz.f32 %0, %1;" : "=f"(r) : "f"(x)); return r; }
__device__ __forceinline__ void mma16816(float (&c)[4], uint32_t a0, uint32_t a1, uint32_t a2, uint32_t a3, uint32_t b0, uint32_t b1) {
    asm("mma.sync.aligned.m16n8k16.row.col.f32.bf16.bf16.f32 {%0,%1,%2,%3}, {%4,%5,%6,%7}, {%8,%9}, {%0,%1,%2,%3};"
        : "+f"(c[0]), "+f"(c[1]), "+f"(c[2]), "+f"(c[3]) : "r"(a0), "r"(a1), "r"(a2), "r"(a3), "r"(b0), "r"(b1));
}
__device__ __forceinline__ void mma1688(float (&c)[4], uint32_t a0, uint32_t a1, uint32_t b0) {
    asm("mma.sync.aligned.m16n8k8.row.col.f32.bf16.bf16.f32 {%0,%1,%2,%3}, {%4,%5}, {%6}, {%0,%1,%2,%3};"
        : "+f"(c[0]), "+f"(c[1]), "+f"(c[2]), "+f"(c[3]) : "r"(a0), "r"(a1), "r"(b0));
}
__device__ __forceinline__ float quad_sum(float v) { v += __shfl_xor_sync(~0u, v, 1); v += __shfl_xor_sync(~0u, v, 2); return v; }
__device__ __forceinline__ float quad_max(float v) { v = fmaxf(v, __shfl_xor_sync(~0u, v, 1)); v = fmaxf(v, __shfl_xor_sync(~0u, v, 2)); return v; }
__device__ __forceinline__ uint64_t make_desc(uint32_t addr, uint32_t lbo, bool swz, uint32_t sbo = 1024) {
    const uint32_t lo = __shfl_sync(~0u, ((addr & 0x3FFFF) >> 4) | ((lbo >> 4) << 16), 0);
    const uint32_t hi = __shfl_sync(~0u, (swz ? 0x40000000u : 0u) + (sbo >> 4) + (threadIdx.x & 31), 0);
    return ((uint64_t)hi << 32) | lo;
}
template <int I, int N, class F> __device__ __forceinline__ void static_for(F&& f) {
    if constexpr (I < N) { f(std::integral_constant<int, I>{}); static_for<I + 1, N>(f); }
}
__device__ __forceinline__ uint32_t opaque(uint32_t v) { asm volatile("" : "+r"(v)); return v; }
template <int BOFF, int SCALE_D>
__device__ __forceinline__ void wgmma_rs_n56(float (&d)[28], uint32_t a0, uint32_t a1, uint32_t a2, uint32_t a3, uint64_t db) {
    asm volatile("{ .reg .b64 db; add.s64 db, %32, %33;\n"
        "wgmma.mma_async.sync.aligned.m64n56k16.f32.bf16.bf16 "
        "{%0, %1, %2, %3, %4, %5, %6, %7, %8, %9, %10, %11, %12, %13, %14, %15, %16, %17, %18, %19, %20, %21, %22, %23, %24, %25, %26, %27}, "
        "{%28, %29, %30, %31}, db, %34, 1, 1, 1; }"
        : "+f"(d[0]), "+f"(d[1]), "+f"(d[2]), "+f"(d[3]), "+f"(d[4]), "+f"(d[5]), "+f"(d[6]), "+f"(d[7]),
        "+f"(d[8]), "+f"(d[9]), "+f"(d[10]), "+f"(d[11]), "+f"(d[12]), "+f"(d[13]), "+f"(d[14]), "+f"(d[15]),
        "+f"(d[16]), "+f"(d[17]), "+f"(d[18]), "+f"(d[19]), "+f"(d[20]), "+f"(d[21]), "+f"(d[22]), "+f"(d[23]),
        "+f"(d[24]), "+f"(d[25]), "+f"(d[26]), "+f"(d[27])
        : "r"(a0), "r"(a1), "r"(a2), "r"(a3), "l"(db), "n"(BOFF >> 4), "n"(SCALE_D));
}
template <int AOFF, int BOFF, int MMAJOR>
__device__ __forceinline__ void wgmma_ss_n56(float (&d)[28], uint64_t da, uint64_t db) {
    asm volatile("{ .reg .b64 da, db; add.s64 da, %28, %30; add.s64 db, %29, %31;\n"
        "wgmma.mma_async.sync.aligned.m64n56k16.f32.bf16.bf16 "
        "{%0, %1, %2, %3, %4, %5, %6, %7, %8, %9, %10, %11, %12, %13, %14, %15, %16, %17, %18, %19, %20, %21, %22, %23, %24, %25, %26, %27}, "
        "da, db, 1, 1, 1, %32, 1; }"
        : "+f"(d[0]), "+f"(d[1]), "+f"(d[2]), "+f"(d[3]), "+f"(d[4]), "+f"(d[5]), "+f"(d[6]), "+f"(d[7]),
        "+f"(d[8]), "+f"(d[9]), "+f"(d[10]), "+f"(d[11]), "+f"(d[12]), "+f"(d[13]), "+f"(d[14]), "+f"(d[15]),
        "+f"(d[16]), "+f"(d[17]), "+f"(d[18]), "+f"(d[19]), "+f"(d[20]), "+f"(d[21]), "+f"(d[22]), "+f"(d[23]),
        "+f"(d[24]), "+f"(d[25]), "+f"(d[26]), "+f"(d[27])
        : "l"(da), "l"(db), "n"(AOFF >> 4), "n"(BOFF >> 4), "n"(MMAJOR));
}
template <int AOFF, int BOFF, int MMAJOR>
__device__ __forceinline__ void wgmma_ss_n112(float (&d)[28], float (&e)[28], uint64_t da, uint64_t db) {
    asm volatile("{ .reg .b64 da, db; add.s64 da, %56, %58; add.s64 db, %57, %59;\n"
        "wgmma.mma_async.sync.aligned.m64n112k16.f32.bf16.bf16 "
        "{%0, %1, %2, %3, %4, %5, %6, %7, %8, %9, %10, %11, %12, %13, %14, %15, %16, %17, %18, %19, %20, %21, %22, %23, %24, %25, %26, %27, %28, %29, %30, %31, %32, %33, %34, %35, %36, %37, %38, %39, %40, %41, %42, %43, %44, %45, %46, %47, %48, %49, %50, %51, %52, %53, %54, %55}, "
        "da, db, 1, 1, 1, %60, 1; }"
        : "+f"(d[0]), "+f"(d[1]), "+f"(d[2]), "+f"(d[3]), "+f"(d[4]), "+f"(d[5]), "+f"(d[6]), "+f"(d[7]),
        "+f"(d[8]), "+f"(d[9]), "+f"(d[10]), "+f"(d[11]), "+f"(d[12]), "+f"(d[13]), "+f"(d[14]), "+f"(d[15]),
        "+f"(d[16]), "+f"(d[17]), "+f"(d[18]), "+f"(d[19]), "+f"(d[20]), "+f"(d[21]), "+f"(d[22]), "+f"(d[23]),
        "+f"(d[24]), "+f"(d[25]), "+f"(d[26]), "+f"(d[27]), "+f"(e[0]), "+f"(e[1]), "+f"(e[2]), "+f"(e[3]),
        "+f"(e[4]), "+f"(e[5]), "+f"(e[6]), "+f"(e[7]), "+f"(e[8]), "+f"(e[9]), "+f"(e[10]), "+f"(e[11]),
        "+f"(e[12]), "+f"(e[13]), "+f"(e[14]), "+f"(e[15]), "+f"(e[16]), "+f"(e[17]), "+f"(e[18]), "+f"(e[19]),
        "+f"(e[20]), "+f"(e[21]), "+f"(e[22]), "+f"(e[23]), "+f"(e[24]), "+f"(e[25]), "+f"(e[26]), "+f"(e[27])
        : "l"(da), "l"(db), "n"(AOFF >> 4), "n"(BOFF >> 4), "n"(MMAJOR));
}
template <int BOFF, int SCALE_D>
__device__ __forceinline__ void wgmma_rs_n112(float (&d)[28], float (&e)[28], uint32_t a0, uint32_t a1, uint32_t a2, uint32_t a3, uint64_t db) {
    asm volatile("{ .reg .b64 db; add.s64 db, %60, %61;\n"
        "wgmma.mma_async.sync.aligned.m64n112k16.f32.bf16.bf16 "
        "{%0, %1, %2, %3, %4, %5, %6, %7, %8, %9, %10, %11, %12, %13, %14, %15, %16, %17, %18, %19, %20, %21, %22, %23, %24, %25, %26, %27, %28, %29, %30, %31, %32, %33, %34, %35, %36, %37, %38, %39, %40, %41, %42, %43, %44, %45, %46, %47, %48, %49, %50, %51, %52, %53, %54, %55}, "
        "{%56, %57, %58, %59}, db, %62, 1, 1, 1; }"
        : "+f"(d[0]), "+f"(d[1]), "+f"(d[2]), "+f"(d[3]), "+f"(d[4]), "+f"(d[5]), "+f"(d[6]), "+f"(d[7]),
        "+f"(d[8]), "+f"(d[9]), "+f"(d[10]), "+f"(d[11]), "+f"(d[12]), "+f"(d[13]), "+f"(d[14]), "+f"(d[15]),
        "+f"(d[16]), "+f"(d[17]), "+f"(d[18]), "+f"(d[19]), "+f"(d[20]), "+f"(d[21]), "+f"(d[22]), "+f"(d[23]),
        "+f"(d[24]), "+f"(d[25]), "+f"(d[26]), "+f"(d[27]), "+f"(e[0]), "+f"(e[1]), "+f"(e[2]), "+f"(e[3]),
        "+f"(e[4]), "+f"(e[5]), "+f"(e[6]), "+f"(e[7]), "+f"(e[8]), "+f"(e[9]), "+f"(e[10]), "+f"(e[11]),
        "+f"(e[12]), "+f"(e[13]), "+f"(e[14]), "+f"(e[15]), "+f"(e[16]), "+f"(e[17]), "+f"(e[18]), "+f"(e[19]),
        "+f"(e[20]), "+f"(e[21]), "+f"(e[22]), "+f"(e[23]), "+f"(e[24]), "+f"(e[25]), "+f"(e[26]), "+f"(e[27])
        : "r"(a0), "r"(a1), "r"(a2), "r"(a3), "l"(db), "n"(BOFF >> 4), "n"(SCALE_D));
}

struct Params {
    const __nv_bfloat16 *x, *wqkv;
    Scratch* sc;
    const __nv_bfloat16 *wo, *w1, *w2, *b1, *b2;
    __nv_bfloat16* out;
};

__global__ void __cluster_dims__(2, 1, 1) __launch_bounds__(384, 1)
fused_kernel(const Params prm, const __grid_constant__ CUtensorMap mX2, const __grid_constant__ CUtensorMap mX, const __grid_constant__ CUtensorMap mWqkv,
             const __grid_constant__ CUtensorMap mWo, const __grid_constant__ CUtensorMap mW1,
             const __grid_constant__ CUtensorMap mW2)
{
    extern __shared__ __align__(1024) unsigned char smem_raw[];
    if (threadIdx.x < 126) {
        const uint32_t i = threadIdx.x, t = clk32() + (i >> 5) * PFD;
        const char* px = (const char*)prm.x + (blockIdx.x * 16 + (i & 15)) * 896 + (i >> 4) * 128;
        const char* pw = (const char*)prm.wqkv + blockIdx.x * 2688 + i * 128 + (896 - 112 * 128);
        spin_until(t);
        asm volatile("prefetch.global.L2 [%0];" :: "l"(i < 112 ? px : pw) : "memory");
    }
    if (threadIdx.x == 128) { asm volatile("prefetch.tensormap [%0];" :: "l"(&mX2) : "memory"); asm volatile("prefetch.tensormap [%0];" :: "l"(&mWqkv) : "memory"); }
    uint32_t sb = (uint32_t)__cvta_generic_to_shared(smem_raw);
    asm volatile("mov.u32 %0, %0;" : "+r"(sb));
    const uint32_t bar0 = sb + SM_BAR;
    auto BAR = [&](int i) { return bar0 + 8u * i; };

    const int tid = threadIdx.x, lane = tid & 31;
    const int warp = __shfl_sync(~0u, tid >> 5, 0);
    const int b = __shfl_sync(~0u, (int)blockIdx.x, 0);
    const int rank = b & 1;
    const int cl = (b >> 1) - 4, cq = ((cl - 32) * 37) >> 8;
    const int res = cl < 0 ? 0 : cl < 32 ? cl & 7 : cl - 31 - 7 * cq;
    const int rnd = cl < 0 ? cl + 8 : cl < 32 ? cl >> 3 : 4 + cq;
    const int hg = (res & 1) * 4 + (rnd & 3);
    const int ti = (res >> 1) * 4 + (rnd >> 2) * 2 + rank;
    const int a2p = res & 1, a2j = rnd & 3;
    const int a2s = ti * 2 + a2p;
    const bool g1_on = rnd != 7;
    const int g1j = (rnd < 6 ? rnd : res) & 1, g1f = rnd < 6 ? res * 3 + (rnd >> 1) : 24 + (res >> 1);
    const int g2j = rnd & 1, g2s = res * 4 + (rnd >> 1);
    uint32_t pbar0;
    asm volatile("mapa.shared::cluster.u32 %0, %1, %2;" : "=r"(pbar0) : "r"(bar0), "r"(rank ^ 1));
    auto pair_arrive = [&](int i) { __syncwarp(); const bool l = elect_one(); mbar_arrive_if(BAR(i), l); mbar_arrive_remote_if(pbar0 + 8u * i, l); };
    const int wcol = hg * 56 - (hg & 1) * 8;

    if (warp == 8) {
        if (elect_one()) {
            #pragma unroll
            for (int i = 0; i < B_WQF; i++) mbar_init(BAR(i), 1);
            asm volatile("fence.mbarrier_init.release.cluster;" ::: "memory");
            fence_async_smem();
            #pragma unroll
            for (int kb = 0; kb < 7 - XLATE; kb++) {
                tma3d(sb + kb * 16384, &mX2, kb * 64, ti * 64, 0, BAR(B_XF + kb));
                mbar_expect(BAR(B_XF + kb), 16384);
                if (kb == 0 && PFX != 3) asm volatile("prefetch.tensormap [%0];" :: "l"(&mWqkv) : "memory");
            }
        }
    } else if (warp > 8) {
        if (elect_one()) {
            if (warp == 9) {
                #pragma unroll
                for (int i = B_WQF; i < B_AF; i++) mbar_init(BAR(i), i < B_XC ? 1 : i < B_A1D ? 16 : i < B_BE ? 8 : 4);
            } else if (warp == 10) {
                #pragma unroll
                for (int i = B_AF; i < B_BF; i++) mbar_init(BAR(i), 1);
            } else {
                #pragma unroll
                for (int i = B_BF; i < B_COUNT; i++) mbar_init(BAR(i), i == B_HD ? 8 : 1);
            }
            asm volatile("fence.mbarrier_init.release.cluster;" ::: "memory");
            fence_async_smem();
        }
    }
    __syncwarp();
    __syncthreads();
    asm volatile("barrier.cluster.arrive.relaxed.aligned;" ::: "memory");
    if (tid < 256) TR(0);
    if (tid == 0) TRG(61);

    if (warp >= 8) {
        asm volatile("setmaxnreg.dec.sync.aligned.u32 40;");
        asm volatile("barrier.cluster.wait.aligned;" ::: "memory");
        auto fetch_halo = [&](int p, uint32_t tag) {
            uint4 u[4];
            #pragma unroll
            for (int c = 0; c < 4; c++) u[c] = make_uint4(0u, 0u, 0u, 0u);
            const uint4* hp = opaque_ptr(&prm.sc->halo[(((ti - 1) * 8 + hg) * 2 + p) * 128 + lane]);
            mbar_wait(BAR(B_KVC), 0);
            if (p == 0) TRW(51);
            sleep_until(clk32() + HDELAY);
            if (ti > 0) {
                int it = 0;
                do {
                    #pragma unroll
                    for (int c = 0; c < 4; c++) u[c] = ld_rlx4(hp + c * 32);
                    if (it) RETRY_COUNT(4);
                    if (++it > kSpinLimit) { TIMEOUT(101); break; }
                } while (__any_sync(~0u, ((u[0].x ^ tag) | (u[1].x ^ tag) | (u[2].x ^ tag) | (u[3].x ^ tag)) & ~lane & 1));
            }
            #pragma unroll
            for (int c = 0; c < 4; c++) sts4(sb + SM_STG + p * 8192 + 3 * 2048 + lane * 16 + c * 512, u[c].x, u[c].y, u[c].z, u[c].w);
            warp_arrive(BAR(B_HL + p));
        };
        if (warp & 1) {
            uint32_t tag;
            if (warp == 11) {
                tag = *(volatile uint32_t*)&prm.sc->epoch + 1;
            #pragma unroll 1
            for (int i = 0; i < 8; i++) prm.sc->halo[(ti * 8 + hg) * 256 + i * 32 + lane] = make_uint4(~tag, 0u, 0u, 0u);
            ((uint4*)prm.sc->stats)[(a2s * 4 + a2j) * 64 + lane] = ((uint4*)prm.sc->stats)[(a2s * 4 + a2j) * 64 + 32 + lane] = make_uint4(~tag, ~tag, ~tag, ~tag);
            prm.sc->flag_h[(a2s * 4 + a2j) * FS + lane] = 0;
            prm.sc->flag_o[(ti * 8 + hg) * FS + lane] = 0;
            __syncwarp();
            if (lane == 0) {
                asm volatile("st.shared.v2.u32 [%0], {%1, %2};" :: "r"(sb + SM_EPOCH), "r"(tag), "r"(gtime32()) : "memory");
                mbar_arrive(BAR(B_EP));
            }
            if (lane < 8) mbar_expect(BAR(B_RF + lane), 1792);
            __syncwarp();
            TRW(44);
            } else {
                mbar_wait(BAR(B_EP), 0);
                tag = lds1(sb + SM_EPOCH);
            }
            uint32_t* ofl = opaque_ptr(&prm.sc->flag_o[(ti * 8 + hg) * FS]);
            fetch_halo((warp >> 1) & 1, tag);
            if (warp == 11) {
                mbar_wait2(BAR(B_A1D), 0, BAR(B_HL), 0);
                if (lane == 0) st_flag(ofl, tag);
                __syncwarp();
            }
        }
        if (warp < 10) {
          auto load_slab = [&](int s, bool second) {
              if (!second) tma2d(sb + s * 8192, &mW1, (s & 1) * kF + g1f * 64, (rank * 8 + (s >> 1)) * 64, BAR(B_AF));
              else         tma2d(sb + s * 8192, &mW2, g2s * 64, (rank * 14 + s - 1) * 64, BAR(B_AF));
          };
          const char* pw2 = (const char*)prm.w2 + ((b >> 6) * 896 + (b & 63)) * 4096;
          if (warp == 8) {
            if (elect_one()) {
                #pragma unroll 1
                for (int s = 0; s < 7; s++) {
                    mbar_expect(BAR(B_WKVF + s), 16384);
                    tma2d_mc(sb + SM_WKV + s * 16384 + rank * 8192, &mWqkv, (1 + rank) * kD + wcol, s * 64, BAR(B_WKVF + s));
                    if (s == 0) {
                        #pragma unroll
                        for (int kb = 7 - XLATE; kb < 7; kb++) {
                            tma3d(sb + kb * 16384, &mX2, kb * 64, ti * 64, 0, BAR(B_XF + kb));
                            mbar_expect(BAR(B_XF + kb), 16384);
                        }
                    }
                }
            }
            __syncwarp();
            mbar_wait(BAR(B_XC), 0);
            if (elect_one()) {
                asm volatile("prefetch.tensormap [%0];" :: "l"(&mX) : "memory");
                asm volatile("prefetch.tensormap [%0];" :: "l"(&mWo) : "memory");
                asm volatile("prefetch.tensormap [%0];" :: "l"(&mW1) : "memory");
                asm volatile("prefetch.tensormap [%0];" :: "l"(&mW2) : "memory");
                mbar_expect(BAR(B_AF), (g1_on ? NPRE : 14) * 8192);
                mbar_expect(BAR(B_WQF), 57344);
                #pragma unroll 1
                for (int s = rank; s < 7; s += 2) tma2d_mc(sb + SM_WQ + s * 8192, &mWqkv, wcol, s * 64, BAR(B_WQF));
                mbar_expect(BAR(B_XRF), 16384);
                tma2d(sb + SM_XR, &mX, a2p * kD + a2j * 112, ti * 64, BAR(B_XRF));
                tma2d(sb + SM_XR + 8192, &mX, a2p * kD + a2j * 112 + 48, ti * 64, BAR(B_XRF));
            }
            __syncwarp();
            #pragma unroll 1
            for (int q = 0; q < 4; q++) {
                mbar_wait(BAR(B_KV3 + (q >> 1)), 0);
                if (q == 3) mbar_wait2(BAR(B_HL), 0, BAR(B_HL + 1), 0);
                if (elect_one()) {
                    if (!(q & 1)) mbar_expect(BAR(B_WOF + (q >> 1)), 57344);
                    tma2d_mc(sb + SM_WKV + q * 28672 + rank * 14336, &mWo, a2j * 112 + (q & 1) * 48, (q >> 1) * 224 + rank * 112, BAR(B_WOF + (q >> 1)));
                    if (g1_on && q == AFIRST) { load_slab(0, false); load_slab(1, false); load_slab(2, false); }
                }
                __syncwarp();
            }
            if (g1_on) {
                mbar_wait2(BAR(B_XD), 0, BAR(B_OL + 3), 0);
                #pragma unroll 1
                for (int i = 3; i < NPRE; i++) {
                    if (i == 7) mbar_wait(BAR(B_OC), 0);
                    if (elect_one()) load_slab(i, false);
                    __syncwarp();
                }
            } else {
                mbar_arrive_if(BAR((lane < 16 ? B_BE : B_BF) + (lane & 3)), lane < 20);
                mbar_wait(BAR(B_HD), 0);
                mbar_arrive_remote_if(pbar0 + 8u * B_PD, lane == 0);
                mbar_wait(BAR(B_GO), 0);
                uint32_t tg = lds1(sb + SM_TG + 4);
                tg += max((int)(lds1(sb + SM_TG2) - tg), 0);
                int it = 0;
                while ((int)(gtime32() - tg) < 0 && ++it < 256) {}
                const uint32_t t0 = clk32();
                if (lane < 2) {
                    asm volatile("st.shared.u32 [%0], %1;" :: "r"(sb + SM_TG + 8 + lane * 4), "r"(t0 + (lane ? CN3 : CN2)) : "memory");
                    mbar_arrive(BAR(B_GD + lane));
                }
                __syncwarp();
                #pragma unroll 1
                for (int s = 1; s < 15; s++) {
                    sleep_until(t0 + W2OFF + s * W2PACE);
                    if (elect_one()) { bulk_prefetch(pw2 + (s - 1) * 64 * 4096, 4096); load_slab(s, true); }
                    __syncwarp();
                }
            }
          } else {
            TRW(58);
            const uint32_t tag = lds1(sb + SM_EPOCH);
            if (lane < 4) mbar_expect(BAR(B_OL + lane), 14336);
            #pragma unroll 1
            for (int e = 0; e < 2; e++) {
                const uint32_t* fp = e ? &prm.sc->flag_h[(rank * 64 + lane) * FS] : &prm.sc->flag_o[(ti * 8 + (lane & 7)) * FS];
                if (e) {
                    mbar_wait2(BAR(B_OF + 2), 0, BAR(B_OF + 3), 0);
                    if (lane == 0) st_flag(&prm.sc->flag_h[(a2s * 4 + a2j) * FS], tag);
                    __syncwarp();
                    TRW(57);
                    sleep_until(clk32() + PDELAY);
                }
                uint64_t v0 = 0, v1 = e ? 0 : tag;
                int it = 0;
                do {
                    ld_flag_if(v0, fp, (uint32_t)v0 != tag); ld_flag_if(v1, fp + 32 * FS, (uint32_t)v1 != tag);
                    if (++it > kSpinLimit) { TIMEOUT(108); break; }
                } while (__any_sync(~0u, (uint32_t)v0 != tag || (uint32_t)v1 != tag));
                const uint32_t gbase = __shfl_sync(~0u, (uint32_t)(v0 >> 32), 0);
                const uint32_t tg = gbase + (e ? DELTA : DELTAO)
                                  + __reduce_max_sync(~0u, max((int)((uint32_t)(v0 >> 32) - gbase) - e * (lane >> 2) * SOFF, e ? (int)((uint32_t)(v1 >> 32) - gbase) - 8 * SOFF : 0));
                TRW(e ? 40 : 53);
                mbar_wait(BAR(B_A1D), 0);
                if (elect_one()) {
                    if (e) {
                        asm volatile("st.async.shared::cluster.mbarrier::complete_tx::bytes.b32 [%0], %1, [%2];"
                                     :: "r"(pbar0 + (SM_TG2 - SM_BAR)), "r"(tg), "r"(pbar0 + 8u * B_GO) : "memory");
                        asm volatile("st.shared.u32 [%0], %1;" :: "r"(sb + SM_TG + 4), "r"(tg) : "memory");
                        mbar_expect(BAR(B_GO), 4);
                    } else {
                        it = 0;
                        while ((int)(gtime32() - tg) < 0 && ++it < 256) {}
                        #pragma unroll
                        for (int i = 0; i < 4; i++) bulk_g2s(sb + SM_WQ + i * 14336, &prm.sc->o[(a2s * 4 + i) * 896], 14336, BAR(B_OL + i));
                    }
                }
                __syncwarp();
            }
          }
          if (elect_one()) {
              const int h = ~warp & 1;
              constexpr uint32_t T = 57344, BO = 2 * 14336;
              const char* src1 = (const char*)&prm.sc->hn[(rank * 16 + h) * 3584 + g1j * 896];
              const char* src2 = (const char*)&prm.sc->g[(rank * 14 + h) * 3584 + g2j * 896];
              uint64_t masks = g1_on ? (h ? kSegMasks1 : kSegMasks0) : 0x80 | 0x80 << 10;
              const uint32_t bl = BAR(B_BL + h * NB);
              uint32_t s8 = (g1_on ? NB - 2 + h : 4 + h) * 8, lap = 3, tmin = 0;
              uint32_t pfm = g1_on && !h ? 0x3fffu << (PF2R + 1) : 0;
              const CUtensorMap* am = &mW1;
              uint32_t ad = sb + (NPRE + h) * 8192, astep = 16384; int ac0 = h * kF + g1f * 64, ac1 = (rank * 8 + NPRE / 2) * 64;
              CAP_DECL(ti_, 0);
              #pragma unroll 1
              for (int seg = g1_on ? 0 : 3; seg < 5; seg++) {
                  const char* src = (seg < 3 ? src1 : src2) + (~seg & 1) * BO;
                  uint32_t m = (uint32_t)masks & 0x3ff;
                  masks >>= 10;
                  const uint32_t pace = seg == 4 ? PACEB : seg == 3 ? PACEA : PACE2;
                  if (seg == 2) {
                      mbar_wait(BAR(B_PL), 0);
                      mbar_arrive_remote_if(pbar0 + 8u * B_PD, h);
                      am = &mW2; ad = sb + 8192; astep = 8192; ac0 = g2s * 64; ac1 = rank * 14 * 64;
                  } else {
                      const int gate = seg - (seg > 2);
                      mbar_wait(BAR(B_HD + gate), 0);
                      tmin = lds1(sb + SM_TG + gate * 4);
                      if (gate < 2) {
                          tmin += max((int)(lds1(gate ? sb + SM_TG2 : sb + SM_TG) - tmin), 0);
                          int it = 0;
                          while ((int)(gtime32() - tmin) < 0 && ++it < 256) {}
                          tmin = clk32();
                      }
                      tmin += h * PACE1;
                  }
                  #pragma unroll 1
                  do {
                      const uint32_t dst = sb + SM_B + s8 * 1792;
                      spin_until(tmin);
                      mbar_wait_fast(BAR(B_BE) + s8 + (lap & 1) * (NB * 8), lap >> 1 & 1);
                      if (seg) {
                          bulk_g2s(dst, src, 14336, bl + s8);
                          mbar_expect(bl + s8, 14336);
                          CAP(ti_);
                      }
                      tmin += pace;
                      src += 2 * T;
                      s8 += 16;
                      if (s8 >= NB * 8) { s8 -= NB * 8; lap++; }
                      if (m & 1) {
                          mbar_expect_more(bl + s8, 8192);
                          tma2d(ad, am, ac0, ac1, bl + s8);
                          ad += astep; ac1 += 64;
                      }
                      if (pfm & 1) { bulk_prefetch(pw2, 4096); pw2 += 64 * 4096; }
                      pfm >>= 1;
                      m >>= 1;
                  } while (m != 1);
                  if (seg == 0) lap = 3;
              }
          }
        } else {
          auto pull_w1 = [&](int s0, int s1, uint32_t pace) {
            const char* p1 = (const char*)prm.w1 + ((b >> 6) * 1024 + (b & 63) * 2) * 3584 + min(lane, 27) * 128;
            uint32_t tnext = clk32();
            #pragma unroll 1
            for (int i = s0; i < s1; i++) {
                while ((int)(clk32() - tnext) < 0) __nanosleep(40);
                asm volatile("prefetch.global.L2 [%0];" :: "l"(p1 + ((i >> 1) * 128 + (i & 1)) * 3584));
                tnext += pace;
            }
          };
          if (warp == 10) {
            mbar_wait(BAR(PFBAR), 0);
            if (lane < 27) asm volatile("prefetch.global.L2 [%0];" :: "l"(lane < 25 ? (const char*)prm.wo + min(b * 25 + lane, 3135) * 128
                                                                          : lane == 25 ? (const char*)prm.b1 + (b % 28) * 128 : (const char*)prm.b2 + (b & 31) * 128));
            pull_w1(0, PFN, PFPACE);
            mbar_wait(BAR(B_EP), 0);
          }
          const uint32_t tag = lds1(sb + SM_EPOCH);
          const int h = warp & 1;
          const bool lead = elect_one();
          const uint32_t wo = lane * 132, l3 = lane < 16 ? 12288 : 0;
          uint32_t base = sb + SM_WQ, bl = BAR(B_OL), bf = BAR(B_OF), m = 4, rph = 0;
          #pragma unroll 1
          for (int e = 0; e < 2; e++) {
              uint32_t s8 = (e && !g1_on ? 4 + h : h) * 8;
              #pragma unroll 1
              do {
                  const uint32_t dst = base + s8 * 1792;
                  auto stale = [&]() {
                      uint32_t d;
                      asm volatile("{ .reg .b32 x, y, z, u;\n"
                                   "ld.shared.u32 x, [%1]; ld.shared.u32 y, [%1 + 4096]; ld.shared.u32 z, [%1 + 8192]; ld.shared.u32 u, [%2];\n"
                                   "lop3.b32 x, x, y, %3, 0x7e; lop3.b32 z, z, u, %3, 0x7e; lop3.b32 %0, x, z, 1, 0xa8; }"
                                   : "=r"(d) : "r"(dst + wo), "r"(dst + (wo + l3)), "r"(tag) : "memory");
                      return __any_sync(~0u, d);
                  };
                  mbar_wait_fast(bl + s8, m & 1);
                  bool bad = stale();
                  mbar_arrive_if(bf + s8, lead && !bad);
                  if (bad) {
                      const int p = 2 * __clz(m) - 2 + h;
                      RETRY_COUNT(!e ? 1 : p < 32 ? 0 : !g1_on ? 5 : p < 46 ? 2 : 6);
                      const int st = (p > 15) + (p > 31) + (p > 45), s = p - (st < 3 ? 16 * st : 46);
                      const char* src = (const char*)(!e ? &prm.sc->o[(a2s * 4 + p - 56) * 896] : st < 2 ? &prm.sc->hn[(rank * 16 + s) * 3584 + (g1j + 2 * st) * 896]
                                                                                                      : &prm.sc->g[(rank * 14 + s) * 3584 + (g2j + 2 * st - 4) * 896]);
                      int it = 0;
                      do {
                          if (++it > kSpinLimit) { TIMEOUT(111); break; }
                          const uint32_t* q = (const uint32_t*)(src + wo);
                          if (it > RELOAD1 && __any_sync(~0u, ((ld_rlx(q) ^ tag) | (ld_rlx(q + 1024) ^ tag) | (ld_rlx(q + 2048) ^ tag) | (ld_rlx(q + l3 / 4) ^ tag)) & 1)) continue;
                          if (lead) {
                              mbar_expect(BAR(B_RT + h), 14336);
                              bulk_g2s(dst, src, 14336, BAR(B_RT + h));
                          }
                          __syncwarp();
                          mbar_wait(BAR(B_RT + h), rph);
                          rph ^= 1;
                          bad = stale();
                      } while (bad);
                      mbar_arrive_if(bf + s8, lead);
                  }
                  s8 += 16;
                  if (s8 >= NB * 8) s8 -= NB * 8;
                  m >>= 1;
              } while (m != 1);
              if (PFN < 16 && !e && !h) pull_w1(PFN, 16, PFPACE2);
              base = sb + SM_B; bl = BAR(B_BL + h * NB); bf = BAR(B_BF); m = g1_on ? 0x4fe03f80 : 0x7f80;
          }
        }
    } else {
        asm volatile("setmaxnreg.inc.sync.aligned.u32 232;");
        asm volatile("barrier.cluster.wait.aligned;" ::: "memory");
        const int wg = warp >> 2, w = warp & 3;
        const int g = lane >> 2, t = lane & 3;
        uint32_t tag;
        __nv_bfloat16 bias1a, bias1b;
        {
            const uint64_t dw = make_desc(sb + (hg & 1) * 16, 0, true);
            uint32_t a[28][4];
            float sm[4][4] = {};
            {
                const int r = w * 16 + (lane & 15);
                uint32_t xa[4];
                #pragma unroll
                for (int q = 0; q < 4; q++) xa[q] = opaque(sb + wg * 8192 + r * 128 + (((q * 2 + (lane >> 4)) ^ (r & 7)) << 4));
                const uint32_t one = opaque(0x3F803F80u), one2 = opaque(0x3F803F80u);
                #pragma unroll
                for (int k = 0; k < 28; k++) {
                    if ((k & 3) == 0) mbar_wait(BAR(B_XF + (k >> 2)), 0);
                    uint32_t (&f)[4] = a[k];
                    asm volatile("ldmatrix.sync.aligned.m8n8.x4.shared.b16 {%0,%1,%2,%3}, [%4];"
                                 : "=r"(f[0]), "=r"(f[1]), "=r"(f[2]), "=r"(f[3]) : "r"(xa[k & 3] + (k >> 2) * 16384) : "memory");
                    if (k < 24) mma16816(sm[k & 3], f[0], f[1], f[2], f[3], one, one2);
                }
                pair_arrive(B_XC);
                const bool wok = mbar_test(BAR(B_WKVF), 0);
                #pragma unroll
                for (int k = 24; k < 28; k++) mma16816(sm[k & 3], a[k][0], a[k][1], a[k][2], a[k][3], one, one2);
                if (W0E && !wok) mbar_wait(BAR(B_WKVF), 0);
            }
            const float mean0 = ((sm[0][0] + sm[1][0]) + (sm[2][0] + sm[3][0])) * (1.f / kD);
            const float mean1 = ((sm[0][2] + sm[1][2]) + (sm[2][2] + sm[3][2])) * (1.f / kD);
            const uint32_t mb0 = pack_bf16(mean0, mean0), mb1 = pack_bf16(mean1, mean1);
            TR(1);
            float ak[28], av[28], aq[28];
            float ss0 = 0.f, ss1 = 0.f, ss2 = 0.f, ss3 = 0.f;
            uint32_t p0, p1;
            static_for<0, 7>([&](auto S_) {
                constexpr int s = decltype(S_)::value;
                auto centre = [&](int q) {
                    uint32_t (&f)[4] = a[s * 4 + q];
                    f[0] = sub_bf16x2(f[0], mb0); f[1] = sub_bf16x2(f[1], mb1);
                    f[2] = sub_bf16x2(f[2], mb0); f[3] = sub_bf16x2(f[3], mb1);
                };
                if (s || !W0E) {
                    #pragma unroll
                    for (int q = 0; q < 4; q++) centre(q);
                    mbar_wait(BAR(B_WKVF + s), 0);
                    wg_fence();
                }
                static_for<0, 4>([&](auto Q_) {
                    constexpr int q = decltype(Q_)::value;
                    uint32_t (&f)[4] = a[s * 4 + q];
                    if (s == 0 && W0E) { centre(q); wg_fence(); }
                    wgmma_rs_n56<SM_WKV + s * 16384 + q * 2048, (s | q) != 0>(ak, f[0], f[1], f[2], f[3], dw);
                    wgmma_rs_n56<SM_WKV + s * 16384 + q * 2048 + 8192, (s | q) != 0>(av, f[0], f[1], f[2], f[3], dw);
                });
                wg_commit();
                if (s == 4) { wg_wait<1>(); pair_arrive(B_KV3); }
                if (s < W0F) mbar_wait(BAR(B_WKVF), 0);
                #pragma unroll
                for (int q = 0; q < 8; q++) {
                    const uint32_t u0 = a[s * 4 + q / 2][(q & 1) * 2], u1 = a[s * 4 + q / 2][(q & 1) * 2 + 1];
                    if (q == 0 && (VCH == 1 || (s & 1) || s == 0)) { p0 = sqr_bf16x2(u0); p1 = sqr_bf16x2(u1); }
                    else { p0 = sqa_bf16x2(u0, p0); p1 = sqa_bf16x2(u1, p1); }
                }
                if (VCH == 1 || !(s & 1)) { ss0 += bf_lo(p0); ss2 += bf_hi(p0); ss1 += bf_lo(p1); ss3 += bf_hi(p1); }
            });
            auto q_chunk = [&](auto K0_, auto K1_) {
                wg_fence();
                static_for<decltype(K0_)::value, decltype(K1_)::value>([&](auto K_) {
                    constexpr int k = decltype(K_)::value;
                    wgmma_rs_n56<SM_WQ + k * 2048, k != 0>(aq, a[k][0], a[k][1], a[k][2], a[k][3], dw);
                });
                wg_commit();
            };
            #define QCHUNK(k0, k1) q_chunk(std::integral_constant<int, k0>{}, std::integral_constant<int, k1>{})
            const float dl0 = mean0 - bf_lo(mb0), dl1 = mean1 - bf_lo(mb1);
            const float rs0 = rsq(fmaxf(quad_sum(ss0 + ss2) * (1.f / kD) - dl0 * dl0, 0.f) + kEps);
            const float rs1 = rsq(fmaxf(quad_sum(ss1 + ss3) * (1.f / kD) - dl1 * dl1, 0.f) + kEps);
            float rk[3][2];
            rk[1][0] = __shfl_sync(~0u, rs0, t * 8); rk[1][1] = __shfl_sync(~0u, rs0, t * 8 + 4);
            rk[2][0] = __shfl_sync(~0u, rs1, t * 8); rk[2][1] = __shfl_sync(~0u, rs1, t * 8 + 4);
            const uint32_t stg = sb + SM_STG + wg * 8192 + lane * 16;
            uint4* hp = (w == 3 ? &prm.sc->halo[((ti * 8 + hg) * 2 + wg) * 128] : (uint4*)(smem_raw + SM_STG + wg * 8192 + w * 2048)) + lane;
            mbar_wait2(BAR(B_EP), 0, BAR(B_WQF), 0);
            tag = lds1(sb + SM_EPOCH);
            QCHUNK(0, QC0);
            wg_wait<1>();
            reg_fence(ak); reg_fence(av);
            TR(2);
            uint32_t kf[3][7], vf[3][7];
            #pragma unroll
            for (int c = 0; c < 7; c++) {
                kf[2][c] = pack_bf16(ak[4 * c + 2], ak[4 * c + 3]);
                vf[2][c] = movm(pack_bf16(av[4 * c + 2], av[4 * c + 3]));
            }
            const uint32_t om = ~lane & 1;
            kf[2][0] = set_par(kf[2][0], om, tag); kf[2][4] = set_par(kf[2][4], om, tag);
            vf[2][1] = set_par(vf[2][1], om, tag); vf[2][5] = set_par(vf[2][5], om, tag);
            st_gen4(hp,      kf[2][0], kf[2][1], kf[2][2], kf[2][3]);
            st_gen4(hp + 32, kf[2][4], kf[2][5], kf[2][6], vf[2][0]);
            st_gen4(hp + 64, vf[2][1], vf[2][2], vf[2][3], vf[2][4]);
            st_gen4(hp + 96, vf[2][5], vf[2][6], __float_as_uint(rk[2][0]), __float_as_uint(rk[2][1]));
            pair_arrive(B_KVC);
            QCHUNK(QC0, QC1);
            #pragma unroll
            for (int c = 0; c < 7; c++) {
                kf[1][c] = pack_bf16(ak[4 * c], ak[4 * c + 1]);
                vf[1][c] = movm(pack_bf16(av[4 * c], av[4 * c + 1]));
            }
            QCHUNK(QC1, QC2);
            named_bar(1 + wg, 128);
            uint32_t* op = opaque_ptr((uint32_t*)&prm.sc->o[((ti * 2 + wg) * 56 + hg * 7) * 64] + w * 64 + lane);
            const uint32_t om0 = opaque((lane & 7) == w * 2), om1 = opaque((lane & 7) == w * 2 + 1);
            QCHUNK(QC2, 28);
            #undef QCHUNK
            const bool gt0 = 2 * t > g, gt1 = 2 * t + 1 > g, no_prev = ti == 0 && w == 0;
            const float kf0 = gt0 ? rk[1][0] : rk[2][0], kf1 = gt1 ? rk[1][1] : rk[2][1];
            constexpr float kScale = 0.18898223650461362f * 1.4426950408889634f;
            const float sq0 = rs0 * kScale, sf0 = kf0 * (rs1 * kScale), sf1 = kf1 * (rs1 * kScale);
            const float NEG = -__int_as_float(0x7f800000);
            const float nb0 = gt0 && no_prev ? NEG : 0.f, nb1 = gt1 && no_prev ? NEG : 0.f;
            const uint32_t mk = opaque((gt0 ? 0x0000ffffu : 0u) | (gt1 ? 0xffff0000u : 0u));
            const uint32_t sr = stg + ((w + 3) & 3) * 2048, hbar = BAR(w == 0 ? B_HL + wg : B_EP);
            mbar_wait(BAR(B_EP), 0);
            wg_wait<0>();
            reg_fence(aq);
            warp_arrive(BAR(B_A1D));
            TR(3);
            uint32_t qf[8][2];
            #pragma unroll
            for (int c = 0; c < 7; c++) {
                qf[c + (c > 3)][0] = pack_bf16(aq[4 * c], aq[4 * c + 1]);
                qf[c + (c > 3)][1] = pack_bf16(aq[4 * c + 2], aq[4 * c + 3]);
            }
            qf[4][0] = t >= 2 ? qf[3][0] : 0u; qf[4][1] = t >= 2 ? qf[3][1] : 0u;
            qf[3][0] = t < 2 ? qf[3][0] : 0u;  qf[3][1] = t < 2 ? qf[3][1] : 0u;
            float sc[2][3][4];
            auto scores = [&](int n) {
                #pragma unroll
                for (int hd = 0; hd < 2; hd++) {
                    sc[hd][n][0] = sc[hd][n][1] = sc[hd][n][2] = sc[hd][n][3] = 0.f;
                    mma16816(sc[hd][n], qf[4 * hd][0], qf[4 * hd][1], qf[4 * hd + 1][0], qf[4 * hd + 1][1], kf[n][3 * hd], kf[n][3 * hd + 1]);
                    mma16816(sc[hd][n], qf[4 * hd + 2][0], qf[4 * hd + 2][1], qf[4 * hd + 3][0], qf[4 * hd + 3][1], kf[n][3 * hd + 2], kf[n][3 * hd + 3]);
                }
            };
            scores(1); scores(2);
            mbar_wait(hbar, 0);
            {
                const uint4 u0 = lds4(sr), u1 = lds4(sr + 512), u3 = lds4(sr + 1536), u2 = lds4(sr + 1024);
                kf[0][0] = u0.x; kf[0][1] = u0.y; kf[0][2] = u0.z; kf[0][3] = u0.w;
                kf[0][4] = u1.x; kf[0][5] = u1.y; kf[0][6] = u1.z; vf[0][0] = u1.w;
                vf[0][1] = u2.x; vf[0][2] = u2.y; vf[0][3] = u2.z; vf[0][4] = u2.w;
                vf[0][5] = u3.x; vf[0][6] = u3.y; rk[0][0] = __uint_as_float(u3.z); rk[0][1] = __uint_as_float(u3.w);
            }
            TR(4);
            scores(0);
            const float ke0 = gt0 ? rk[0][0] : rk[1][0], ke1 = gt1 ? rk[0][1] : rk[1][1];
            const float se0 = ke0 * sq0, se1 = ke1 * sq0;
            uint32_t ow[7][2];
            #pragma unroll
            for (int hd = 0; hd < 2; hd++) {
                const int c0 = hd * 3;
                float (&sc_)[3][4] = sc[hd];
                const float e0 = fmaf(gt0 ? sc_[0][0] : sc_[1][0], se0, nb0), e1 = fmaf(gt1 ? sc_[0][1] : sc_[1][1], se1, nb1);
                const float f0 = (gt0 ? sc_[1][2] : sc_[2][2]) * sf0, f1 = (gt1 ? sc_[1][3] : sc_[2][3]) * sf1;
                const float me = quad_max(fmaxf(e0, e1)), mf = quad_max(fmaxf(f0, f1));
                const float p0 = ex2(e0 - me), p1 = ex2(e1 - me), r0 = ex2(f0 - mf), r1 = ex2(f1 - mf);
                const float ie = rcp(quad_sum(p0 + p1)), jf = rcp(quad_sum(r0 + r1));
                const uint32_t pp = pack_bf16(p0 * ke0 * ie, p1 * ke1 * ie), rp = pack_bf16(r0 * kf0 * jf, r1 * kf1 * jf);
                const uint32_t a0 = pp & ~mk, a1 = rp & mk, a3 = rp & ~mk, a4 = pp & mk, zero = opaque(0u), zero2 = opaque(0u);
                #pragma unroll
                for (int c = 0; c < 4; c++) {
                    float o[4] = {0.f, 0.f, 0.f, 0.f};
                    mma16816(o, a0, a1, zero, a3, vf[1][c0 + c], vf[2][c0 + c]);
                    mma1688(o, a4, zero2, vf[0][c0 + c]);
                    const uint32_t lo = pack_bf16(o[0], o[1]), hi = pack_bf16(o[2], o[3]);
                    if (hd == 1 && c == 0) { if (t >= 2) { ow[3][0] = lo; ow[3][1] = hi; } }
                    else { ow[c0 + c][0] = lo; ow[c0 + c][1] = hi; }
                }
            }
            #pragma unroll
            for (int c = 0; c < 7; c++) {
                stg1(op + c * 256,      set_par(ow[c][0], om0, tag));
                stg1(op + c * 256 + 32, set_par(ow[c][1], om1, tag));
            }
            TR(5);
        }
        float as[28], ac[28];
        uint32_t xch, peer_xch, gm[2][4], *gp1, *gp2;
        const uint32_t *hp, *ht;
        const uint2* hq;
        uint64_t da0, db0;
        const int cg2 = (g2j + 2 * wg) * 2 + (rank ^ 1), cg1 = (g1j + 2 * wg) * 2 + (rank ^ (g1f < 14));
        const bool lead = elect_one();
        {
            const int cg = a2j * 2 + wg;
            float acc2[28];
            mbar_wait(BAR(B_XRF), 0);
            {
                const uint32_t xa = sb + SM_XR + wg * 8192 + (w * 16 + (lane & 15)) * 128;
                #pragma unroll
                for (int c = 0; c < 4; c++) {
                    uint32_t xr[4];
                    asm volatile("ldmatrix.sync.aligned.m8n8.x4.shared.b16 {%0,%1,%2,%3}, [%4];"
                                 : "=r"(xr[0]), "=r"(xr[1]), "=r"(xr[2]), "=r"(xr[3])
                                 : "r"(xa + ((((c * 2 + wg + (lane >> 4)) ^ lane) & 7) << 4)) : "memory");
                    #pragma unroll
                    for (int e = 0; e < (c < 3 ? 4 : 2); e++) { acc2[8 * c + 2 * e] = bf_lo(xr[e]); acc2[8 * c + 2 * e + 1] = bf_hi(xr[e]); }
                }
            }
            uint32_t* spw = opaque_ptr(&prm.sc->stats[((a2s * 8 + cg) * 4 + w) * 32 + lane]);
            const uint32_t* spr = opaque_ptr(&prm.sc->stats[(a2s * 32 + w) * 32 + lane]);
            uint32_t* rp = opaque_ptr((uint32_t*)&prm.sc->rows[a2s * 64 + w * 16 + (t >> 1) * 8 + g] + (t & 1));
            const int cgs = cg ^ (a2s >> 4);
            uint32_t* np = opaque_ptr((uint32_t*)&prm.sc->hn[(a2s * 56 + cgs * 7) * 64] + w * 64 + lane);
            const uint64_t dwo = make_desc(sb + SM_WKV + wg * (28672 + 16), 0, true);
            const uint64_t doa = make_desc(sb + SM_WQ, 1024, false, 128);
            bias1a = prm.b1[g1f * 64 + w * 16 + g]; bias1b = prm.b1[g1f * 64 + w * 16 + 8 + g];
            const __nv_bfloat16 bias2 = prm.b2[ti * 128 + (w * 16 + (t >> 1) * 8 + g) * 2 + a2p];
            reg_fence(acc2);
            fence_async_smem();
            warp_arrive(BAR(B_XD));
            {
                xch = opaque(sb + SM_XCH + w * 1792 + lane * 16);
                asm volatile("mapa.shared::cluster.u32 %0, %1, %2;" : "=r"(peer_xch) : "r"(xch), "r"(rank ^ 1));
                const int hcg = cg2 ^ (g2s >> 4), hrg = (g2s & 1) * 4 + w;
                const uint32_t* hl = (const uint32_t*)&prm.sc->hn[((g2s >> 1) * 112 + hcg * 7) * 64 + hrg * 8];
                hp = opaque_ptr(hl + (g & 1) * 14336 + (g >> 1) * 4 + t);
                ht = opaque_ptr(hl + (lane & 1) * 14336 + min(lane >> 1, 6) * 256 + ((min(lane >> 1, 6) - (hcg & 1)) & 3) * 8 + hrg);
                hq = opaque_ptr(&prm.sc->rows[((g2s >> 1) * 2 + (g & 1)) * 64 + hrg * 8 + (g >> 1)]);
                gp1 = opaque_ptr((uint32_t*)&prm.sc->g[(g1f * 56 + cg1 * 7) * 64] + w * 64 + lane);
                gp2 = opaque_ptr((uint32_t*)(prm.out + (size_t)(g2s * 64 + w * 16 + lane / 7) * kD + cg2 * 56) + (lane % 7) * 4);
                da0 = make_desc(sb, 0, true); db0 = make_desc(sb + SM_B, 128, false);
            }
            static_for<0, 4>([&](auto P_) {
                constexpr int P = decltype(P_)::value;
                if (P == 0) mbar_wait(BAR(B_WOF), 0);
                if (P == 2) mbar_wait2(BAR(B_OF + P), 0, BAR(B_WOF + 1), 0); else mbar_wait(BAR(B_OF + P), 0);
                if (P == 0) TR(6);
                wg_fence();
                static_for<0, 7>([&](auto K_) { constexpr int k = decltype(K_)::value;
                    wgmma_ss_n56<P * 14336 + k * 2048, (P >> 1) * 57344 + (P & 1) * 14336 + k * 2048, 0>(acc2, doa, dwo); });
                if (P) wg_commit();
                if (P == 2) { wg_wait<1>(); warp_arrive(BAR(B_OC)); }
            });
            wg_wait<0>();
            reg_fence(acc2);
            TR(7);
            float s0 = 0.f, s1 = 0.f, q0 = 0.f, q1 = 0.f;
            #pragma unroll
            for (int c = 0; c < 7; c++) {
                s0 += acc2[4 * c] + acc2[4 * c + 1];     q0 = fmaf(acc2[4 * c], acc2[4 * c], fmaf(acc2[4 * c + 1], acc2[4 * c + 1], q0));
                s1 += acc2[4 * c + 2] + acc2[4 * c + 3]; q1 = fmaf(acc2[4 * c + 2], acc2[4 * c + 2], fmaf(acc2[4 * c + 3], acc2[4 * c + 3], q1));
            }
            const bool th = t >= 2, to = t & 1;
            const float sa = (th ? s1 : s0) + __shfl_xor_sync(~0u, th ? s0 : s1, 2), qa = (th ? q1 : q0) + __shfl_xor_sync(~0u, th ? q0 : q1, 2);
            const float part = (to ? qa : sa) + __shfl_xor_sync(~0u, to ? sa : qa, 1);
            stg1(spw, set_par(__float_as_uint(part), 1u, tag));
            const uint32_t tpoll = clk32() + SDELAY;
            TR(8);
            warp_arrive(BAR(B_HD));
            uint32_t nm[2][4], us[8];
            spin_until(tpoll);
            #pragma unroll
            for (int i = 0; i < 8; i++) us[i] = ld_rlx(spr + i * 128);
            #pragma unroll
            for (int i = 0; i < 8; i++) {
                nm[i >> 2][i & 3] = lane == ((i - (cgs & 1)) & 3) * 8 + w * 2 + (i >> 2);
                gm[i >> 2][i & 3] = opaque(lane == ((i - (cg1 & 1)) & 3) * 8 + w * 2 + (i >> 2));
            }
            #pragma unroll
            for (int c = 0; c < 28; c++) { ac[c] = 0.5f * __bfloat162float(c & 2 ? bias1b : bias1a); as[c] = 0.f; }
            reg_fence(as); reg_fence(ac);
            {
                int it = 0;
                while (true) {
                    uint32_t bad = 0;
                    #pragma unroll
                    for (int i = 0; i < 8; i++) bad |= us[i] ^ tag;
                    if (!__any_sync(~0u, bad & 1)) break;
                    RETRY_COUNT(3);
                    if (++it > kSpinLimit) { TIMEOUT(103); break; }
                    #pragma unroll
                    for (int i = 0; i < 8; i++) us[i] = ld_rlx(spr + i * 128);
                }
            }
            TR(9);
            const float tot = (((__uint_as_float(us[0]) + __uint_as_float(us[1])) + (__uint_as_float(us[2]) + __uint_as_float(us[3])))
                            + ((__uint_as_float(us[4]) + __uint_as_float(us[5])) + (__uint_as_float(us[6]) + __uint_as_float(us[7])))) * (1.f / kD);
            const float oth = __shfl_xor_sync(~0u, tot, 1);
            const float mean = to ? oth : tot;
            const float var = fmaxf(fmaf(-mean, mean, to ? tot : oth), 0.f);
            const float rra = rsq(fmaf(var, 4.f + 4.f * kEps, 4.f * kEps * kEps)), mra = -mean * rra;
            const float rrb = __shfl_xor_sync(~0u, rra, 2), mrb = __shfl_xor_sync(~0u, mra, 2);
            const float rr0 = th ? rrb : rra, mr0 = th ? mrb : mra, rr1 = th ? rra : rrb, mr1 = th ? mra : mrb;
            #pragma unroll
            for (int c = 0; c < 7; c++) {
                stg1(np + c * 256,      set_par(pack_bf16(fmaf(acc2[4 * c], rr0, mr0), fmaf(acc2[4 * c + 1], rr0, mr0)), nm[0][c & 3], tag));
                stg1(np + c * 256 + 32, set_par(pack_bf16(fmaf(acc2[4 * c + 2], rr1, mr1), fmaf(acc2[4 * c + 3], rr1, mr1)), nm[1][c & 3], tag));
            }
            TR(10);
            if (cg == 0) stg1(rp, set_par(__float_as_uint(to ? mean + __bfloat162float(bias2) : rcp(rra)), 1u, tag));
        }
        auto send = [&]() {
            const uint32_t rf = pbar0 + (B_RF + warp) * 8;
            #pragma unroll
            for (int c = 0; c < 4; c++) {
                const uint32_t p0 = pack_bf16(as[8 * c], as[8 * c + 1]), p1 = pack_bf16(as[8 * c + 2], as[8 * c + 3]);
                if (c < 3) {
                    const uint32_t p2 = pack_bf16(as[8 * c + 4], as[8 * c + 5]), p3 = pack_bf16(as[8 * c + 6], as[8 * c + 7]);
                    asm volatile("st.async.shared::cluster.mbarrier::complete_tx::bytes.v4.b32 [%0], {%1,%2,%3,%4}, [%5];"
                                 :: "r"(peer_xch + c * 512), "r"(p0), "r"(p1), "r"(p2), "r"(p3), "r"(rf) : "memory");
                } else {
                    asm volatile("st.async.shared::cluster.mbarrier::complete_tx::bytes.v2.b32 [%0], {%1,%2}, [%3];"
                                 :: "r"(peer_xch + 1536 - lane * 8), "r"(p0), "r"(p1), "r"(rf) : "memory");
                }
            }
        };
        auto receive = [&](uint32_t (&pk)[14], uint32_t phase) {
            mbar_wait(BAR(B_RF + warp), phase);
            #pragma unroll
            for (int c = 0; c < 3; c++) { const uint4 u = lds4(xch + c * 512); pk[4 * c] = u.x; pk[4 * c + 1] = u.y; pk[4 * c + 2] = u.z; pk[4 * c + 3] = u.w; }
            const uint2 u = lds2(xch + 1536 - lane * 8); pk[12] = u.x; pk[13] = u.y;
        };
        uint2 rw[2]; uint32_t tw;
        auto load_rows = [&]() { tw = ld_rlx(ht); rw[0] = ld_rlx2(hq); rw[1] = ld_rlx2(hq + 4); };
        rw[0] = rw[1] = make_uint2(0u, 0u); tw = ~tag;
        #pragma unroll 1
        for (int ge = 0;; ge++) {
          if (ge || g1_on) {
            const int use = ge * 2 + wg;
            int entry = ge ? 1 : 2 * wg, stop = 0;
            uint64_t da = da0 + (ge ? -3 : wg ? NR - 10 : 0) * 512;
            bool rel = lead && use == 1;
            const uint32_t xfree = BAR(use > (g1_on ? 0 : 2) ? B_RE + use - 1 : B_PD);
            mbar_wait(BAR(B_AF), 0);
            if (ge && (wg || g1_on)) named_bar(5 - wg, 256);
            TR(11 + ge * 4);
            auto step = [&](auto I_) {
                constexpr int i = decltype(I_)::value, sl = i % NB, ao = i * 8192, bo = sl * 14336;
                mbar_wait_fast(BAR(B_BF + sl), i / NB);
                wg_fence();
                wgmma_ss_n112<ao,        bo,       1>(as, ac, da, db0);
                wgmma_ss_n112<ao + 2048, bo + 256, 1>(as, ac, da, db0);
                wgmma_ss_n112<ao + 4096, bo + 512, 1>(as, ac, da, db0);
                wgmma_ss_n112<ao + 6144, bo + 768, 1>(as, ac, da, db0);
                wg_commit();
                if (i == 1 && stop == 1) named_arrive(4, 256);
                if (i == 3 && (use == 1 || use == 2)) named_arrive(4 + wg, 256);
                wg_wait<1>();
                mbar_arrive_if(BAR(B_BE + (13 + i) % 14), rel);
                rel = lead;
            };
            #pragma unroll 1
            while (true) {
                if (entry < 1) {
                    static_for<0, 2>(step);
                    if (stop == 1) break;
                    static_for<2, 4>(step);
                    if (stop) break;
                }
                if (entry < 2) static_for<4, 10>(step);
                else {
                    uint32_t af[NR * 4][4];
                    mbar_wait(BAR(B_GO), 0);
                    const uint32_t tp = lds1(sb + SM_TG + 4) + PLOFF;
                    int it = 0;
                    while ((int)(gtime32() - tp) < 0 && ++it < 256) __nanosleep(20);
                    const uint32_t la = sb + ((lane >> 4) * 8 + (lane & 7)) * 128 + (((w * 2 + ((lane >> 3) & 1)) ^ (lane & 7)) << 4);
                    #pragma unroll
                    for (int k = 0; k < NR * 4; k++)
                        asm volatile("ldmatrix.sync.aligned.m8n8.x4.trans.shared.b16 {%0,%1,%2,%3}, [%4];"
                                     : "=r"(af[k][0]), "=r"(af[k][1]), "=r"(af[k][2]), "=r"(af[k][3]) : "r"(la + k * 2048) : "memory");
                    __syncwarp();
                    mbar_arrive_if(BAR(B_PL), lead);
                    named_bar(4, 256);
                    static_for<0, NR>([&](auto I_) {
                        constexpr int i = decltype(I_)::value, sl = (16 + i) % NB, o = sl * 14336;
                        mbar_wait_fast(BAR(B_BF + sl), (16 + i) / NB & 1);
                        wg_fence();
                        wgmma_rs_n112<o,       1>(as, ac, af[4 * i][0], af[4 * i][1], af[4 * i][2], af[4 * i][3], db0);
                        wgmma_rs_n112<o + 256, 1>(as, ac, af[4 * i + 1][0], af[4 * i + 1][1], af[4 * i + 1][2], af[4 * i + 1][3], db0);
                        wgmma_rs_n112<o + 512, 1>(as, ac, af[4 * i + 2][0], af[4 * i + 2][1], af[4 * i + 2][2], af[4 * i + 2][3], db0);
                        wgmma_rs_n112<o + 768, 1>(as, ac, af[4 * i + 3][0], af[4 * i + 3][1], af[4 * i + 3][2], af[4 * i + 3][3], db0);
                        wg_commit();
                        if (i) { wg_wait<1>(); mbar_arrive_if(BAR(B_BE + (15 + i) % (2 * NB)), lead); }
                    });
                }
                static_for<10, 14>(step);
                entry = 0; stop = use + 1; da += 14 * 512;
            }
            const uint32_t prev = BAR(B_BE + (use ? 3 : 1));
            const bool xok = mbar_test(xfree, 0);
            wg_wait<0>();
            reg_fence(as); reg_fence(ac);
            mbar_arrive_if(prev, lead);
            if (!xok) mbar_wait(xfree, 0);
            if (ge) break;
            send();
            load_rows();
            TR(12);
            uint32_t pk[14];
            receive(pk, 0);
            TR(13);
            #pragma unroll
            for (int c = 0; c < 14; c++) {
                float r[2];
                #pragma unroll
                for (int e = 0; e < 2; e++) {
                    const float u = ac[2 * c + e] + (e ? bf_hi(pk[c]) : bf_lo(pk[c]));
                    r[e] = fmaf(u, tanh_hw(u * fmaf(u * u, 8.f * 0.7978845608f * 0.044715f, 2.f * 0.7978845608f)), u);
                }
                stg1(gp1 + (c >> 1) * 256 + (c & 1) * 32, set_par(pack_bf16(r[0], r[1]), gm[c & 1][(c >> 1) & 3], tag));
            }
            named_bar(1 + wg, 128);
            if (w == 0 && lane == 0) {
                asm volatile("st.shared.u32 [%0], %1;" :: "r"(sb + SM_TG + 8 + wg * 4), "r"(clk32() + (wg ? XSPECB : XSPEC)) : "memory");
                mbar_arrive(BAR(B_GD + wg));
            }
            if (lead) mbar_expect(BAR(B_RF + warp), 1792);
            mbar_arrive_remote_if(pbar0 + (B_RE + wg) * 8, lead);
            TR(14);
          } else mbar_wait(BAR(B_GD), 0);
            {
                int it = 0;
                while (__any_sync(~0u, ((tw ^ tag) | (rw[0].x ^ tag) | (rw[0].y ^ tag) | (rw[1].x ^ tag) | (rw[1].y ^ tag)) & 1)) {
                    if (++it > kSpinLimit) { TIMEOUT(110); break; }
                    load_rows();
                }
                uint32_t hw[14];
                #pragma unroll
                for (int c = 0; c < 14; c++) hw[c] = ld_rlx(hp + (c >> 1) * 256 + (c & 1) * 16);
                #pragma unroll
                for (int c = 0; c < 14; c++) {
                    ac[2 * c]     = fmaf(bf_lo(hw[c]), __uint_as_float(rw[c & 1].x), __uint_as_float(rw[c & 1].y));
                    ac[2 * c + 1] = fmaf(bf_hi(hw[c]), __uint_as_float(rw[c & 1].x), __uint_as_float(rw[c & 1].y));
                    as[2 * c] = as[2 * c + 1] = 0.f;
                }
                reg_fence(as); reg_fence(ac);
            }
        }
        uint32_t po[14], pk[14];
        if (!wg) sleep_until(clk32() + w * STAG2);
        send();
        #pragma unroll
        for (int c = 0; c < 14; c++) po[c] = opaque(pack_bf16(ac[2 * c], ac[2 * c + 1]));
        TR(16);
        receive(pk, g1_on);
        TR(17);
        #pragma unroll
        for (int c = 0; c < 14; c++) pk[c] = add_bf16x2(po[c], pk[c]);
        __syncwarp();
        const uint32_t sa = xch - lane * 16 + (lane & 15) * 112 + (lane >> 4) * 16;
        #pragma unroll
        for (int m = 0; m < 3; m++)
            asm volatile("stmatrix.sync.aligned.m8n8.x4.shared.b16 [%0], {%1,%2,%3,%4};"
                         :: "r"(sa + m * 32), "r"(pk[4 * m]), "r"(pk[4 * m + 1]), "r"(pk[4 * m + 2]), "r"(pk[4 * m + 3]) : "memory");
        asm volatile("stmatrix.sync.aligned.m8n8.x2.shared.b16 [%0], {%1,%2};" :: "r"(sa + 96), "r"(pk[12]), "r"(pk[13]) : "memory");
        __syncwarp();
        if (lane < 28) {
            #pragma unroll
            for (int i = 0; i < 4; i++) { const uint4 u = lds4(xch + i * 448); stg4(gp2 + i * 896, u.x, u.y, u.z, u.w); }
        }
        __syncwarp();
        mbar_arrive_remote_if(pbar0 + (B_RE + 2) * 8, lead && wg == 0);
        TR(18);
        if (tid == 128) TRG(62);
        if (b == 0 && tid == 128) prm.sc->epoch = tag;
    }
}

typedef CUresult (*EncodeFn)(CUtensorMap*, CUtensorMapDataType, cuuint32_t, void*, const cuuint64_t*, const cuuint64_t*,
                             const cuuint32_t*, const cuuint32_t*, CUtensorMapInterleave, CUtensorMapSwizzle,
                             CUtensorMapL2promotion, CUtensorMapFloatOOBfill);

void make_map(EncodeFn enc, CUtensorMap* m, const void* base, uint64_t cols, uint64_t rows, uint32_t box_rows) {
    cuuint64_t dims[2] = {cols, rows};
    cuuint64_t strides[1] = {cols * 2};
    cuuint32_t box[2] = {64, box_rows};
    cuuint32_t es[2] = {1, 1};
    enc(m, CU_TENSOR_MAP_DATA_TYPE_BFLOAT16, 2, const_cast<void*>(base), dims, strides, box, es, CU_TENSOR_MAP_INTERLEAVE_NONE,
        CU_TENSOR_MAP_SWIZZLE_128B, CU_TENSOR_MAP_L2_PROMOTION_L2_128B, CU_TENSOR_MAP_FLOAT_OOB_FILL_NONE);
}

}

extern "C" void kernel_launch(void* const* d_in, const int* in_sizes, int n_in, void* d_out, int out_size) {
    (void)in_sizes; (void)n_in; (void)out_size;
    void* fn = nullptr;
    cudaDriverEntryPointQueryResult qr;
    cudaGetDriverEntryPoint("cuTensorMapEncodeTiled", &fn, cudaEnableDefault, &qr);
    EncodeFn enc = (EncodeFn)fn;
    CUtensorMap mX2, mX, mWqkv, mWo, mW1, mW2;
    {
        cuuint64_t dims[3] = {kD, kS / 2, 2}, strides[2] = {4 * kD, 2 * kD};
        cuuint32_t box[3] = {64, 64, 2}, es[3] = {1, 1, 1};
        enc(&mX2, CU_TENSOR_MAP_DATA_TYPE_BFLOAT16, 3, d_in[0], dims, strides, box, es, CU_TENSOR_MAP_INTERLEAVE_NONE,
            CU_TENSOR_MAP_SWIZZLE_128B, CU_TENSOR_MAP_L2_PROMOTION_L2_128B, CU_TENSOR_MAP_FLOAT_OOB_FILL_NONE);
    }
    make_map(enc, &mX, d_in[0], 2 * kD, kS / 2, 64);
    make_map(enc, &mWqkv, d_in[1], 3 * kD, kD, 64);
    make_map(enc, &mWo, d_in[2], kD, kD, 112);
    make_map(enc, &mW1, d_in[4], 2 * kF, kS / 2, 64);
    make_map(enc, &mW2, d_in[6], kS, kF, 64);
    Params prm;
    prm.x = (const __nv_bfloat16*)d_in[0];
    prm.wqkv = (const __nv_bfloat16*)d_in[1];
    prm.wo = (const __nv_bfloat16*)d_in[2];
    prm.w1 = (const __nv_bfloat16*)d_in[4];
    prm.b1 = (const __nv_bfloat16*)d_in[5];
    prm.w2 = (const __nv_bfloat16*)d_in[6];
    prm.b2 = (const __nv_bfloat16*)d_in[7];
    prm.out = (__nv_bfloat16*)d_out;
    cudaGetSymbolAddress((void**)&prm.sc, g_scratch);
    cudaFuncSetAttribute(fused_kernel, cudaFuncAttributeMaxDynamicSharedMemorySize, SM_TOTAL);
    fused_kernel<<<128, 384, SM_TOTAL, cudaStreamPerThread>>>(prm, mX2, mX, mWqkv, mWo, mW1, mW2);
}
```

```cpp
#include <cuda_runtime.h>
#include <cuda.h>
#include <cuda_bf16.h>
#include <stdint.h>
#include <type_traits>

namespace {

constexpr int kS = 2048, kD = 448, kF = 1792;
constexpr float kEps = 1e-5f;

#define FS 32
struct Scratch {
    uint4    o[32 * 56 * 64];
    uint4    hn[32 * 56 * 64];
    uint4    g[28 * 56 * 64];
    uint4    halo[16 * 8 * 2 * 4 * 32];
    uint32_t stats[32 * 8 * 4 * 32];
    uint2    rows[32 * 64];
    uint32_t flag_o[16 * 8 * FS];
    uint32_t flag_h[32 * 4 * FS];
    uint32_t epoch;
};
__device__ __align__(1024) Scratch g_scratch;
#define TIMEOUT(code)
#define RETRY_COUNT(i)
#define CAP_DECL(n, k)
#define CAP(n)
#define CAP_SKIP(n)
#define EV(i, dep)
#define TR2(idx)
#define TR(idx)
#define TRW(idx)
#define TRG(idx)

constexpr uint32_t SM_WKV  = 114688;
constexpr uint32_t SM_XR   = 24576;
constexpr uint32_t SM_STG  = 40960;
constexpr uint32_t SM_WQ   = 57344;
constexpr uint32_t SM_XCH  = 0;
constexpr uint32_t SM_B    = 131072;
constexpr uint32_t SM_BAR  = 231424;
constexpr uint32_t SM_TOTAL = SM_BAR + 1024;
constexpr int NB = 7;
#define SH1 0
#define SH2 0
#define SH2N 5
#define SH3 0
#define NSPEC 4
#define XSPEC 500
#define C2 0
#define C3 0
#define CN2 7200
#define CN3 10900
constexpr int B_XF = 0, B_WKVF = 7, B_WQF = 14, B_XRF = 15, B_WOF = 16,
              B_XC = 18, B_KV3 = 19, B_KVC = 20,
              B_A1D = 21, B_XD = 22, B_OC = 23,
              B_BE = 24  , B_RE = B_BE + 2 * NB,
              B_PL = B_RE + 3, B_AF = B_PL + 1, B_BL = B_AF + 1  , B_OL = B_BL + 2 * NB  ,
              B_BF = B_OL + 4  , B_OF = B_BF + NB, B_RF = B_OF + 4, B_EP = B_RF + 8, B_PD = B_EP + 1, B_RT = B_PD + 1, B_HL = B_RT + 2,
              B_HD = B_HL + 2  , B_GO = B_HD + 1, B_GD = B_GO + 1, B_COUNT = B_GD + 2;
#define WEARLY 6
#define PF0 126
#define TMPF 2
#define RSTE 2
#define POLLP 1
#define PROBEP 1
#define LOADP 1
#define LOADW 64
#define NOB 0
#define AEARLY 5
#define W1PACE 400
#define W2PACE 350
#define PFPACE 330
#define PFBAR (B_XF + 6)
#define DELTA 1600
#define DELTA2 DELTA
#define BPACE 230
#define BURST 2
#define W1OFF 350
#define W2OFF 800
#define XPACE 0
#define PSTAG 200
constexpr uint32_t SM_EPOCH = SM_BAR + B_COUNT * 8, SM_TG = SM_EPOCH + 4  , SM_TG2 = SM_TG + 16  , SM_TR = SM_BAR + 768;

#define HDELAY 0
#define QC0 4
#define QC1 10
#define QC2 16
#define HPOS 1
#define XSPECB 750
#define PACE1 120
#define PACE2 400
#define RELOAD1 1
#define VCH 1
#define SOFF 0
#define XW 1
#define XLAG 0
#define PFX 3
#define PFD 250
#define SDELAY 300
#define PDELAY 500
#define NPRE 10
#define PREPACE 0
#define AFIRST 1
#define DELTAO 800
#define NS 0
#define GCH 14
#define OCH 14
#define ICH 14
#define PACKO
#define NR 8
#define HMODE 2
#define HOFF0 (-100)
#define HOFF1 900
#define STAG1 0
#define STAG2 400
#define PLOFF (-250)
#define HSRC h
#define WO1 1
#define WOD 300
#define WOP 400
#define WOP0 0
#define KV5 1
#define XLATE 0
#define W0E 1
#define W0F 2
#define PACEA 400
#define PACEB 300
#define PFN 16
#define PFPACE2 300
#define PF2R 1
#define PFW 4
#define PFBAR2 PFBAR
#define WOQ 3
#define W1Q 3
#define APOS1 ((1ull << 4) | (1ull << 8) | (1ull << 12) | (1ull << 5) | (1ull << 9) | (1ull << 13))
#define APOS2 (0x5555555ull << 17)
constexpr uint32_t seg_mask(int h, int p0, int p1) {
    uint32_t m = 0; int n = 0;
    for (int p = p0; p < p1; p++) if ((p & 1) == h) m |= (uint32_t)(((APOS1 | APOS2) >> p) & 1) << n++;
    return m | 1u << n;
}
constexpr uint64_t seg_masks(int h) {
    return 2 | (uint64_t)seg_mask(h, 0, 16) << 10 | (uint64_t)seg_mask(h, 16, 32) << 20
             | (uint64_t)seg_mask(h, 32, 46) << 30 | (uint64_t)seg_mask(h, 46, 60) << 40;
}
constexpr uint64_t kSegMasks0 = seg_masks(0), kSegMasks1 = seg_masks(1);

constexpr int kSpinLimit = 1 << 15;
__device__ __forceinline__ bool elect_one() {
    uint32_t p;
    asm volatile("{ .reg .pred P; elect.sync _|P, 0xffffffff; selp.u32 %0, 1, 0, P; }" : "=r"(p));
    return p;
}
__device__ __forceinline__ void mbar_init(uint32_t bar, uint32_t cnt) { asm volatile("mbarrier.init.shared::cta.b64 [%0], %1;" :: "r"(bar), "r"(cnt)); }
__device__ __forceinline__ void mbar_expect(uint32_t bar, uint32_t bytes) { asm volatile("mbarrier.arrive.expect_tx.shared::cta.b64 _, [%0], %1;" :: "r"(bar), "r"(bytes) : "memory"); }
__device__ __forceinline__ void mbar_expect_more(uint32_t bar, uint32_t bytes) { asm volatile("mbarrier.expect_tx.relaxed.cta.shared::cta.b64 [%0], %1;" :: "r"(bar), "r"(bytes) : "memory"); }
__device__ __forceinline__ void mbar_arrive(uint32_t bar) { asm volatile("mbarrier.arrive.shared::cta.b64 _, [%0];" :: "r"(bar) : "memory"); }
__device__ __forceinline__ void mbar_wait(uint32_t bar, uint32_t parity) {
    uint32_t ok; int it = 0;
    do {
        asm volatile("{ .reg .pred p; mbarrier.try_wait.parity.shared::cta.b64 p, [%1], %2; selp.u32 %0, 1, 0, p; }"
                     : "=r"(ok) : "r"(bar), "r"(parity) : "memory");
        if (++it > kSpinLimit) { TIMEOUT((bar & 1023) >> 3); break; }
    } while (!ok);
}
__device__ __forceinline__ bool mbar_try(uint32_t bar, uint32_t parity) {
    uint32_t ok;
    asm volatile("{ .reg .pred p; mbarrier.try_wait.parity.shared::cta.b64 p, [%1], %2; selp.u32 %0, 1, 0, p; }" : "=r"(ok) : "r"(bar), "r"(parity) : "memory");
    return ok;
}
__device__ __forceinline__ bool mbar_test(uint32_t bar, uint32_t parity) {
    uint32_t ok;
    asm volatile("{ .reg .pred p; mbarrier.test_wait.parity.shared::cta.b64 p, [%1], %2; selp.u32 %0, 1, 0, p; }" : "=r"(ok) : "r"(bar), "r"(parity) : "memory");
    return ok;
}
__device__ __forceinline__ void mbar_wait_fast(uint32_t bar, uint32_t parity) { if (!mbar_try(bar, parity)) mbar_wait(bar, parity); }
__device__ __forceinline__ void mbar_wait2(uint32_t bar0, uint32_t par0, uint32_t bar1, uint32_t par1) {
    uint32_t ok; int it = 0;
    do {
        asm volatile("{ .reg .pred p, q; mbarrier.try_wait.parity.shared::cta.b64 p, [%1], %2;\n"
                     "mbarrier.try_wait.parity.shared::cta.b64 q, [%3], %4; and.pred p, p, q; selp.u32 %0, 1, 0, p; }"
                     : "=r"(ok) : "r"(bar0), "r"(par0), "r"(bar1), "r"(par1) : "memory");
        if (++it > kSpinLimit) { TIMEOUT((bar0 & 1023) >> 3); break; }
    } while (!ok);
}
__device__ __forceinline__ void sched_fence(uint32_t v) {
    asm volatile("{ .reg .pred p; .reg .b32 x; mov.b32 x, %0;\nL: setp.eq.u32 p, x, 0xffffffff; @p mov.u32 x, %%clock; @p bra L; }" :: "r"(v) : "memory");
}
template <int N> __device__ __forceinline__ void reg_fence(float (&d)[N]) {
    #pragma unroll
    for (int i = 0; i < N; i++) asm volatile("" : "+f"(d[i]) :: "memory");
}
__device__ __forceinline__ void mbar_wait_cluster(uint32_t bar, uint32_t parity) {
    uint32_t ok; int it = 0;
    do {
        asm volatile("{ .reg .pred p; mbarrier.try_wait.parity.acquire.cluster.shared::cta.b64 p, [%1], %2; selp.u32 %0, 1, 0, p; }"
                     : "=r"(ok) : "r"(bar), "r"(parity) : "memory");
        if (++it > kSpinLimit) { TIMEOUT((bar & 1023) >> 3); break; }
    } while (!ok);
}
__device__ __forceinline__ void mbar_arrive_if(uint32_t bar, bool pred) {
    asm volatile("{ .reg .pred p; setp.ne.u32 p, %1, 0; @p mbarrier.arrive.shared::cta.b64 _, [%0]; }" :: "r"(bar), "r"((uint32_t)pred) : "memory");
}
template <int P> __device__ __forceinline__ void tick() {
    if (P > 1) { const uint32_t t = ((uint32_t)clock() | (P - 1)) + 1; while ((int)((uint32_t)clock() - t) < 0) {} }
}
__device__ __forceinline__ void warp_arrive(uint32_t bar) { __syncwarp(); if (elect_one()) mbar_arrive(bar); }
__device__ __forceinline__ void tma2d(uint32_t dst, const CUtensorMap* m, int c0, int c1, uint32_t bar) {
    asm volatile("cp.async.bulk.tensor.2d.shared::cluster.global.mbarrier::complete_tx::bytes [%0], [%1, {%3, %4}], [%2];"
                 :: "r"(dst), "l"(m), "r"(bar), "r"(c0), "r"(c1) : "memory");
}
__device__ __forceinline__ void tma3d(uint32_t dst, const CUtensorMap* m, int c0, int c1, int c2, uint32_t bar) {
    asm volatile("cp.async.bulk.tensor.3d.shared::cluster.global.mbarrier::complete_tx::bytes [%0], [%1, {%3, %4, %5}], [%2];"
                 :: "r"(dst), "l"(m), "r"(bar), "r"(c0), "r"(c1), "r"(c2) : "memory");
}
__device__ __forceinline__ void tma2d_mc(uint32_t dst, const CUtensorMap* m, int c0, int c1, uint32_t bar) {
    asm volatile("cp.async.bulk.tensor.2d.shared::cluster.global.mbarrier::complete_tx::bytes.multicast::cluster [%0], [%1, {%3, %4}], [%2], %5;"
                 :: "r"(dst), "l"(m), "r"(bar), "r"(c0), "r"(c1), "h"((uint16_t)3) : "memory");
}
__device__ __forceinline__ void bulk_g2s_mc(uint32_t dst, const void* src, uint32_t bytes, uint32_t bar) {
    asm volatile("cp.async.bulk.shared::cluster.global.mbarrier::complete_tx::bytes.multicast::cluster [%0], [%1], %2, [%3], %4;"
                 :: "r"(dst), "l"(src), "r"(bytes), "r"(bar), "h"((uint16_t)3) : "memory");
}
__device__ __forceinline__ void mbar_arrive_remote_if(uint32_t cluster_bar, bool pred) {
    asm volatile("{ .reg .pred p; setp.ne.u32 p, %1, 0; @p mbarrier.arrive.shared::cluster.b64 _, [%0]; }" :: "r"(cluster_bar), "r"((uint32_t)pred) : "memory");
}
__device__ __forceinline__ void bulk_g2s(uint32_t dst, const void* src, uint32_t bytes, uint32_t bar) {
    asm volatile("cp.async.bulk.shared::cluster.global.mbarrier::complete_tx::bytes [%0], [%1], %2, [%3];"
                 :: "r"(dst), "l"(src), "r"(bytes), "r"(bar) : "memory");
}
__device__ __forceinline__ void bulk_prefetch(const void* src, uint32_t bytes) { asm volatile("cp.async.bulk.prefetch.L2.global [%0], %1;" :: "l"(src), "r"(bytes) : "memory"); }
__device__ __forceinline__ void wg_fence()  { asm volatile("wgmma.fence.sync.aligned;" ::: "memory"); }
__device__ __forceinline__ void wg_commit() { asm volatile("wgmma.commit_group.sync.aligned;" ::: "memory"); }
template <int N> __device__ __forceinline__ void wg_wait() { asm volatile("wgmma.wait_group.sync.aligned %0;" :: "n"(N) : "memory"); }
__device__ __forceinline__ void named_bar(int id, int n) { asm volatile("bar.sync %0, %1;" :: "r"(id), "r"(n) : "memory"); }
__device__ __forceinline__ void named_arrive(int id, int n) { asm volatile("bar.arrive %0, %1;" :: "r"(id), "r"(n) : "memory"); }
__device__ __forceinline__ bool mbar_try2(uint32_t bar0, uint32_t par0, uint32_t bar1, uint32_t par1) {
    uint32_t ok;
    asm volatile("{ .reg .pred p, q; mbarrier.test_wait.parity.shared::cta.b64 p, [%1], %2;\n"
                 "mbarrier.test_wait.parity.shared::cta.b64 q, [%3], %4; and.pred p, p, q; selp.u32 %0, 1, 0, p; }"
                 : "=r"(ok) : "r"(bar0), "r"(par0), "r"(bar1), "r"(par1) : "memory");
    return ok;
}
__device__ __forceinline__ void fence_gpu() { asm volatile("fence.release.gpu;" ::: "memory"); }
__device__ __forceinline__ void fence_async_global() { asm volatile("fence.proxy.async.global;" ::: "memory"); }
__device__ __forceinline__ void fence_async_smem() { asm volatile("fence.proxy.async.shared::cta;" ::: "memory"); }
__device__ __forceinline__ uint32_t gtime32() { uint64_t t; asm volatile("mov.u64 %0, %%globaltimer;" : "=l"(t) :: "memory"); return (uint32_t)t; }
__device__ __forceinline__ uint32_t clk32() { uint64_t t; asm volatile("mov.u64 %0, %%clock64;" : "=l"(t) :: "memory"); return (uint32_t)t; }
__device__ __forceinline__ void spin_until(uint32_t t) { while ((int)(clk32() - t) < 0) {} }
#define SLEEPNS 20
__device__ __forceinline__ void sleep_until(uint32_t t) { while ((int)(clk32() - t) < 0) { if (SLEEPNS) __nanosleep(SLEEPNS); } }
__device__ __forceinline__ void st_flag(uint32_t* p, uint32_t v) {
    const uint64_t w = ((uint64_t)gtime32() << 32) | v;
    asm volatile("st.relaxed.gpu.global.u64 [%0], %1;" :: "l"(p), "l"(w) : "memory");
}
__device__ __forceinline__ void ld_flag_if(uint64_t& v, const uint32_t* p, bool pred) {
    asm volatile("{ .reg .pred p; setp.ne.u32 p, %2, 0; @p ld.relaxed.gpu.global.u64 %0, [%1]; }" : "+l"(v) : "l"(p), "r"((uint32_t)pred) : "memory");
}
__device__ __forceinline__ uint32_t ld_acq(const uint32_t* p) { uint32_t v; asm volatile("ld.acquire.gpu.global.u32 %0, [%1];" : "=r"(v) : "l"(p) : "memory"); return v; }
__device__ __forceinline__ uint32_t ld_rlx(const uint32_t* p) { uint32_t v; asm volatile("ld.relaxed.gpu.global.u32 %0, [%1];" : "=r"(v) : "l"(p) : "memory"); return v; }
template <class T> __device__ __forceinline__ T* opaque_ptr(T* p) { asm volatile("" : "+l"(p)); return p; }
__device__ __forceinline__ uint4 ld_rlx4(const uint4* p) {
    uint4 v; asm volatile("ld.relaxed.gpu.global.v4.u32 {%0,%1,%2,%3}, [%4];" : "=r"(v.x), "=r"(v.y), "=r"(v.z), "=r"(v.w) : "l"(p) : "memory"); return v;
}
__device__ __forceinline__ void st_ll(uint4* p, uint32_t a, uint32_t b, uint32_t tag) {
    uint64_t lo = ((uint64_t)tag << 32) | a, hi = ((uint64_t)tag << 32) | b;
    asm volatile("st.relaxed.gpu.global.v2.u64 [%0], {%1,%2};" :: "l"(p), "l"(lo), "l"(hi) : "memory");
}
__device__ __forceinline__ bool ld_ll(const uint4* p, uint32_t& a, uint32_t& b, uint32_t tag) {
    uint64_t lo, hi;
    asm volatile("ld.relaxed.gpu.global.v2.u64 {%0,%1}, [%2];" : "=l"(lo), "=l"(hi) : "l"(p) : "memory");
    a = (uint32_t)lo; b = (uint32_t)hi;
    return (uint32_t)(lo >> 32) == tag && (uint32_t)(hi >> 32) == tag;
}
__device__ __forceinline__ uint2 ld_acq2(const uint2* p) {
    uint2 v; asm volatile("ld.acquire.gpu.global.v2.u32 {%0,%1}, [%2];" : "=r"(v.x), "=r"(v.y) : "l"(p) : "memory"); return v;
}
__device__ __forceinline__ uint2 ld_rlx2(const uint2* p) {
    uint2 v; asm volatile("ld.relaxed.gpu.global.v2.u32 {%0,%1}, [%2];" : "=r"(v.x), "=r"(v.y) : "l"(p) : "memory"); return v;
}
__device__ __forceinline__ void stg1(uint32_t* p, uint32_t v) { asm volatile("st.global.u32 [%0], %1;" :: "l"(p), "r"(v) : "memory"); }
__device__ __forceinline__ void stg2(void* p, uint32_t x, uint32_t y) { asm volatile("st.global.v2.u32 [%0], {%1,%2};" :: "l"(p), "r"(x), "r"(y) : "memory"); }
__device__ __forceinline__ void stg4(void* p, uint32_t x, uint32_t y, uint32_t z, uint32_t w) { asm volatile("st.global.v4.u32 [%0], {%1,%2,%3,%4};" :: "l"(p), "r"(x), "r"(y), "r"(z), "r"(w) : "memory"); }
__device__ __forceinline__ uint32_t lds1(uint32_t a) { uint32_t v; asm volatile("ld.shared.u32 %0, [%1];" : "=r"(v) : "r"(a) : "memory"); return v; }
__device__ __forceinline__ uint2 lds2(uint32_t a) { uint2 v; asm volatile("ld.shared.v2.u32 {%0,%1}, [%2];" : "=r"(v.x), "=r"(v.y) : "r"(a) : "memory"); return v; }
__device__ __forceinline__ uint32_t set_par(uint32_t v, uint32_t mask, uint32_t par) {
    uint32_t r; asm("lop3.b32 %0, %1, %2, %3, 0xb8;" : "=r"(r) : "r"(v), "r"(mask), "r"(par)); return r;
}
__device__ __forceinline__ void st_gen4(void* p, uint32_t x, uint32_t y, uint32_t z, uint32_t w) { asm volatile("st.v4.u32 [%0], {%1,%2,%3,%4};" :: "l"(p), "r"(x), "r"(y), "r"(z), "r"(w) : "memory"); }
__device__ __forceinline__ float tanh_hw(float x) { float r; asm("tanh.approx.f32 %0, %1;" : "=f"(r) : "f"(x)); return r; }
__device__ __forceinline__ bool bar_any(int id, int n, bool v) {
    uint32_t r;
    asm volatile("{ .reg .pred p, q; setp.ne.u32 p, %3, 0; bar.red.or.pred q, %1, %2, p; selp.u32 %0, 1, 0, q; }" : "=r"(r) : "r"(id), "r"(n), "r"((uint32_t)v) : "memory");
    return r;
}
__device__ __forceinline__ void sts4(uint32_t a, uint32_t x, uint32_t y, uint32_t z, uint32_t w) { asm volatile("st.shared.v4.u32 [%0], {%1,%2,%3,%4};" :: "r"(a), "r"(x), "r"(y), "r"(z), "r"(w) : "memory"); }
__device__ __forceinline__ uint4 lds4(uint32_t a) { uint4 v; asm volatile("ld.shared.v4.u32 {%0,%1,%2,%3}, [%4];" : "=r"(v.x), "=r"(v.y), "=r"(v.z), "=r"(v.w) : "r"(a) : "memory"); return v; }
__device__ __forceinline__ uint32_t pack_bf16(float lo, float hi) { uint32_t r; asm("cvt.rn.bf16x2.f32 %0, %1, %2;" : "=r"(r) : "f"(hi), "f"(lo)); return r; }
__device__ __forceinline__ float bf_lo(uint32_t v) { return __uint_as_float(v << 16); }
__device__ __forceinline__ float bf_hi(uint32_t v) { return __uint_as_float(v & 0xffff0000u); }
__device__ __forceinline__ uint32_t sub_bf16x2(uint32_t a, uint32_t b) { uint32_t r; asm volatile("sub.rn.bf16x2 %0, %1, %2;" : "=r"(r) : "r"(a), "r"(b)); return r; }
__device__ __forceinline__ uint32_t add_bf16x2(uint32_t a, uint32_t b) { uint32_t r; asm volatile("add.rn.bf16x2 %0, %1, %2;" : "=r"(r) : "r"(a), "r"(b)); return r; }
__device__ __forceinline__ uint32_t sqr_bf16x2(uint32_t a) { uint32_t r; asm volatile("mul.rn.bf16x2 %0, %1, %1;" : "=r"(r) : "r"(a)); return r; }
__device__ __forceinline__ uint32_t sqa_bf16x2(uint32_t a, uint32_t c) { uint32_t r; asm volatile("fma.rn.bf16x2 %0, %1, %1, %2;" : "=r"(r) : "r"(a), "r"(c)); return r; }
__device__ __forceinline__ uint32_t movm(uint32_t a) { uint32_t r; asm volatile("movmatrix.sync.aligned.m8n8.trans.b16 %0, %1;" : "=r"(r) : "r"(a)); return r; }
__device__ __forceinline__ float ex2(float x) { float r; asm("ex2.approx.ftz.f32 %0, %1;" : "=f"(r) : "f"(x)); return r; }
__device__ __forceinline__ float rsq(float x) { float r; asm("rsqrt.approx.ftz.f32 %0, %1;" : "=f"(r) : "f"(x)); return r; }
__device__ __forceinline__ float rcp(float x) { float r; asm("rcp.approx.ftz.f32 %0, %1;" : "=f"(r) : "f"(x)); return r; }
__device__ __forceinline__ void mma16816(float (&c)[4], uint32_t a0, uint32_t a1, uint32_t a2, uint32_t a3, uint32_t b0, uint32_t b1) {
    asm("mma.sync.aligned.m16n8k16.row.col.f32.bf16.bf16.f32 {%0,%1,%2,%3}, {%4,%5,%6,%7}, {%8,%9}, {%0,%1,%2,%3};"
        : "+f"(c[0]), "+f"(c[1]), "+f"(c[2]), "+f"(c[3]) : "r"(a0), "r"(a1), "r"(a2), "r"(a3), "r"(b0), "r"(b1));
}
__device__ __forceinline__ void mma1688(float (&c)[4], uint32_t a0, uint32_t a1, uint32_t b0) {
    asm("mma.sync.aligned.m16n8k8.row.col.f32.bf16.bf16.f32 {%0,%1,%2,%3}, {%4,%5}, {%6}, {%0,%1,%2,%3};"
        : "+f"(c[0]), "+f"(c[1]), "+f"(c[2]), "+f"(c[3]) : "r"(a0), "r"(a1), "r"(b0));
}
__device__ __forceinline__ float quad_sum(float v) { v += __shfl_xor_sync(~0u, v, 1); v += __shfl_xor_sync(~0u, v, 2); return v; }
__device__ __forceinline__ float quad_max(float v) { v = fmaxf(v, __shfl_xor_sync(~0u, v, 1)); v = fmaxf(v, __shfl_xor_sync(~0u, v, 2)); return v; }
__device__ __forceinline__ uint64_t make_desc(uint32_t addr, uint32_t lbo, bool swz, uint32_t sbo = 1024) {
    const uint32_t lo = __shfl_sync(~0u, ((addr & 0x3FFFF) >> 4) | ((lbo >> 4) << 16), 0);
    const uint32_t hi = __shfl_sync(~0u, (swz ? 0x40000000u : 0u) + (sbo >> 4) + (threadIdx.x & 31), 0);
    return ((uint64_t)hi << 32) | lo;
}
template <int I, int N, class F> __device__ __forceinline__ void static_for(F&& f) {
    if constexpr (I < N) { f(std::integral_constant<int, I>{}); static_for<I + 1, N>(f); }
}
__device__ __forceinline__ uint32_t opaque(uint32_t v) { asm volatile("" : "+r"(v)); return v; }
template <int BOFF, int SCALE_D>
__device__ __forceinline__ void wgmma_rs_n56(float (&d)[28], uint32_t a0, uint32_t a1, uint32_t a2, uint32_t a3, uint64_t db) {
    asm volatile("{ .reg .b64 db; add.s64 db, %32, %33;\n"
        "wgmma.mma_async.sync.aligned.m64n56k16.f32.bf16.bf16 "
        "{%0, %1, %2, %3, %4, %5, %6, %7, %8, %9, %10, %11, %12, %13, %14, %15, %16, %17, %18, %19, %20, %21, %22, %23, %24, %25, %26, %27}, "
        "{%28, %29, %30, %31}, db, %34, 1, 1, 1; }"
        : "+f"(d[0]), "+f"(d[1]), "+f"(d[2]), "+f"(d[3]), "+f"(d[4]), "+f"(d[5]), "+f"(d[6]), "+f"(d[7]),
        "+f"(d[8]), "+f"(d[9]), "+f"(d[10]), "+f"(d[11]), "+f"(d[12]), "+f"(d[13]), "+f"(d[14]), "+f"(d[15]),
        "+f"(d[16]), "+f"(d[17]), "+f"(d[18]), "+f"(d[19]), "+f"(d[20]), "+f"(d[21]), "+f"(d[22]), "+f"(d[23]),
        "+f"(d[24]), "+f"(d[25]), "+f"(d[26]), "+f"(d[27])
        : "r"(a0), "r"(a1), "r"(a2), "r"(a3), "l"(db), "n"(BOFF >> 4), "n"(SCALE_D));
}
template <int AOFF, int BOFF, int MMAJOR>
__device__ __forceinline__ void wgmma_ss_n56(float (&d)[28], uint64_t da, uint64_t db) {
    asm volatile("{ .reg .b64 da, db; add.s64 da, %28, %30; add.s64 db, %29, %31;\n"
        "wgmma.mma_async.sync.aligned.m64n56k16.f32.bf16.bf16 "
        "{%0, %1, %2, %3, %4, %5, %6, %7, %8, %9, %10, %11, %12, %13, %14, %15, %16, %17, %18, %19, %20, %21, %22, %23, %24, %25, %26, %27}, "
        "da, db, 1, 1, 1, %32, 1; }"
        : "+f"(d[0]), "+f"(d[1]), "+f"(d[2]), "+f"(d[3]), "+f"(d[4]), "+f"(d[5]), "+f"(d[6]), "+f"(d[7]),
        "+f"(d[8]), "+f"(d[9]), "+f"(d[10]), "+f"(d[11]), "+f"(d[12]), "+f"(d[13]), "+f"(d[14]), "+f"(d[15]),
        "+f"(d[16]), "+f"(d[17]), "+f"(d[18]), "+f"(d[19]), "+f"(d[20]), "+f"(d[21]), "+f"(d[22]), "+f"(d[23]),
        "+f"(d[24]), "+f"(d[25]), "+f"(d[26]), "+f"(d[27])
        : "l"(da), "l"(db), "n"(AOFF >> 4), "n"(BOFF >> 4), "n"(MMAJOR));
}
template <int AOFF, int BOFF, int MMAJOR>
__device__ __forceinline__ void wgmma_ss_n112(float (&d)[28], float (&e)[28], uint64_t da, uint64_t db) {
    asm volatile("{ .reg .b64 da, db; add.s64 da, %56, %58; add.s64 db, %57, %59;\n"
        "wgmma.mma_async.sync.aligned.m64n112k16.f32.bf16.bf16 "
        "{%0, %1, %2, %3, %4, %5, %6, %7, %8, %9, %10, %11, %12, %13, %14, %15, %16, %17, %18, %19, %20, %21, %22, %23, %24, %25, %26, %27, %28, %29, %30, %31, %32, %33, %34, %35, %36, %37, %38, %39, %40, %41, %42, %43, %44, %45, %46, %47, %48, %49, %50, %51, %52, %53, %54, %55}, "
        "da, db, 1, 1, 1, %60, 1; }"
        : "+f"(d[0]), "+f"(d[1]), "+f"(d[2]), "+f"(d[3]), "+f"(d[4]), "+f"(d[5]), "+f"(d[6]), "+f"(d[7]),
        "+f"(d[8]), "+f"(d[9]), "+f"(d[10]), "+f"(d[11]), "+f"(d[12]), "+f"(d[13]), "+f"(d[14]), "+f"(d[15]),
        "+f"(d[16]), "+f"(d[17]), "+f"(d[18]), "+f"(d[19]), "+f"(d[20]), "+f"(d[21]), "+f"(d[22]), "+f"(d[23]),
        "+f"(d[24]), "+f"(d[25]), "+f"(d[26]), "+f"(d[27]), "+f"(e[0]), "+f"(e[1]), "+f"(e[2]), "+f"(e[3]),
        "+f"(e[4]), "+f"(e[5]), "+f"(e[6]), "+f"(e[7]), "+f"(e[8]), "+f"(e[9]), "+f"(e[10]), "+f"(e[11]),
        "+f"(e[12]), "+f"(e[13]), "+f"(e[14]), "+f"(e[15]), "+f"(e[16]), "+f"(e[17]), "+f"(e[18]), "+f"(e[19]),
        "+f"(e[20]), "+f"(e[21]), "+f"(e[22]), "+f"(e[23]), "+f"(e[24]), "+f"(e[25]), "+f"(e[26]), "+f"(e[27])
        : "l"(da), "l"(db), "n"(AOFF >> 4), "n"(BOFF >> 4), "n"(MMAJOR));
}
template <int BOFF, int SCALE_D>
__device__ __forceinline__ void wgmma_rs_n112(float (&d)[28], float (&e)[28], uint32_t a0, uint32_t a1, uint32_t a2, uint32_t a3, uint64_t db) {
    asm volatile("{ .reg .b64 db; add.s64 db, %60, %61;\n"
        "wgmma.mma_async.sync.aligned.m64n112k16.f32.bf16.bf16 "
        "{%0, %1, %2, %3, %4, %5, %6, %7, %8, %9, %10, %11, %12, %13, %14, %15, %16, %17, %18, %19, %20, %21, %22, %23, %24, %25, %26, %27, %28, %29, %30, %31, %32, %33, %34, %35, %36, %37, %38, %39, %40, %41, %42, %43, %44, %45, %46, %47, %48, %49, %50, %51, %52, %53, %54, %55}, "
        "{%56, %57, %58, %59}, db, %62, 1, 1, 1; }"
        : "+f"(d[0]), "+f"(d[1]), "+f"(d[2]), "+f"(d[3]), "+f"(d[4]), "+f"(d[5]), "+f"(d[6]), "+f"(d[7]),
        "+f"(d[8]), "+f"(d[9]), "+f"(d[10]), "+f"(d[11]), "+f"(d[12]), "+f"(d[13]), "+f"(d[14]), "+f"(d[15]),
        "+f"(d[16]), "+f"(d[17]), "+f"(d[18]), "+f"(d[19]), "+f"(d[20]), "+f"(d[21]), "+f"(d[22]), "+f"(d[23]),
        "+f"(d[24]), "+f"(d[25]), "+f"(d[26]), "+f"(d[27]), "+f"(e[0]), "+f"(e[1]), "+f"(e[2]), "+f"(e[3]),
        "+f"(e[4]), "+f"(e[5]), "+f"(e[6]), "+f"(e[7]), "+f"(e[8]), "+f"(e[9]), "+f"(e[10]), "+f"(e[11]),
        "+f"(e[12]), "+f"(e[13]), "+f"(e[14]), "+f"(e[15]), "+f"(e[16]), "+f"(e[17]), "+f"(e[18]), "+f"(e[19]),
        "+f"(e[20]), "+f"(e[21]), "+f"(e[22]), "+f"(e[23]), "+f"(e[24]), "+f"(e[25]), "+f"(e[26]), "+f"(e[27])
        : "r"(a0), "r"(a1), "r"(a2), "r"(a3), "l"(db), "n"(BOFF >> 4), "n"(SCALE_D));
}

struct Params {
    const __nv_bfloat16 *x, *wqkv;
    Scratch* sc;
    const __nv_bfloat16 *wo, *w1, *w2, *b1, *b2;
    __nv_bfloat16* out;
};

__global__ void __cluster_dims__(2, 1, 1) __launch_bounds__(384, 1)
fused_kernel(const Params prm, const __grid_constant__ CUtensorMap mX2, const __grid_constant__ CUtensorMap mX, const __grid_constant__ CUtensorMap mWqkv,
             const __grid_constant__ CUtensorMap mWo, const __grid_constant__ CUtensorMap mW1,
             const __grid_constant__ CUtensorMap mW2)
{
    extern __shared__ __align__(1024) unsigned char smem_raw[];
    if (threadIdx.x < 126) {
        const uint32_t i = threadIdx.x, t = clk32() + (i >> 5) * PFD;
        const char* px = (const char*)prm.x + (blockIdx.x * 16 + (i & 15)) * 896 + (i >> 4) * 128;
        const char* pw = (const char*)prm.wqkv + blockIdx.x * 2688 + i * 128 + (896 - 112 * 128);
        spin_until(t);
        asm volatile("prefetch.global.L2 [%0];" :: "l"(i < 112 ? px : pw) : "memory");
    }
    if (threadIdx.x == 128) { asm volatile("prefetch.tensormap [%0];" :: "l"(&mX2) : "memory"); asm volatile("prefetch.tensormap [%0];" :: "l"(&mWqkv) : "memory"); }
    uint32_t sb = (uint32_t)__cvta_generic_to_shared(smem_raw);
    asm volatile("mov.u32 %0, %0;" : "+r"(sb));
    const uint32_t bar0 = sb + SM_BAR;
    auto BAR = [&](int i) { return bar0 + 8u * i; };

    const int tid = threadIdx.x, lane = tid & 31;
    const int warp = __shfl_sync(~0u, tid >> 5, 0);
    const int b = __shfl_sync(~0u, (int)blockIdx.x, 0);
    const int rank = b & 1;
    const int cl = (b >> 1) - 4, cq = ((cl - 32) * 37) >> 8;
    const int res = cl < 0 ? 0 : cl < 32 ? cl & 7 : cl - 31 - 7 * cq;
    const int rnd = cl < 0 ? cl + 8 : cl < 32 ? cl >> 3 : 4 + cq;
    const int hg = (res & 1) * 4 + (rnd & 3);
    const int ti = (res >> 1) * 4 + (rnd >> 2) * 2 + rank;
    const int a2p = res & 1, a2j = rnd & 3;
    const int a2s = ti * 2 + a2p;
    const bool g1_on = rnd != 7;
    const int g1j = (rnd < 6 ? rnd : res) & 1, g1f = rnd < 6 ? res * 3 + (rnd >> 1) : 24 + (res >> 1);
    const int g2j = rnd & 1, g2s = res * 4 + (rnd >> 1);
    uint32_t pbar0;
    asm volatile("mapa.shared::cluster.u32 %0, %1, %2;" : "=r"(pbar0) : "r"(bar0), "r"(rank ^ 1));
    auto pair_arrive = [&](int i) { __syncwarp(); const bool l = elect_one(); mbar_arrive_if(BAR(i), l); mbar_arrive_remote_if(pbar0 + 8u * i, l); };
    const int wcol = hg * 56 - (hg & 1) * 8;

    if (warp == 8) {
        if (elect_one()) {
            #pragma unroll
            for (int i = 0; i < B_WQF; i++) mbar_init(BAR(i), 1);
            asm volatile("fence.mbarrier_init.release.cluster;" ::: "memory");
            fence_async_smem();
            #pragma unroll
            for (int kb = 0; kb < 7 - XLATE; kb++) {
                tma3d(sb + kb * 16384, &mX2, kb * 64, ti * 64, 0, BAR(B_XF + kb));
                mbar_expect(BAR(B_XF + kb), 16384);
                if (kb == 0 && PFX != 3) asm volatile("prefetch.tensormap [%0];" :: "l"(&mWqkv) : "memory");
            }
        }
    } else if (warp > 8) {
        if (elect_one()) {
            if (warp == 9) {
                #pragma unroll
                for (int i = B_WQF; i < B_AF; i++) mbar_init(BAR(i), i < B_XC ? 1 : i < B_A1D ? 16 : i < B_BE ? 8 : 4);
            } else if (warp == 10) {
                #pragma unroll
                for (int i = B_AF; i < B_BF; i++) mbar_init(BAR(i), 1);
            } else {
                #pragma unroll
                for (int i = B_BF; i < B_COUNT; i++) mbar_init(BAR(i), i == B_HD ? 8 : 1);
            }
            asm volatile("fence.mbarrier_init.release.cluster;" ::: "memory");
            fence_async_smem();
        }
    }
    __syncwarp();
    __syncthreads();
    asm volatile("barrier.cluster.arrive.relaxed.aligned;" ::: "memory");
    if (tid < 256) TR(0);
    if (tid == 0) TRG(61);

    if (warp >= 8) {
        asm volatile("setmaxnreg.dec.sync.aligned.u32 40;");
        asm volatile("barrier.cluster.wait.aligned;" ::: "memory");
        auto fetch_halo = [&](int p, uint32_t tag) {
            uint4 u[4];
            #pragma unroll
            for (int c = 0; c < 4; c++) u[c] = make_uint4(0u, 0u, 0u, 0u);
            const uint4* hp = opaque_ptr(&prm.sc->halo[(((ti - 1) * 8 + hg) * 2 + p) * 128 + lane]);
            mbar_wait(BAR(B_KVC), 0);
            if (p == 0) TRW(51);
            sleep_until(clk32() + HDELAY);
            if (ti > 0) {
                int it = 0;
                do {
                    #pragma unroll
                    for (int c = 0; c < 4; c++) u[c] = ld_rlx4(hp + c * 32);
                    if (it) RETRY_COUNT(4);
                    if (++it > kSpinLimit) { TIMEOUT(101); break; }
                } while (__any_sync(~0u, ((u[0].x ^ tag) | (u[1].x ^ tag) | (u[2].x ^ tag) | (u[3].x ^ tag)) & ~lane & 1));
            }
            #pragma unroll
            for (int c = 0; c < 4; c++) sts4(sb + SM_STG + p * 8192 + 3 * 2048 + lane * 16 + c * 512, u[c].x, u[c].y, u[c].z, u[c].w);
            warp_arrive(BAR(B_HL + p));
        };
        if (warp & 1) {
            uint32_t tag;
            if (warp == 11) {
                tag = *(volatile uint32_t*)&prm.sc->epoch + 1;
            #pragma unroll 1
            for (int i = 0; i < 8; i++) prm.sc->halo[(ti * 8 + hg) * 256 + i * 32 + lane] = make_uint4(~tag, 0u, 0u, 0u);
            ((uint4*)prm.sc->stats)[(a2s * 4 + a2j) * 64 + lane] = ((uint4*)prm.sc->stats)[(a2s * 4 + a2j) * 64 + 32 + lane] = make_uint4(~tag, ~tag, ~tag, ~tag);
            prm.sc->flag_h[(a2s * 4 + a2j) * FS + lane] = 0;
            prm.sc->flag_o[(ti * 8 + hg) * FS + lane] = 0;
            __syncwarp();
            if (lane == 0) {
                asm volatile("st.shared.v2.u32 [%0], {%1, %2};" :: "r"(sb + SM_EPOCH), "r"(tag), "r"(gtime32()) : "memory");
                mbar_arrive(BAR(B_EP));
            }
            if (lane < 8) mbar_expect(BAR(B_RF + lane), 1792);
            __syncwarp();
            TRW(44);
            } else {
                mbar_wait(BAR(B_EP), 0);
                tag = lds1(sb + SM_EPOCH);
            }
            uint32_t* ofl = opaque_ptr(&prm.sc->flag_o[(ti * 8 + hg) * FS]);
            fetch_halo((warp >> 1) & 1, tag);
            if (warp == 11) {
                mbar_wait2(BAR(B_A1D), 0, BAR(B_HL), 0);
                if (lane == 0) st_flag(ofl, tag);
                __syncwarp();
            }
        }
        if (warp < 10) {
          auto load_slab = [&](int s, bool second) {
              if (!second) tma2d(sb + s * 8192, &mW1, (s & 1) * kF + g1f * 64, (rank * 8 + (s >> 1)) * 64, BAR(B_AF));
              else         tma2d(sb + s * 8192, &mW2, g2s * 64, (rank * 14 + s - 1) * 64, BAR(B_AF));
          };
          const char* pw2 = (const char*)prm.w2 + ((b >> 6) * 896 + (b & 63) + PFW * 64) * 4096;
          if (warp == 8) {
            if (elect_one()) {
                #pragma unroll 1
                for (int s = 0; s < 7; s++) {
                    mbar_expect(BAR(B_WKVF + s), 16384);
                    tma2d_mc(sb + SM_WKV + s * 16384 + rank * 8192, &mWqkv, (1 + rank) * kD + wcol, s * 64, BAR(B_WKVF + s));
                    if (s == 0) {
                        #pragma unroll
                        for (int kb = 7 - XLATE; kb < 7; kb++) {
                            tma3d(sb + kb * 16384, &mX2, kb * 64, ti * 64, 0, BAR(B_XF + kb));
                            mbar_expect(BAR(B_XF + kb), 16384);
                        }
                    }
                }
            }
            __syncwarp();
            mbar_wait(BAR(B_XC), 0);
            if (elect_one()) {
                asm volatile("prefetch.tensormap [%0];" :: "l"(&mX) : "memory");
                asm volatile("prefetch.tensormap [%0];" :: "l"(&mWo) : "memory");
                asm volatile("prefetch.tensormap [%0];" :: "l"(&mW1) : "memory");
                asm volatile("prefetch.tensormap [%0];" :: "l"(&mW2) : "memory");
                mbar_expect(BAR(B_AF), (g1_on ? NPRE : 14) * 8192);
                mbar_expect(BAR(B_WQF), 57344);
                #pragma unroll 1
                for (int s = rank; s < 7; s += 2) tma2d_mc(sb + SM_WQ + s * 8192, &mWqkv, wcol, s * 64, BAR(B_WQF));
                mbar_expect(BAR(B_XRF), 16384);
                tma2d(sb + SM_XR, &mX, a2p * kD + a2j * 112, ti * 64, BAR(B_XRF));
                tma2d(sb + SM_XR + 8192, &mX, a2p * kD + a2j * 112 + 48, ti * 64, BAR(B_XRF));
            }
            __syncwarp();
            #pragma unroll 1
            for (int q = 0; q < 4; q++) {
                mbar_wait(BAR(B_KV3 + (q >> 1)), 0);
                if (q == WOQ) mbar_wait2(BAR(B_HL), 0, BAR(B_HL + 1), 0);
                if (elect_one()) {
                    if (!(q & 1)) mbar_expect(BAR(B_WOF + (q >> 1)), 57344);
                    tma2d_mc(sb + SM_WKV + q * 28672 + rank * 14336, &mWo, a2j * 112 + (q & 1) * 48, (q >> 1) * 224 + rank * 112, BAR(B_WOF + (q >> 1)));
                    if (g1_on && q == AFIRST) { load_slab(0, false); load_slab(1, false); load_slab(2, false); }
                }
                __syncwarp();
            }
            if (g1_on) {
                mbar_wait2(BAR(B_XD), 0, BAR(B_OL + 3), 0);
                #pragma unroll 1
                for (int i = 3; i < NPRE; i++) {
                    if (i == 7) mbar_wait(BAR(B_OC), 0);
                    if (elect_one()) load_slab(i, false);
                    __syncwarp();
                }
            } else {
                mbar_arrive_if(BAR((lane < 16 ? B_BE : B_BF) + (lane & 3)), lane < 20);
                mbar_wait(BAR(B_HD), 0);
                mbar_arrive_remote_if(pbar0 + 8u * B_PD, lane == 0);
                mbar_wait(BAR(B_GO), 0);
                uint32_t tg = lds1(sb + SM_TG + 4);
                tg += max((int)(lds1(sb + SM_TG2) - tg), 0);
                int it = 0;
                while ((int)(gtime32() - tg) < 0 && ++it < 256) {}
                const uint32_t t0 = clk32();
                if (lane < 2) {
                    asm volatile("st.shared.u32 [%0], %1;" :: "r"(sb + SM_TG + 8 + lane * 4), "r"(t0 + (lane ? CN3 : CN2)) : "memory");
                    mbar_arrive(BAR(B_GD + lane));
                }
                __syncwarp();
                #pragma unroll 1
                for (int s = 1; s < 15; s++) {
                    sleep_until(t0 + W2OFF + s * W2PACE);
                    if (elect_one()) { if (s < 15 - PFW) bulk_prefetch(pw2 + (s - 1) * 64 * 4096, 4096); load_slab(s, true); }
                    __syncwarp();
                }
            }
          } else {
            TRW(58);
            const uint32_t tag = lds1(sb + SM_EPOCH);
            if (lane < 4) mbar_expect(BAR(B_OL + lane), 14336);
            #pragma unroll 1
            for (int e = 0; e < 2; e++) {
                const uint32_t* fp = e ? &prm.sc->flag_h[(rank * 64 + lane) * FS] : &prm.sc->flag_o[(ti * 8 + (lane & 7)) * FS];
                if (e) {
                    mbar_wait2(BAR(B_OF + 2), 0, BAR(B_OF + 3), 0);
                    if (lane == 0) st_flag(&prm.sc->flag_h[(a2s * 4 + a2j) * FS], tag);
                    __syncwarp();
                    TRW(57);
                    sleep_until(clk32() + PDELAY);
                }
                uint64_t v0 = 0, v1 = e ? 0 : tag;
                int it = 0;
                do {
                    ld_flag_if(v0, fp, (uint32_t)v0 != tag); ld_flag_if(v1, fp + 32 * FS, (uint32_t)v1 != tag);
                    if (++it > kSpinLimit) { TIMEOUT(108); break; }
                } while (__any_sync(~0u, (uint32_t)v0 != tag || (uint32_t)v1 != tag));
                const uint32_t gbase = __shfl_sync(~0u, (uint32_t)(v0 >> 32), 0);
                const uint32_t tg = gbase + (e ? DELTA : DELTAO)
                                  + __reduce_max_sync(~0u, max((int)((uint32_t)(v0 >> 32) - gbase) - e * (lane >> 2) * SOFF, e ? (int)((uint32_t)(v1 >> 32) - gbase) - 8 * SOFF : 0));
                TRW(e ? 40 : 53);
                mbar_wait(BAR(B_A1D), 0);
                if (elect_one()) {
                    if (e) {
                        asm volatile("st.async.shared::cluster.mbarrier::complete_tx::bytes.b32 [%0], %1, [%2];"
                                     :: "r"(pbar0 + (SM_TG2 - SM_BAR)), "r"(tg), "r"(pbar0 + 8u * B_GO) : "memory");
                        asm volatile("st.shared.u32 [%0], %1;" :: "r"(sb + SM_TG + 4), "r"(tg) : "memory");
                        mbar_expect(BAR(B_GO), 4);
                    } else {
                        it = 0;
                        while ((int)(gtime32() - tg) < 0 && ++it < 256) {}
                        #pragma unroll
                        for (int i = 0; i < 4; i++) bulk_g2s(sb + SM_WQ + i * 14336, &prm.sc->o[(a2s * 4 + i) * 896], 14336, BAR(B_OL + i));
                    }
                }
                __syncwarp();
            }
          }
          if (elect_one()) {
              const int h = ~warp & 1;
              constexpr uint32_t T = 57344, BO = 2 * 14336;
              const char* src1 = (const char*)&prm.sc->hn[(rank * 16 + h) * 3584 + g1j * 896];
              const char* src2 = (const char*)&prm.sc->g[(rank * 14 + h) * 3584 + g2j * 896];
              uint64_t masks = g1_on ? (h ? kSegMasks1 : kSegMasks0) : 0x80 | 0x80 << 10;
              const uint32_t bl = BAR(B_BL + h * NB);
              uint32_t s8 = (g1_on ? NB - 2 + h : 4 + h) * 8, lap = 3, tmin = 0;
              uint32_t pfm = g1_on && !h ? 0x3fffu >> PFW << (PF2R + 1) : 0;
              const CUtensorMap* am = &mW1;
              uint32_t ad = sb + (NPRE + h) * 8192, astep = 16384; int ac0 = h * kF + g1f * 64, ac1 = (rank * 8 + NPRE / 2) * 64;
              CAP_DECL(ti_, 0);
              #pragma unroll 1
              for (int seg = g1_on ? 0 : 3; seg < 5; seg++) {
                  const char* src = (seg < 3 ? src1 : src2) + (~seg & 1) * BO;
                  uint32_t m = (uint32_t)masks & 0x3ff;
                  masks >>= 10;
                  const uint32_t pace = seg == 4 ? PACEB : seg == 3 ? PACEA : PACE2;
                  if (seg == 2) {
                      mbar_wait(BAR(B_PL), 0);
                      mbar_arrive_remote_if(pbar0 + 8u * B_PD, h);
                      am = &mW2; ad = sb + 8192; astep = 8192; ac0 = g2s * 64; ac1 = rank * 14 * 64;
                  } else {
                      const int gate = seg - (seg > 2);
                      mbar_wait(BAR(B_HD + gate), 0);
                      tmin = lds1(sb + SM_TG + gate * 4);
                      if (gate < 2) {
                          tmin += max((int)(lds1(gate ? sb + SM_TG2 : sb + SM_TG) - tmin), 0);
                          int it = 0;
                          while ((int)(gtime32() - tmin) < 0 && ++it < 256) {}
                          tmin = clk32();
                      }
                      tmin += h * PACE1;
                  }
                  #pragma unroll 1
                  do {
                      const uint32_t dst = sb + SM_B + s8 * 1792;
                      spin_until(tmin);
                      mbar_wait_fast(BAR(B_BE) + s8 + (lap & 1) * (NB * 8), lap >> 1 & 1);
                      if (seg) {
                          bulk_g2s(dst, src, 14336, bl + s8);
                          mbar_expect(bl + s8, 14336);
                          CAP(ti_);
                      }
                      tmin += pace;
                      src += 2 * T;
                      s8 += 16;
                      if (s8 >= NB * 8) { s8 -= NB * 8; lap++; }
                      if (m & 1) {
                          mbar_expect_more(bl + s8, 8192);
                          tma2d(ad, am, ac0, ac1, bl + s8);
                          ad += astep; ac1 += 64;
                      }
                      if (pfm & 1) { bulk_prefetch(pw2, 4096); pw2 += 64 * 4096; }
                      pfm >>= 1;
                      m >>= 1;
                  } while (m != 1);
                  if (seg == 0) lap = 3;
              }
          }
        } else {
          auto pull_w1 = [&](int s0, int s1, uint32_t pace) {
            const char* p1 = (const char*)prm.w1 + ((b >> 6) * 1024 + (b & 63) * 2) * 3584 + min(lane, 27) * 128;
            const char* p2 = (const char*)prm.w2 + ((b >> 6) * 896 + (b & 63)) * 4096 + lane * 128;
            uint32_t tnext = clk32();
            #pragma unroll 1
            for (int i = s0; i < s1; i++) {
                while ((int)(clk32() - tnext) < 0) __nanosleep(40);
                asm volatile("prefetch.global.L2 [%0];" :: "l"(i < 16 ? p1 + ((i >> 1) * 128 + (i & 1)) * 3584 : p2 + (i - 16) * 64 * 4096));
                tnext += pace;
            }
          };
          if (warp == 10) {
            mbar_wait(BAR(PFBAR), 0);
            if (lane < 27) asm volatile("prefetch.global.L2 [%0];" :: "l"(lane < 25 ? (const char*)prm.wo + min(b * 25 + lane, 3135) * 128
                                                                          : lane == 25 ? (const char*)prm.b1 + (b % 28) * 128 : (const char*)prm.b2 + (b & 31) * 128));
            mbar_wait(BAR(PFBAR2), 0);
            pull_w1(0, PFN, PFPACE);
            mbar_wait(BAR(B_EP), 0);
          }
          const uint32_t tag = lds1(sb + SM_EPOCH);
          const int h = warp & 1;
          const bool lead = elect_one();
          const uint32_t wo = lane * 132, l3 = lane < 16 ? 12288 : 0;
          uint32_t base = sb + SM_WQ, bl = BAR(B_OL), bf = BAR(B_OF), m = 4, rph = 0;
          #pragma unroll 1
          for (int e = 0; e < 2; e++) {
              uint32_t s8 = (e && !g1_on ? 4 + h : h) * 8;
              #pragma unroll 1
              do {
                  const uint32_t dst = base + s8 * 1792;
                  auto stale = [&]() {
                      uint32_t d;
                      asm volatile("{ .reg .b32 x, y, z, u;\n"
                                   "ld.shared.u32 x, [%1]; ld.shared.u32 y, [%1 + 4096]; ld.shared.u32 z, [%1 + 8192]; ld.shared.u32 u, [%2];\n"
                                   "lop3.b32 x, x, y, %3, 0x7e; lop3.b32 z, z, u, %3, 0x7e; lop3.b32 %0, x, z, 1, 0xa8; }"
                                   : "=r"(d) : "r"(dst + wo), "r"(dst + (wo + l3)), "r"(tag) : "memory");
                      return __any_sync(~0u, d);
                  };
                  mbar_wait_fast(bl + s8, m & 1);
                  bool bad = stale();
                  mbar_arrive_if(bf + s8, lead && !bad);
                  if (bad) {
                      const int p = 2 * __clz(m) - 2 + h;
                      RETRY_COUNT(!e ? 1 : p < 32 ? 0 : !g1_on ? 5 : p < 46 ? 2 : 6);
                      const int st = (p > 15) + (p > 31) + (p > 45), s = p - (st < 3 ? 16 * st : 46);
                      const char* src = (const char*)(!e ? &prm.sc->o[(a2s * 4 + p - 56) * 896] : st < 2 ? &prm.sc->hn[(rank * 16 + s) * 3584 + (g1j + 2 * st) * 896]
                                                                                                      : &prm.sc->g[(rank * 14 + s) * 3584 + (g2j + 2 * st - 4) * 896]);
                      int it = 0;
                      do {
                          if (++it > kSpinLimit) { TIMEOUT(111); break; }
                          const uint32_t* q = (const uint32_t*)(src + wo);
                          if (it > RELOAD1 && __any_sync(~0u, ((ld_rlx(q) ^ tag) | (ld_rlx(q + 1024) ^ tag) | (ld_rlx(q + 2048) ^ tag) | (ld_rlx(q + l3 / 4) ^ tag)) & 1)) continue;
                          if (lead) {
                              mbar_expect(BAR(B_RT + h), 14336);
                              bulk_g2s(dst, src, 14336, BAR(B_RT + h));
                          }
                          __syncwarp();
                          mbar_wait(BAR(B_RT + h), rph);
                          rph ^= 1;
                          bad = stale();
                      } while (bad);
                      mbar_arrive_if(bf + s8, lead);
                  }
                  s8 += 16;
                  if (s8 >= NB * 8) s8 -= NB * 8;
                  m >>= 1;
              } while (m != 1);
              if (PFN < 16 + PFW && !e && !h) pull_w1(PFN, 16 + PFW, PFPACE2);
              base = sb + SM_B; bl = BAR(B_BL + h * NB); bf = BAR(B_BF); m = g1_on ? 0x4fe03f80 : 0x7f80;
          }
        }
    } else {
        asm volatile("setmaxnreg.inc.sync.aligned.u32 232;");
        asm volatile("barrier.cluster.wait.aligned;" ::: "memory");
        const int wg = warp >> 2, w = warp & 3;
        const int g = lane >> 2, t = lane & 3;
        uint32_t tag;
        __nv_bfloat16 bias1a, bias1b;
        {
            const uint64_t dw = make_desc(sb + (hg & 1) * 16, 0, true);
            uint32_t a[28][4];
            float sm[4][4] = {};
            {
                const int r = w * 16 + (lane & 15);
                uint32_t xa[4];
                #pragma unroll
                for (int q = 0; q < 4; q++) xa[q] = opaque(sb + wg * 8192 + r * 128 + (((q * 2 + (lane >> 4)) ^ (r & 7)) << 4));
                const uint32_t one = opaque(0x3F803F80u), one2 = opaque(0x3F803F80u);
                #pragma unroll
                for (int k = 0; k < 28; k++) {
                    if ((k & 3) == 0) mbar_wait(BAR(B_XF + (k >> 2)), 0);
                    uint32_t (&f)[4] = a[k];
                    asm volatile("ldmatrix.sync.aligned.m8n8.x4.shared.b16 {%0,%1,%2,%3}, [%4];"
                                 : "=r"(f[0]), "=r"(f[1]), "=r"(f[2]), "=r"(f[3]) : "r"(xa[k & 3] + (k >> 2) * 16384) : "memory");
                    if (k < 24) mma16816(sm[k & 3], f[0], f[1], f[2], f[3], one, one2);
                }
                pair_arrive(B_XC);
                const bool wok = mbar_test(BAR(B_WKVF), 0);
                #pragma unroll
                for (int k = 24; k < 28; k++) mma16816(sm[k & 3], a[k][0], a[k][1], a[k][2], a[k][3], one, one2);
                if (W0E && !wok) mbar_wait(BAR(B_WKVF), 0);
            }
            const float mean0 = ((sm[0][0] + sm[1][0]) + (sm[2][0] + sm[3][0])) * (1.f / kD);
            const float mean1 = ((sm[0][2] + sm[1][2]) + (sm[2][2] + sm[3][2])) * (1.f / kD);
            const uint32_t mb0 = pack_bf16(mean0, mean0), mb1 = pack_bf16(mean1, mean1);
            TR(1);
            float ak[28], av[28], aq[28];
            float ss0 = 0.f, ss1 = 0.f, ss2 = 0.f, ss3 = 0.f;
            uint32_t p0, p1;
            static_for<0, 7>([&](auto S_) {
                constexpr int s = decltype(S_)::value;
                auto centre = [&](int q) {
                    uint32_t (&f)[4] = a[s * 4 + q];
                    f[0] = sub_bf16x2(f[0], mb0); f[1] = sub_bf16x2(f[1], mb1);
                    f[2] = sub_bf16x2(f[2], mb0); f[3] = sub_bf16x2(f[3], mb1);
                };
                if (s || !W0E) {
                    #pragma unroll
                    for (int q = 0; q < 4; q++) centre(q);
                    mbar_wait(BAR(B_WKVF + s), 0);
                    wg_fence();
                }
                static_for<0, 4>([&](auto Q_) {
                    constexpr int q = decltype(Q_)::value;
                    uint32_t (&f)[4] = a[s * 4 + q];
                    if (s == 0 && W0E) { centre(q); wg_fence(); }
                    wgmma_rs_n56<SM_WKV + s * 16384 + q * 2048, (s | q) != 0>(ak, f[0], f[1], f[2], f[3], dw);
                    wgmma_rs_n56<SM_WKV + s * 16384 + q * 2048 + 8192, (s | q) != 0>(av, f[0], f[1], f[2], f[3], dw);
                });
                wg_commit();
                if (s == 4) { wg_wait<1>(); pair_arrive(B_KV3); }
                if (s < W0F) mbar_wait(BAR(B_WKVF), 0);
                #pragma unroll
                for (int q = 0; q < 8; q++) {
                    const uint32_t u0 = a[s * 4 + q / 2][(q & 1) * 2], u1 = a[s * 4 + q / 2][(q & 1) * 2 + 1];
                    if (q == 0 && (VCH == 1 || (s & 1) || s == 0)) { p0 = sqr_bf16x2(u0); p1 = sqr_bf16x2(u1); }
                    else { p0 = sqa_bf16x2(u0, p0); p1 = sqa_bf16x2(u1, p1); }
                }
                if (VCH == 1 || !(s & 1)) { ss0 += bf_lo(p0); ss2 += bf_hi(p0); ss1 += bf_lo(p1); ss3 += bf_hi(p1); }
            });
            auto q_chunk = [&](auto K0_, auto K1_) {
                wg_fence();
                static_for<decltype(K0_)::value, decltype(K1_)::value>([&](auto K_) {
                    constexpr int k = decltype(K_)::value;
                    wgmma_rs_n56<SM_WQ + k * 2048, k != 0>(aq, a[k][0], a[k][1], a[k][2], a[k][3], dw);
                });
                wg_commit();
            };
            #define QCHUNK(k0, k1) q_chunk(std::integral_constant<int, k0>{}, std::integral_constant<int, k1>{})
            const float dl0 = mean0 - bf_lo(mb0), dl1 = mean1 - bf_lo(mb1);
            const float rs0 = rsq(fmaxf(quad_sum(ss0 + ss2) * (1.f / kD) - dl0 * dl0, 0.f) + kEps);
            const float rs1 = rsq(fmaxf(quad_sum(ss1 + ss3) * (1.f / kD) - dl1 * dl1, 0.f) + kEps);
            float rk[3][2];
            rk[1][0] = __shfl_sync(~0u, rs0, t * 8); rk[1][1] = __shfl_sync(~0u, rs0, t * 8 + 4);
            rk[2][0] = __shfl_sync(~0u, rs1, t * 8); rk[2][1] = __shfl_sync(~0u, rs1, t * 8 + 4);
            const uint32_t stg = sb + SM_STG + wg * 8192 + lane * 16;
            uint4* hp = (w == 3 ? &prm.sc->halo[((ti * 8 + hg) * 2 + wg) * 128] : (uint4*)(smem_raw + SM_STG + wg * 8192 + w * 2048)) + lane;
            mbar_wait2(BAR(B_EP), 0, BAR(B_WQF), 0);
            tag = lds1(sb + SM_EPOCH);
            QCHUNK(0, QC0);
            wg_wait<1>();
            reg_fence(ak); reg_fence(av);
            TR(2);
            uint32_t kf[3][7], vf[3][7];
            #pragma unroll
            for (int c = 0; c < 7; c++) {
                kf[2][c] = pack_bf16(ak[4 * c + 2], ak[4 * c + 3]);
                vf[2][c] = movm(pack_bf16(av[4 * c + 2], av[4 * c + 3]));
            }
            const uint32_t om = ~lane & 1;
            kf[2][0] = set_par(kf[2][0], om, tag); kf[2][4] = set_par(kf[2][4], om, tag);
            vf[2][1] = set_par(vf[2][1], om, tag); vf[2][5] = set_par(vf[2][5], om, tag);
            st_gen4(hp,      kf[2][0], kf[2][1], kf[2][2], kf[2][3]);
            st_gen4(hp + 32, kf[2][4], kf[2][5], kf[2][6], vf[2][0]);
            st_gen4(hp + 64, vf[2][1], vf[2][2], vf[2][3], vf[2][4]);
            st_gen4(hp + 96, vf[2][5], vf[2][6], __float_as_uint(rk[2][0]), __float_as_uint(rk[2][1]));
            pair_arrive(B_KVC);
            QCHUNK(QC0, QC1);
            #pragma unroll
            for (int c = 0; c < 7; c++) {
                kf[1][c] = pack_bf16(ak[4 * c], ak[4 * c + 1]);
                vf[1][c] = movm(pack_bf16(av[4 * c], av[4 * c + 1]));
            }
            QCHUNK(QC1, QC2);
            named_bar(1 + wg, 128);
            uint32_t* op = opaque_ptr((uint32_t*)&prm.sc->o[((ti * 2 + wg) * 56 + hg * 7) * 64] + w * 64 + lane);
            const uint32_t om0 = opaque((lane & 7) == w * 2), om1 = opaque((lane & 7) == w * 2 + 1);
            QCHUNK(QC2, 28);
            #undef QCHUNK
            const bool gt0 = 2 * t > g, gt1 = 2 * t + 1 > g, no_prev = ti == 0 && w == 0;
            const float kf0 = gt0 ? rk[1][0] : rk[2][0], kf1 = gt1 ? rk[1][1] : rk[2][1];
            constexpr float kScale = 0.18898223650461362f * 1.4426950408889634f;
            const float sq0 = rs0 * kScale, sf0 = kf0 * (rs1 * kScale), sf1 = kf1 * (rs1 * kScale);
            const float NEG = -__int_as_float(0x7f800000);
            const float nb0 = gt0 && no_prev ? NEG : 0.f, nb1 = gt1 && no_prev ? NEG : 0.f;
            const uint32_t mk = opaque((gt0 ? 0x0000ffffu : 0u) | (gt1 ? 0xffff0000u : 0u));
            const uint32_t sr = stg + ((w + 3) & 3) * 2048, hbar = BAR(w == 0 ? B_HL + wg : B_EP);
            mbar_wait(BAR(B_EP), 0);
            wg_wait<0>();
            reg_fence(aq);
            warp_arrive(BAR(B_A1D));
            TR(3);
            uint32_t qf[8][2];
            #pragma unroll
            for (int c = 0; c < 7; c++) {
                qf[c + (c > 3)][0] = pack_bf16(aq[4 * c], aq[4 * c + 1]);
                qf[c + (c > 3)][1] = pack_bf16(aq[4 * c + 2], aq[4 * c + 3]);
            }
            qf[4][0] = t >= 2 ? qf[3][0] : 0u; qf[4][1] = t >= 2 ? qf[3][1] : 0u;
            qf[3][0] = t < 2 ? qf[3][0] : 0u;  qf[3][1] = t < 2 ? qf[3][1] : 0u;
            float sc[2][3][4];
            auto scores = [&](int n) {
                #pragma unroll
                for (int hd = 0; hd < 2; hd++) {
                    sc[hd][n][0] = sc[hd][n][1] = sc[hd][n][2] = sc[hd][n][3] = 0.f;
                    mma16816(sc[hd][n], qf[4 * hd][0], qf[4 * hd][1], qf[4 * hd + 1][0], qf[4 * hd + 1][1], kf[n][3 * hd], kf[n][3 * hd + 1]);
                    mma16816(sc[hd][n], qf[4 * hd + 2][0], qf[4 * hd + 2][1], qf[4 * hd + 3][0], qf[4 * hd + 3][1], kf[n][3 * hd + 2], kf[n][3 * hd + 3]);
                }
            };
            scores(1); scores(2);
            mbar_wait(hbar, 0);
            {
                const uint4 u0 = lds4(sr), u1 = lds4(sr + 512), u3 = lds4(sr + 1536), u2 = lds4(sr + 1024);
                kf[0][0] = u0.x; kf[0][1] = u0.y; kf[0][2] = u0.z; kf[0][3] = u0.w;
                kf[0][4] = u1.x; kf[0][5] = u1.y; kf[0][6] = u1.z; vf[0][0] = u1.w;
                vf[0][1] = u2.x; vf[0][2] = u2.y; vf[0][3] = u2.z; vf[0][4] = u2.w;
                vf[0][5] = u3.x; vf[0][6] = u3.y; rk[0][0] = __uint_as_float(u3.z); rk[0][1] = __uint_as_float(u3.w);
            }
            TR(4);
            scores(0);
            const float ke0 = gt0 ? rk[0][0] : rk[1][0], ke1 = gt1 ? rk[0][1] : rk[1][1];
            const float se0 = ke0 * sq0, se1 = ke1 * sq0;
            uint32_t ow[7][2];
            #pragma unroll
            for (int hd = 0; hd < 2; hd++) {
                const int c0 = hd * 3;
                float (&sc_)[3][4] = sc[hd];
                const float e0 = fmaf(gt0 ? sc_[0][0] : sc_[1][0], se0, nb0), e1 = fmaf(gt1 ? sc_[0][1] : sc_[1][1], se1, nb1);
                const float f0 = (gt0 ? sc_[1][2] : sc_[2][2]) * sf0, f1 = (gt1 ? sc_[1][3] : sc_[2][3]) * sf1;
                const float me = quad_max(fmaxf(e0, e1)), mf = quad_max(fmaxf(f0, f1));
                const float p0 = ex2(e0 - me), p1 = ex2(e1 - me), r0 = ex2(f0 - mf), r1 = ex2(f1 - mf);
                const float ie = rcp(quad_sum(p0 + p1)), jf = rcp(quad_sum(r0 + r1));
                const uint32_t pp = pack_bf16(p0 * ke0 * ie, p1 * ke1 * ie), rp = pack_bf16(r0 * kf0 * jf, r1 * kf1 * jf);
                const uint32_t a0 = pp & ~mk, a1 = rp & mk, a3 = rp & ~mk, a4 = pp & mk, zero = opaque(0u), zero2 = opaque(0u);
                #pragma unroll
                for (int c = 0; c < 4; c++) {
                    float o[4] = {0.f, 0.f, 0.f, 0.f};
                    mma16816(o, a0, a1, zero, a3, vf[1][c0 + c], vf[2][c0 + c]);
                    mma1688(o, a4, zero2, vf[0][c0 + c]);
                    const uint32_t lo = pack_bf16(o[0], o[1]), hi = pack_bf16(o[2], o[3]);
                    if (hd == 1 && c == 0) { if (t >= 2) { ow[3][0] = lo; ow[3][1] = hi; } }
                    else { ow[c0 + c][0] = lo; ow[c0 + c][1] = hi; }
                }
            }
            #pragma unroll
            for (int c = 0; c < 7; c++) {
                stg1(op + c * 256,      set_par(ow[c][0], om0, tag));
                stg1(op + c * 256 + 32, set_par(ow[c][1], om1, tag));
            }
            TR(5);
        }
        float as[28], ac[28];
        uint32_t xch, peer_xch, gm[2][4], *gp1, *gp2;
        const uint32_t *hp, *ht;
        const uint2* hq;
        uint64_t da0, db0;
        const int cg2 = (g2j + 2 * wg) * 2 + (rank ^ 1), cg1 = (g1j + 2 * wg) * 2 + (rank ^ (g1f < 14));
        const bool lead = elect_one();
        {
            const int cg = a2j * 2 + wg;
            float acc2[28];
            mbar_wait(BAR(B_XRF), 0);
            {
                const uint32_t xa = sb + SM_XR + wg * 8192 + (w * 16 + (lane & 15)) * 128;
                #pragma unroll
                for (int c = 0; c < 4; c++) {
                    uint32_t xr[4];
                    asm volatile("ldmatrix.sync.aligned.m8n8.x4.shared.b16 {%0,%1,%2,%3}, [%4];"
                                 : "=r"(xr[0]), "=r"(xr[1]), "=r"(xr[2]), "=r"(xr[3])
                                 : "r"(xa + ((((c * 2 + wg + (lane >> 4)) ^ lane) & 7) << 4)) : "memory");
                    #pragma unroll
                    for (int e = 0; e < (c < 3 ? 4 : 2); e++) { acc2[8 * c + 2 * e] = bf_lo(xr[e]); acc2[8 * c + 2 * e + 1] = bf_hi(xr[e]); }
                }
            }
            uint32_t* spw = opaque_ptr(&prm.sc->stats[((a2s * 8 + cg) * 4 + w) * 32 + lane]);
            const uint32_t* spr = opaque_ptr(&prm.sc->stats[(a2s * 32 + w) * 32 + lane]);
            uint32_t* rp = opaque_ptr((uint32_t*)&prm.sc->rows[a2s * 64 + w * 16 + (t >> 1) * 8 + g] + (t & 1));
            const int cgs = cg ^ (a2s >> 4);
            uint32_t* np = opaque_ptr((uint32_t*)&prm.sc->hn[(a2s * 56 + cgs * 7) * 64] + w * 64 + lane);
            const uint64_t dwo = make_desc(sb + SM_WKV + wg * (28672 + 16), 0, true);
            const uint64_t doa = make_desc(sb + SM_WQ, 1024, false, 128);
            bias1a = prm.b1[g1f * 64 + w * 16 + g]; bias1b = prm.b1[g1f * 64 + w * 16 + 8 + g];
            const __nv_bfloat16 bias2 = prm.b2[ti * 128 + (w * 16 + (t >> 1) * 8 + g) * 2 + a2p];
            reg_fence(acc2);
            fence_async_smem();
            warp_arrive(BAR(B_XD));
            {
                xch = opaque(sb + SM_XCH + w * 1792 + lane * 16);
                asm volatile("mapa.shared::cluster.u32 %0, %1, %2;" : "=r"(peer_xch) : "r"(xch), "r"(rank ^ 1));
                const int hcg = cg2 ^ (g2s >> 4), hrg = (g2s & 1) * 4 + w;
                const uint32_t* hl = (const uint32_t*)&prm.sc->hn[((g2s >> 1) * 112 + hcg * 7) * 64 + hrg * 8];
                hp = opaque_ptr(hl + (g & 1) * 14336 + (g >> 1) * 4 + t);
                ht = opaque_ptr(hl + (lane & 1) * 14336 + min(lane >> 1, 6) * 256 + ((min(lane >> 1, 6) - (hcg & 1)) & 3) * 8 + hrg);
                hq = opaque_ptr(&prm.sc->rows[((g2s >> 1) * 2 + (g & 1)) * 64 + hrg * 8 + (g >> 1)]);
                gp1 = opaque_ptr((uint32_t*)&prm.sc->g[(g1f * 56 + cg1 * 7) * 64] + w * 64 + lane);
                gp2 = opaque_ptr((uint32_t*)(prm.out + (size_t)(g2s * 64 + w * 16 + lane / 7) * kD + cg2 * 56) + (lane % 7) * 4);
                da0 = make_desc(sb, 0, true); db0 = make_desc(sb + SM_B, 128, false);
            }
            static_for<0, 4>([&](auto P_) {
                constexpr int P = decltype(P_)::value;
                if (P == 0) mbar_wait(BAR(B_WOF), 0);
                if (P == 2) mbar_wait2(BAR(B_OF + P), 0, BAR(B_WOF + 1), 0); else mbar_wait(BAR(B_OF + P), 0);
                if (P == 0) TR(6);
                wg_fence();
                static_for<0, 7>([&](auto K_) { constexpr int k = decltype(K_)::value;
                    wgmma_ss_n56<P * 14336 + k * 2048, (P >> 1) * 57344 + (P & 1) * 14336 + k * 2048, 0>(acc2, doa, dwo); });
                if (P) wg_commit();
                if (P == 2) { wg_wait<1>(); warp_arrive(BAR(B_OC)); }
            });
            wg_wait<0>();
            reg_fence(acc2);
            TR(7);
            float s0 = 0.f, s1 = 0.f, q0 = 0.f, q1 = 0.f;
            #pragma unroll
            for (int c = 0; c < 7; c++) {
                s0 += acc2[4 * c] + acc2[4 * c + 1];     q0 = fmaf(acc2[4 * c], acc2[4 * c], fmaf(acc2[4 * c + 1], acc2[4 * c + 1], q0));
                s1 += acc2[4 * c + 2] + acc2[4 * c + 3]; q1 = fmaf(acc2[4 * c + 2], acc2[4 * c + 2], fmaf(acc2[4 * c + 3], acc2[4 * c + 3], q1));
            }
            const bool th = t >= 2, to = t & 1;
            const float sa = (th ? s1 : s0) + __shfl_xor_sync(~0u, th ? s0 : s1, 2), qa = (th ? q1 : q0) + __shfl_xor_sync(~0u, th ? q0 : q1, 2);
            const float part = (to ? qa : sa) + __shfl_xor_sync(~0u, to ? sa : qa, 1);
            stg1(spw, set_par(__float_as_uint(part), 1u, tag));
            const uint32_t tpoll = clk32() + SDELAY;
            TR(8);
            warp_arrive(BAR(B_HD));
            uint32_t nm[2][4], us[8];
            spin_until(tpoll);
            #pragma unroll
            for (int i = 0; i < 8; i++) us[i] = ld_rlx(spr + i * 128);
            #pragma unroll
            for (int i = 0; i < 8; i++) {
                nm[i >> 2][i & 3] = lane == ((i - (cgs & 1)) & 3) * 8 + w * 2 + (i >> 2);
                gm[i >> 2][i & 3] = opaque(lane == ((i - (cg1 & 1)) & 3) * 8 + w * 2 + (i >> 2));
            }
            #pragma unroll
            for (int c = 0; c < 28; c++) { ac[c] = 0.5f * __bfloat162float(c & 2 ? bias1b : bias1a); as[c] = 0.f; }
            reg_fence(as); reg_fence(ac);
            {
                int it = 0;
                while (true) {
                    uint32_t bad = 0;
                    #pragma unroll
                    for (int i = 0; i < 8; i++) bad |= us[i] ^ tag;
                    if (!__any_sync(~0u, bad & 1)) break;
                    RETRY_COUNT(3);
                    if (++it > kSpinLimit) { TIMEOUT(103); break; }
                    #pragma unroll
                    for (int i = 0; i < 8; i++) us[i] = ld_rlx(spr + i * 128);
                }
            }
            TR(9);
            const float tot = (((__uint_as_float(us[0]) + __uint_as_float(us[1])) + (__uint_as_float(us[2]) + __uint_as_float(us[3])))
                            + ((__uint_as_float(us[4]) + __uint_as_float(us[5])) + (__uint_as_float(us[6]) + __uint_as_float(us[7])))) * (1.f / kD);
            const float oth = __shfl_xor_sync(~0u, tot, 1);
            const float mean = to ? oth : tot;
            const float var = fmaxf(fmaf(-mean, mean, to ? tot : oth), 0.f);
            const float rra = rsq(fmaf(var, 4.f + 4.f * kEps, 4.f * kEps * kEps)), mra = -mean * rra;
            const float rrb = __shfl_xor_sync(~0u, rra, 2), mrb = __shfl_xor_sync(~0u, mra, 2);
            const float rr0 = th ? rrb : rra, mr0 = th ? mrb : mra, rr1 = th ? rra : rrb, mr1 = th ? mra : mrb;
            #pragma unroll
            for (int c = 0; c < 7; c++) {
                stg1(np + c * 256,      set_par(pack_bf16(fmaf(acc2[4 * c], rr0, mr0), fmaf(acc2[4 * c + 1], rr0, mr0)), nm[0][c & 3], tag));
                stg1(np + c * 256 + 32, set_par(pack_bf16(fmaf(acc2[4 * c + 2], rr1, mr1), fmaf(acc2[4 * c + 3], rr1, mr1)), nm[1][c & 3], tag));
            }
            TR(10);
            if (cg == 0) stg1(rp, set_par(__float_as_uint(to ? mean + __bfloat162float(bias2) : rcp(rra)), 1u, tag));
        }
        auto send = [&]() {
            const uint32_t rf = pbar0 + (B_RF + warp) * 8;
            #pragma unroll
            for (int c = 0; c < 4; c++) {
                const uint32_t p0 = pack_bf16(as[8 * c], as[8 * c + 1]), p1 = pack_bf16(as[8 * c + 2], as[8 * c + 3]);
                if (c < 3) {
                    const uint32_t p2 = pack_bf16(as[8 * c + 4], as[8 * c + 5]), p3 = pack_bf16(as[8 * c + 6], as[8 * c + 7]);
                    asm volatile("st.async.shared::cluster.mbarrier::complete_tx::bytes.v4.b32 [%0], {%1,%2,%3,%4}, [%5];"
                                 :: "r"(peer_xch + c * 512), "r"(p0), "r"(p1), "r"(p2), "r"(p3), "r"(rf) : "memory");
                } else {
                    asm volatile("st.async.shared::cluster.mbarrier::complete_tx::bytes.v2.b32 [%0], {%1,%2}, [%3];"
                                 :: "r"(peer_xch + 1536 - lane * 8), "r"(p0), "r"(p1), "r"(rf) : "memory");
                }
            }
        };
        auto receive = [&](uint32_t (&pk)[14], uint32_t phase) {
            mbar_wait(BAR(B_RF + warp), phase);
            #pragma unroll
            for (int c = 0; c < 3; c++) { const uint4 u = lds4(xch + c * 512); pk[4 * c] = u.x; pk[4 * c + 1] = u.y; pk[4 * c + 2] = u.z; pk[4 * c + 3] = u.w; }
            const uint2 u = lds2(xch + 1536 - lane * 8); pk[12] = u.x; pk[13] = u.y;
        };
        uint2 rw[2]; uint32_t tw;
        auto load_rows = [&]() { tw = ld_rlx(ht); rw[0] = ld_rlx2(hq); rw[1] = ld_rlx2(hq + 4); };
        rw[0] = rw[1] = make_uint2(0u, 0u); tw = ~tag;
        #pragma unroll 1
        for (int ge = 0;; ge++) {
          if (ge || g1_on) {
            const int use = ge * 2 + wg;
            int entry = ge ? 1 : 2 * wg, stop = 0;
            uint64_t da = da0 + (ge ? -3 : wg ? NR - 10 : 0) * 512;
            bool rel = lead && use == 1;
            const uint32_t xfree = BAR(use > (g1_on ? 0 : 2) ? B_RE + use - 1 : B_PD);
            mbar_wait(BAR(B_AF), 0);
            if (ge && (wg || g1_on)) named_bar(5 - wg, 256);
            TR(11 + ge * 4);
            auto step = [&](auto I_) {
                constexpr int i = decltype(I_)::value, sl = i % NB, ao = i * 8192, bo = sl * 14336;
                mbar_wait_fast(BAR(B_BF + sl), i / NB);
                wg_fence();
                wgmma_ss_n112<ao,        bo,       1>(as, ac, da, db0);
                wgmma_ss_n112<ao + 2048, bo + 256, 1>(as, ac, da, db0);
                wgmma_ss_n112<ao + 4096, bo + 512, 1>(as, ac, da, db0);
                wgmma_ss_n112<ao + 6144, bo + 768, 1>(as, ac, da, db0);
                wg_commit();
                if (i == 1 && stop == 1) named_arrive(4, 256);
                if (i == 3 && (use == 1 || use == 2)) named_arrive(4 + wg, 256);
                wg_wait<1>();
                mbar_arrive_if(BAR(B_BE + (13 + i) % 14), rel);
                rel = lead;
            };
            #pragma unroll 1
            while (true) {
                if (entry < 1) {
                    static_for<0, 2>(step);
                    if (stop == 1) break;
                    static_for<2, 4>(step);
                    if (stop) break;
                }
                if (entry < 2) static_for<4, 10>(step);
                else {
                    uint32_t af[NR * 4][4];
                    mbar_wait(BAR(B_GO), 0);
                    const uint32_t tp = lds1(sb + SM_TG + 4) + PLOFF;
                    int it = 0;
                    while ((int)(gtime32() - tp) < 0 && ++it < 256) __nanosleep(20);
                    const uint32_t la = sb + ((lane >> 4) * 8 + (lane & 7)) * 128 + (((w * 2 + ((lane >> 3) & 1)) ^ (lane & 7)) << 4);
                    #pragma unroll
                    for (int k = 0; k < NR * 4; k++)
                        asm volatile("ldmatrix.sync.aligned.m8n8.x4.trans.shared.b16 {%0,%1,%2,%3}, [%4];"
                                     : "=r"(af[k][0]), "=r"(af[k][1]), "=r"(af[k][2]), "=r"(af[k][3]) : "r"(la + k * 2048) : "memory");
                    __syncwarp();
                    mbar_arrive_if(BAR(B_PL), lead);
                    named_bar(4, 256);
                    static_for<0, NR>([&](auto I_) {
                        constexpr int i = decltype(I_)::value, sl = (16 + i) % NB, o = sl * 14336;
                        mbar_wait_fast(BAR(B_BF + sl), (16 + i) / NB & 1);
                        wg_fence();
                        wgmma_rs_n112<o,       1>(as, ac, af[4 * i][0], af[4 * i][1], af[4 * i][2], af[4 * i][3], db0);
                        wgmma_rs_n112<o + 256, 1>(as, ac, af[4 * i + 1][0], af[4 * i + 1][1], af[4 * i + 1][2], af[4 * i + 1][3], db0);
                        wgmma_rs_n112<o + 512, 1>(as, ac, af[4 * i + 2][0], af[4 * i + 2][1], af[4 * i + 2][2], af[4 * i + 2][3], db0);
                        wgmma_rs_n112<o + 768, 1>(as, ac, af[4 * i + 3][0], af[4 * i + 3][1], af[4 * i + 3][2], af[4 * i + 3][3], db0);
                        wg_commit();
                        if (i) { wg_wait<1>(); mbar_arrive_if(BAR(B_BE + (15 + i) % (2 * NB)), lead); }
                    });
                }
                static_for<10, 14>(step);
                entry = 0; stop = use + 1; da += 14 * 512;
            }
            const uint32_t prev = BAR(B_BE + (use ? 3 : 1));
            const bool xok = mbar_test(xfree, 0);
            wg_wait<0>();
            reg_fence(as); reg_fence(ac);
            mbar_arrive_if(prev, lead);
            if (!xok) mbar_wait(xfree, 0);
            if (ge) break;
            send();
            load_rows();
            TR(12);
            uint32_t pk[14];
            receive(pk, 0);
            TR(13);
            #pragma unroll
            for (int c = 0; c < 14; c++) {
                float r[2];
                #pragma unroll
                for (int e = 0; e < 2; e++) {
                    const float u = ac[2 * c + e] + (e ? bf_hi(pk[c]) : bf_lo(pk[c]));
                    r[e] = fmaf(u, tanh_hw(u * fmaf(u * u, 8.f * 0.7978845608f * 0.044715f, 2.f * 0.7978845608f)), u);
                }
                stg1(gp1 + (c >> 1) * 256 + (c & 1) * 32, set_par(pack_bf16(r[0], r[1]), gm[c & 1][(c >> 1) & 3], tag));
            }
            named_bar(1 + wg, 128);
            if (w == 0 && lane == 0) {
                asm volatile("st.shared.u32 [%0], %1;" :: "r"(sb + SM_TG + 8 + wg * 4), "r"(clk32() + (wg ? XSPECB : XSPEC)) : "memory");
                mbar_arrive(BAR(B_GD + wg));
            }
            if (lead) mbar_expect(BAR(B_RF + warp), 1792);
            mbar_arrive_remote_if(pbar0 + (B_RE + wg) * 8, lead);
            TR(14);
          } else mbar_wait(BAR(B_GD), 0);
            {
                int it = 0;
                while (__any_sync(~0u, ((tw ^ tag) | (rw[0].x ^ tag) | (rw[0].y ^ tag) | (rw[1].x ^ tag) | (rw[1].y ^ tag)) & 1)) {
                    if (++it > kSpinLimit) { TIMEOUT(110); break; }
                    load_rows();
                }
                uint32_t hw[14];
                #pragma unroll
                for (int c = 0; c < 14; c++) hw[c] = ld_rlx(hp + (c >> 1) * 256 + (c & 1) * 16);
                #pragma unroll
                for (int c = 0; c < 14; c++) {
                    ac[2 * c]     = fmaf(bf_lo(hw[c]), __uint_as_float(rw[c & 1].x), __uint_as_float(rw[c & 1].y));
                    ac[2 * c + 1] = fmaf(bf_hi(hw[c]), __uint_as_float(rw[c & 1].x), __uint_as_float(rw[c & 1].y));
                    as[2 * c] = as[2 * c + 1] = 0.f;
                }
                reg_fence(as); reg_fence(ac);
            }
        }
        uint32_t po[14], pk[14];
        if (!wg) sleep_until(clk32() + w * STAG2);
        send();
        #pragma unroll
        for (int c = 0; c < 14; c++) po[c] = opaque(pack_bf16(ac[2 * c], ac[2 * c + 1]));
        TR(16);
        receive(pk, g1_on);
        TR(17);
        #pragma unroll
        for (int c = 0; c < 14; c++) pk[c] = add_bf16x2(po[c], pk[c]);
        __syncwarp();
        const uint32_t sa = xch - lane * 16 + (lane & 15) * 112 + (lane >> 4) * 16;
        #pragma unroll
        for (int m = 0; m < 3; m++)
            asm volatile("stmatrix.sync.aligned.m8n8.x4.shared.b16 [%0], {%1,%2,%3,%4};"
                         :: "r"(sa + m * 32), "r"(pk[4 * m]), "r"(pk[4 * m + 1]), "r"(pk[4 * m + 2]), "r"(pk[4 * m + 3]) : "memory");
        asm volatile("stmatrix.sync.aligned.m8n8.x2.shared.b16 [%0], {%1,%2};" :: "r"(sa + 96), "r"(pk[12]), "r"(pk[13]) : "memory");
        __syncwarp();
        if (lane < 28) {
            #pragma unroll
            for (int i = 0; i < 4; i++) { const uint4 u = lds4(xch + i * 448); stg4(gp2 + i * 896, u.x, u.y, u.z, u.w); }
        }
        __syncwarp();
        mbar_arrive_remote_if(pbar0 + (B_RE + 2) * 8, lead && wg == 0);
        TR(18);
        if (tid == 128) TRG(62);
        if (b == 0 && tid == 128) prm.sc->epoch = tag;
    }
}

typedef CUresult (*EncodeFn)(CUtensorMap*, CUtensorMapDataType, cuuint32_t, void*, const cuuint64_t*, const cuuint64_t*,
                             const cuuint32_t*, const cuuint32_t*, CUtensorMapInterleave, CUtensorMapSwizzle,
                             CUtensorMapL2promotion, CUtensorMapFloatOOBfill);

void make_map(EncodeFn enc, CUtensorMap* m, const void* base, uint64_t cols, uint64_t rows, uint32_t box_rows) {
    cuuint64_t dims[2] = {cols, rows};
    cuuint64_t strides[1] = {cols * 2};
    cuuint32_t box[2] = {64, box_rows};
    cuuint32_t es[2] = {1, 1};
    enc(m, CU_TENSOR_MAP_DATA_TYPE_BFLOAT16, 2, const_cast<void*>(base), dims, strides, box, es, CU_TENSOR_MAP_INTERLEAVE_NONE,
        CU_TENSOR_MAP_SWIZZLE_128B, CU_TENSOR_MAP_L2_PROMOTION_L2_128B, CU_TENSOR_MAP_FLOAT_OOB_FILL_NONE);
}

}

extern "C" void kernel_launch(void* const* d_in, const int* in_sizes, int n_in, void* d_out, int out_size) {
    (void)in_sizes; (void)n_in; (void)out_size;
    void* fn = nullptr;
    cudaDriverEntryPointQueryResult qr;
    cudaGetDriverEntryPoint("cuTensorMapEncodeTiled", &fn, cudaEnableDefault, &qr);
    EncodeFn enc = (EncodeFn)fn;
    CUtensorMap mX2, mX, mWqkv, mWo, mW1, mW2;
    {
        cuuint64_t dims[3] = {kD, kS / 2, 2}, strides[2] = {4 * kD, 2 * kD};
        cuuint32_t box[3] = {64, 64, 2}, es[3] = {1, 1, 1};
        enc(&mX2, CU_TENSOR_MAP_DATA_TYPE_BFLOAT16, 3, d_in[0], dims, strides, box, es, CU_TENSOR_MAP_INTERLEAVE_NONE,
            CU_TENSOR_MAP_SWIZZLE_128B, CU_TENSOR_MAP_L2_PROMOTION_L2_128B, CU_TENSOR_MAP_FLOAT_OOB_FILL_NONE);
    }
    make_map(enc, &mX, d_in[0], 2 * kD, kS / 2, 64);
    make_map(enc, &mWqkv, d_in[1], 3 * kD, kD, 64);
    make_map(enc, &mWo, d_in[2], kD, kD, 112);
    make_map(enc, &mW1, d_in[4], 2 * kF, kS / 2, 64);
    make_map(enc, &mW2, d_in[6], kS, kF, 64);
    Params prm;
    prm.x = (const __nv_bfloat16*)d_in[0];
    prm.wqkv = (const __nv_bfloat16*)d_in[1];
    prm.wo = (const __nv_bfloat16*)d_in[2];
    prm.w1 = (const __nv_bfloat16*)d_in[4];
    prm.b1 = (const __nv_bfloat16*)d_in[5];
    prm.w2 = (const __nv_bfloat16*)d_in[6];
    prm.b2 = (const __nv_bfloat16*)d_in[7];
    prm.out = (__nv_bfloat16*)d_out;
    cudaGetSymbolAddress((void**)&prm.sc, g_scratch);
    cudaFuncSetAttribute(fused_kernel, cudaFuncAttributeMaxDynamicSharedMemorySize, SM_TOTAL);
    fused_kernel<<<128, 384, SM_TOTAL, cudaStreamPerThread>>>(prm, mX2, mX, mWqkv, mWo, mW1, mW2);
}
```

```cpp
#include <cuda_runtime.h>
#include <cuda.h>
#include <cuda_bf16.h>
#include <stdint.h>
#include <type_traits>

namespace {

constexpr int kS = 2048, kD = 448, kF = 1792;
constexpr float kEps = 1e-5f;

#define FS 32
struct Scratch {
    uint4    o[32 * 56 * 64];
    uint4    hn[32 * 56 * 64];
    uint4    g[28 * 56 * 64];
    uint4    halo[16 * 8 * 2 * 4 * 32];
    uint32_t stats[32 * 8 * 4 * 32];
    uint2    rows[32 * 64];
    uint32_t flag_o[16 * 8 * FS];
    uint32_t flag_h[32 * 4 * FS];
    uint32_t epoch;
};
__device__ __align__(1024) Scratch g_scratch;
#define TIMEOUT(code)
#define RETRY_COUNT(i)
#define CAP_DECL(n, k)
#define CAP(n)
#define CAP_SKIP(n)
#define EV(i, dep)
#define TR2(idx)
#define TR(idx)
#define TRW(idx)
#define TRG(idx)

constexpr uint32_t SM_WKV  = 114688;
constexpr uint32_t SM_XR   = 24576;
constexpr uint32_t SM_STG  = 40960;
constexpr uint32_t SM_WQ   = 57344;
constexpr uint32_t SM_XCH  = 0;
constexpr uint32_t SM_B    = 131072;
constexpr uint32_t SM_BAR  = 231424;
constexpr uint32_t SM_TOTAL = SM_BAR + 1024;
constexpr int NB = 7;
#define SH1 0
#define SH2 0
#define SH2N 5
#define SH3 0
#define NSPEC 4
#define XSPEC 500
#define C2 0
#define C3 0
#define CN2 7200
#define CN3 10900
constexpr int B_XF = 0, B_WKVF = 7, B_WQF = 14, B_XRF = 15, B_WOF = 16,
              B_XC = 18, B_KV3 = 19, B_KVC = 20,
              B_A1D = 21, B_XD = 22, B_OC = 23,
              B_BE = 24  , B_RE = B_BE + 2 * NB,
              B_PL = B_RE + 3, B_AF = B_PL + 1, B_BL = B_AF + 1  , B_OL = B_BL + 2 * NB  ,
              B_BF = B_OL + 4  , B_OF = B_BF + NB, B_RF = B_OF + 4, B_EP = B_RF + 8, B_PD = B_EP + 1, B_OD = B_PD + 1, B_RT = B_OD + 1, B_HL = B_RT + 2,
              B_HD = B_HL + 2  , B_GO = B_HD + 1, B_GD = B_GO + 1, B_COUNT = B_GD + 2;
#define WEARLY 6
#define PF0 126
#define TMPF 2
#define RSTE 2
#define POLLP 1
#define PROBEP 1
#define LOADP 1
#define LOADW 64
#define NOB 0
#define AEARLY 5
#define W1PACE 400
#define W2PACE 350
#define PFPACE 330
#define PFBAR (B_XF + 6)
#define DELTA 2144
#define DELTA2 DELTA
#define BPACE 230
#define BURST 2
#define W1OFF 350
#define W2OFF 800
#define XPACE 0
#define PSTAG 200
constexpr uint32_t SM_EPOCH = SM_BAR + B_COUNT * 8, SM_TG = SM_EPOCH + 4  , SM_TG2 = SM_TG + 16  , SM_ORD = SM_TG2 + 4  , SM_TR = SM_BAR + 768;

#define HDELAY 0
#define QC0 4
#define QC1 10
#define QC2 16
#define HPOS 1
#define XSPECB 750
#define PACE1 120
#define PACE2 400
#define RELOAD1 1
#define VCH 1
#define SOFF 0
#define XW 1
#define XLAG 0
#define PFX 3
#define PFD 250
#define SDELAY 300
#define PDELAY 500
#define NPRE 10
#define PREPACE 0
#define AFIRST 1
#define DELTAO 864
#define NS 0
#define GCH 14
#define OCH 14
#define ICH 14
#define PACKO
#define NR 8
#define HMODE 2
#define HOFF0 (-100)
#define HOFF1 900
#define STAG1 0
#define STAG2 400
#define PLOFF (-250)
#define HSRC h
#define WO1 1
#define WOD 300
#define WOP 400
#define WOP0 0
#define KV5 1
#define XLATE 0
#define W0E 1
#define W0F 2
#define PACEA 400
#define PACEB 300
#define PFN 16
#define PFPACE2 300
#define PF2R 1
#define PFW 4
#define PFBAR2 PFBAR
#define WOQ 3
#define DMIN 608
#define CHUNKNS 250
#define W1Q 3
#define APOS1 ((1ull << 4) | (1ull << 8) | (1ull << 12) | (1ull << 5) | (1ull << 9) | (1ull << 13))
#define APOS2 (0x5555555ull << 17)
constexpr uint32_t seg_mask(int h, int p0, int p1) {
    uint32_t m = 0; int n = 0;
    for (int p = p0; p < p1; p++) if ((p & 1) == h) m |= (uint32_t)(((APOS1 | APOS2) >> p) & 1) << n++;
    return m | 1u << n;
}
constexpr uint64_t seg_masks(int h) {
    return 2 | (uint64_t)seg_mask(h, 0, 16) << 10 | (uint64_t)seg_mask(h, 16, 32) << 20
             | (uint64_t)seg_mask(h, 32, 46) << 30 | (uint64_t)seg_mask(h, 46, 60) << 40;
}
constexpr uint64_t kSegMasks0 = seg_masks(0), kSegMasks1 = seg_masks(1);

constexpr int kSpinLimit = 1 << 15;
__device__ __forceinline__ bool elect_one() {
    uint32_t p;
    asm volatile("{ .reg .pred P; elect.sync _|P, 0xffffffff; selp.u32 %0, 1, 0, P; }" : "=r"(p));
    return p;
}
__device__ __forceinline__ void mbar_init(uint32_t bar, uint32_t cnt) { asm volatile("mbarrier.init.shared::cta.b64 [%0], %1;" :: "r"(bar), "r"(cnt)); }
__device__ __forceinline__ void mbar_expect(uint32_t bar, uint32_t bytes) { asm volatile("mbarrier.arrive.expect_tx.shared::cta.b64 _, [%0], %1;" :: "r"(bar), "r"(bytes) : "memory"); }
__device__ __forceinline__ void mbar_expect_more(uint32_t bar, uint32_t bytes) { asm volatile("mbarrier.expect_tx.relaxed.cta.shared::cta.b64 [%0], %1;" :: "r"(bar), "r"(bytes) : "memory"); }
__device__ __forceinline__ void mbar_arrive(uint32_t bar) { asm volatile("mbarrier.arrive.shared::cta.b64 _, [%0];" :: "r"(bar) : "memory"); }
__device__ __forceinline__ void mbar_wait(uint32_t bar, uint32_t parity) {
    uint32_t ok; int it = 0;
    do {
        asm volatile("{ .reg .pred p; mbarrier.try_wait.parity.shared::cta.b64 p, [%1], %2; selp.u32 %0, 1, 0, p; }"
                     : "=r"(ok) : "r"(bar), "r"(parity) : "memory");
        if (++it > kSpinLimit) { TIMEOUT((bar & 1023) >> 3); break; }
    } while (!ok);
}
__device__ __forceinline__ bool mbar_try(uint32_t bar, uint32_t parity) {
    uint32_t ok;
    asm volatile("{ .reg .pred p; mbarrier.try_wait.parity.shared::cta.b64 p, [%1], %2; selp.u32 %0, 1, 0, p; }" : "=r"(ok) : "r"(bar), "r"(parity) : "memory");
    return ok;
}
__device__ __forceinline__ bool mbar_test(uint32_t bar, uint32_t parity) {
    uint32_t ok;
    asm volatile("{ .reg .pred p; mbarrier.test_wait.parity.shared::cta.b64 p, [%1], %2; selp.u32 %0, 1, 0, p; }" : "=r"(ok) : "r"(bar), "r"(parity) : "memory");
    return ok;
}
__device__ __forceinline__ void mbar_wait_fast(uint32_t bar, uint32_t parity) { if (!mbar_try(bar, parity)) mbar_wait(bar, parity); }
__device__ __forceinline__ void mbar_wait2(uint32_t bar0, uint32_t par0, uint32_t bar1, uint32_t par1) {
    uint32_t ok; int it = 0;
    do {
        asm volatile("{ .reg .pred p, q; mbarrier.try_wait.parity.shared::cta.b64 p, [%1], %2;\n"
                     "mbarrier.try_wait.parity.shared::cta.b64 q, [%3], %4; and.pred p, p, q; selp.u32 %0, 1, 0, p; }"
                     : "=r"(ok) : "r"(bar0), "r"(par0), "r"(bar1), "r"(par1) : "memory");
        if (++it > kSpinLimit) { TIMEOUT((bar0 & 1023) >> 3); break; }
    } while (!ok);
}
__device__ __forceinline__ void sched_fence(uint32_t v) {
    asm volatile("{ .reg .pred p; .reg .b32 x; mov.b32 x, %0;\nL: setp.eq.u32 p, x, 0xffffffff; @p mov.u32 x, %%clock; @p bra L; }" :: "r"(v) : "memory");
}
template <int N> __device__ __forceinline__ void reg_fence(float (&d)[N]) {
    #pragma unroll
    for (int i = 0; i < N; i++) asm volatile("" : "+f"(d[i]) :: "memory");
}
__device__ __forceinline__ void mbar_wait_cluster(uint32_t bar, uint32_t parity) {
    uint32_t ok; int it = 0;
    do {
        asm volatile("{ .reg .pred p; mbarrier.try_wait.parity.acquire.cluster.shared::cta.b64 p, [%1], %2; selp.u32 %0, 1, 0, p; }"
                     : "=r"(ok) : "r"(bar), "r"(parity) : "memory");
        if (++it > kSpinLimit) { TIMEOUT((bar & 1023) >> 3); break; }
    } while (!ok);
}
__device__ __forceinline__ void mbar_arrive_if(uint32_t bar, bool pred) {
    asm volatile("{ .reg .pred p; setp.ne.u32 p, %1, 0; @p mbarrier.arrive.shared::cta.b64 _, [%0]; }" :: "r"(bar), "r"((uint32_t)pred) : "memory");
}
template <int P> __device__ __forceinline__ void tick() {
    if (P > 1) { const uint32_t t = ((uint32_t)clock() | (P - 1)) + 1; while ((int)((uint32_t)clock() - t) < 0) {} }
}
__device__ __forceinline__ void warp_arrive(uint32_t bar) { __syncwarp(); if (elect_one()) mbar_arrive(bar); }
__device__ __forceinline__ void tma2d(uint32_t dst, const CUtensorMap* m, int c0, int c1, uint32_t bar) {
    asm volatile("cp.async.bulk.tensor.2d.shared::cluster.global.mbarrier::complete_tx::bytes [%0], [%1, {%3, %4}], [%2];"
                 :: "r"(dst), "l"(m), "r"(bar), "r"(c0), "r"(c1) : "memory");
}
__device__ __forceinline__ void tma3d(uint32_t dst, const CUtensorMap* m, int c0, int c1, int c2, uint32_t bar) {
    asm volatile("cp.async.bulk.tensor.3d.shared::cluster.global.mbarrier::complete_tx::bytes [%0], [%1, {%3, %4, %5}], [%2];"
                 :: "r"(dst), "l"(m), "r"(bar), "r"(c0), "r"(c1), "r"(c2) : "memory");
}
__device__ __forceinline__ void tma2d_mc(uint32_t dst, const CUtensorMap* m, int c0, int c1, uint32_t bar) {
    asm volatile("cp.async.bulk.tensor.2d.shared::cluster.global.mbarrier::complete_tx::bytes.multicast::cluster [%0], [%1, {%3, %4}], [%2], %5;"
                 :: "r"(dst), "l"(m), "r"(bar), "r"(c0), "r"(c1), "h"((uint16_t)3) : "memory");
}
__device__ __forceinline__ void bulk_g2s_mc(uint32_t dst, const void* src, uint32_t bytes, uint32_t bar) {
    asm volatile("cp.async.bulk.shared::cluster.global.mbarrier::complete_tx::bytes.multicast::cluster [%0], [%1], %2, [%3], %4;"
                 :: "r"(dst), "l"(src), "r"(bytes), "r"(bar), "h"((uint16_t)3) : "memory");
}
__device__ __forceinline__ void mbar_arrive_remote_if(uint32_t cluster_bar, bool pred) {
    asm volatile("{ .reg .pred p; setp.ne.u32 p, %1, 0; @p mbarrier.arrive.shared::cluster.b64 _, [%0]; }" :: "r"(cluster_bar), "r"((uint32_t)pred) : "memory");
}
__device__ __forceinline__ void bulk_g2s(uint32_t dst, const void* src, uint32_t bytes, uint32_t bar) {
    asm volatile("cp.async.bulk.shared::cluster.global.mbarrier::complete_tx::bytes [%0], [%1], %2, [%3];"
                 :: "r"(dst), "l"(src), "r"(bytes), "r"(bar) : "memory");
}
__device__ __forceinline__ void bulk_prefetch(const void* src, uint32_t bytes) { asm volatile("cp.async.bulk.prefetch.L2.global [%0], %1;" :: "l"(src), "r"(bytes) : "memory"); }
__device__ __forceinline__ void wg_fence()  { asm volatile("wgmma.fence.sync.aligned;" ::: "memory"); }
__device__ __forceinline__ void wg_commit() { asm volatile("wgmma.commit_group.sync.aligned;" ::: "memory"); }
template <int N> __device__ __forceinline__ void wg_wait() { asm volatile("wgmma.wait_group.sync.aligned %0;" :: "n"(N) : "memory"); }
__device__ __forceinline__ void named_bar(int id, int n) { asm volatile("bar.sync %0, %1;" :: "r"(id), "r"(n) : "memory"); }
__device__ __forceinline__ void named_arrive(int id, int n) { asm volatile("bar.arrive %0, %1;" :: "r"(id), "r"(n) : "memory"); }
__device__ __forceinline__ bool mbar_try2(uint32_t bar0, uint32_t par0, uint32_t bar1, uint32_t par1) {
    uint32_t ok;
    asm volatile("{ .reg .pred p, q; mbarrier.test_wait.parity.shared::cta.b64 p, [%1], %2;\n"
                 "mbarrier.test_wait.parity.shared::cta.b64 q, [%3], %4; and.pred p, p, q; selp.u32 %0, 1, 0, p; }"
                 : "=r"(ok) : "r"(bar0), "r"(par0), "r"(bar1), "r"(par1) : "memory");
    return ok;
}
__device__ __forceinline__ void fence_gpu() { asm volatile("fence.release.gpu;" ::: "memory"); }
__device__ __forceinline__ void fence_async_global() { asm volatile("fence.proxy.async.global;" ::: "memory"); }
__device__ __forceinline__ void fence_async_smem() { asm volatile("fence.proxy.async.shared::cta;" ::: "memory"); }
__device__ __forceinline__ uint32_t gtime32() { uint64_t t; asm volatile("mov.u64 %0, %%globaltimer;" : "=l"(t) :: "memory"); return (uint32_t)t; }
__device__ __forceinline__ uint32_t clk32() { uint64_t t; asm volatile("mov.u64 %0, %%clock64;" : "=l"(t) :: "memory"); return (uint32_t)t; }
__device__ __forceinline__ void spin_until(uint32_t t) { while ((int)(clk32() - t) < 0) {} }
#define SLEEPNS 20
__device__ __forceinline__ void sleep_until(uint32_t t) { while ((int)(clk32() - t) < 0) { if (SLEEPNS) __nanosleep(SLEEPNS); } }
__device__ __forceinline__ void st_flag(uint32_t* p, uint32_t v, uint32_t time) {
    const uint64_t w = ((uint64_t)time << 32) | v;
    asm volatile("st.relaxed.gpu.global.u64 [%0], %1;" :: "l"(p), "l"(w) : "memory");
}
__device__ __forceinline__ void ld_flag_if(uint64_t& v, const uint32_t* p, bool pred) {
    asm volatile("{ .reg .pred p; setp.ne.u32 p, %2, 0; @p ld.relaxed.gpu.global.u64 %0, [%1]; }" : "+l"(v) : "l"(p), "r"((uint32_t)pred) : "memory");
}
__device__ __forceinline__ uint32_t ld_acq(const uint32_t* p) { uint32_t v; asm volatile("ld.acquire.gpu.global.u32 %0, [%1];" : "=r"(v) : "l"(p) : "memory"); return v; }
__device__ __forceinline__ uint32_t ld_rlx(const uint32_t* p) { uint32_t v; asm volatile("ld.relaxed.gpu.global.u32 %0, [%1];" : "=r"(v) : "l"(p) : "memory"); return v; }
template <class T> __device__ __forceinline__ T* opaque_ptr(T* p) { asm volatile("" : "+l"(p)); return p; }
__device__ __forceinline__ uint4 ld_rlx4(const uint4* p) {
    uint4 v; asm volatile("ld.relaxed.gpu.global.v4.u32 {%0,%1,%2,%3}, [%4];" : "=r"(v.x), "=r"(v.y), "=r"(v.z), "=r"(v.w) : "l"(p) : "memory"); return v;
}
__device__ __forceinline__ void st_ll(uint4* p, uint32_t a, uint32_t b, uint32_t tag) {
    uint64_t lo = ((uint64_t)tag << 32) | a, hi = ((uint64_t)tag << 32) | b;
    asm volatile("st.relaxed.gpu.global.v2.u64 [%0], {%1,%2};" :: "l"(p), "l"(lo), "l"(hi) : "memory");
}
__device__ __forceinline__ bool ld_ll(const uint4* p, uint32_t& a, uint32_t& b, uint32_t tag) {
    uint64_t lo, hi;
    asm volatile("ld.relaxed.gpu.global.v2.u64 {%0,%1}, [%2];" : "=l"(lo), "=l"(hi) : "l"(p) : "memory");
    a = (uint32_t)lo; b = (uint32_t)hi;
    return (uint32_t)(lo >> 32) == tag && (uint32_t)(hi >> 32) == tag;
}
__device__ __forceinline__ uint2 ld_acq2(const uint2* p) {
    uint2 v; asm volatile("ld.acquire.gpu.global.v2.u32 {%0,%1}, [%2];" : "=r"(v.x), "=r"(v.y) : "l"(p) : "memory"); return v;
}
__device__ __forceinline__ uint2 ld_rlx2(const uint2* p) {
    uint2 v; asm volatile("ld.relaxed.gpu.global.v2.u32 {%0,%1}, [%2];" : "=r"(v.x), "=r"(v.y) : "l"(p) : "memory"); return v;
}
__device__ __forceinline__ void stg1(uint32_t* p, uint32_t v) { asm volatile("st.global.u32 [%0], %1;" :: "l"(p), "r"(v) : "memory"); }
__device__ __forceinline__ void stg2(void* p, uint32_t x, uint32_t y) { asm volatile("st.global.v2.u32 [%0], {%1,%2};" :: "l"(p), "r"(x), "r"(y) : "memory"); }
__device__ __forceinline__ void stg4(void* p, uint32_t x, uint32_t y, uint32_t z, uint32_t w) { asm volatile("st.global.v4.u32 [%0], {%1,%2,%3,%4};" :: "l"(p), "r"(x), "r"(y), "r"(z), "r"(w) : "memory"); }
__device__ __forceinline__ uint32_t lds1(uint32_t a) { uint32_t v; asm volatile("ld.shared.u32 %0, [%1];" : "=r"(v) : "r"(a) : "memory"); return v; }
__device__ __forceinline__ uint2 lds2(uint32_t a) { uint2 v; asm volatile("ld.shared.v2.u32 {%0,%1}, [%2];" : "=r"(v.x), "=r"(v.y) : "r"(a) : "memory"); return v; }
__device__ __forceinline__ uint32_t set_par(uint32_t v, uint32_t mask, uint32_t par) {
    uint32_t r; asm("lop3.b32 %0, %1, %2, %3, 0xb8;" : "=r"(r) : "r"(v), "r"(mask), "r"(par)); return r;
}
__device__ __forceinline__ void st_gen4(void* p, uint32_t x, uint32_t y, uint32_t z, uint32_t w) { asm volatile("st.v4.u32 [%0], {%1,%2,%3,%4};" :: "l"(p), "r"(x), "r"(y), "r"(z), "r"(w) : "memory"); }
__device__ __forceinline__ float tanh_hw(float x) { float r; asm("tanh.approx.f32 %0, %1;" : "=f"(r) : "f"(x)); return r; }
__device__ __forceinline__ bool bar_any(int id, int n, bool v) {
    uint32_t r;
    asm volatile("{ .reg .pred p, q; setp.ne.u32 p, %3, 0; bar.red.or.pred q, %1, %2, p; selp.u32 %0, 1, 0, q; }" : "=r"(r) : "r"(id), "r"(n), "r"((uint32_t)v) : "memory");
    return r;
}
__device__ __forceinline__ void sts4(uint32_t a, uint32_t x, uint32_t y, uint32_t z, uint32_t w) { asm volatile("st.shared.v4.u32 [%0], {%1,%2,%3,%4};" :: "r"(a), "r"(x), "r"(y), "r"(z), "r"(w) : "memory"); }
__device__ __forceinline__ uint4 lds4(uint32_t a) { uint4 v; asm volatile("ld.shared.v4.u32 {%0,%1,%2,%3}, [%4];" : "=r"(v.x), "=r"(v.y), "=r"(v.z), "=r"(v.w) : "r"(a) : "memory"); return v; }
__device__ __forceinline__ uint32_t pack_bf16(float lo, float hi) { uint32_t r; asm("cvt.rn.bf16x2.f32 %0, %1, %2;" : "=r"(r) : "f"(hi), "f"(lo)); return r; }
__device__ __forceinline__ float bf_lo(uint32_t v) { return __uint_as_float(v << 16); }
__device__ __forceinline__ float bf_hi(uint32_t v) { return __uint_as_float(v & 0xffff0000u); }
__device__ __forceinline__ uint32_t sub_bf16x2(uint32_t a, uint32_t b) { uint32_t r; asm volatile("sub.rn.bf16x2 %0, %1, %2;" : "=r"(r) : "r"(a), "r"(b)); return r; }
__device__ __forceinline__ uint32_t add_bf16x2(uint32_t a, uint32_t b) { uint32_t r; asm volatile("add.rn.bf16x2 %0, %1, %2;" : "=r"(r) : "r"(a), "r"(b)); return r; }
__device__ __forceinline__ uint32_t sqr_bf16x2(uint32_t a) { uint32_t r; asm volatile("mul.rn.bf16x2 %0, %1, %1;" : "=r"(r) : "r"(a)); return r; }
__device__ __forceinline__ uint32_t sqa_bf16x2(uint32_t a, uint32_t c) { uint32_t r; asm volatile("fma.rn.bf16x2 %0, %1, %1, %2;" : "=r"(r) : "r"(a), "r"(c)); return r; }
__device__ __forceinline__ uint32_t movm(uint32_t a) { uint32_t r; asm volatile("movmatrix.sync.aligned.m8n8.trans.b16 %0, %1;" : "=r"(r) : "r"(a)); return r; }
__device__ __forceinline__ float ex2(float x) { float r; asm("ex2.approx.ftz.f32 %0, %1;" : "=f"(r) : "f"(x)); return r; }
__device__ __forceinline__ float rsq(float x) { float r; asm("rsqrt.approx.ftz.f32 %0, %1;" : "=f"(r) : "f"(x)); return r; }
__device__ __forceinline__ float rcp(float x) { float r; asm("rcp.approx.ftz.f32 %0, %1;" : "=f"(r) : "f"(x)); return r; }
__device__ __forceinline__ void mma16816(float (&c)[4], uint32_t a0, uint32_t a1, uint32_t a2, uint32_t a3, uint32_t b0, uint32_t b1) {
    asm("mma.sync.aligned.m16n8k16.row.col.f32.bf16.bf16.f32 {%0,%1,%2,%3}, {%4,%5,%6,%7}, {%8,%9}, {%0,%1,%2,%3};"
        : "+f"(c[0]), "+f"(c[1]), "+f"(c[2]), "+f"(c[3]) : "r"(a0), "r"(a1), "r"(a2), "r"(a3), "r"(b0), "r"(b1));
}
__device__ __forceinline__ void mma1688(float (&c)[4], uint32_t a0, uint32_t a1, uint32_t b0) {
    asm("mma.sync.aligned.m16n8k8.row.col.f32.bf16.bf16.f32 {%0,%1,%2,%3}, {%4,%5}, {%6}, {%0,%1,%2,%3};"
        : "+f"(c[0]), "+f"(c[1]), "+f"(c[2]), "+f"(c[3]) : "r"(a0), "r"(a1), "r"(b0));
}
__device__ __forceinline__ float quad_sum(float v) { v += __shfl_xor_sync(~0u, v, 1); v += __shfl_xor_sync(~0u, v, 2); return v; }
__device__ __forceinline__ float quad_max(float v) { v = fmaxf(v, __shfl_xor_sync(~0u, v, 1)); v = fmaxf(v, __shfl_xor_sync(~0u, v, 2)); return v; }
__device__ __forceinline__ uint64_t make_desc(uint32_t addr, uint32_t lbo, bool swz, uint32_t sbo = 1024) {
    const uint32_t lo = __shfl_sync(~0u, ((addr & 0x3FFFF) >> 4) | ((lbo >> 4) << 16), 0);
    const uint32_t hi = __shfl_sync(~0u, (swz ? 0x40000000u : 0u) + (sbo >> 4) + (threadIdx.x & 31), 0);
    return ((uint64_t)hi << 32) | lo;
}
template <int I, int N, class F> __device__ __forceinline__ void static_for(F&& f) {
    if constexpr (I < N) { f(std::integral_constant<int, I>{}); static_for<I + 1, N>(f); }
}
__device__ __forceinline__ uint32_t opaque(uint32_t v) { asm volatile("" : "+r"(v)); return v; }
template <int BOFF, int SCALE_D>
__device__ __forceinline__ void wgmma_rs_n56(float (&d)[28], uint32_t a0, uint32_t a1, uint32_t a2, uint32_t a3, uint64_t db) {
    asm volatile("{ .reg .b64 db; add.s64 db, %32, %33;\n"
        "wgmma.mma_async.sync.aligned.m64n56k16.f32.bf16.bf16 "
        "{%0, %1, %2, %3, %4, %5, %6, %7, %8, %9, %10, %11, %12, %13, %14, %15, %16, %17, %18, %19, %20, %21, %22, %23, %24, %25, %26, %27}, "
        "{%28, %29, %30, %31}, db, %34, 1, 1, 1; }"
        : "+f"(d[0]), "+f"(d[1]), "+f"(d[2]), "+f"(d[3]), "+f"(d[4]), "+f"(d[5]), "+f"(d[6]), "+f"(d[7]),
        "+f"(d[8]), "+f"(d[9]), "+f"(d[10]), "+f"(d[11]), "+f"(d[12]), "+f"(d[13]), "+f"(d[14]), "+f"(d[15]),
        "+f"(d[16]), "+f"(d[17]), "+f"(d[18]), "+f"(d[19]), "+f"(d[20]), "+f"(d[21]), "+f"(d[22]), "+f"(d[23]),
        "+f"(d[24]), "+f"(d[25]), "+f"(d[26]), "+f"(d[27])
        : "r"(a0), "r"(a1), "r"(a2), "r"(a3), "l"(db), "n"(BOFF >> 4), "n"(SCALE_D));
}
template <int AOFF, int BOFF, int MMAJOR>
__device__ __forceinline__ void wgmma_ss_n56(float (&d)[28], uint64_t da, uint64_t db) {
    asm volatile("{ .reg .b64 da, db; add.s64 da, %28, %30; add.s64 db, %29, %31;\n"
        "wgmma.mma_async.sync.aligned.m64n56k16.f32.bf16.bf16 "
        "{%0, %1, %2, %3, %4, %5, %6, %7, %8, %9, %10, %11, %12, %13, %14, %15, %16, %17, %18, %19, %20, %21, %22, %23, %24, %25, %26, %27}, "
        "da, db, 1, 1, 1, %32, 1; }"
        : "+f"(d[0]), "+f"(d[1]), "+f"(d[2]), "+f"(d[3]), "+f"(d[4]), "+f"(d[5]), "+f"(d[6]), "+f"(d[7]),
        "+f"(d[8]), "+f"(d[9]), "+f"(d[10]), "+f"(d[11]), "+f"(d[12]), "+f"(d[13]), "+f"(d[14]), "+f"(d[15]),
        "+f"(d[16]), "+f"(d[17]), "+f"(d[18]), "+f"(d[19]), "+f"(d[20]), "+f"(d[21]), "+f"(d[22]), "+f"(d[23]),
        "+f"(d[24]), "+f"(d[25]), "+f"(d[26]), "+f"(d[27])
        : "l"(da), "l"(db), "n"(AOFF >> 4), "n"(BOFF >> 4), "n"(MMAJOR));
}
template <int AOFF, int BOFF, int MMAJOR>
__device__ __forceinline__ void wgmma_ss_n112(float (&d)[28], float (&e)[28], uint64_t da, uint64_t db) {
    asm volatile("{ .reg .b64 da, db; add.s64 da, %56, %58; add.s64 db, %57, %59;\n"
        "wgmma.mma_async.sync.aligned.m64n112k16.f32.bf16.bf16 "
        "{%0, %1, %2, %3, %4, %5, %6, %7, %8, %9, %10, %11, %12, %13, %14, %15, %16, %17, %18, %19, %20, %21, %22, %23, %24, %25, %26, %27, %28, %29, %30, %31, %32, %33, %34, %35, %36, %37, %38, %39, %40, %41, %42, %43, %44, %45, %46, %47, %48, %49, %50, %51, %52, %53, %54, %55}, "
        "da, db, 1, 1, 1, %60, 1; }"
        : "+f"(d[0]), "+f"(d[1]), "+f"(d[2]), "+f"(d[3]), "+f"(d[4]), "+f"(d[5]), "+f"(d[6]), "+f"(d[7]),
        "+f"(d[8]), "+f"(d[9]), "+f"(d[10]), "+f"(d[11]), "+f"(d[12]), "+f"(d[13]), "+f"(d[14]), "+f"(d[15]),
        "+f"(d[16]), "+f"(d[17]), "+f"(d[18]), "+f"(d[19]), "+f"(d[20]), "+f"(d[21]), "+f"(d[22]), "+f"(d[23]),
        "+f"(d[24]), "+f"(d[25]), "+f"(d[26]), "+f"(d[27]), "+f"(e[0]), "+f"(e[1]), "+f"(e[2]), "+f"(e[3]),
        "+f"(e[4]), "+f"(e[5]), "+f"(e[6]), "+f"(e[7]), "+f"(e[8]), "+f"(e[9]), "+f"(e[10]), "+f"(e[11]),
        "+f"(e[12]), "+f"(e[13]), "+f"(e[14]), "+f"(e[15]), "+f"(e[16]), "+f"(e[17]), "+f"(e[18]), "+f"(e[19]),
        "+f"(e[20]), "+f"(e[21]), "+f"(e[22]), "+f"(e[23]), "+f"(e[24]), "+f"(e[25]), "+f"(e[26]), "+f"(e[27])
        : "l"(da), "l"(db), "n"(AOFF >> 4), "n"(BOFF >> 4), "n"(MMAJOR));
}
template <int BOFF, int SCALE_D>
__device__ __forceinline__ void wgmma_rs_n112(float (&d)[28], float (&e)[28], uint32_t a0, uint32_t a1, uint32_t a2, uint32_t a3, uint64_t db) {
    asm volatile("{ .reg .b64 db; add.s64 db, %60, %61;\n"
        "wgmma.mma_async.sync.aligned.m64n112k16.f32.bf16.bf16 "
        "{%0, %1, %2, %3, %4, %5, %6, %7, %8, %9, %10, %11, %12, %13, %14, %15, %16, %17, %18, %19, %20, %21, %22, %23, %24, %25, %26, %27, %28, %29, %30, %31, %32, %33, %34, %35, %36, %37, %38, %39, %40, %41, %42, %43, %44, %45, %46, %47, %48, %49, %50, %51, %52, %53, %54, %55}, "
        "{%56, %57, %58, %59}, db, %62, 1, 1, 1; }"
        : "+f"(d[0]), "+f"(d[1]), "+f"(d[2]), "+f"(d[3]), "+f"(d[4]), "+f"(d[5]), "+f"(d[6]), "+f"(d[7]),
        "+f"(d[8]), "+f"(d[9]), "+f"(d[10]), "+f"(d[11]), "+f"(d[12]), "+f"(d[13]), "+f"(d[14]), "+f"(d[15]),
        "+f"(d[16]), "+f"(d[17]), "+f"(d[18]), "+f"(d[19]), "+f"(d[20]), "+f"(d[21]), "+f"(d[22]), "+f"(d[23]),
        "+f"(d[24]), "+f"(d[25]), "+f"(d[26]), "+f"(d[27]), "+f"(e[0]), "+f"(e[1]), "+f"(e[2]), "+f"(e[3]),
        "+f"(e[4]), "+f"(e[5]), "+f"(e[6]), "+f"(e[7]), "+f"(e[8]), "+f"(e[9]), "+f"(e[10]), "+f"(e[11]),
        "+f"(e[12]), "+f"(e[13]), "+f"(e[14]), "+f"(e[15]), "+f"(e[16]), "+f"(e[17]), "+f"(e[18]), "+f"(e[19]),
        "+f"(e[20]), "+f"(e[21]), "+f"(e[22]), "+f"(e[23]), "+f"(e[24]), "+f"(e[25]), "+f"(e[26]), "+f"(e[27])
        : "r"(a0), "r"(a1), "r"(a2), "r"(a3), "l"(db), "n"(BOFF >> 4), "n"(SCALE_D));
}

struct Params {
    const __nv_bfloat16 *x, *wqkv;
    Scratch* sc;
    const __nv_bfloat16 *wo, *w1, *w2, *b1, *b2;
    __nv_bfloat16* out;
};

__global__ void __cluster_dims__(2, 1, 1) __launch_bounds__(384, 1)
fused_kernel(const Params prm, const __grid_constant__ CUtensorMap mX2, const __grid_constant__ CUtensorMap mX, const __grid_constant__ CUtensorMap mWqkv,
             const __grid_constant__ CUtensorMap mWo, const __grid_constant__ CUtensorMap mW1,
             const __grid_constant__ CUtensorMap mW2)
{
    extern __shared__ __align__(1024) unsigned char smem_raw[];
    if (threadIdx.x < 126) {
        const uint32_t i = threadIdx.x, t = clk32() + (i >> 5) * PFD;
        const char* px = (const char*)prm.x + (blockIdx.x * 16 + (i & 15)) * 896 + (i >> 4) * 128;
        const char* pw = (const char*)prm.wqkv + blockIdx.x * 2688 + i * 128 + (896 - 112 * 128);
        spin_until(t);
        asm volatile("prefetch.global.L2 [%0];" :: "l"(i < 112 ? px : pw) : "memory");
    }
    if (threadIdx.x == 128) { asm volatile("prefetch.tensormap [%0];" :: "l"(&mX2) : "memory"); asm volatile("prefetch.tensormap [%0];" :: "l"(&mWqkv) : "memory"); }
    uint32_t sb = (uint32_t)__cvta_generic_to_shared(smem_raw);
    asm volatile("mov.u32 %0, %0;" : "+r"(sb));
    const uint32_t bar0 = sb + SM_BAR;
    auto BAR = [&](int i) { return bar0 + 8u * i; };

    const int tid = threadIdx.x, lane = tid & 31;
    const int warp = __shfl_sync(~0u, tid >> 5, 0);
    const int b = __shfl_sync(~0u, (int)blockIdx.x, 0);
    const int rank = b & 1;
    const int cl = (b >> 1) - 4, cq = ((cl - 32) * 37) >> 8;
    const int res = cl < 0 ? 0 : cl < 32 ? cl & 7 : cl - 31 - 7 * cq;
    const int rnd = cl < 0 ? cl + 8 : cl < 32 ? cl >> 3 : 4 + cq;
    const int hg = (res & 1) * 4 + (rnd & 3);
    const int ti = (res >> 1) * 4 + (rnd >> 2) * 2 + rank;
    const int a2p = res & 1, a2j = rnd & 3;
    const int a2s = ti * 2 + a2p;
    const bool g1_on = rnd != 7;
    const int g1j = (rnd < 6 ? rnd : res) & 1, g1f = rnd < 6 ? res * 3 + (rnd >> 1) : 24 + (res >> 1);
    const int g2j = rnd & 1, g2s = res * 4 + (rnd >> 1);
    uint32_t pbar0;
    asm volatile("mapa.shared::cluster.u32 %0, %1, %2;" : "=r"(pbar0) : "r"(bar0), "r"(rank ^ 1));
    auto pair_arrive = [&](int i) { __syncwarp(); const bool l = elect_one(); mbar_arrive_if(BAR(i), l); mbar_arrive_remote_if(pbar0 + 8u * i, l); };
    const int wcol = hg * 56 - (hg & 1) * 8;

    if (warp == 8) {
        if (elect_one()) {
            #pragma unroll
            for (int i = 0; i < B_WQF; i++) mbar_init(BAR(i), 1);
            asm volatile("fence.mbarrier_init.release.cluster;" ::: "memory");
            fence_async_smem();
            #pragma unroll
            for (int kb = 0; kb < 7 - XLATE; kb++) {
                tma3d(sb + kb * 16384, &mX2, kb * 64, ti * 64, 0, BAR(B_XF + kb));
                mbar_expect(BAR(B_XF + kb), 16384);
                if (kb == 0 && PFX != 3) asm volatile("prefetch.tensormap [%0];" :: "l"(&mWqkv) : "memory");
            }
        }
    } else if (warp > 8) {
        if (elect_one()) {
            if (warp == 9) {
                #pragma unroll
                for (int i = B_WQF; i < B_AF; i++) mbar_init(BAR(i), i < B_XC ? 1 : i < B_A1D ? 16 : i < B_BE ? 8 : 4);
            } else if (warp == 10) {
                #pragma unroll
                for (int i = B_AF; i < B_BF; i++) mbar_init(BAR(i), 1);
            } else {
                #pragma unroll
                for (int i = B_BF; i < B_COUNT; i++) mbar_init(BAR(i), i == B_HD ? 8 : 1);
            }
            asm volatile("fence.mbarrier_init.release.cluster;" ::: "memory");
            fence_async_smem();
        }
    }
    __syncwarp();
    __syncthreads();
    asm volatile("barrier.cluster.arrive.relaxed.aligned;" ::: "memory");
    if (tid < 256) TR(0);
    if (tid == 0) TRG(61);

    if (warp >= 8) {
        asm volatile("setmaxnreg.dec.sync.aligned.u32 40;");
        asm volatile("barrier.cluster.wait.aligned;" ::: "memory");
        auto fetch_halo = [&](int p, uint32_t tag) {
            uint4 u[4];
            #pragma unroll
            for (int c = 0; c < 4; c++) u[c] = make_uint4(0u, 0u, 0u, 0u);
            const uint4* hp = opaque_ptr(&prm.sc->halo[(((ti - 1) * 8 + hg) * 2 + p) * 128 + lane]);
            mbar_wait(BAR(B_KVC), 0);
            if (p == 0) TRW(51);
            sleep_until(clk32() + HDELAY);
            if (ti > 0) {
                int it = 0;
                do {
                    #pragma unroll
                    for (int c = 0; c < 4; c++) u[c] = ld_rlx4(hp + c * 32);
                    if (it) RETRY_COUNT(4);
                    if (++it > kSpinLimit) { TIMEOUT(101); break; }
                } while (__any_sync(~0u, ((u[0].x ^ tag) | (u[1].x ^ tag) | (u[2].x ^ tag) | (u[3].x ^ tag)) & ~lane & 1));
            }
            #pragma unroll
            for (int c = 0; c < 4; c++) sts4(sb + SM_STG + p * 8192 + 3 * 2048 + lane * 16 + c * 512, u[c].x, u[c].y, u[c].z, u[c].w);
            warp_arrive(BAR(B_HL + p));
        };
        if (warp & 1) {
            uint32_t tag;
            if (warp == 11) {
                tag = *(volatile uint32_t*)&prm.sc->epoch + 1;
            #pragma unroll 1
            for (int i = 0; i < 8; i++) prm.sc->halo[(ti * 8 + hg) * 256 + i * 32 + lane] = make_uint4(~tag, 0u, 0u, 0u);
            ((uint4*)prm.sc->stats)[(a2s * 4 + a2j) * 64 + lane] = ((uint4*)prm.sc->stats)[(a2s * 4 + a2j) * 64 + 32 + lane] = make_uint4(~tag, ~tag, ~tag, ~tag);
            prm.sc->flag_h[(a2s * 4 + a2j) * FS + lane] = 0;
            prm.sc->flag_o[(ti * 8 + hg) * FS + lane] = 0;
            __syncwarp();
            if (lane == 0) {
                asm volatile("st.shared.v2.u32 [%0], {%1, %2};" :: "r"(sb + SM_EPOCH), "r"(tag), "r"(gtime32()) : "memory");
                mbar_arrive(BAR(B_EP));
            }
            if (lane < 8) mbar_expect(BAR(B_RF + lane), 1792);
            __syncwarp();
            TRW(44);
            } else {
                mbar_wait(BAR(B_EP), 0);
                tag = lds1(sb + SM_EPOCH);
            }
            uint32_t* ofl = opaque_ptr(&prm.sc->flag_o[(ti * 8 + hg) * FS]);
            fetch_halo((warp >> 1) & 1, tag);
            if (warp == 11) {
                mbar_wait2(BAR(B_A1D), 0, BAR(B_HL), 0);
                if (lane == 0) st_flag(ofl, tag, gtime32());
                __syncwarp();
            }
        }
        if (warp < 10) {
          auto load_slab = [&](int s, bool second) {
              if (!second) tma2d(sb + s * 8192, &mW1, (s & 1) * kF + g1f * 64, (rank * 8 + (s >> 1)) * 64, BAR(B_AF));
              else         tma2d(sb + s * 8192, &mW2, g2s * 64, (rank * 14 + s - 1) * 64, BAR(B_AF));
          };
          const char* pw2 = (const char*)prm.w2 + ((b >> 6) * 896 + (b & 63) + PFW * 64) * 4096;
          if (warp == 8) {
            if (elect_one()) {
                #pragma unroll 1
                for (int s = 0; s < 7; s++) {
                    mbar_expect(BAR(B_WKVF + s), 16384);
                    tma2d_mc(sb + SM_WKV + s * 16384 + rank * 8192, &mWqkv, (1 + rank) * kD + wcol, s * 64, BAR(B_WKVF + s));
                    if (s == 0) {
                        #pragma unroll
                        for (int kb = 7 - XLATE; kb < 7; kb++) {
                            tma3d(sb + kb * 16384, &mX2, kb * 64, ti * 64, 0, BAR(B_XF + kb));
                            mbar_expect(BAR(B_XF + kb), 16384);
                        }
                    }
                }
            }
            __syncwarp();
            mbar_wait(BAR(B_XC), 0);
            if (elect_one()) {
                asm volatile("prefetch.tensormap [%0];" :: "l"(&mX) : "memory");
                asm volatile("prefetch.tensormap [%0];" :: "l"(&mWo) : "memory");
                asm volatile("prefetch.tensormap [%0];" :: "l"(&mW1) : "memory");
                asm volatile("prefetch.tensormap [%0];" :: "l"(&mW2) : "memory");
                mbar_expect(BAR(B_AF), (g1_on ? NPRE : 14) * 8192);
                mbar_expect(BAR(B_WQF), 57344);
                #pragma unroll 1
                for (int s = rank; s < 7; s += 2) tma2d_mc(sb + SM_WQ + s * 8192, &mWqkv, wcol, s * 64, BAR(B_WQF));
                mbar_expect(BAR(B_XRF), 16384);
                tma2d(sb + SM_XR, &mX, a2p * kD + a2j * 112, ti * 64, BAR(B_XRF));
                tma2d(sb + SM_XR + 8192, &mX, a2p * kD + a2j * 112 + 48, ti * 64, BAR(B_XRF));
            }
            __syncwarp();
            #pragma unroll 1
            for (int q = 0; q < 4; q++) {
                mbar_wait(BAR(B_KV3 + (q >> 1)), 0);
                if (q == WOQ) mbar_wait2(BAR(B_HL), 0, BAR(B_HL + 1), 0);
                if (elect_one()) {
                    if (!(q & 1)) mbar_expect(BAR(B_WOF + (q >> 1)), 57344);
                    tma2d_mc(sb + SM_WKV + q * 28672 + rank * 14336, &mWo, a2j * 112 + (q & 1) * 48, (q >> 1) * 224 + rank * 112, BAR(B_WOF + (q >> 1)));
                    if (g1_on && q == AFIRST) { load_slab(0, false); load_slab(1, false); load_slab(2, false); }
                }
                __syncwarp();
            }
            if (g1_on) {
                mbar_wait2(BAR(B_XD), 0, BAR(B_OL + 3), 0);
                #pragma unroll 1
                for (int i = 3; i < NPRE; i++) {
                    if (i == 7) mbar_wait(BAR(B_OC), 0);
                    if (elect_one()) load_slab(i, false);
                    __syncwarp();
                }
            } else {
                mbar_arrive_if(BAR((lane < 16 ? B_BE : B_BF) + (lane & 3)), lane < 20);
                mbar_wait(BAR(B_HD), 0);
                mbar_arrive_remote_if(pbar0 + 8u * B_PD, lane == 0);
                mbar_wait(BAR(B_GO), 0);
                uint32_t tg = lds1(sb + SM_TG + 4);
                tg += max((int)(lds1(sb + SM_TG2) - tg), 0);
                int it = 0;
                while ((int)(gtime32() - tg) < 0 && ++it < 256) {}
                const uint32_t t0 = clk32();
                if (lane < 2) {
                    asm volatile("st.shared.u32 [%0], %1;" :: "r"(sb + SM_TG + 8 + lane * 4), "r"(t0 + (lane ? CN3 : CN2)) : "memory");
                    mbar_arrive(BAR(B_GD + lane));
                }
                __syncwarp();
                #pragma unroll 1
                for (int s = 1; s < 15; s++) {
                    sleep_until(t0 + W2OFF + s * W2PACE);
                    if (elect_one()) { if (s < 15 - PFW) bulk_prefetch(pw2 + (s - 1) * 64 * 4096, 4096); load_slab(s, true); }
                    __syncwarp();
                }
            }
          } else {
            TRW(58);
            const uint32_t tag = lds1(sb + SM_EPOCH);
            if (lane < 4) mbar_expect(BAR(B_OL + lane), 14336);
            const uint32_t gbase = lds1(sb + SM_TG);
            const bool lead = elect_one();
            mbar_wait(BAR(B_A1D), 0);
            #pragma unroll 1
            for (int e = 0; e < 2; e++) {
                const uint32_t* fp0 = e ? &prm.sc->flag_h[(rank * 64 + lane) * FS] : &prm.sc->flag_o[(ti * 8 + (lane & 3) * 2) * FS];
                const uint32_t* fp1 = fp0 + (e ? 32 * FS : FS);
                if (e) {
                    int t0 = 0;
                    #pragma unroll 1
                    for (int i = 0; i < 4; i++) { mbar_wait(BAR(B_OF + i), 0); t0 = max(t0, (int)(gtime32() - gbase) - i * CHUNKNS); }
                    if (lead) st_flag(&prm.sc->flag_h[(a2s * 4 + a2j) * FS], tag, gbase + t0);
                    __syncwarp();
                    TRW(57);
                    sleep_until(clk32() + PDELAY);
                }
                uint64_t v0 = 0, v1 = 0;
                int it = 0;
                do {
                    ld_flag_if(v0, fp0, (uint32_t)v0 != tag); ld_flag_if(v1, fp1, (uint32_t)v1 != tag);
                    if (++it > kSpinLimit) { TIMEOUT(108); break; }
                } while (__any_sync(~0u, (uint32_t)v0 != tag || (uint32_t)v1 != tag));
                const int d = max((int)((uint32_t)(v0 >> 32) - gbase), (int)((uint32_t)(v1 >> 32) - gbase)), dmax = __reduce_max_sync(~0u, d);
                TRW(e ? 40 : 53);
                if (e) {
                    if (lead) {
                        const uint32_t tg = gbase + dmax + DELTA;
                        asm volatile("st.async.shared::cluster.mbarrier::complete_tx::bytes.b32 [%0], %1, [%2];"
                                     :: "r"(pbar0 + (SM_TG2 - SM_BAR)), "r"(tg), "r"(pbar0 + 8u * B_GO) : "memory");
                        asm volatile("st.shared.u32 [%0], %1;" :: "r"(sb + SM_TG + 4), "r"(tg) : "memory");
                        mbar_expect(BAR(B_GO), 4);
                    }
                } else {
                    int key = max(d + DELTAO, dmax + DMIN) * 4 + (lane & 3);
                    uint32_t order = 0;
                    #pragma unroll 1
                    for (int i = 0; i < 4; i++) {
                        const int m = __reduce_min_sync(~0u, key);
                        const uint4* src = &prm.sc->o[(a2s * 4 + (m & 3)) * 896];
                        it = 0;
                        while ((int)(gtime32() - gbase) < m >> 2 && ++it < 256) {}
                        if (lead) bulk_g2s(sb + SM_WQ + i * 14336, src, 14336, BAR(B_OL + i));
                        if (key == m) key = 0x7fffffff;
                        order |= (m & 3) << i * 2;
                    }
                    if (lead) {
                        asm volatile("st.shared.u32 [%0], %1;" :: "r"(sb + SM_ORD), "r"(order) : "memory");
                        mbar_arrive(BAR(B_OD));
                    }
                }
                __syncwarp();
            }
          }
          if (elect_one()) {
              const int h = ~warp & 1;
              constexpr uint32_t T = 57344, BO = 2 * 14336;
              const char* src1 = (const char*)&prm.sc->hn[(rank * 16 + h) * 3584 + g1j * 896];
              const char* src2 = (const char*)&prm.sc->g[(rank * 14 + h) * 3584 + g2j * 896];
              uint64_t masks = g1_on ? (h ? kSegMasks1 : kSegMasks0) : 0x80 | 0x80 << 10;
              const uint32_t bl = BAR(B_BL + h * NB);
              uint32_t s8 = (g1_on ? NB - 2 + h : 4 + h) * 8, lap = 3, tmin = 0;
              uint32_t pfm = g1_on && !h ? 0x3fffu >> PFW << (PF2R + 1) : 0;
              const CUtensorMap* am = &mW1;
              uint32_t ad = sb + (NPRE + h) * 8192, astep = 16384; int ac0 = h * kF + g1f * 64, ac1 = (rank * 8 + NPRE / 2) * 64;
              CAP_DECL(ti_, 0);
              #pragma unroll 1
              for (int seg = g1_on ? 0 : 3; seg < 5; seg++) {
                  const char* src = (seg < 3 ? src1 : src2) + (~seg & 1) * BO;
                  uint32_t m = (uint32_t)masks & 0x3ff;
                  masks >>= 10;
                  const uint32_t pace = seg == 4 ? PACEB : seg == 3 ? PACEA : PACE2;
                  if (seg == 2) {
                      mbar_wait(BAR(B_PL), 0);
                      mbar_arrive_remote_if(pbar0 + 8u * B_PD, h);
                      am = &mW2; ad = sb + 8192; astep = 8192; ac0 = g2s * 64; ac1 = rank * 14 * 64;
                  } else {
                      const int gate = seg - (seg > 2);
                      mbar_wait(BAR(B_HD + gate), 0);
                      tmin = lds1(sb + SM_TG + gate * 4);
                      if (gate < 2) {
                          tmin += max((int)(lds1(gate ? sb + SM_TG2 : sb + SM_TG) - tmin), 0);
                          int it = 0;
                          while ((int)(gtime32() - tmin) < 0 && ++it < 256) {}
                          tmin = clk32();
                      }
                      tmin += h * PACE1;
                  }
                  #pragma unroll 1
                  do {
                      const uint32_t dst = sb + SM_B + s8 * 1792;
                      spin_until(tmin);
                      mbar_wait_fast(BAR(B_BE) + s8 + (lap & 1) * (NB * 8), lap >> 1 & 1);
                      if (seg) {
                          bulk_g2s(dst, src, 14336, bl + s8);
                          mbar_expect(bl + s8, 14336);
                          CAP(ti_);
                      }
                      tmin += pace;
                      src += 2 * T;
                      s8 += 16;
                      if (s8 >= NB * 8) { s8 -= NB * 8; lap++; }
                      if (m & 1) {
                          mbar_expect_more(bl + s8, 8192);
                          tma2d(ad, am, ac0, ac1, bl + s8);
                          ad += astep; ac1 += 64;
                      }
                      if (pfm & 1) { bulk_prefetch(pw2, 4096); pw2 += 64 * 4096; }
                      pfm >>= 1;
                      m >>= 1;
                  } while (m != 1);
                  if (seg == 0) lap = 3;
              }
          }
        } else {
          auto pull_w1 = [&](int s0, int s1, uint32_t pace) {
            const char* p1 = (const char*)prm.w1 + ((b >> 6) * 1024 + (b & 63) * 2) * 3584 + min(lane, 27) * 128;
            const char* p2 = (const char*)prm.w2 + ((b >> 6) * 896 + (b & 63)) * 4096 + lane * 128;
            uint32_t tnext = clk32();
            #pragma unroll 1
            for (int i = s0; i < s1; i++) {
                while ((int)(clk32() - tnext) < 0) __nanosleep(40);
                asm volatile("prefetch.global.L2 [%0];" :: "l"(i < 16 ? p1 + ((i >> 1) * 128 + (i & 1)) * 3584 : p2 + (i - 16) * 64 * 4096));
                tnext += pace;
            }
          };
          if (warp == 10) {
            mbar_wait(BAR(PFBAR), 0);
            if (lane < 27) asm volatile("prefetch.global.L2 [%0];" :: "l"(lane < 25 ? (const char*)prm.wo + min(b * 25 + lane, 3135) * 128
                                                                          : lane == 25 ? (const char*)prm.b1 + (b % 28) * 128 : (const char*)prm.b2 + (b & 31) * 128));
            mbar_wait(BAR(PFBAR2), 0);
            pull_w1(0, PFN, PFPACE);
            mbar_wait(BAR(B_EP), 0);
          }
          const uint32_t tag = lds1(sb + SM_EPOCH);
          const int h = warp & 1;
          const bool lead = elect_one();
          const uint32_t wo = lane * 132, l3 = lane < 16 ? 12288 : 0;
          uint32_t base = sb + SM_WQ, bl = BAR(B_OL), bf = BAR(B_OF), m = 4, rph = 0;
          #pragma unroll 1
          for (int e = 0; e < 2; e++) {
              uint32_t s8 = (e && !g1_on ? 4 + h : h) * 8;
              #pragma unroll 1
              do {
                  const uint32_t dst = base + s8 * 1792;
                  auto stale = [&]() {
                      uint32_t d;
                      asm volatile("{ .reg .b32 x, y, z, u;\n"
                                   "ld.shared.u32 x, [%1]; ld.shared.u32 y, [%1 + 4096]; ld.shared.u32 z, [%1 + 8192]; ld.shared.u32 u, [%2];\n"
                                   "lop3.b32 x, x, y, %3, 0x7e; lop3.b32 z, z, u, %3, 0x7e; lop3.b32 %0, x, z, 1, 0xa8; }"
                                   : "=r"(d) : "r"(dst + wo), "r"(dst + (wo + l3)), "r"(tag) : "memory");
                      return __any_sync(~0u, d);
                  };
                  mbar_wait_fast(bl + s8, m & 1);
                  bool bad = stale();
                  mbar_arrive_if(bf + s8, lead && !bad);
                  if (bad) {
                      const int p = 2 * __clz(m) - 2 + h;
                      RETRY_COUNT(!e ? 1 : p < 32 ? 0 : !g1_on ? 5 : p < 46 ? 2 : 6);
                      const int st = (p > 15) + (p > 31) + (p > 45), s = p - (st < 3 ? 16 * st : 46);
                      mbar_wait(BAR(B_OD), 0);
                      const char* src = (const char*)(!e ? &prm.sc->o[(a2s * 4 + (lds1(sb + SM_ORD) >> (p * 2 & 7) & 3)) * 896] : st < 2 ? &prm.sc->hn[(rank * 16 + s) * 3584 + (g1j + 2 * st) * 896]
                                                                                                      : &prm.sc->g[(rank * 14 + s) * 3584 + (g2j + 2 * st - 4) * 896]);
                      int it = 0;
                      do {
                          if (++it > kSpinLimit) { TIMEOUT(111); break; }
                          const uint32_t* q = (const uint32_t*)(src + wo);
                          if (it > RELOAD1 && __any_sync(~0u, ((ld_rlx(q) ^ tag) | (ld_rlx(q + 1024) ^ tag) | (ld_rlx(q + 2048) ^ tag) | (ld_rlx(q + l3 / 4) ^ tag)) & 1)) continue;
                          if (lead) {
                              mbar_expect(BAR(B_RT + h), 14336);
                              bulk_g2s(dst, src, 14336, BAR(B_RT + h));
                          }
                          __syncwarp();
                          mbar_wait(BAR(B_RT + h), rph);
                          rph ^= 1;
                          bad = stale();
                      } while (bad);
                      mbar_arrive_if(bf + s8, lead);
                  }
                  s8 += 16;
                  if (s8 >= NB * 8) s8 -= NB * 8;
                  m >>= 1;
              } while (m != 1);
              if (PFN < 16 + PFW && !e && !h) pull_w1(PFN, 16 + PFW, PFPACE2);
              base = sb + SM_B; bl = BAR(B_BL + h * NB); bf = BAR(B_BF); m = g1_on ? 0x4fe03f80 : 0x7f80;
          }
        }
    } else {
        asm volatile("setmaxnreg.inc.sync.aligned.u32 232;");
        asm volatile("barrier.cluster.wait.aligned;" ::: "memory");
        const int wg = warp >> 2, w = warp & 3;
        const int g = lane >> 2, t = lane & 3;
        uint32_t tag;
        __nv_bfloat16 bias1a, bias1b;
        {
            const uint64_t dw = make_desc(sb + (hg & 1) * 16, 0, true);
            uint32_t a[28][4];
            float sm[4][4] = {};
            {
                const int r = w * 16 + (lane & 15);
                uint32_t xa[4];
                #pragma unroll
                for (int q = 0; q < 4; q++) xa[q] = opaque(sb + wg * 8192 + r * 128 + (((q * 2 + (lane >> 4)) ^ (r & 7)) << 4));
                const uint32_t one = opaque(0x3F803F80u), one2 = opaque(0x3F803F80u);
                #pragma unroll
                for (int k = 0; k < 28; k++) {
                    if ((k & 3) == 0) mbar_wait(BAR(B_XF + (k >> 2)), 0);
                    uint32_t (&f)[4] = a[k];
                    asm volatile("ldmatrix.sync.aligned.m8n8.x4.shared.b16 {%0,%1,%2,%3}, [%4];"
                                 : "=r"(f[0]), "=r"(f[1]), "=r"(f[2]), "=r"(f[3]) : "r"(xa[k & 3] + (k >> 2) * 16384) : "memory");
                    if (k < 24) mma16816(sm[k & 3], f[0], f[1], f[2], f[3], one, one2);
                }
                pair_arrive(B_XC);
                const bool wok = mbar_test(BAR(B_WKVF), 0);
                #pragma unroll
                for (int k = 24; k < 28; k++) mma16816(sm[k & 3], a[k][0], a[k][1], a[k][2], a[k][3], one, one2);
                if (W0E && !wok) mbar_wait(BAR(B_WKVF), 0);
            }
            const float mean0 = ((sm[0][0] + sm[1][0]) + (sm[2][0] + sm[3][0])) * (1.f / kD);
            const float mean1 = ((sm[0][2] + sm[1][2]) + (sm[2][2] + sm[3][2])) * (1.f / kD);
            const uint32_t mb0 = pack_bf16(mean0, mean0), mb1 = pack_bf16(mean1, mean1);
            TR(1);
            float ak[28], av[28], aq[28];
            float ss0 = 0.f, ss1 = 0.f, ss2 = 0.f, ss3 = 0.f;
            uint32_t p0, p1;
            static_for<0, 7>([&](auto S_) {
                constexpr int s = decltype(S_)::value;
                auto centre = [&](int q) {
                    uint32_t (&f)[4] = a[s * 4 + q];
                    f[0] = sub_bf16x2(f[0], mb0); f[1] = sub_bf16x2(f[1], mb1);
                    f[2] = sub_bf16x2(f[2], mb0); f[3] = sub_bf16x2(f[3], mb1);
                };
                if (s || !W0E) {
                    #pragma unroll
                    for (int q = 0; q < 4; q++) centre(q);
                    mbar_wait(BAR(B_WKVF + s), 0);
                    wg_fence();
                }
                static_for<0, 4>([&](auto Q_) {
                    constexpr int q = decltype(Q_)::value;
                    uint32_t (&f)[4] = a[s * 4 + q];
                    if (s == 0 && W0E) { centre(q); wg_fence(); }
                    wgmma_rs_n56<SM_WKV + s * 16384 + q * 2048, (s | q) != 0>(ak, f[0], f[1], f[2], f[3], dw);
                    wgmma_rs_n56<SM_WKV + s * 16384 + q * 2048 + 8192, (s | q) != 0>(av, f[0], f[1], f[2], f[3], dw);
                });
                wg_commit();
                if (s == 4) { wg_wait<1>(); pair_arrive(B_KV3); }
                if (s < W0F) mbar_wait(BAR(B_WKVF), 0);
                #pragma unroll
                for (int q = 0; q < 8; q++) {
                    const uint32_t u0 = a[s * 4 + q / 2][(q & 1) * 2], u1 = a[s * 4 + q / 2][(q & 1) * 2 + 1];
                    if (q == 0 && (VCH == 1 || (s & 1) || s == 0)) { p0 = sqr_bf16x2(u0); p1 = sqr_bf16x2(u1); }
                    else { p0 = sqa_bf16x2(u0, p0); p1 = sqa_bf16x2(u1, p1); }
                }
                if (VCH == 1 || !(s & 1)) { ss0 += bf_lo(p0); ss2 += bf_hi(p0); ss1 += bf_lo(p1); ss3 += bf_hi(p1); }
            });
            auto q_chunk = [&](auto K0_, auto K1_) {
                wg_fence();
                static_for<decltype(K0_)::value, decltype(K1_)::value>([&](auto K_) {
                    constexpr int k = decltype(K_)::value;
                    wgmma_rs_n56<SM_WQ + k * 2048, k != 0>(aq, a[k][0], a[k][1], a[k][2], a[k][3], dw);
                });
                wg_commit();
            };
            #define QCHUNK(k0, k1) q_chunk(std::integral_constant<int, k0>{}, std::integral_constant<int, k1>{})
            const float dl0 = mean0 - bf_lo(mb0), dl1 = mean1 - bf_lo(mb1);
            const float rs0 = rsq(fmaxf(quad_sum(ss0 + ss2) * (1.f / kD) - dl0 * dl0, 0.f) + kEps);
            const float rs1 = rsq(fmaxf(quad_sum(ss1 + ss3) * (1.f / kD) - dl1 * dl1, 0.f) + kEps);
            float rk[3][2];
            rk[1][0] = __shfl_sync(~0u, rs0, t * 8); rk[1][1] = __shfl_sync(~0u, rs0, t * 8 + 4);
            rk[2][0] = __shfl_sync(~0u, rs1, t * 8); rk[2][1] = __shfl_sync(~0u, rs1, t * 8 + 4);
            const uint32_t stg = sb + SM_STG + wg * 8192 + lane * 16;
            uint4* hp = (w == 3 ? &prm.sc->halo[((ti * 8 + hg) * 2 + wg) * 128] : (uint4*)(smem_raw + SM_STG + wg * 8192 + w * 2048)) + lane;
            mbar_wait2(BAR(B_EP), 0, BAR(B_WQF), 0);
            tag = lds1(sb + SM_EPOCH);
            QCHUNK(0, QC0);
            wg_wait<1>();
            reg_fence(ak); reg_fence(av);
            TR(2);
            uint32_t kf[3][7], vf[3][7];
            #pragma unroll
            for (int c = 0; c < 7; c++) {
                kf[2][c] = pack_bf16(ak[4 * c + 2], ak[4 * c + 3]);
                vf[2][c] = movm(pack_bf16(av[4 * c + 2], av[4 * c + 3]));
            }
            const uint32_t om = ~lane & 1;
            kf[2][0] = set_par(kf[2][0], om, tag); kf[2][4] = set_par(kf[2][4], om, tag);
            vf[2][1] = set_par(vf[2][1], om, tag); vf[2][5] = set_par(vf[2][5], om, tag);
            st_gen4(hp,      kf[2][0], kf[2][1], kf[2][2], kf[2][3]);
            st_gen4(hp + 32, kf[2][4], kf[2][5], kf[2][6], vf[2][0]);
            st_gen4(hp + 64, vf[2][1], vf[2][2], vf[2][3], vf[2][4]);
            st_gen4(hp + 96, vf[2][5], vf[2][6], __float_as_uint(rk[2][0]), __float_as_uint(rk[2][1]));
            pair_arrive(B_KVC);
            QCHUNK(QC0, QC1);
            #pragma unroll
            for (int c = 0; c < 7; c++) {
                kf[1][c] = pack_bf16(ak[4 * c], ak[4 * c + 1]);
                vf[1][c] = movm(pack_bf16(av[4 * c], av[4 * c + 1]));
            }
            QCHUNK(QC1, QC2);
            named_bar(1 + wg, 128);
            uint32_t* op = opaque_ptr((uint32_t*)&prm.sc->o[((ti * 2 + wg) * 56 + hg * 7) * 64] + w * 64 + lane);
            const uint32_t om0 = opaque((lane & 7) == w * 2), om1 = opaque((lane & 7) == w * 2 + 1);
            QCHUNK(QC2, 28);
            #undef QCHUNK
            const bool gt0 = 2 * t > g, gt1 = 2 * t + 1 > g, no_prev = ti == 0 && w == 0;
            const float kf0 = gt0 ? rk[1][0] : rk[2][0], kf1 = gt1 ? rk[1][1] : rk[2][1];
            constexpr float kScale = 0.18898223650461362f * 1.4426950408889634f;
            const float sq0 = rs0 * kScale, sf0 = kf0 * (rs1 * kScale), sf1 = kf1 * (rs1 * kScale);
            const float NEG = -__int_as_float(0x7f800000);
            const float nb0 = gt0 && no_prev ? NEG : 0.f, nb1 = gt1 && no_prev ? NEG : 0.f;
            const uint32_t mk = opaque((gt0 ? 0x0000ffffu : 0u) | (gt1 ? 0xffff0000u : 0u));
            const uint32_t sr = stg + ((w + 3) & 3) * 2048, hbar = BAR(w == 0 ? B_HL + wg : B_EP);
            mbar_wait(BAR(B_EP), 0);
            wg_wait<0>();
            reg_fence(aq);
            warp_arrive(BAR(B_A1D));
            TR(3);
            uint32_t qf[8][2];
            #pragma unroll
            for (int c = 0; c < 7; c++) {
                qf[c + (c > 3)][0] = pack_bf16(aq[4 * c], aq[4 * c + 1]);
                qf[c + (c > 3)][1] = pack_bf16(aq[4 * c + 2], aq[4 * c + 3]);
            }
            qf[4][0] = t >= 2 ? qf[3][0] : 0u; qf[4][1] = t >= 2 ? qf[3][1] : 0u;
            qf[3][0] = t < 2 ? qf[3][0] : 0u;  qf[3][1] = t < 2 ? qf[3][1] : 0u;
            float sc[2][3][4];
            auto scores = [&](int n) {
                #pragma unroll
                for (int hd = 0; hd < 2; hd++) {
                    sc[hd][n][0] = sc[hd][n][1] = sc[hd][n][2] = sc[hd][n][3] = 0.f;
                    mma16816(sc[hd][n], qf[4 * hd][0], qf[4 * hd][1], qf[4 * hd + 1][0], qf[4 * hd + 1][1], kf[n][3 * hd], kf[n][3 * hd + 1]);
                    mma16816(sc[hd][n], qf[4 * hd + 2][0], qf[4 * hd + 2][1], qf[4 * hd + 3][0], qf[4 * hd + 3][1], kf[n][3 * hd + 2], kf[n][3 * hd + 3]);
                }
            };
            scores(1); scores(2);
            mbar_wait(hbar, 0);
            {
                const uint4 u0 = lds4(sr), u1 = lds4(sr + 512), u3 = lds4(sr + 1536), u2 = lds4(sr + 1024);
                kf[0][0] = u0.x; kf[0][1] = u0.y; kf[0][2] = u0.z; kf[0][3] = u0.w;
                kf[0][4] = u1.x; kf[0][5] = u1.y; kf[0][6] = u1.z; vf[0][0] = u1.w;
                vf[0][1] = u2.x; vf[0][2] = u2.y; vf[0][3] = u2.z; vf[0][4] = u2.w;
                vf[0][5] = u3.x; vf[0][6] = u3.y; rk[0][0] = __uint_as_float(u3.z); rk[0][1] = __uint_as_float(u3.w);
            }
            TR(4);
            scores(0);
            const float ke0 = gt0 ? rk[0][0] : rk[1][0], ke1 = gt1 ? rk[0][1] : rk[1][1];
            const float se0 = ke0 * sq0, se1 = ke1 * sq0;
            uint32_t ow[7][2];
            #pragma unroll
            for (int hd = 0; hd < 2; hd++) {
                const int c0 = hd * 3;
                float (&sc_)[3][4] = sc[hd];
                const float e0 = fmaf(gt0 ? sc_[0][0] : sc_[1][0], se0, nb0), e1 = fmaf(gt1 ? sc_[0][1] : sc_[1][1], se1, nb1);
                const float f0 = (gt0 ? sc_[1][2] : sc_[2][2]) * sf0, f1 = (gt1 ? sc_[1][3] : sc_[2][3]) * sf1;
                const float me = quad_max(fmaxf(e0, e1)), mf = quad_max(fmaxf(f0, f1));
                const float p0 = ex2(e0 - me), p1 = ex2(e1 - me), r0 = ex2(f0 - mf), r1 = ex2(f1 - mf);
                const float ie = rcp(quad_sum(p0 + p1)), jf = rcp(quad_sum(r0 + r1));
                const uint32_t pp = pack_bf16(p0 * ke0 * ie, p1 * ke1 * ie), rp = pack_bf16(r0 * kf0 * jf, r1 * kf1 * jf);
                const uint32_t a0 = pp & ~mk, a1 = rp & mk, a3 = rp & ~mk, a4 = pp & mk, zero = opaque(0u), zero2 = opaque(0u);
                #pragma unroll
                for (int c = 0; c < 4; c++) {
                    float o[4] = {0.f, 0.f, 0.f, 0.f};
                    mma16816(o, a0, a1, zero, a3, vf[1][c0 + c], vf[2][c0 + c]);
                    mma1688(o, a4, zero2, vf[0][c0 + c]);
                    const uint32_t lo = pack_bf16(o[0], o[1]), hi = pack_bf16(o[2], o[3]);
                    if (hd == 1 && c == 0) { if (t >= 2) { ow[3][0] = lo; ow[3][1] = hi; } }
                    else { ow[c0 + c][0] = lo; ow[c0 + c][1] = hi; }
                }
            }
            #pragma unroll
            for (int c = 0; c < 7; c++) {
                stg1(op + c * 256,      set_par(ow[c][0], om0, tag));
                stg1(op + c * 256 + 32, set_par(ow[c][1], om1, tag));
            }
            TR(5);
        }
        float as[28], ac[28];
        uint32_t xch, peer_xch, gm[2][4], *gp1, *gp2;
        const uint32_t *hp, *ht;
        const uint2* hq;
        uint64_t da0, db0;
        const int cg2 = (g2j + 2 * wg) * 2 + (rank ^ 1), cg1 = (g1j + 2 * wg) * 2 + (rank ^ (g1f < 14));
        const bool lead = elect_one();
        {
            const int cg = a2j * 2 + wg;
            float acc2[28];
            mbar_wait(BAR(B_XRF), 0);
            {
                const uint32_t xa = sb + SM_XR + wg * 8192 + (w * 16 + (lane & 15)) * 128;
                #pragma unroll
                for (int c = 0; c < 4; c++) {
                    uint32_t xr[4];
                    asm volatile("ldmatrix.sync.aligned.m8n8.x4.shared.b16 {%0,%1,%2,%3}, [%4];"
                                 : "=r"(xr[0]), "=r"(xr[1]), "=r"(xr[2]), "=r"(xr[3])
                                 : "r"(xa + ((((c * 2 + wg + (lane >> 4)) ^ lane) & 7) << 4)) : "memory");
                    #pragma unroll
                    for (int e = 0; e < (c < 3 ? 4 : 2); e++) { acc2[8 * c + 2 * e] = bf_lo(xr[e]); acc2[8 * c + 2 * e + 1] = bf_hi(xr[e]); }
                }
            }
            uint32_t* spw = opaque_ptr(&prm.sc->stats[((a2s * 8 + cg) * 4 + w) * 32 + lane]);
            const uint32_t* spr = opaque_ptr(&prm.sc->stats[(a2s * 32 + w) * 32 + lane]);
            uint32_t* rp = opaque_ptr((uint32_t*)&prm.sc->rows[a2s * 64 + w * 16 + (t >> 1) * 8 + g] + (t & 1));
            const int cgs = cg ^ (a2s >> 4);
            uint32_t* np = opaque_ptr((uint32_t*)&prm.sc->hn[(a2s * 56 + cgs * 7) * 64] + w * 64 + lane);
            const uint64_t dwo = make_desc(sb + SM_WKV + wg * (28672 + 16), 0, true);
            const uint64_t doa = make_desc(sb + SM_WQ, 1024, false, 128);
            bias1a = prm.b1[g1f * 64 + w * 16 + g]; bias1b = prm.b1[g1f * 64 + w * 16 + 8 + g];
            const __nv_bfloat16 bias2 = prm.b2[ti * 128 + (w * 16 + (t >> 1) * 8 + g) * 2 + a2p];
            reg_fence(acc2);
            fence_async_smem();
            warp_arrive(BAR(B_XD));
            {
                xch = opaque(sb + SM_XCH + w * 1792 + lane * 16);
                asm volatile("mapa.shared::cluster.u32 %0, %1, %2;" : "=r"(peer_xch) : "r"(xch), "r"(rank ^ 1));
                const int hcg = cg2 ^ (g2s >> 4), hrg = (g2s & 1) * 4 + w;
                const uint32_t* hl = (const uint32_t*)&prm.sc->hn[((g2s >> 1) * 112 + hcg * 7) * 64 + hrg * 8];
                hp = opaque_ptr(hl + (g & 1) * 14336 + (g >> 1) * 4 + t);
                ht = opaque_ptr(hl + (lane & 1) * 14336 + min(lane >> 1, 6) * 256 + ((min(lane >> 1, 6) - (hcg & 1)) & 3) * 8 + hrg);
                hq = opaque_ptr(&prm.sc->rows[((g2s >> 1) * 2 + (g & 1)) * 64 + hrg * 8 + (g >> 1)]);
                gp1 = opaque_ptr((uint32_t*)&prm.sc->g[(g1f * 56 + cg1 * 7) * 64] + w * 64 + lane);
                gp2 = opaque_ptr((uint32_t*)(prm.out + (size_t)(g2s * 64 + w * 16 + lane / 7) * kD + cg2 * 56) + (lane % 7) * 4);
                da0 = make_desc(sb, 0, true); db0 = make_desc(sb + SM_B, 128, false);
            }
            mbar_wait2(BAR(B_WOF), 0, BAR(B_WOF + 1), 0);
            mbar_wait(BAR(B_OD), 0);
            const uint32_t order = __shfl_sync(~0u, lds1(sb + SM_ORD), 0);
            static_for<0, 4>([&](auto P_) {
                constexpr int P = decltype(P_)::value;
                const uint64_t dwp = dwo + ((order >> (2 * P + 1) & 1) * 3584 + (order >> 2 * P & 1) * 896);
                mbar_wait(BAR(B_OF + P), 0);
                if (P == 0) TR(6);
                wg_fence();
                static_for<0, 7>([&](auto K_) { constexpr int k = decltype(K_)::value;
                    wgmma_ss_n56<P * 14336 + k * 2048, k * 2048, 0>(acc2, doa, dwp); });
                if (P) wg_commit();
                if (P == 2) { wg_wait<1>(); warp_arrive(BAR(B_OC)); }
            });
            wg_wait<0>();
            reg_fence(acc2);
            TR(7);
            float s0 = 0.f, s1 = 0.f, q0 = 0.f, q1 = 0.f;
            #pragma unroll
            for (int c = 0; c < 7; c++) {
                s0 += acc2[4 * c] + acc2[4 * c + 1];     q0 = fmaf(acc2[4 * c], acc2[4 * c], fmaf(acc2[4 * c + 1], acc2[4 * c + 1], q0));
                s1 += acc2[4 * c + 2] + acc2[4 * c + 3]; q1 = fmaf(acc2[4 * c + 2], acc2[4 * c + 2], fmaf(acc2[4 * c + 3], acc2[4 * c + 3], q1));
            }
            const bool th = t >= 2, to = t & 1;
            const float sa = (th ? s1 : s0) + __shfl_xor_sync(~0u, th ? s0 : s1, 2), qa = (th ? q1 : q0) + __shfl_xor_sync(~0u, th ? q0 : q1, 2);
            const float part = (to ? qa : sa) + __shfl_xor_sync(~0u, to ? sa : qa, 1);
            stg1(spw, set_par(__float_as_uint(part), 1u, tag));
            const uint32_t tpoll = clk32() + SDELAY;
            TR(8);
            warp_arrive(BAR(B_HD));
            uint32_t nm[2][4], us[8];
            spin_until(tpoll);
            #pragma unroll
            for (int i = 0; i < 8; i++) us[i] = ld_rlx(spr + i * 128);
            #pragma unroll
            for (int i = 0; i < 8; i++) {
                nm[i >> 2][i & 3] = lane == ((i - (cgs & 1)) & 3) * 8 + w * 2 + (i >> 2);
                gm[i >> 2][i & 3] = opaque(lane == ((i - (cg1 & 1)) & 3) * 8 + w * 2 + (i >> 2));
            }
            #pragma unroll
            for (int c = 0; c < 28; c++) { ac[c] = 0.5f * __bfloat162float(c & 2 ? bias1b : bias1a); as[c] = 0.f; }
            reg_fence(as); reg_fence(ac);
            {
                int it = 0;
                while (true) {
                    uint32_t bad = 0;
                    #pragma unroll
                    for (int i = 0; i < 8; i++) bad |= us[i] ^ tag;
                    if (!__any_sync(~0u, bad & 1)) break;
                    RETRY_COUNT(3);
                    if (++it > kSpinLimit) { TIMEOUT(103); break; }
                    #pragma unroll
                    for (int i = 0; i < 8; i++) us[i] = ld_rlx(spr + i * 128);
                }
            }
            TR(9);
            const float tot = (((__uint_as_float(us[0]) + __uint_as_float(us[1])) + (__uint_as_float(us[2]) + __uint_as_float(us[3])))
                            + ((__uint_as_float(us[4]) + __uint_as_float(us[5])) + (__uint_as_float(us[6]) + __uint_as_float(us[7])))) * (1.f / kD);
            const float oth = __shfl_xor_sync(~0u, tot, 1);
            const float mean = to ? oth : tot;
            const float var = fmaxf(fmaf(-mean, mean, to ? tot : oth), 0.f);
            const float rra = rsq(fmaf(var, 4.f + 4.f * kEps, 4.f * kEps * kEps)), mra = -mean * rra;
            const float rrb = __shfl_xor_sync(~0u, rra, 2), mrb = __shfl_xor_sync(~0u, mra, 2);
            const float rr0 = th ? rrb : rra, mr0 = th ? mrb : mra, rr1 = th ? rra : rrb, mr1 = th ? mra : mrb;
            #pragma unroll
            for (int c = 0; c < 7; c++) {
                stg1(np + c * 256,      set_par(pack_bf16(fmaf(acc2[4 * c], rr0, mr0), fmaf(acc2[4 * c + 1], rr0, mr0)), nm[0][c & 3], tag));
                stg1(np + c * 256 + 32, set_par(pack_bf16(fmaf(acc2[4 * c + 2], rr1, mr1), fmaf(acc2[4 * c + 3], rr1, mr1)), nm[1][c & 3], tag));
            }
            TR(10);
            if (cg == 0) stg1(rp, set_par(__float_as_uint(to ? mean + __bfloat162float(bias2) : rcp(rra)), 1u, tag));
        }
        auto send = [&]() {
            const uint32_t rf = pbar0 + (B_RF + warp) * 8;
            #pragma unroll
            for (int c = 0; c < 4; c++) {
                const uint32_t p0 = pack_bf16(as[8 * c], as[8 * c + 1]), p1 = pack_bf16(as[8 * c + 2], as[8 * c + 3]);
                if (c < 3) {
                    const uint32_t p2 = pack_bf16(as[8 * c + 4], as[8 * c + 5]), p3 = pack_bf16(as[8 * c + 6], as[8 * c + 7]);
                    asm volatile("st.async.shared::cluster.mbarrier::complete_tx::bytes.v4.b32 [%0], {%1,%2,%3,%4}, [%5];"
                                 :: "r"(peer_xch + c * 512), "r"(p0), "r"(p1), "r"(p2), "r"(p3), "r"(rf) : "memory");
                } else {
                    asm volatile("st.async.shared::cluster.mbarrier::complete_tx::bytes.v2.b32 [%0], {%1,%2}, [%3];"
                                 :: "r"(peer_xch + 1536 - lane * 8), "r"(p0), "r"(p1), "r"(rf) : "memory");
                }
            }
        };
        auto receive = [&](uint32_t (&pk)[14], uint32_t phase) {
            mbar_wait(BAR(B_RF + warp), phase);
            #pragma unroll
            for (int c = 0; c < 3; c++) { const uint4 u = lds4(xch + c * 512); pk[4 * c] = u.x; pk[4 * c + 1] = u.y; pk[4 * c + 2] = u.z; pk[4 * c + 3] = u.w; }
            const uint2 u = lds2(xch + 1536 - lane * 8); pk[12] = u.x; pk[13] = u.y;
        };
        uint2 rw[2]; uint32_t tw;
        auto load_rows = [&]() { tw = ld_rlx(ht); rw[0] = ld_rlx2(hq); rw[1] = ld_rlx2(hq + 4); };
        rw[0] = rw[1] = make_uint2(0u, 0u); tw = ~tag;
        #pragma unroll 1
        for (int ge = 0;; ge++) {
          if (ge || g1_on) {
            const int use = ge * 2 + wg;
            int entry = ge ? 1 : 2 * wg, stop = 0;
            uint64_t da = da0 + (ge ? -3 : wg ? NR - 10 : 0) * 512;
            bool rel = lead && use == 1;
            const uint32_t xfree = BAR(use > (g1_on ? 0 : 2) ? B_RE + use - 1 : B_PD);
            mbar_wait(BAR(B_AF), 0);
            if (ge && (wg || g1_on)) named_bar(5 - wg, 256);
            TR(11 + ge * 4);
            auto step = [&](auto I_) {
                constexpr int i = decltype(I_)::value, sl = i % NB, ao = i * 8192, bo = sl * 14336;
                mbar_wait_fast(BAR(B_BF + sl), i / NB);
                wg_fence();
                wgmma_ss_n112<ao,        bo,       1>(as, ac, da, db0);
                wgmma_ss_n112<ao + 2048, bo + 256, 1>(as, ac, da, db0);
                wgmma_ss_n112<ao + 4096, bo + 512, 1>(as, ac, da, db0);
                wgmma_ss_n112<ao + 6144, bo + 768, 1>(as, ac, da, db0);
                wg_commit();
                if (i == 1 && stop == 1) named_arrive(4, 256);
                if (i == 3 && (use == 1 || use == 2)) named_arrive(4 + wg, 256);
                wg_wait<1>();
                mbar_arrive_if(BAR(B_BE + (13 + i) % 14), rel);
                rel = lead;
            };
            #pragma unroll 1
            while (true) {
                if (entry < 1) {
                    static_for<0, 2>(step);
                    if (stop == 1) break;
                    static_for<2, 4>(step);
                    if (stop) break;
                }
                if (entry < 2) static_for<4, 10>(step);
                else {
                    uint32_t af[NR * 4][4];
                    mbar_wait(BAR(B_GO), 0);
                    const uint32_t tp = lds1(sb + SM_TG + 4) + PLOFF;
                    int it = 0;
                    while ((int)(gtime32() - tp) < 0 && ++it < 256) __nanosleep(20);
                    const uint32_t la = sb + ((lane >> 4) * 8 + (lane & 7)) * 128 + (((w * 2 + ((lane >> 3) & 1)) ^ (lane & 7)) << 4);
                    #pragma unroll
                    for (int k = 0; k < NR * 4; k++)
                        asm volatile("ldmatrix.sync.aligned.m8n8.x4.trans.shared.b16 {%0,%1,%2,%3}, [%4];"
                                     : "=r"(af[k][0]), "=r"(af[k][1]), "=r"(af[k][2]), "=r"(af[k][3]) : "r"(la + k * 2048) : "memory");
                    __syncwarp();
                    mbar_arrive_if(BAR(B_PL), lead);
                    named_bar(4, 256);
                    static_for<0, NR>([&](auto I_) {
                        constexpr int i = decltype(I_)::value, sl = (16 + i) % NB, o = sl * 14336;
                        mbar_wait_fast(BAR(B_BF + sl), (16 + i) / NB & 1);
                        wg_fence();
                        wgmma_rs_n112<o,       1>(as, ac, af[4 * i][0], af[4 * i][1], af[4 * i][2], af[4 * i][3], db0);
                        wgmma_rs_n112<o + 256, 1>(as, ac, af[4 * i + 1][0], af[4 * i + 1][1], af[4 * i + 1][2], af[4 * i + 1][3], db0);
                        wgmma_rs_n112<o + 512, 1>(as, ac, af[4 * i + 2][0], af[4 * i + 2][1], af[4 * i + 2][2], af[4 * i + 2][3], db0);
                        wgmma_rs_n112<o + 768, 1>(as, ac, af[4 * i + 3][0], af[4 * i + 3][1], af[4 * i + 3][2], af[4 * i + 3][3], db0);
                        wg_commit();
                        if (i) { wg_wait<1>(); mbar_arrive_if(BAR(B_BE + (15 + i) % (2 * NB)), lead); }
                    });
                }
                static_for<10, 14>(step);
                entry = 0; stop = use + 1; da += 14 * 512;
            }
            const uint32_t prev = BAR(B_BE + (use ? 3 : 1));
            const bool xok = mbar_test(xfree, 0);
            wg_wait<0>();
            reg_fence(as); reg_fence(ac);
            mbar_arrive_if(prev, lead);
            if (!xok) mbar_wait(xfree, 0);
            if (ge) break;
            send();
            load_rows();
            TR(12);
            uint32_t pk[14];
            receive(pk, 0);
            TR(13);
            #pragma unroll
            for (int c = 0; c < 14; c++) {
                float r[2];
                #pragma unroll
                for (int e = 0; e < 2; e++) {
                    const float u = ac[2 * c + e] + (e ? bf_hi(pk[c]) : bf_lo(pk[c]));
                    r[e] = fmaf(u, tanh_hw(u * fmaf(u * u, 8.f * 0.7978845608f * 0.044715f, 2.f * 0.7978845608f)), u);
                }
                stg1(gp1 + (c >> 1) * 256 + (c & 1) * 32, set_par(pack_bf16(r[0], r[1]), gm[c & 1][(c >> 1) & 3], tag));
            }
            named_bar(1 + wg, 128);
            if (w == 0 && lane == 0) {
                asm volatile("st.shared.u32 [%0], %1;" :: "r"(sb + SM_TG + 8 + wg * 4), "r"(clk32() + (wg ? XSPECB : XSPEC)) : "memory");
                mbar_arrive(BAR(B_GD + wg));
            }
            if (lead) mbar_expect(BAR(B_RF + warp), 1792);
            mbar_arrive_remote_if(pbar0 + (B_RE + wg) * 8, lead);
            TR(14);
          } else mbar_wait(BAR(B_GD), 0);
            {
                int it = 0;
                while (__any_sync(~0u, ((tw ^ tag) | (rw[0].x ^ tag) | (rw[0].y ^ tag) | (rw[1].x ^ tag) | (rw[1].y ^ tag)) & 1)) {
                    if (++it > kSpinLimit) { TIMEOUT(110); break; }
                    load_rows();
                }
                uint32_t hw[14];
                #pragma unroll
                for (int c = 0; c < 14; c++) hw[c] = ld_rlx(hp + (c >> 1) * 256 + (c & 1) * 16);
                #pragma unroll
                for (int c = 0; c < 14; c++) {
                    ac[2 * c]     = fmaf(bf_lo(hw[c]), __uint_as_float(rw[c & 1].x), __uint_as_float(rw[c & 1].y));
                    ac[2 * c + 1] = fmaf(bf_hi(hw[c]), __uint_as_float(rw[c & 1].x), __uint_as_float(rw[c & 1].y));
                    as[2 * c] = as[2 * c + 1] = 0.f;
                }
                reg_fence(as); reg_fence(ac);
            }
        }
        uint32_t po[14], pk[14];
        if (!wg) sleep_until(clk32() + w * STAG2);
        send();
        #pragma unroll
        for (int c = 0; c < 14; c++) po[c] = opaque(pack_bf16(ac[2 * c], ac[2 * c + 1]));
        TR(16);
        receive(pk, g1_on);
        TR(17);
        #pragma unroll
        for (int c = 0; c < 14; c++) pk[c] = add_bf16x2(po[c], pk[c]);
        __syncwarp();
        const uint32_t sa = xch - lane * 16 + (lane & 15) * 112 + (lane >> 4) * 16;
        #pragma unroll
        for (int m = 0; m < 3; m++)
            asm volatile("stmatrix.sync.aligned.m8n8.x4.shared.b16 [%0], {%1,%2,%3,%4};"
                         :: "r"(sa + m * 32), "r"(pk[4 * m]), "r"(pk[4 * m + 1]), "r"(pk[4 * m + 2]), "r"(pk[4 * m + 3]) : "memory");
        asm volatile("stmatrix.sync.aligned.m8n8.x2.shared.b16 [%0], {%1,%2};" :: "r"(sa + 96), "r"(pk[12]), "r"(pk[13]) : "memory");
        __syncwarp();
        if (lane < 28) {
            #pragma unroll
            for (int i = 0; i < 4; i++) { const uint4 u = lds4(xch + i * 448); stg4(gp2 + i * 896, u.x, u.y, u.z, u.w); }
        }
        __syncwarp();
        mbar_arrive_remote_if(pbar0 + (B_RE + 2) * 8, lead && wg == 0);
        TR(18);
        if (tid == 128) TRG(62);
        if (b == 0 && tid == 128) prm.sc->epoch = tag;
    }
}

typedef CUresult (*EncodeFn)(CUtensorMap*, CUtensorMapDataType, cuuint32_t, void*, const cuuint64_t*, const cuuint64_t*,
                             const cuuint32_t*, const cuuint32_t*, CUtensorMapInterleave, CUtensorMapSwizzle,
                             CUtensorMapL2promotion, CUtensorMapFloatOOBfill);

void make_map(EncodeFn enc, CUtensorMap* m, const void* base, uint64_t cols, uint64_t rows, uint32_t box_rows) {
    cuuint64_t dims[2] = {cols, rows};
    cuuint64_t strides[1] = {cols * 2};
    cuuint32_t box[2] = {64, box_rows};
    cuuint32_t es[2] = {1, 1};
    enc(m, CU_TENSOR_MAP_DATA_TYPE_BFLOAT16, 2, const_cast<void*>(base), dims, strides, box, es, CU_TENSOR_MAP_INTERLEAVE_NONE,
        CU_TENSOR_MAP_SWIZZLE_128B, CU_TENSOR_MAP_L2_PROMOTION_L2_128B, CU_TENSOR_MAP_FLOAT_OOB_FILL_NONE);
}

}

extern "C" void kernel_launch(void* const* d_in, const int* in_sizes, int n_in, void* d_out, int out_size) {
    (void)in_sizes; (void)n_in; (void)out_size;
    void* fn = nullptr;
    cudaDriverEntryPointQueryResult qr;
    cudaGetDriverEntryPoint("cuTensorMapEncodeTiled", &fn, cudaEnableDefault, &qr);
    EncodeFn enc = (EncodeFn)fn;
    CUtensorMap mX2, mX, mWqkv, mWo, mW1, mW2;
    {
        cuuint64_t dims[3] = {kD, kS / 2, 2}, strides[2] = {4 * kD, 2 * kD};
        cuuint32_t box[3] = {64, 64, 2}, es[3] = {1, 1, 1};
        enc(&mX2, CU_TENSOR_MAP_DATA_TYPE_BFLOAT16, 3, d_in[0], dims, strides, box, es, CU_TENSOR_MAP_INTERLEAVE_NONE,
            CU_TENSOR_MAP_SWIZZLE_128B, CU_TENSOR_MAP_L2_PROMOTION_L2_128B, CU_TENSOR_MAP_FLOAT_OOB_FILL_NONE);
    }
    make_map(enc, &mX, d_in[0], 2 * kD, kS / 2, 64);
    make_map(enc, &mWqkv, d_in[1], 3 * kD, kD, 64);
    make_map(enc, &mWo, d_in[2], kD, kD, 112);
    make_map(enc, &mW1, d_in[4], 2 * kF, kS / 2, 64);
    make_map(enc, &mW2, d_in[6], kS, kF, 64);
    Params prm;
    prm.x = (const __nv_bfloat16*)d_in[0];
    prm.wqkv = (const __nv_bfloat16*)d_in[1];
    prm.wo = (const __nv_bfloat16*)d_in[2];
    prm.w1 = (const __nv_bfloat16*)d_in[4];
    prm.b1 = (const __nv_bfloat16*)d_in[5];
    prm.w2 = (const __nv_bfloat16*)d_in[6];
    prm.b2 = (const __nv_bfloat16*)d_in[7];
    prm.out = (__nv_bfloat16*)d_out;
    cudaGetSymbolAddress((void**)&prm.sc, g_scratch);
    cudaFuncSetAttribute(fused_kernel, cudaFuncAttributeMaxDynamicSharedMemorySize, SM_TOTAL);
    fused_kernel<<<128, 384, SM_TOTAL, cudaStreamPerThread>>>(prm, mX2, mX, mWqkv, mWo, mW1, mW2);
}
```

```cpp
#include <cuda_runtime.h>
#include <cuda.h>
#include <cuda_bf16.h>
#include <stdint.h>
#include <type_traits>

namespace {

constexpr int kS = 2048, kD = 448, kF = 1792;
constexpr float kEps = 1e-5f;

#define FS 32
struct Scratch {
    uint4    o[32 * 56 * 64];
    uint4    hn[32 * 56 * 64];
    uint4    g[28 * 56 * 64];
    uint4    halo[16 * 8 * 2 * 4 * 32];
    uint32_t stats[32 * 8 * 4 * 32];
    uint2    rows[32 * 64];
    uint32_t flag_o[16 * 8 * FS];
    uint32_t flag_h[32 * 4 * FS];
    uint32_t epoch;
};
__device__ __align__(1024) Scratch g_scratch;
#define TIMEOUT(code)
#define RETRY_COUNT(i)
#define CAP_DECL(n, k)
#define CAP(n)
#define CAP_SKIP(n)
#define K5(i)
#define EV(i, dep)
#define TR2(idx)
#define TR(idx)
#define TRW(idx)
#define TRG(idx)

constexpr uint32_t SM_WKV  = 114688;
constexpr uint32_t SM_XR   = 24576;
constexpr uint32_t SM_STG  = 40960;
constexpr uint32_t SM_WQ   = 57344;
constexpr uint32_t SM_XCH  = 0;
constexpr uint32_t SM_B    = 131072;
constexpr uint32_t SM_BAR  = 231424;
constexpr uint32_t SM_TOTAL = SM_BAR + 1024;
constexpr int NB = 7;
#define SH1 0
#define SH2 0
#define SH2N 5
#define SH3 0
#define NSPEC 4
#define XSPEC 500
#define C2 0
#define C3 0
#define CN2 7200
#define CN3 10900
constexpr int B_XF = 0, B_WKVF = 7, B_WQF = 14, B_XRF = 15, B_WOF = 16,
              B_XC = 18, B_KV3 = 19, B_KVC = 20,
              B_A1D = 21, B_XD = 22, B_OC = 23,
              B_BE = 24  , B_RE = B_BE + 2 * NB,
              B_PL = B_RE + 3, B_AF = B_PL + 1, B_BL = B_AF + 1  , B_OL = B_BL + 2 * NB  ,
              B_BF = B_OL + 4  , B_OF = B_BF + NB, B_RF = B_OF + 4, B_EP = B_RF + 8, B_PD = B_EP + 1, B_OD = B_PD + 1, B_RT = B_OD + 1, B_HL = B_RT + 2,
              B_HD = B_HL + 2  , B_GO = B_HD + 1, B_GD = B_GO + 1, B_COUNT = B_GD + 2;
#define WEARLY 6
#define PF0 126
#define TMPF 2
#define RSTE 2
#define POLLP 1
#define PROBEP 1
#define LOADP 1
#define LOADW 64
#define NOB 0
#define AEARLY 5
#define W1PACE 400
#define W2PACE 350
#define PFPACE 280
#define PFBAR (B_XF + 6)
#define DELTA 2080
#define DELTA2 DELTA
#define BPACE 230
#define BURST 2
#define W1OFF 350
#define W2OFF 800
#define XPACE 0
#define PSTAG 200
constexpr uint32_t SM_EPOCH = SM_BAR + B_COUNT * 8, SM_TG = SM_EPOCH + 4  , SM_TG2 = SM_TG + 16  , SM_ORD = SM_TG2 + 4  , SM_TR = SM_BAR + 768;

#define HDELAY 100
#define QC0 4
#define QC1 10
#define QC2 16
#define HPOS 1
#define XSPECB 750
#define PACE1 120
#define PACE2 400
#define RELOAD1 1
#define VCH 1
#define SOFF 0
#define XW 1
#define XLAG 0
#define PFX 3
#define PFD 250
#define SDELAY 200
#define PDELAY 400
#define NPRE 10
#define PREPACE 0
#define AFIRST 1
#define DELTAO 864
#define NS 0
#define GCH 14
#define OCH 14
#define ICH 14
#define PACKO
#define NR 8
#define HMODE 2
#define HOFF0 (-100)
#define HOFF1 900
#define STAG1 0
#define STAG2 400
#define PLOFF (-250)
#define HSRC h
#define WO1 1
#define WOD 250
#define WOP 400
#define WOP0 0
#define KV5 1
#define XLATE 0
#define W0E 1
#define W0F 2
#define PACEA 400
#define PACEB 300
#define PFN 16
#define PFPACE2 300
#define PF2R 1
#define PFW 4
#define PFBAR2 PFBAR
#define WOQ 3
#define DMIN 608
#define CHUNKNS 250
#define QCA QC0
#define QF 0
#define PF3OFF 300
#define PF3PACE 240
#define NPD 400
#define ANN 4
#define W1Q 3
#define APOS1 ((1ull << 4) | (1ull << 8) | (1ull << 12) | (1ull << 5) | (1ull << 9) | (1ull << 13))
#define APOS2 (0x5555555ull << 17)
constexpr uint32_t seg_mask(int h, int p0, int p1) {
    uint32_t m = 0; int n = 0;
    for (int p = p0; p < p1; p++) if ((p & 1) == h) m |= (uint32_t)(((APOS1 | APOS2) >> p) & 1) << n++;
    return m | 1u << n;
}
constexpr uint64_t seg_masks(int h) {
    return 2 | (uint64_t)seg_mask(h, 0, 16) << 10 | (uint64_t)seg_mask(h, 16, 32) << 20
             | (uint64_t)seg_mask(h, 32, 46) << 30 | (uint64_t)seg_mask(h, 46, 60) << 40;
}
constexpr uint64_t kSegMasks0 = seg_masks(0), kSegMasks1 = seg_masks(1);

constexpr int kSpinLimit = 1 << 15;
__device__ __forceinline__ bool elect_one() {
    uint32_t p;
    asm volatile("{ .reg .pred P; elect.sync _|P, 0xffffffff; selp.u32 %0, 1, 0, P; }" : "=r"(p));
    return p;
}
__device__ __forceinline__ void mbar_init(uint32_t bar, uint32_t cnt) { asm volatile("mbarrier.init.shared::cta.b64 [%0], %1;" :: "r"(bar), "r"(cnt)); }
__device__ __forceinline__ void mbar_expect(uint32_t bar, uint32_t bytes) { asm volatile("mbarrier.arrive.expect_tx.shared::cta.b64 _, [%0], %1;" :: "r"(bar), "r"(bytes) : "memory"); }
__device__ __forceinline__ void mbar_expect_more(uint32_t bar, uint32_t bytes) { asm volatile("mbarrier.expect_tx.relaxed.cta.shared::cta.b64 [%0], %1;" :: "r"(bar), "r"(bytes) : "memory"); }
__device__ __forceinline__ void mbar_arrive(uint32_t bar) { asm volatile("mbarrier.arrive.shared::cta.b64 _, [%0];" :: "r"(bar) : "memory"); }
__device__ __forceinline__ void mbar_wait(uint32_t bar, uint32_t parity) {
    uint32_t ok; int it = 0;
    do {
        asm volatile("{ .reg .pred p; mbarrier.try_wait.parity.shared::cta.b64 p, [%1], %2; selp.u32 %0, 1, 0, p; }"
                     : "=r"(ok) : "r"(bar), "r"(parity) : "memory");
        if (++it > kSpinLimit) { TIMEOUT((bar & 1023) >> 3); break; }
    } while (!ok);
}
__device__ __forceinline__ bool mbar_try(uint32_t bar, uint32_t parity) {
    uint32_t ok;
    asm volatile("{ .reg .pred p; mbarrier.try_wait.parity.shared::cta.b64 p, [%1], %2; selp.u32 %0, 1, 0, p; }" : "=r"(ok) : "r"(bar), "r"(parity) : "memory");
    return ok;
}
__device__ __forceinline__ bool mbar_test(uint32_t bar, uint32_t parity) {
    uint32_t ok;
    asm volatile("{ .reg .pred p; mbarrier.test_wait.parity.shared::cta.b64 p, [%1], %2; selp.u32 %0, 1, 0, p; }" : "=r"(ok) : "r"(bar), "r"(parity) : "memory");
    return ok;
}
__device__ __forceinline__ void mbar_wait_fast(uint32_t bar, uint32_t parity) { if (!mbar_try(bar, parity)) mbar_wait(bar, parity); }
__device__ __forceinline__ void mbar_wait2(uint32_t bar0, uint32_t par0, uint32_t bar1, uint32_t par1) {
    uint32_t ok; int it = 0;
    do {
        asm volatile("{ .reg .pred p, q; mbarrier.try_wait.parity.shared::cta.b64 p, [%1], %2;\n"
                     "mbarrier.try_wait.parity.shared::cta.b64 q, [%3], %4; and.pred p, p, q; selp.u32 %0, 1, 0, p; }"
                     : "=r"(ok) : "r"(bar0), "r"(par0), "r"(bar1), "r"(par1) : "memory");
        if (++it > kSpinLimit) { TIMEOUT((bar0 & 1023) >> 3); break; }
    } while (!ok);
}
__device__ __forceinline__ void sched_fence(uint32_t v) {
    asm volatile("{ .reg .pred p; .reg .b32 x; mov.b32 x, %0;\nL: setp.eq.u32 p, x, 0xffffffff; @p mov.u32 x, %%clock; @p bra L; }" :: "r"(v) : "memory");
}
template <int N> __device__ __forceinline__ void reg_fence(float (&d)[N]) {
    #pragma unroll
    for (int i = 0; i < N; i++) asm volatile("" : "+f"(d[i]) :: "memory");
}
__device__ __forceinline__ void mbar_wait_cluster(uint32_t bar, uint32_t parity) {
    uint32_t ok; int it = 0;
    do {
        asm volatile("{ .reg .pred p; mbarrier.try_wait.parity.acquire.cluster.shared::cta.b64 p, [%1], %2; selp.u32 %0, 1, 0, p; }"
                     : "=r"(ok) : "r"(bar), "r"(parity) : "memory");
        if (++it > kSpinLimit) { TIMEOUT((bar & 1023) >> 3); break; }
    } while (!ok);
}
__device__ __forceinline__ void mbar_arrive_if(uint32_t bar, bool pred) {
    asm volatile("{ .reg .pred p; setp.ne.u32 p, %1, 0; @p mbarrier.arrive.shared::cta.b64 _, [%0]; }" :: "r"(bar), "r"((uint32_t)pred) : "memory");
}
template <int P> __device__ __forceinline__ void tick() {
    if (P > 1) { const uint32_t t = ((uint32_t)clock() | (P - 1)) + 1; while ((int)((uint32_t)clock() - t) < 0) {} }
}
__device__ __forceinline__ void warp_arrive(uint32_t bar) { __syncwarp(); if (elect_one()) mbar_arrive(bar); }
__device__ __forceinline__ void tma2d(uint32_t dst, const CUtensorMap* m, int c0, int c1, uint32_t bar) {
    asm volatile("cp.async.bulk.tensor.2d.shared::cluster.global.mbarrier::complete_tx::bytes [%0], [%1, {%3, %4}], [%2];"
                 :: "r"(dst), "l"(m), "r"(bar), "r"(c0), "r"(c1) : "memory");
}
__device__ __forceinline__ void tma3d(uint32_t dst, const CUtensorMap* m, int c0, int c1, int c2, uint32_t bar) {
    asm volatile("cp.async.bulk.tensor.3d.shared::cluster.global.mbarrier::complete_tx::bytes [%0], [%1, {%3, %4, %5}], [%2];"
                 :: "r"(dst), "l"(m), "r"(bar), "r"(c0), "r"(c1), "r"(c2) : "memory");
}
__device__ __forceinline__ void tma2d_mc(uint32_t dst, const CUtensorMap* m, int c0, int c1, uint32_t bar) {
    asm volatile("cp.async.bulk.tensor.2d.shared::cluster.global.mbarrier::complete_tx::bytes.multicast::cluster [%0], [%1, {%3, %4}], [%2], %5;"
                 :: "r"(dst), "l"(m), "r"(bar), "r"(c0), "r"(c1), "h"((uint16_t)3) : "memory");
}
__device__ __forceinline__ void bulk_g2s_mc(uint32_t dst, const void* src, uint32_t bytes, uint32_t bar) {
    asm volatile("cp.async.bulk.shared::cluster.global.mbarrier::complete_tx::bytes.multicast::cluster [%0], [%1], %2, [%3], %4;"
                 :: "r"(dst), "l"(src), "r"(bytes), "r"(bar), "h"((uint16_t)3) : "memory");
}
__device__ __forceinline__ void mbar_arrive_remote_if(uint32_t cluster_bar, bool pred) {
    asm volatile("{ .reg .pred p; setp.ne.u32 p, %1, 0; @p mbarrier.arrive.shared::cluster.b64 _, [%0]; }" :: "r"(cluster_bar), "r"((uint32_t)pred) : "memory");
}
__device__ __forceinline__ void bulk_g2s(uint32_t dst, const void* src, uint32_t bytes, uint32_t bar) {
    asm volatile("cp.async.bulk.shared::cluster.global.mbarrier::complete_tx::bytes [%0], [%1], %2, [%3];"
                 :: "r"(dst), "l"(src), "r"(bytes), "r"(bar) : "memory");
}
__device__ __forceinline__ void bulk_prefetch(const void* src, uint32_t bytes) { asm volatile("cp.async.bulk.prefetch.L2.global [%0], %1;" :: "l"(src), "r"(bytes) : "memory"); }
__device__ __forceinline__ void wg_fence()  { asm volatile("wgmma.fence.sync.aligned;" ::: "memory"); }
__device__ __forceinline__ void wg_commit() { asm volatile("wgmma.commit_group.sync.aligned;" ::: "memory"); }
template <int N> __device__ __forceinline__ void wg_wait() { asm volatile("wgmma.wait_group.sync.aligned %0;" :: "n"(N) : "memory"); }
__device__ __forceinline__ void named_bar(int id, int n) { asm volatile("bar.sync %0, %1;" :: "r"(id), "r"(n) : "memory"); }
__device__ __forceinline__ void named_arrive(int id, int n) { asm volatile("bar.arrive %0, %1;" :: "r"(id), "r"(n) : "memory"); }
__device__ __forceinline__ bool mbar_try2(uint32_t bar0, uint32_t par0, uint32_t bar1, uint32_t par1) {
    uint32_t ok;
    asm volatile("{ .reg .pred p, q; mbarrier.test_wait.parity.shared::cta.b64 p, [%1], %2;\n"
                 "mbarrier.test_wait.parity.shared::cta.b64 q, [%3], %4; and.pred p, p, q; selp.u32 %0, 1, 0, p; }"
                 : "=r"(ok) : "r"(bar0), "r"(par0), "r"(bar1), "r"(par1) : "memory");
    return ok;
}
__device__ __forceinline__ void fence_gpu() { asm volatile("fence.release.gpu;" ::: "memory"); }
__device__ __forceinline__ void fence_async_global() { asm volatile("fence.proxy.async.global;" ::: "memory"); }
__device__ __forceinline__ void fence_async_smem() { asm volatile("fence.proxy.async.shared::cta;" ::: "memory"); }
__device__ __forceinline__ uint32_t gtime32() { uint64_t t; asm volatile("mov.u64 %0, %%globaltimer;" : "=l"(t) :: "memory"); return (uint32_t)t; }
__device__ __forceinline__ uint32_t clk32() { uint64_t t; asm volatile("mov.u64 %0, %%clock64;" : "=l"(t) :: "memory"); return (uint32_t)t; }
__device__ __forceinline__ void spin_until(uint32_t t) { while ((int)(clk32() - t) < 0) {} }
#define SLEEPNS 20
__device__ __forceinline__ void sleep_until(uint32_t t) { while ((int)(clk32() - t) < 0) { if (SLEEPNS) __nanosleep(SLEEPNS); } }
__device__ __forceinline__ void st_flag(uint32_t* p, uint32_t v, uint32_t time) {
    const uint64_t w = ((uint64_t)time << 32) | v;
    asm volatile("st.relaxed.gpu.global.u64 [%0], %1;" :: "l"(p), "l"(w) : "memory");
}
__device__ __forceinline__ void ld_flag_if(uint64_t& v, const uint32_t* p, bool pred) {
    asm volatile("{ .reg .pred p; setp.ne.u32 p, %2, 0; @p ld.relaxed.gpu.global.u64 %0, [%1]; }" : "+l"(v) : "l"(p), "r"((uint32_t)pred) : "memory");
}
__device__ __forceinline__ uint32_t ld_acq(const uint32_t* p) { uint32_t v; asm volatile("ld.acquire.gpu.global.u32 %0, [%1];" : "=r"(v) : "l"(p) : "memory"); return v; }
__device__ __forceinline__ uint32_t ld_rlx(const uint32_t* p) { uint32_t v; asm volatile("ld.relaxed.gpu.global.u32 %0, [%1];" : "=r"(v) : "l"(p) : "memory"); return v; }
template <class T> __device__ __forceinline__ T* opaque_ptr(T* p) { asm volatile("" : "+l"(p)); return p; }
__device__ __forceinline__ uint4 ld_rlx4(const uint4* p) {
    uint4 v; asm volatile("ld.relaxed.gpu.global.v4.u32 {%0,%1,%2,%3}, [%4];" : "=r"(v.x), "=r"(v.y), "=r"(v.z), "=r"(v.w) : "l"(p) : "memory"); return v;
}
__device__ __forceinline__ void st_ll(uint4* p, uint32_t a, uint32_t b, uint32_t tag) {
    uint64_t lo = ((uint64_t)tag << 32) | a, hi = ((uint64_t)tag << 32) | b;
    asm volatile("st.relaxed.gpu.global.v2.u64 [%0], {%1,%2};" :: "l"(p), "l"(lo), "l"(hi) : "memory");
}
__device__ __forceinline__ bool ld_ll(const uint4* p, uint32_t& a, uint32_t& b, uint32_t tag) {
    uint64_t lo, hi;
    asm volatile("ld.relaxed.gpu.global.v2.u64 {%0,%1}, [%2];" : "=l"(lo), "=l"(hi) : "l"(p) : "memory");
    a = (uint32_t)lo; b = (uint32_t)hi;
    return (uint32_t)(lo >> 32) == tag && (uint32_t)(hi >> 32) == tag;
}
__device__ __forceinline__ uint2 ld_acq2(const uint2* p) {
    uint2 v; asm volatile("ld.acquire.gpu.global.v2.u32 {%0,%1}, [%2];" : "=r"(v.x), "=r"(v.y) : "l"(p) : "memory"); return v;
}
__device__ __forceinline__ uint2 ld_rlx2(const uint2* p) {
    uint2 v; asm volatile("ld.relaxed.gpu.global.v2.u32 {%0,%1}, [%2];" : "=r"(v.x), "=r"(v.y) : "l"(p) : "memory"); return v;
}
__device__ __forceinline__ void stg1(uint32_t* p, uint32_t v) { asm volatile("st.global.u32 [%0], %1;" :: "l"(p), "r"(v) : "memory"); }
__device__ __forceinline__ void stg2(void* p, uint32_t x, uint32_t y) { asm volatile("st.global.v2.u32 [%0], {%1,%2};" :: "l"(p), "r"(x), "r"(y) : "memory"); }
__device__ __forceinline__ void stg4(void* p, uint32_t x, uint32_t y, uint32_t z, uint32_t w) { asm volatile("st.global.v4.u32 [%0], {%1,%2,%3,%4};" :: "l"(p), "r"(x), "r"(y), "r"(z), "r"(w) : "memory"); }
__device__ __forceinline__ uint32_t lds1(uint32_t a) { uint32_t v; asm volatile("ld.shared.u32 %0, [%1];" : "=r"(v) : "r"(a) : "memory"); return v; }
__device__ __forceinline__ uint2 lds2(uint32_t a) { uint2 v; asm volatile("ld.shared.v2.u32 {%0,%1}, [%2];" : "=r"(v.x), "=r"(v.y) : "r"(a) : "memory"); return v; }
__device__ __forceinline__ uint32_t set_par(uint32_t v, uint32_t mask, uint32_t par) {
    uint32_t r; asm("lop3.b32 %0, %1, %2, %3, 0xb8;" : "=r"(r) : "r"(v), "r"(mask), "r"(par)); return r;
}
__device__ __forceinline__ void st_gen4(void* p, uint32_t x, uint32_t y, uint32_t z, uint32_t w) { asm volatile("st.v4.u32 [%0], {%1,%2,%3,%4};" :: "l"(p), "r"(x), "r"(y), "r"(z), "r"(w) : "memory"); }
__device__ __forceinline__ float tanh_hw(float x) { float r; asm("tanh.approx.f32 %0, %1;" : "=f"(r) : "f"(x)); return r; }
__device__ __forceinline__ bool bar_any(int id, int n, bool v) {
    uint32_t r;
    asm volatile("{ .reg .pred p, q; setp.ne.u32 p, %3, 0; bar.red.or.pred q, %1, %2, p; selp.u32 %0, 1, 0, q; }" : "=r"(r) : "r"(id), "r"(n), "r"((uint32_t)v) : "memory");
    return r;
}
__device__ __forceinline__ void sts4(uint32_t a, uint32_t x, uint32_t y, uint32_t z, uint32_t w) { asm volatile("st.shared.v4.u32 [%0], {%1,%2,%3,%4};" :: "r"(a), "r"(x), "r"(y), "r"(z), "r"(w) : "memory"); }
__device__ __forceinline__ uint4 lds4(uint32_t a) { uint4 v; asm volatile("ld.shared.v4.u32 {%0,%1,%2,%3}, [%4];" : "=r"(v.x), "=r"(v.y), "=r"(v.z), "=r"(v.w) : "r"(a) : "memory"); return v; }
__device__ __forceinline__ uint32_t pack_bf16(float lo, float hi) { uint32_t r; asm("cvt.rn.bf16x2.f32 %0, %1, %2;" : "=r"(r) : "f"(hi), "f"(lo)); return r; }
__device__ __forceinline__ float bf_lo(uint32_t v) { return __uint_as_float(v << 16); }
__device__ __forceinline__ float bf_hi(uint32_t v) { return __uint_as_float(v & 0xffff0000u); }
__device__ __forceinline__ uint32_t sub_bf16x2(uint32_t a, uint32_t b) { uint32_t r; asm volatile("sub.rn.bf16x2 %0, %1, %2;" : "=r"(r) : "r"(a), "r"(b)); return r; }
__device__ __forceinline__ uint32_t add_bf16x2(uint32_t a, uint32_t b) { uint32_t r; asm volatile("add.rn.bf16x2 %0, %1, %2;" : "=r"(r) : "r"(a), "r"(b)); return r; }
__device__ __forceinline__ uint32_t sqr_bf16x2(uint32_t a) { uint32_t r; asm volatile("mul.rn.bf16x2 %0, %1, %1;" : "=r"(r) : "r"(a)); return r; }
__device__ __forceinline__ uint32_t sqa_bf16x2(uint32_t a, uint32_t c) { uint32_t r; asm volatile("fma.rn.bf16x2 %0, %1, %1, %2;" : "=r"(r) : "r"(a), "r"(c)); return r; }
__device__ __forceinline__ uint32_t movm(uint32_t a) { uint32_t r; asm volatile("movmatrix.sync.aligned.m8n8.trans.b16 %0, %1;" : "=r"(r) : "r"(a)); return r; }
__device__ __forceinline__ float ex2(float x) { float r; asm("ex2.approx.ftz.f32 %0, %1;" : "=f"(r) : "f"(x)); return r; }
__device__ __forceinline__ float rsq(float x) { float r; asm("rsqrt.approx.ftz.f32 %0, %1;" : "=f"(r) : "f"(x)); return r; }
__device__ __forceinline__ float rcp(float x) { float r; asm("rcp.approx.ftz.f32 %0, %1;" : "=f"(r) : "f"(x)); return r; }
__device__ __forceinline__ void mma16816(float (&c)[4], uint32_t a0, uint32_t a1, uint32_t a2, uint32_t a3, uint32_t b0, uint32_t b1) {
    asm("mma.sync.aligned.m16n8k16.row.col.f32.bf16.bf16.f32 {%0,%1,%2,%3}, {%4,%5,%6,%7}, {%8,%9}, {%0,%1,%2,%3};"
        : "+f"(c[0]), "+f"(c[1]), "+f"(c[2]), "+f"(c[3]) : "r"(a0), "r"(a1), "r"(a2), "r"(a3), "r"(b0), "r"(b1));
}
__device__ __forceinline__ void mma1688(float (&c)[4], uint32_t a0, uint32_t a1, uint32_t b0) {
    asm("mma.sync.aligned.m16n8k8.row.col.f32.bf16.bf16.f32 {%0,%1,%2,%3}, {%4,%5}, {%6}, {%0,%1,%2,%3};"
        : "+f"(c[0]), "+f"(c[1]), "+f"(c[2]), "+f"(c[3]) : "r"(a0), "r"(a1), "r"(b0));
}
__device__ __forceinline__ float quad_sum(float v) { v += __shfl_xor_sync(~0u, v, 1); v += __shfl_xor_sync(~0u, v, 2); return v; }
__device__ __forceinline__ float quad_max(float v) { v = fmaxf(v, __shfl_xor_sync(~0u, v, 1)); v = fmaxf(v, __shfl_xor_sync(~0u, v, 2)); return v; }
__device__ __forceinline__ uint64_t make_desc(uint32_t addr, uint32_t lbo, bool swz, uint32_t sbo = 1024) {
    const uint32_t lo = __shfl_sync(~0u, ((addr & 0x3FFFF) >> 4) | ((lbo >> 4) << 16), 0);
    const uint32_t hi = __shfl_sync(~0u, (swz ? 0x40000000u : 0u) + (sbo >> 4) + (threadIdx.x & 31), 0);
    return ((uint64_t)hi << 32) | lo;
}
template <int I, int N, class F> __device__ __forceinline__ void static_for(F&& f) {
    if constexpr (I < N) { f(std::integral_constant<int, I>{}); static_for<I + 1, N>(f); }
}
__device__ __forceinline__ uint32_t opaque(uint32_t v) { asm volatile("" : "+r"(v)); return v; }
template <int BOFF, int SCALE_D>
__device__ __forceinline__ void wgmma_rs_n56(float (&d)[28], uint32_t a0, uint32_t a1, uint32_t a2, uint32_t a3, uint64_t db) {
    asm volatile("{ .reg .b64 db; add.s64 db, %32, %33;\n"
        "wgmma.mma_async.sync.aligned.m64n56k16.f32.bf16.bf16 "
        "{%0, %1, %2, %3, %4, %5, %6, %7, %8, %9, %10, %11, %12, %13, %14, %15, %16, %17, %18, %19, %20, %21, %22, %23, %24, %25, %26, %27}, "
        "{%28, %29, %30, %31}, db, %34, 1, 1, 1; }"
        : "+f"(d[0]), "+f"(d[1]), "+f"(d[2]), "+f"(d[3]), "+f"(d[4]), "+f"(d[5]), "+f"(d[6]), "+f"(d[7]),
        "+f"(d[8]), "+f"(d[9]), "+f"(d[10]), "+f"(d[11]), "+f"(d[12]), "+f"(d[13]), "+f"(d[14]), "+f"(d[15]),
        "+f"(d[16]), "+f"(d[17]), "+f"(d[18]), "+f"(d[19]), "+f"(d[20]), "+f"(d[21]), "+f"(d[22]), "+f"(d[23]),
        "+f"(d[24]), "+f"(d[25]), "+f"(d[26]), "+f"(d[27])
        : "r"(a0), "r"(a1), "r"(a2), "r"(a3), "l"(db), "n"(BOFF >> 4), "n"(SCALE_D));
}
template <int AOFF, int BOFF, int MMAJOR>
__device__ __forceinline__ void wgmma_ss_n56(float (&d)[28], uint64_t da, uint64_t db) {
    asm volatile("{ .reg .b64 da, db; add.s64 da, %28, %30; add.s64 db, %29, %31;\n"
        "wgmma.mma_async.sync.aligned.m64n56k16.f32.bf16.bf16 "
        "{%0, %1, %2, %3, %4, %5, %6, %7, %8, %9, %10, %11, %12, %13, %14, %15, %16, %17, %18, %19, %20, %21, %22, %23, %24, %25, %26, %27}, "
        "da, db, 1, 1, 1, %32, 1; }"
        : "+f"(d[0]), "+f"(d[1]), "+f"(d[2]), "+f"(d[3]), "+f"(d[4]), "+f"(d[5]), "+f"(d[6]), "+f"(d[7]),
        "+f"(d[8]), "+f"(d[9]), "+f"(d[10]), "+f"(d[11]), "+f"(d[12]), "+f"(d[13]), "+f"(d[14]), "+f"(d[15]),
        "+f"(d[16]), "+f"(d[17]), "+f"(d[18]), "+f"(d[19]), "+f"(d[20]), "+f"(d[21]), "+f"(d[22]), "+f"(d[23]),
        "+f"(d[24]), "+f"(d[25]), "+f"(d[26]), "+f"(d[27])
        : "l"(da), "l"(db), "n"(AOFF >> 4), "n"(BOFF >> 4), "n"(MMAJOR));
}
template <int AOFF, int BOFF, int MMAJOR>
__device__ __forceinline__ void wgmma_ss_n112(float (&d)[28], float (&e)[28], uint64_t da, uint64_t db) {
    asm volatile("{ .reg .b64 da, db; add.s64 da, %56, %58; add.s64 db, %57, %59;\n"
        "wgmma.mma_async.sync.aligned.m64n112k16.f32.bf16.bf16 "
        "{%0, %1, %2, %3, %4, %5, %6, %7, %8, %9, %10, %11, %12, %13, %14, %15, %16, %17, %18, %19, %20, %21, %22, %23, %24, %25, %26, %27, %28, %29, %30, %31, %32, %33, %34, %35, %36, %37, %38, %39, %40, %41, %42, %43, %44, %45, %46, %47, %48, %49, %50, %51, %52, %53, %54, %55}, "
        "da, db, 1, 1, 1, %60, 1; }"
        : "+f"(d[0]), "+f"(d[1]), "+f"(d[2]), "+f"(d[3]), "+f"(d[4]), "+f"(d[5]), "+f"(d[6]), "+f"(d[7]),
        "+f"(d[8]), "+f"(d[9]), "+f"(d[10]), "+f"(d[11]), "+f"(d[12]), "+f"(d[13]), "+f"(d[14]), "+f"(d[15]),
        "+f"(d[16]), "+f"(d[17]), "+f"(d[18]), "+f"(d[19]), "+f"(d[20]), "+f"(d[21]), "+f"(d[22]), "+f"(d[23]),
        "+f"(d[24]), "+f"(d[25]), "+f"(d[26]), "+f"(d[27]), "+f"(e[0]), "+f"(e[1]), "+f"(e[2]), "+f"(e[3]),
        "+f"(e[4]), "+f"(e[5]), "+f"(e[6]), "+f"(e[7]), "+f"(e[8]), "+f"(e[9]), "+f"(e[10]), "+f"(e[11]),
        "+f"(e[12]), "+f"(e[13]), "+f"(e[14]), "+f"(e[15]), "+f"(e[16]), "+f"(e[17]), "+f"(e[18]), "+f"(e[19]),
        "+f"(e[20]), "+f"(e[21]), "+f"(e[22]), "+f"(e[23]), "+f"(e[24]), "+f"(e[25]), "+f"(e[26]), "+f"(e[27])
        : "l"(da), "l"(db), "n"(AOFF >> 4), "n"(BOFF >> 4), "n"(MMAJOR));
}
template <int BOFF, int SCALE_D>
__device__ __forceinline__ void wgmma_rs_n112(float (&d)[28], float (&e)[28], uint32_t a0, uint32_t a1, uint32_t a2, uint32_t a3, uint64_t db) {
    asm volatile("{ .reg .b64 db; add.s64 db, %60, %61;\n"
        "wgmma.mma_async.sync.aligned.m64n112k16.f32.bf16.bf16 "
        "{%0, %1, %2, %3, %4, %5, %6, %7, %8, %9, %10, %11, %12, %13, %14, %15, %16, %17, %18, %19, %20, %21, %22, %23, %24, %25, %26, %27, %28, %29, %30, %31, %32, %33, %34, %35, %36, %37, %38, %39, %40, %41, %42, %43, %44, %45, %46, %47, %48, %49, %50, %51, %52, %53, %54, %55}, "
        "{%56, %57, %58, %59}, db, %62, 1, 1, 1; }"
        : "+f"(d[0]), "+f"(d[1]), "+f"(d[2]), "+f"(d[3]), "+f"(d[4]), "+f"(d[5]), "+f"(d[6]), "+f"(d[7]),
        "+f"(d[8]), "+f"(d[9]), "+f"(d[10]), "+f"(d[11]), "+f"(d[12]), "+f"(d[13]), "+f"(d[14]), "+f"(d[15]),
        "+f"(d[16]), "+f"(d[17]), "+f"(d[18]), "+f"(d[19]), "+f"(d[20]), "+f"(d[21]), "+f"(d[22]), "+f"(d[23]),
        "+f"(d[24]), "+f"(d[25]), "+f"(d[26]), "+f"(d[27]), "+f"(e[0]), "+f"(e[1]), "+f"(e[2]), "+f"(e[3]),
        "+f"(e[4]), "+f"(e[5]), "+f"(e[6]), "+f"(e[7]), "+f"(e[8]), "+f"(e[9]), "+f"(e[10]), "+f"(e[11]),
        "+f"(e[12]), "+f"(e[13]), "+f"(e[14]), "+f"(e[15]), "+f"(e[16]), "+f"(e[17]), "+f"(e[18]), "+f"(e[19]),
        "+f"(e[20]), "+f"(e[21]), "+f"(e[22]), "+f"(e[23]), "+f"(e[24]), "+f"(e[25]), "+f"(e[26]), "+f"(e[27])
        : "r"(a0), "r"(a1), "r"(a2), "r"(a3), "l"(db), "n"(BOFF >> 4), "n"(SCALE_D));
}

struct Params {
    const __nv_bfloat16 *x, *wqkv;
    Scratch* sc;
    const __nv_bfloat16 *wo, *w1, *w2, *b1, *b2;
    __nv_bfloat16* out;
};

__global__ void __cluster_dims__(2, 1, 1) __launch_bounds__(384, 1)
fused_kernel(const Params prm, const __grid_constant__ CUtensorMap mX2, const __grid_constant__ CUtensorMap mX, const __grid_constant__ CUtensorMap mWqkv,
             const __grid_constant__ CUtensorMap mWo, const __grid_constant__ CUtensorMap mW1,
             const __grid_constant__ CUtensorMap mW2)
{
    extern __shared__ __align__(1024) unsigned char smem_raw[];
    if (threadIdx.x < 126) {
        const uint32_t i = threadIdx.x, t = clk32() + (i >> 5) * PFD;
        const char* px = (const char*)prm.x + (blockIdx.x * 16 + (i & 15)) * 896 + (i >> 4) * 128;
        const char* pw = (const char*)prm.wqkv + blockIdx.x * 2688 + i * 128 + (896 - 112 * 128);
        spin_until(t);
        asm volatile("prefetch.global.L2 [%0];" :: "l"(i < 112 ? px : pw) : "memory");
    }
    if (threadIdx.x == 128) { asm volatile("prefetch.tensormap [%0];" :: "l"(&mX2) : "memory"); asm volatile("prefetch.tensormap [%0];" :: "l"(&mWqkv) : "memory"); }
    uint32_t sb = (uint32_t)__cvta_generic_to_shared(smem_raw);
    asm volatile("mov.u32 %0, %0;" : "+r"(sb));
    const uint32_t bar0 = sb + SM_BAR;
    auto BAR = [&](int i) { return bar0 + 8u * i; };

    const int tid = threadIdx.x, lane = tid & 31;
    const int warp = __shfl_sync(~0u, tid >> 5, 0);
    const int b = __shfl_sync(~0u, (int)blockIdx.x, 0);
    const int rank = b & 1;
    const int cl = (b >> 1) - 4, cq = ((cl - 32) * 37) >> 8;
    const int res = cl < 0 ? 0 : cl < 32 ? cl & 7 : cl - 31 - 7 * cq;
    const int rnd = cl < 0 ? cl + 8 : cl < 32 ? cl >> 3 : 4 + cq;
    const int hg = (res & 1) * 4 + (rnd & 3);
    const int ti = (res >> 1) * 4 + (rnd >> 2) * 2 + rank;
    const int a2p = res & 1, a2j = rnd & 3;
    const int a2s = ti * 2 + a2p;
    const bool g1_on = rnd != 7;
    const int g1j = (rnd < 6 ? rnd : res) & 1, g1f = rnd < 6 ? res * 3 + (rnd >> 1) : 24 + (res >> 1);
    const int g2j = rnd & 1, g2s = res * 4 + (rnd >> 1);
    uint32_t pbar0;
    asm volatile("mapa.shared::cluster.u32 %0, %1, %2;" : "=r"(pbar0) : "r"(bar0), "r"(rank ^ 1));
    auto pair_arrive = [&](int i) { __syncwarp(); const bool l = elect_one(); mbar_arrive_if(BAR(i), l); mbar_arrive_remote_if(pbar0 + 8u * i, l); };
    const int wcol = hg * 56 - (hg & 1) * 8;

    if (warp == 8) {
        if (elect_one()) {
            #pragma unroll
            for (int i = 0; i < B_WQF; i++) mbar_init(BAR(i), 1);
            asm volatile("fence.mbarrier_init.release.cluster;" ::: "memory");
            fence_async_smem();
            #pragma unroll
            for (int kb = 0; kb < 7 - XLATE; kb++) {
                tma3d(sb + kb * 16384, &mX2, kb * 64, ti * 64, 0, BAR(B_XF + kb));
                mbar_expect(BAR(B_XF + kb), 16384);
                if (kb == 0 && PFX != 3) asm volatile("prefetch.tensormap [%0];" :: "l"(&mWqkv) : "memory");
            }
        }
    } else if (warp > 8) {
        if (elect_one()) {
            if (warp == 9) {
                #pragma unroll
                for (int i = B_WQF; i < B_AF; i++) mbar_init(BAR(i), i < B_XC ? 1 : i < B_A1D ? 16 : i < B_BE ? 8 : 4);
            } else if (warp == 10) {
                #pragma unroll
                for (int i = B_AF; i < B_BF; i++) mbar_init(BAR(i), 1);
            } else {
                #pragma unroll
                for (int i = B_BF; i < B_COUNT; i++) mbar_init(BAR(i), i == B_HD ? 8 : 1);
            }
            asm volatile("fence.mbarrier_init.release.cluster;" ::: "memory");
            fence_async_smem();
        }
    }
    __syncwarp();
    __syncthreads();
    asm volatile("barrier.cluster.arrive.relaxed.aligned;" ::: "memory");
    if (tid < 256) TR(0);
    if (tid == 0) TRG(61);

    if (warp >= 8) {
        asm volatile("setmaxnreg.dec.sync.aligned.u32 40;");
        asm volatile("barrier.cluster.wait.aligned;" ::: "memory");
        auto fetch_halo = [&](int p, uint32_t tag) {
            uint4 u[4];
            #pragma unroll
            for (int c = 0; c < 4; c++) u[c] = make_uint4(0u, 0u, 0u, 0u);
            const uint4* hp = opaque_ptr(&prm.sc->halo[(((ti - 1) * 8 + hg) * 2 + p) * 128 + lane]);
            mbar_wait(BAR(B_KVC), 0);
            if (p == 0) TRW(51);
            sleep_until(clk32() + HDELAY);
            if (ti > 0) {
                int it = 0;
                do {
                    #pragma unroll
                    for (int c = 0; c < 4; c++) u[c] = ld_rlx4(hp + c * 32);
                    if (it) RETRY_COUNT(4);
                    if (++it > kSpinLimit) { TIMEOUT(101); break; }
                } while (__any_sync(~0u, ((u[0].x ^ tag) | (u[1].x ^ tag) | (u[2].x ^ tag) | (u[3].x ^ tag)) & ~lane & 1));
            }
            #pragma unroll
            for (int c = 0; c < 4; c++) sts4(sb + SM_STG + p * 8192 + 3 * 2048 + lane * 16 + c * 512, u[c].x, u[c].y, u[c].z, u[c].w);
            warp_arrive(BAR(B_HL + p));
        };
        auto poll_flags = [&](const uint32_t* fp, int step, uint32_t tag, uint32_t gbase) {
            uint64_t v0 = 0, v1 = 0;
            int it = 0;
            do {
                ld_flag_if(v0, fp, (uint32_t)v0 != tag); ld_flag_if(v1, fp + step, (uint32_t)v1 != tag);
                if (++it > kSpinLimit) { TIMEOUT(108); break; }
            } while (__any_sync(~0u, (uint32_t)v0 != tag || (uint32_t)v1 != tag));
            return max((int)((uint32_t)(v0 >> 32) - gbase), (int)((uint32_t)(v1 >> 32) - gbase));
        };
        if (warp & 1) {
            uint32_t tag;
            if (warp == 11) {
                tag = *(volatile uint32_t*)&prm.sc->epoch + 1;
            #pragma unroll 1
            for (int i = 0; i < 8; i++) prm.sc->halo[(ti * 8 + hg) * 256 + i * 32 + lane] = make_uint4(~tag, 0u, 0u, 0u);
            ((uint4*)prm.sc->stats)[(a2s * 4 + a2j) * 64 + lane] = ((uint4*)prm.sc->stats)[(a2s * 4 + a2j) * 64 + 32 + lane] = make_uint4(~tag, ~tag, ~tag, ~tag);
            prm.sc->flag_h[(a2s * 4 + a2j) * FS + lane] = 0;
            prm.sc->flag_o[(ti * 8 + hg) * FS + lane] = 0;
            __syncwarp();
            if (lane == 0) {
                asm volatile("st.shared.v2.u32 [%0], {%1, %2};" :: "r"(sb + SM_EPOCH), "r"(tag), "r"(gtime32()) : "memory");
                mbar_arrive(BAR(B_EP));
            }
            if (lane < 8) mbar_expect(BAR(B_RF + lane), 1792);
            __syncwarp();
            TRW(44);
            } else {
                mbar_wait(BAR(B_EP), 0);
                tag = lds1(sb + SM_EPOCH);
            }
            uint32_t* ofl = opaque_ptr(&prm.sc->flag_o[(ti * 8 + hg) * FS]);
            fetch_halo((warp >> 1) & 1, tag);
            if (warp == 11) {
                mbar_wait2(BAR(B_A1D), 0, BAR(B_HL), 0);
                if (lane == 0) st_flag(ofl, tag, gtime32());
                __syncwarp();
            }
        }
        if (warp < 10) {
          auto load_slab = [&](int s, bool second) {
              if (!second) tma2d(sb + s * 8192, &mW1, (s & 1) * kF + g1f * 64, (rank * 8 + (s >> 1)) * 64, BAR(B_AF));
              else         tma2d(sb + s * 8192, &mW2, g2s * 64, (rank * 14 + s - 1) * 64, BAR(B_AF));
          };
          const char* pw2 = (const char*)prm.w2 + ((b >> 6) * 896 + (b & 63) + PFW * 64) * 4096;
          if (warp == 8) {
            if (elect_one()) {
                #pragma unroll 1
                for (int s = 0; s < 7; s++) {
                    mbar_expect(BAR(B_WKVF + s), 16384);
                    tma2d_mc(sb + SM_WKV + s * 16384 + rank * 8192, &mWqkv, (1 + rank) * kD + wcol, s * 64, BAR(B_WKVF + s));
                    if (s == 0) {
                        #pragma unroll
                        for (int kb = 7 - XLATE; kb < 7; kb++) {
                            tma3d(sb + kb * 16384, &mX2, kb * 64, ti * 64, 0, BAR(B_XF + kb));
                            mbar_expect(BAR(B_XF + kb), 16384);
                        }
                    }
                }
            }
            __syncwarp();
            mbar_wait(BAR(B_XC), 0);
            if (elect_one()) {
                asm volatile("prefetch.tensormap [%0];" :: "l"(&mX) : "memory");
                asm volatile("prefetch.tensormap [%0];" :: "l"(&mWo) : "memory");
                asm volatile("prefetch.tensormap [%0];" :: "l"(&mW1) : "memory");
                asm volatile("prefetch.tensormap [%0];" :: "l"(&mW2) : "memory");
                mbar_expect(BAR(B_AF), (g1_on ? NPRE : 14) * 8192);
                mbar_expect(BAR(B_WQF), 57344);
                #pragma unroll 1
                for (int s = rank; s < 7; s += 2) tma2d_mc(sb + SM_WQ + s * 8192, &mWqkv, wcol, s * 64, BAR(B_WQF));
                mbar_expect(BAR(B_XRF), 16384);
                tma2d(sb + SM_XR, &mX, a2p * kD + a2j * 112, ti * 64, BAR(B_XRF));
                tma2d(sb + SM_XR + 8192, &mX, a2p * kD + a2j * 112 + 48, ti * 64, BAR(B_XRF));
            }
            __syncwarp();
            #pragma unroll 1
            for (int q = 0; q < 4; q++) {
                mbar_wait(BAR(B_KV3 + (q >> 1)), 0);
                if (q == 2) spin_until(clk32() + WOD);
                if (q == WOQ) mbar_wait2(BAR(B_HL), 0, BAR(B_HL + 1), 0);
                if (elect_one()) {
                    if (!(q & 1)) mbar_expect(BAR(B_WOF + (q >> 1)), 57344);
                    tma2d_mc(sb + SM_WKV + q * 28672 + rank * 14336, &mWo, a2j * 112 + (q & 1) * 48, (q >> 1) * 224 + rank * 112, BAR(B_WOF + (q >> 1)));
                    if (g1_on && q == AFIRST) { load_slab(0, false); load_slab(1, false); load_slab(2, false); }
                }
                __syncwarp();
            }
            if (g1_on) {
                mbar_wait2(BAR(B_XD), 0, BAR(B_OL + 3), 0);
                #pragma unroll 1
                for (int i = 3; i < NPRE; i++) {
                    if (i == 7) mbar_wait(BAR(B_OC), 0);
                    if (elect_one()) load_slab(i, false);
                    __syncwarp();
                }
            } else {
                mbar_arrive_if(BAR((lane < 16 ? B_BE : B_BF) + (lane & 3)), lane < 20);
                mbar_wait(BAR(B_HD), 0);
                mbar_arrive_remote_if(pbar0 + 8u * B_PD, lane == 0);
                mbar_wait(BAR(B_GO), 0);
                uint32_t tg = lds1(sb + SM_TG + 4);
                tg += max((int)(lds1(sb + SM_TG2) - tg), 0);
                int it = 0;
                while ((int)(gtime32() - tg) < 0 && ++it < 256) {}
                const uint32_t t0 = clk32();
                if (lane < 2) {
                    asm volatile("st.shared.u32 [%0], %1;" :: "r"(sb + SM_TG + 8 + lane * 4), "r"(t0 + (lane ? CN3 : CN2)) : "memory");
                    mbar_arrive(BAR(B_GD + lane));
                }
                __syncwarp();
                #pragma unroll 1
                for (int s = 1; s < 15; s++) {
                    sleep_until(t0 + W2OFF + s * W2PACE);
                    if (elect_one()) { if (s < 15 - PFW) bulk_prefetch(pw2 + (s - 1) * 64 * 4096, 4096); load_slab(s, true); }
                    __syncwarp();
                }
            }
          } else {
            TRW(58);
            const uint32_t tag = lds1(sb + SM_EPOCH);
            if (lane < 4) mbar_expect(BAR(B_OL + lane), 14336);
            const uint32_t gbase = lds1(sb + SM_TG);
            const bool lead = elect_one();
            uint32_t* hfl = opaque_ptr(&prm.sc->flag_h[(a2s * 4 + a2j) * FS]);
            mbar_wait(BAR(B_A1D), 0);
            const int d = poll_flags(&prm.sc->flag_o[(ti * 8 + (lane & 3) * 2) * FS], FS, tag, gbase);
            TRW(53);
            int key = max(d + DELTAO, __reduce_max_sync(~0u, d) + DMIN) * 4 + (lane & 3);
            uint32_t order = 0;
            #pragma unroll 1
            for (int i = 0; i < 4; i++) {
                const int m = __reduce_min_sync(~0u, key);
                const uint4* src = &prm.sc->o[(a2s * 4 + (m & 3)) * 896];
                int it = 0;
                while ((int)(gtime32() - gbase) < m >> 2 && ++it < 256) {}
                if (lead) bulk_g2s(sb + SM_WQ + i * 14336, src, 14336, BAR(B_OL + i));
                if (key == m) key = 0x7fffffff;
                order |= (m & 3) << i * 2;
            }
            if (lead) {
                asm volatile("st.shared.u32 [%0], %1;" :: "r"(sb + SM_ORD), "r"(order) : "memory");
                mbar_arrive(BAR(B_OD));
            }
            __syncwarp();
            int t0 = 0;
            #pragma unroll 1
            for (int i = 0; i < 4; i++) { mbar_wait(BAR((i < ANN ? B_OF : B_OL) + i), 0); t0 = max(t0, (int)(gtime32() - gbase) - i * CHUNKNS); }
            if (lead) st_flag(hfl, tag, gbase + t0);
            __syncwarp();
            TRW(57);
          }
          if (elect_one()) {
              const int h = ~warp & 1;
              constexpr uint32_t T = 57344, BO = 2 * 14336;
              const char* src1 = (const char*)&prm.sc->hn[(rank * 16 + h) * 3584 + g1j * 896];
              const char* src2 = (const char*)&prm.sc->g[(rank * 14 + h) * 3584 + g2j * 896];
              uint64_t masks = g1_on ? (h ? kSegMasks1 : kSegMasks0) : 0x80 | 0x80 << 10;
              const uint32_t bl = BAR(B_BL + h * NB);
              uint32_t s8 = (g1_on ? NB - 2 + h : 4 + h) * 8, lap = 3, tmin = 0;
              const CUtensorMap* am = &mW1;
              uint32_t ad = sb + (NPRE + h) * 8192, astep = 16384; int ac0 = h * kF + g1f * 64, ac1 = (rank * 8 + NPRE / 2) * 64;
              CAP_DECL(ti_, 0);
              #pragma unroll 1
              for (int seg = g1_on ? 0 : 3; seg < 5; seg++) {
                  const char* src = (seg < 3 ? src1 : src2) + (~seg & 1) * BO;
                  uint32_t m = (uint32_t)masks & 0x3ff;
                  masks >>= 10;
                  const uint32_t pace = seg == 4 ? PACEB : seg == 3 ? PACEA : PACE2;
                  if (seg == 2) {
                      mbar_wait(BAR(B_PL), 0);
                      mbar_arrive_remote_if(pbar0 + 8u * B_PD, h);
                      am = &mW2; ad = sb + 8192; astep = 8192; ac0 = g2s * 64; ac1 = rank * 14 * 64;
                  } else {
                      const int gate = seg - (seg > 2);
                      mbar_wait(BAR(B_HD + gate), 0);
                      tmin = lds1(sb + SM_TG + gate * 4);
                      if (gate < 2) {
                          tmin += max((int)(lds1(gate ? sb + SM_TG2 : sb + SM_TG) - tmin), 0);
                          int it = 0;
                          while ((int)(gtime32() - tmin) < 0 && ++it < 256) {}
                          tmin = clk32();
                      }
                      tmin += h * PACE1;
                  }
                  #pragma unroll 1
                  do {
                      const uint32_t dst = sb + SM_B + s8 * 1792;
                      spin_until(tmin);
                      mbar_wait_fast(BAR(B_BE) + s8 + (lap & 1) * (NB * 8), lap >> 1 & 1);
                      if (seg) {
                          bulk_g2s(dst, src, 14336, bl + s8);
                          mbar_expect(bl + s8, 14336);
                          CAP(ti_);
                      }
                      tmin += pace;
                      src += 2 * T;
                      s8 += 16;
                      if (s8 >= NB * 8) { s8 -= NB * 8; lap++; }
                      if (m & 1) {
                          mbar_expect_more(bl + s8, 8192);
                          tma2d(ad, am, ac0, ac1, bl + s8);
                          ad += astep; ac1 += 64;
                      }
                      m >>= 1;
                  } while (m != 1);
                  if (seg == 0) lap = 3;
              }
          }
        } else {
          if (warp == 10) {
            mbar_wait(BAR(PFBAR), 0);
            if (lane < 27) asm volatile("prefetch.global.L2 [%0];" :: "l"(lane < 25 ? (const char*)prm.wo + min(b * 25 + lane, 3135) * 128
                                                                          : lane == 25 ? (const char*)prm.b1 + (b % 28) * 128 : (const char*)prm.b2 + (b & 31) * 128));
            const char* p1 = (const char*)prm.w1 + ((b >> 6) * 1024 + (b & 63) * 2) * 3584 + min(lane, 27) * 128;
            uint32_t tnext = clk32();
            #pragma unroll 1
            for (int i = 0; i < 16; i++) {
                while ((int)(clk32() - tnext) < 0) __nanosleep(40);
                asm volatile("prefetch.global.L2 [%0];" :: "l"(p1 + ((i >> 1) * 128 + (i & 1)) * 3584));
                tnext += PFPACE;
            }
            mbar_wait(BAR(B_EP), 0);
          }
          const uint32_t tag = lds1(sb + SM_EPOCH);
          const int h = warp & 1;
          const bool lead = elect_one();
          const uint32_t wo = lane * 132, l3 = lane < 16 ? 12288 : 0;
          uint32_t base = sb + SM_WQ, bl = BAR(B_OL), bf = BAR(B_OF), m = 4, rph = 0;
          #pragma unroll 1
          for (int e = 0; e < 2; e++) {
              uint32_t s8 = (e && !g1_on ? 4 + h : h) * 8;
              #pragma unroll 1
              do {
                  const uint32_t dst = base + s8 * 1792;
                  auto stale = [&]() {
                      uint32_t d;
                      asm volatile("{ .reg .b32 x, y, z, u;\n"
                                   "ld.shared.u32 x, [%1]; ld.shared.u32 y, [%1 + 4096]; ld.shared.u32 z, [%1 + 8192]; ld.shared.u32 u, [%2];\n"
                                   "lop3.b32 x, x, y, %3, 0x7e; lop3.b32 z, z, u, %3, 0x7e; lop3.b32 %0, x, z, 1, 0xa8; }"
                                   : "=r"(d) : "r"(dst + wo), "r"(dst + (wo + l3)), "r"(tag) : "memory");
                      return __any_sync(~0u, d);
                  };
                  mbar_wait_fast(bl + s8, m & 1);
                  bool bad = stale();
                  mbar_arrive_if(bf + s8, lead && !bad);
                  if (bad) {
                      const int p = 2 * __clz(m) - 2 + h;
                      RETRY_COUNT(!e ? 1 : p < 32 ? 0 : !g1_on ? 5 : p < 46 ? 2 : 6);
                      const int st = (p > 15) + (p > 31) + (p > 45), s = p - (st < 3 ? 16 * st : 46);
                      mbar_wait(BAR(B_OD), 0);
                      const char* src = (const char*)(!e ? &prm.sc->o[(a2s * 4 + (lds1(sb + SM_ORD) >> (p * 2 & 7) & 3)) * 896] : st < 2 ? &prm.sc->hn[(rank * 16 + s) * 3584 + (g1j + 2 * st) * 896]
                                                                                                      : &prm.sc->g[(rank * 14 + s) * 3584 + (g2j + 2 * st - 4) * 896]);
                      int it = 0;
                      do {
                          if (++it > kSpinLimit) { TIMEOUT(111); break; }
                          const uint32_t* q = (const uint32_t*)(src + wo);
                          if (it > RELOAD1 && __any_sync(~0u, ((ld_rlx(q) ^ tag) | (ld_rlx(q + 1024) ^ tag) | (ld_rlx(q + 2048) ^ tag) | (ld_rlx(q + l3 / 4) ^ tag)) & 1)) continue;
                          if (lead) {
                              mbar_expect(BAR(B_RT + h), 14336);
                              bulk_g2s(dst, src, 14336, BAR(B_RT + h));
                          }
                          __syncwarp();
                          mbar_wait(BAR(B_RT + h), rph);
                          rph ^= 1;
                          bad = stale();
                      } while (bad);
                      mbar_arrive_if(bf + s8, lead);
                  }
                  s8 += 16;
                  if (s8 >= NB * 8) s8 -= NB * 8;
                  m >>= 1;
              } while (m != 1);
              if (e) break;
              if (h) {
                  const uint32_t gbase = lds1(sb + SM_TG);
                  sleep_until(clk32() + PDELAY);
                  const uint32_t tg = gbase + DELTA + __reduce_max_sync(~0u, poll_flags(&prm.sc->flag_h[(rank * 64 + lane) * FS], 32 * FS, tag, gbase));
                  TRW(40);
                  if (lead) {
                      asm volatile("st.async.shared::cluster.mbarrier::complete_tx::bytes.b32 [%0], %1, [%2];"
                                   :: "r"(pbar0 + (SM_TG2 - SM_BAR)), "r"(tg), "r"(pbar0 + 8u * B_GO) : "memory");
                      asm volatile("st.shared.u32 [%0], %1;" :: "r"(sb + SM_TG + 4), "r"(tg) : "memory");
                      mbar_expect(BAR(B_GO), 4);
                  }
                  __syncwarp();
              } else {
                  const char* p2 = (const char*)prm.w2 + ((b >> 6) * 896 + (b & 63)) * 4096 + lane * 128;
                  #pragma unroll 1
                  for (int i = 0; i < PFW; i++) {
                      asm volatile("prefetch.global.L2 [%0];" :: "l"(p2 + i * 64 * 4096));
                      sleep_until(clk32() + PFPACE2);
                  }
              }
              base = sb + SM_B; bl = BAR(B_BL + h * NB); bf = BAR(B_BF); m = g1_on ? 0x4fe03f80 : 0x7f80;
          }
        }
    } else {
        asm volatile("setmaxnreg.inc.sync.aligned.u32 232;");
        asm volatile("barrier.cluster.wait.aligned;" ::: "memory");
        const int wg = warp >> 2, w = warp & 3;
        const int g = lane >> 2, t = lane & 3;
        uint32_t tag;
        __nv_bfloat16 bias1a, bias1b;
        {
            const uint64_t dw = make_desc(sb + (hg & 1) * 16, 0, true);
            uint4* const hp = opaque_ptr((w == 3 ? &prm.sc->halo[((ti * 8 + hg) * 2 + wg) * 128] : (uint4*)(smem_raw + SM_STG + wg * 8192 + w * 2048)) + lane);
            uint32_t a[28][4];
            float sm[4][4] = {};
            {
                const int r = w * 16 + (lane & 15);
                uint32_t xa[4];
                #pragma unroll
                for (int q = 0; q < 4; q++) xa[q] = opaque(sb + wg * 8192 + r * 128 + (((q * 2 + (lane >> 4)) ^ (r & 7)) << 4));
                const uint32_t one = opaque(0x3F803F80u), one2 = opaque(0x3F803F80u);
                #pragma unroll
                for (int k = 0; k < 28; k++) {
                    if ((k & 3) == 0) mbar_wait(BAR(B_XF + (k >> 2)), 0);
                    uint32_t (&f)[4] = a[k];
                    asm volatile("ldmatrix.sync.aligned.m8n8.x4.shared.b16 {%0,%1,%2,%3}, [%4];"
                                 : "=r"(f[0]), "=r"(f[1]), "=r"(f[2]), "=r"(f[3]) : "r"(xa[k & 3] + (k >> 2) * 16384) : "memory");
                    if (k < 24) mma16816(sm[k & 3], f[0], f[1], f[2], f[3], one, one2);
                }
                pair_arrive(B_XC);
                const bool wok = mbar_test(BAR(B_WKVF), 0);
                #pragma unroll
                for (int k = 24; k < 28; k++) mma16816(sm[k & 3], a[k][0], a[k][1], a[k][2], a[k][3], one, one2);
                if (W0E && !wok) mbar_wait(BAR(B_WKVF), 0);
            }
            const float mean0 = ((sm[0][0] + sm[1][0]) + (sm[2][0] + sm[3][0])) * (1.f / kD);
            const float mean1 = ((sm[0][2] + sm[1][2]) + (sm[2][2] + sm[3][2])) * (1.f / kD);
            const uint32_t mb0 = pack_bf16(mean0, mean0), mb1 = pack_bf16(mean1, mean1);
            TR(1);
            K5(0);
            float ak[28], av[28], aq[28];
            float ss0 = 0.f, ss1 = 0.f, ss2 = 0.f, ss3 = 0.f;
            uint32_t p0, p1;
            bool qok;
            static_for<0, 7>([&](auto S_) {
                constexpr int s = decltype(S_)::value;
                auto centre = [&](int q) {
                    uint32_t (&f)[4] = a[s * 4 + q];
                    f[0] = sub_bf16x2(f[0], mb0); f[1] = sub_bf16x2(f[1], mb1);
                    f[2] = sub_bf16x2(f[2], mb0); f[3] = sub_bf16x2(f[3], mb1);
                };
                if (s || !W0E) {
                    #pragma unroll
                    for (int q = 0; q < 4; q++) centre(q);
                    mbar_wait(BAR(B_WKVF + s), 0);
                    if (s == 6) qok = mbar_test(BAR(B_WQF), 0);
                    wg_fence();
                }
                static_for<0, 4>([&](auto Q_) {
                    constexpr int q = decltype(Q_)::value;
                    uint32_t (&f)[4] = a[s * 4 + q];
                    if (s == 0 && W0E) { centre(q); wg_fence(); }
                    wgmma_rs_n56<SM_WKV + s * 16384 + q * 2048, (s | q) != 0>(ak, f[0], f[1], f[2], f[3], dw);
                    wgmma_rs_n56<SM_WKV + s * 16384 + q * 2048 + 8192, (s | q) != 0>(av, f[0], f[1], f[2], f[3], dw);
                });
                wg_commit();
                K5(1 + s);
                if (s == 4) { wg_wait<1>(); pair_arrive(B_KV3); }
                if (s < 2) mbar_wait(BAR(s ? B_EP : B_WKVF), 0);
                if (s == 1) tag = lds1(sb + SM_EPOCH);
                #pragma unroll
                for (int q = 0; q < 8; q++) {
                    const uint32_t u0 = a[s * 4 + q / 2][(q & 1) * 2], u1 = a[s * 4 + q / 2][(q & 1) * 2 + 1];
                    if (q == 0 && (VCH == 1 || (s & 1) || s == 0)) { p0 = sqr_bf16x2(u0); p1 = sqr_bf16x2(u1); }
                    else { p0 = sqa_bf16x2(u0, p0); p1 = sqa_bf16x2(u1, p1); }
                }
                if (VCH == 1 || !(s & 1)) { ss0 += bf_lo(p0); ss2 += bf_hi(p0); ss1 += bf_lo(p1); ss3 += bf_hi(p1); }
            });
            auto q_chunk = [&](auto K0_, auto K1_) {
                wg_fence();
                static_for<decltype(K0_)::value, decltype(K1_)::value>([&](auto K_) {
                    constexpr int k = decltype(K_)::value;
                    wgmma_rs_n56<SM_WQ + k * 2048, k != 0>(aq, a[k][0], a[k][1], a[k][2], a[k][3], dw);
                });
                wg_commit();
            };
            #define QCHUNK(k0, k1) q_chunk(std::integral_constant<int, k0>{}, std::integral_constant<int, k1>{})
            const float dl0 = mean0 - bf_lo(mb0), dl1 = mean1 - bf_lo(mb1);
            const float rs0 = rsq(fmaxf(quad_sum(ss0 + ss2) * (1.f / kD) - dl0 * dl0, 0.f) + kEps);
            const float rs1 = rsq(fmaxf(quad_sum(ss1 + ss3) * (1.f / kD) - dl1 * dl1, 0.f) + kEps);
            float rk[3][2];
            rk[1][0] = __shfl_sync(~0u, rs0, t * 8); rk[1][1] = __shfl_sync(~0u, rs0, t * 8 + 4);
            rk[2][0] = __shfl_sync(~0u, rs1, t * 8); rk[2][1] = __shfl_sync(~0u, rs1, t * 8 + 4);
            const uint32_t stg = sb + SM_STG + wg * 8192 + lane * 16;
            if (!qok) mbar_wait(BAR(B_WQF), 0);
            K5(8);
            QCHUNK(0, QC0);
            K5(9);
            wg_wait<1>();
            K5(10);
            reg_fence(ak); reg_fence(av);
            TR(2);
            uint32_t kf[3][7], vf[3][7];
            #pragma unroll
            for (int c = 0; c < 7; c++) {
                kf[2][c] = pack_bf16(ak[4 * c + 2], ak[4 * c + 3]);
                vf[2][c] = movm(pack_bf16(av[4 * c + 2], av[4 * c + 3]));
            }
            if (QCA > QC0) QCHUNK(QC0, QCA);
            const uint32_t om = ~lane & 1;
            kf[2][0] = set_par(kf[2][0], om, tag); kf[2][4] = set_par(kf[2][4], om, tag);
            vf[2][1] = set_par(vf[2][1], om, tag); vf[2][5] = set_par(vf[2][5], om, tag);
            st_gen4(hp,      kf[2][0], kf[2][1], kf[2][2], kf[2][3]);
            st_gen4(hp + 32, kf[2][4], kf[2][5], kf[2][6], vf[2][0]);
            st_gen4(hp + 64, vf[2][1], vf[2][2], vf[2][3], vf[2][4]);
            st_gen4(hp + 96, vf[2][5], vf[2][6], __float_as_uint(rk[2][0]), __float_as_uint(rk[2][1]));
            pair_arrive(B_KVC);
            K5(11);
            QCHUNK(QCA, QC1);
            if (QF & 1) mbar_wait(BAR(B_EP), 0);
            K5(12);
            #pragma unroll
            for (int c = 0; c < 7; c++) {
                kf[1][c] = pack_bf16(ak[4 * c], ak[4 * c + 1]);
                vf[1][c] = movm(pack_bf16(av[4 * c], av[4 * c + 1]));
            }
            QCHUNK(QC1, QC2);
            K5(13);
            named_bar(1 + wg, 128);
            uint32_t* op = opaque_ptr((uint32_t*)&prm.sc->o[((ti * 2 + wg) * 56 + hg * 7) * 64] + w * 64 + lane);
            const uint32_t om0 = opaque((lane & 7) == w * 2), om1 = opaque((lane & 7) == w * 2 + 1);
            QCHUNK(QC2, 28);
            K5(14);
            #undef QCHUNK
            const bool gt0 = 2 * t > g, gt1 = 2 * t + 1 > g, no_prev = ti == 0 && w == 0;
            const float kf0 = gt0 ? rk[1][0] : rk[2][0], kf1 = gt1 ? rk[1][1] : rk[2][1];
            constexpr float kScale = 0.18898223650461362f * 1.4426950408889634f;
            const float sq0 = rs0 * kScale, sf0 = kf0 * (rs1 * kScale), sf1 = kf1 * (rs1 * kScale);
            const float NEG = -__int_as_float(0x7f800000);
            const float nb0 = gt0 && no_prev ? NEG : 0.f, nb1 = gt1 && no_prev ? NEG : 0.f;
            const uint32_t mk = opaque((gt0 ? 0x0000ffffu : 0u) | (gt1 ? 0xffff0000u : 0u));
            const uint32_t sr = stg + ((w + 3) & 3) * 2048, hbar = BAR(w == 0 ? B_HL + wg : B_EP);
            mbar_wait(BAR(B_EP), 0);
            wg_wait<0>();
            reg_fence(aq);
            warp_arrive(BAR(B_A1D));
            K5(15);
            TR(3);
            uint32_t qf[8][2];
            #pragma unroll
            for (int c = 0; c < 7; c++) {
                qf[c + (c > 3)][0] = pack_bf16(aq[4 * c], aq[4 * c + 1]);
                qf[c + (c > 3)][1] = pack_bf16(aq[4 * c + 2], aq[4 * c + 3]);
            }
            qf[4][0] = t >= 2 ? qf[3][0] : 0u; qf[4][1] = t >= 2 ? qf[3][1] : 0u;
            qf[3][0] = t < 2 ? qf[3][0] : 0u;  qf[3][1] = t < 2 ? qf[3][1] : 0u;
            float sc[2][3][4];
            auto scores = [&](int n) {
                #pragma unroll
                for (int hd = 0; hd < 2; hd++) {
                    sc[hd][n][0] = sc[hd][n][1] = sc[hd][n][2] = sc[hd][n][3] = 0.f;
                    mma16816(sc[hd][n], qf[4 * hd][0], qf[4 * hd][1], qf[4 * hd + 1][0], qf[4 * hd + 1][1], kf[n][3 * hd], kf[n][3 * hd + 1]);
                    mma16816(sc[hd][n], qf[4 * hd + 2][0], qf[4 * hd + 2][1], qf[4 * hd + 3][0], qf[4 * hd + 3][1], kf[n][3 * hd + 2], kf[n][3 * hd + 3]);
                }
            };
            scores(1); scores(2);
            mbar_wait(hbar, 0);
            {
                const uint4 u0 = lds4(sr), u1 = lds4(sr + 512), u3 = lds4(sr + 1536), u2 = lds4(sr + 1024);
                kf[0][0] = u0.x; kf[0][1] = u0.y; kf[0][2] = u0.z; kf[0][3] = u0.w;
                kf[0][4] = u1.x; kf[0][5] = u1.y; kf[0][6] = u1.z; vf[0][0] = u1.w;
                vf[0][1] = u2.x; vf[0][2] = u2.y; vf[0][3] = u2.z; vf[0][4] = u2.w;
                vf[0][5] = u3.x; vf[0][6] = u3.y; rk[0][0] = __uint_as_float(u3.z); rk[0][1] = __uint_as_float(u3.w);
            }
            TR(4);
            scores(0);
            const float ke0 = gt0 ? rk[0][0] : rk[1][0], ke1 = gt1 ? rk[0][1] : rk[1][1];
            const float se0 = ke0 * sq0, se1 = ke1 * sq0;
            uint32_t ow[7][2];
            #pragma unroll
            for (int hd = 0; hd < 2; hd++) {
                const int c0 = hd * 3;
                float (&sc_)[3][4] = sc[hd];
                const float e0 = fmaf(gt0 ? sc_[0][0] : sc_[1][0], se0, nb0), e1 = fmaf(gt1 ? sc_[0][1] : sc_[1][1], se1, nb1);
                const float f0 = (gt0 ? sc_[1][2] : sc_[2][2]) * sf0, f1 = (gt1 ? sc_[1][3] : sc_[2][3]) * sf1;
                const float me = quad_max(fmaxf(e0, e1)), mf = quad_max(fmaxf(f0, f1));
                const float p0 = ex2(e0 - me), p1 = ex2(e1 - me), r0 = ex2(f0 - mf), r1 = ex2(f1 - mf);
                const float ie = rcp(quad_sum(p0 + p1)), jf = rcp(quad_sum(r0 + r1));
                const uint32_t pp = pack_bf16(p0 * ke0 * ie, p1 * ke1 * ie), rp = pack_bf16(r0 * kf0 * jf, r1 * kf1 * jf);
                const uint32_t a0 = pp & ~mk, a1 = rp & mk, a3 = rp & ~mk, a4 = pp & mk, zero = opaque(0u), zero2 = opaque(0u);
                #pragma unroll
                for (int c = 0; c < 4; c++) {
                    float o[4] = {0.f, 0.f, 0.f, 0.f};
                    mma16816(o, a0, a1, zero, a3, vf[1][c0 + c], vf[2][c0 + c]);
                    mma1688(o, a4, zero2, vf[0][c0 + c]);
                    const uint32_t lo = pack_bf16(o[0], o[1]), hi = pack_bf16(o[2], o[3]);
                    if (hd == 1 && c == 0) { if (t >= 2) { ow[3][0] = lo; ow[3][1] = hi; } }
                    else { ow[c0 + c][0] = lo; ow[c0 + c][1] = hi; }
                }
            }
            #pragma unroll
            for (int c = 0; c < 7; c++) {
                stg1(op + c * 256,      set_par(ow[c][0], om0, tag));
                stg1(op + c * 256 + 32, set_par(ow[c][1], om1, tag));
            }
            TR(5);
        }
        float as[28], ac[28];
        uint32_t xch, peer_xch, gm[2][4], *gp1, *gp2;
        const uint32_t *hp, *ht;
        const uint2* hq;
        uint64_t da0, db0;
        const int cg2 = (g2j + 2 * wg) * 2 + (rank ^ 1), cg1 = (g1j + 2 * wg) * 2 + (rank ^ (g1f < 14));
        const bool lead = elect_one();
        {
            const int cg = a2j * 2 + wg;
            float acc2[28];
            mbar_wait(BAR(B_XRF), 0);
            {
                const uint32_t xa = sb + SM_XR + wg * 8192 + (w * 16 + (lane & 15)) * 128;
                #pragma unroll
                for (int c = 0; c < 4; c++) {
                    uint32_t xr[4];
                    asm volatile("ldmatrix.sync.aligned.m8n8.x4.shared.b16 {%0,%1,%2,%3}, [%4];"
                                 : "=r"(xr[0]), "=r"(xr[1]), "=r"(xr[2]), "=r"(xr[3])
                                 : "r"(xa + ((((c * 2 + wg + (lane >> 4)) ^ lane) & 7) << 4)) : "memory");
                    #pragma unroll
                    for (int e = 0; e < (c < 3 ? 4 : 2); e++) { acc2[8 * c + 2 * e] = bf_lo(xr[e]); acc2[8 * c + 2 * e + 1] = bf_hi(xr[e]); }
                }
            }
            uint32_t* spw = opaque_ptr(&prm.sc->stats[((a2s * 8 + cg) * 4 + w) * 32 + lane]);
            const uint32_t* spr = opaque_ptr(&prm.sc->stats[(a2s * 32 + w) * 32 + lane]);
            uint32_t* rp = opaque_ptr((uint32_t*)&prm.sc->rows[a2s * 64 + w * 16 + (t >> 1) * 8 + g] + (t & 1));
            const int cgs = cg ^ (a2s >> 4);
            uint32_t* np = opaque_ptr((uint32_t*)&prm.sc->hn[(a2s * 56 + cgs * 7) * 64] + w * 64 + lane);
            const uint64_t dwo = make_desc(sb + SM_WKV + wg * (28672 + 16), 0, true);
            const uint64_t doa = make_desc(sb + SM_WQ, 1024, false, 128);
            bias1a = prm.b1[g1f * 64 + w * 16 + g]; bias1b = prm.b1[g1f * 64 + w * 16 + 8 + g];
            const __nv_bfloat16 bias2 = prm.b2[ti * 128 + (w * 16 + (t >> 1) * 8 + g) * 2 + a2p];
            reg_fence(acc2);
            fence_async_smem();
            warp_arrive(BAR(B_XD));
            {
                xch = opaque(sb + SM_XCH + w * 1792 + lane * 16);
                asm volatile("mapa.shared::cluster.u32 %0, %1, %2;" : "=r"(peer_xch) : "r"(xch), "r"(rank ^ 1));
                const int hcg = cg2 ^ (g2s >> 4), hrg = (g2s & 1) * 4 + w;
                const uint32_t* hl = (const uint32_t*)&prm.sc->hn[((g2s >> 1) * 112 + hcg * 7) * 64 + hrg * 8];
                hp = opaque_ptr(hl + (g & 1) * 14336 + (g >> 1) * 4 + t);
                ht = opaque_ptr(hl + (lane & 1) * 14336 + min(lane >> 1, 6) * 256 + ((min(lane >> 1, 6) - (hcg & 1)) & 3) * 8 + hrg);
                hq = opaque_ptr(&prm.sc->rows[((g2s >> 1) * 2 + (g & 1)) * 64 + hrg * 8 + (g >> 1)]);
                gp1 = opaque_ptr((uint32_t*)&prm.sc->g[(g1f * 56 + cg1 * 7) * 64] + w * 64 + lane);
                gp2 = opaque_ptr((uint32_t*)(prm.out + (size_t)(g2s * 64 + w * 16 + lane / 7) * kD + cg2 * 56) + (lane % 7) * 4);
                da0 = make_desc(sb, 0, true); db0 = make_desc(sb + SM_B, 128, false);
            }
            mbar_wait2(BAR(B_WOF), 0, BAR(B_WOF + 1), 0);
            mbar_wait(BAR(B_OD), 0);
            const uint32_t order = __shfl_sync(~0u, lds1(sb + SM_ORD), 0);
            static_for<0, 4>([&](auto P_) {
                constexpr int P = decltype(P_)::value;
                const uint64_t dwp = dwo + ((order >> (2 * P + 1) & 1) * 3584 + (order >> 2 * P & 1) * 896);
                mbar_wait(BAR(B_OF + P), 0);
                if (P == 0) TR(6);
                wg_fence();
                static_for<0, 7>([&](auto K_) { constexpr int k = decltype(K_)::value;
                    wgmma_ss_n56<P * 14336 + k * 2048, k * 2048, 0>(acc2, doa, dwp); });
                if (P) wg_commit();
                if (P == 2) { wg_wait<1>(); warp_arrive(BAR(B_OC)); }
            });
            wg_wait<0>();
            reg_fence(acc2);
            TR(7);
            float s0 = 0.f, s1 = 0.f, q0 = 0.f, q1 = 0.f;
            #pragma unroll
            for (int c = 0; c < 7; c++) {
                s0 += acc2[4 * c] + acc2[4 * c + 1];     q0 = fmaf(acc2[4 * c], acc2[4 * c], fmaf(acc2[4 * c + 1], acc2[4 * c + 1], q0));
                s1 += acc2[4 * c + 2] + acc2[4 * c + 3]; q1 = fmaf(acc2[4 * c + 2], acc2[4 * c + 2], fmaf(acc2[4 * c + 3], acc2[4 * c + 3], q1));
            }
            const bool th = t >= 2, to = t & 1;
            const float sa = (th ? s1 : s0) + __shfl_xor_sync(~0u, th ? s0 : s1, 2), qa = (th ? q1 : q0) + __shfl_xor_sync(~0u, th ? q0 : q1, 2);
            const float part = (to ? qa : sa) + __shfl_xor_sync(~0u, to ? sa : qa, 1);
            stg1(spw, set_par(__float_as_uint(part), 1u, tag));
            const uint32_t tpoll = clk32() + SDELAY;
            TR(8);
            warp_arrive(BAR(B_HD));
            uint32_t nm[2][4], us[8];
            spin_until(tpoll);
            #pragma unroll
            for (int i = 0; i < 8; i++) us[i] = ld_rlx(spr + i * 128);
            #pragma unroll
            for (int i = 0; i < 8; i++) {
                nm[i >> 2][i & 3] = lane == ((i - (cgs & 1)) & 3) * 8 + w * 2 + (i >> 2);
                gm[i >> 2][i & 3] = opaque(lane == ((i - (cg1 & 1)) & 3) * 8 + w * 2 + (i >> 2));
            }
            #pragma unroll
            for (int c = 0; c < 28; c++) { ac[c] = 0.5f * __bfloat162float(c & 2 ? bias1b : bias1a); as[c] = 0.f; }
            reg_fence(as); reg_fence(ac);
            {
                int it = 0;
                while (true) {
                    uint32_t bad = 0;
                    #pragma unroll
                    for (int i = 0; i < 8; i++) bad |= us[i] ^ tag;
                    if (!__any_sync(~0u, bad & 1)) break;
                    RETRY_COUNT(3);
                    if (++it > kSpinLimit) { TIMEOUT(103); break; }
                    #pragma unroll
                    for (int i = 0; i < 8; i++) us[i] = ld_rlx(spr + i * 128);
                }
            }
            TR(9);
            const float tot = (((__uint_as_float(us[0]) + __uint_as_float(us[1])) + (__uint_as_float(us[2]) + __uint_as_float(us[3])))
                            + ((__uint_as_float(us[4]) + __uint_as_float(us[5])) + (__uint_as_float(us[6]) + __uint_as_float(us[7])))) * (1.f / kD);
            const float oth = __shfl_xor_sync(~0u, tot, 1);
            const float mean = to ? oth : tot;
            const float var = fmaxf(fmaf(-mean, mean, to ? tot : oth), 0.f);
            const float rra = rsq(fmaf(var, 4.f + 4.f * kEps, 4.f * kEps * kEps)), mra = -mean * rra;
            const float rrb = __shfl_xor_sync(~0u, rra, 2), mrb = __shfl_xor_sync(~0u, mra, 2);
            const float rr0 = th ? rrb : rra, mr0 = th ? mrb : mra, rr1 = th ? rra : rrb, mr1 = th ? mra : mrb;
            #pragma unroll
            for (int c = 0; c < 7; c++) {
                stg1(np + c * 256,      set_par(pack_bf16(fmaf(acc2[4 * c], rr0, mr0), fmaf(acc2[4 * c + 1], rr0, mr0)), nm[0][c & 3], tag));
                stg1(np + c * 256 + 32, set_par(pack_bf16(fmaf(acc2[4 * c + 2], rr1, mr1), fmaf(acc2[4 * c + 3], rr1, mr1)), nm[1][c & 3], tag));
            }
            TR(10);
            if (cg == 0) stg1(rp, set_par(__float_as_uint(to ? mean + __bfloat162float(bias2) : rcp(rra)), 1u, tag));
        }
        auto send = [&]() {
            const uint32_t rf = pbar0 + (B_RF + warp) * 8;
            #pragma unroll
            for (int c = 0; c < 4; c++) {
                const uint32_t p0 = pack_bf16(as[8 * c], as[8 * c + 1]), p1 = pack_bf16(as[8 * c + 2], as[8 * c + 3]);
                if (c < 3) {
                    const uint32_t p2 = pack_bf16(as[8 * c + 4], as[8 * c + 5]), p3 = pack_bf16(as[8 * c + 6], as[8 * c + 7]);
                    asm volatile("st.async.shared::cluster.mbarrier::complete_tx::bytes.v4.b32 [%0], {%1,%2,%3,%4}, [%5];"
                                 :: "r"(peer_xch + c * 512), "r"(p0), "r"(p1), "r"(p2), "r"(p3), "r"(rf) : "memory");
                } else {
                    asm volatile("st.async.shared::cluster.mbarrier::complete_tx::bytes.v2.b32 [%0], {%1,%2}, [%3];"
                                 :: "r"(peer_xch + 1536 - lane * 8), "r"(p0), "r"(p1), "r"(rf) : "memory");
                }
            }
        };
        auto receive = [&](uint32_t (&pk)[14], uint32_t phase) {
            mbar_wait(BAR(B_RF + warp), phase);
            #pragma unroll
            for (int c = 0; c < 3; c++) { const uint4 u = lds4(xch + c * 512); pk[4 * c] = u.x; pk[4 * c + 1] = u.y; pk[4 * c + 2] = u.z; pk[4 * c + 3] = u.w; }
            const uint2 u = lds2(xch + 1536 - lane * 8); pk[12] = u.x; pk[13] = u.y;
        };
        uint2 rw[2]; uint32_t tw;
        auto load_rows = [&]() { tw = ld_rlx(ht); rw[0] = ld_rlx2(hq); rw[1] = ld_rlx2(hq + 4); };
        rw[0] = rw[1] = make_uint2(0u, 0u); tw = ~tag;
        #pragma unroll 1
        for (int ge = 0;; ge++) {
          if (ge || g1_on) {
            const int use = ge * 2 + wg;
            int entry = ge ? 1 : 2 * wg, stop = 0;
            uint64_t da = da0 + (ge ? -3 : wg ? NR - 10 : 0) * 512;
            bool rel = lead && use == 1;
            const uint32_t xfree = BAR(use > (g1_on ? 0 : 2) ? B_RE + use - 1 : B_PD);
            mbar_wait(BAR(B_AF), 0);
            if (ge && (wg || g1_on)) named_bar(5 - wg, 256);
            TR(11 + ge * 4);
            auto step = [&](auto I_) {
                constexpr int i = decltype(I_)::value, sl = i % NB, ao = i * 8192, bo = sl * 14336;
                mbar_wait_fast(BAR(B_BF + sl), i / NB);
                wg_fence();
                wgmma_ss_n112<ao,        bo,       1>(as, ac, da, db0);
                wgmma_ss_n112<ao + 2048, bo + 256, 1>(as, ac, da, db0);
                wgmma_ss_n112<ao + 4096, bo + 512, 1>(as, ac, da, db0);
                wgmma_ss_n112<ao + 6144, bo + 768, 1>(as, ac, da, db0);
                wg_commit();
                if (i == 1 && stop == 1) named_arrive(4, 256);
                if (i == 3 && (use == 1 || use == 2)) named_arrive(4 + wg, 256);
                wg_wait<1>();
                mbar_arrive_if(BAR(B_BE + (13 + i) % 14), rel);
                rel = lead;
            };
            #pragma unroll 1
            while (true) {
                if (entry < 1) {
                    static_for<0, 2>(step);
                    if (stop == 1) break;
                    static_for<2, 4>(step);
                    if (stop) break;
                }
                if (entry < 2) static_for<4, 10>(step);
                else {
                    uint32_t af[NR * 4][4];
                    mbar_wait(BAR(B_GO), 0);
                    const uint32_t tp = lds1(sb + SM_TG + 4) + PLOFF;
                    int it = 0;
                    while ((int)(gtime32() - tp) < 0 && ++it < 256) __nanosleep(20);
                    const uint32_t la = sb + ((lane >> 4) * 8 + (lane & 7)) * 128 + (((w * 2 + ((lane >> 3) & 1)) ^ (lane & 7)) << 4);
                    #pragma unroll
                    for (int k = 0; k < NR * 4; k++)
                        asm volatile("ldmatrix.sync.aligned.m8n8.x4.trans.shared.b16 {%0,%1,%2,%3}, [%4];"
                                     : "=r"(af[k][0]), "=r"(af[k][1]), "=r"(af[k][2]), "=r"(af[k][3]) : "r"(la + k * 2048) : "memory");
                    __syncwarp();
                    mbar_arrive_if(BAR(B_PL), lead);
                    if (w == 0) {
                        const char* p2 = (const char*)prm.w2 + ((b >> 6) * 896 + (b & 63) + PFW * 64) * 4096 + lane * 128;
                        #pragma unroll 1
                        for (int i = 0; i < 14 - PFW; i++) {
                            it = 0;
                            while ((int)(gtime32() - tp) < PF3OFF + i * PF3PACE && ++it < 256) __nanosleep(40);
                            asm volatile("prefetch.global.L2 [%0];" :: "l"(p2 + i * 64 * 4096));
                        }
                    }
                    named_bar(4, 256);
                    static_for<0, NR>([&](auto I_) {
                        constexpr int i = decltype(I_)::value, sl = (16 + i) % NB, o = sl * 14336;
                        mbar_wait_fast(BAR(B_BF + sl), (16 + i) / NB & 1);
                        wg_fence();
                        wgmma_rs_n112<o,       1>(as, ac, af[4 * i][0], af[4 * i][1], af[4 * i][2], af[4 * i][3], db0);
                        wgmma_rs_n112<o + 256, 1>(as, ac, af[4 * i + 1][0], af[4 * i + 1][1], af[4 * i + 1][2], af[4 * i + 1][3], db0);
                        wgmma_rs_n112<o + 512, 1>(as, ac, af[4 * i + 2][0], af[4 * i + 2][1], af[4 * i + 2][2], af[4 * i + 2][3], db0);
                        wgmma_rs_n112<o + 768, 1>(as, ac, af[4 * i + 3][0], af[4 * i + 3][1], af[4 * i + 3][2], af[4 * i + 3][3], db0);
                        wg_commit();
                        if (i) { wg_wait<1>(); mbar_arrive_if(BAR(B_BE + (15 + i) % (2 * NB)), lead); }
                    });
                }
                static_for<10, 14>(step);
                entry = 0; stop = use + 1; da += 14 * 512;
            }
            const uint32_t prev = BAR(B_BE + (use ? 3 : 1));
            const bool xok = mbar_test(xfree, 0);
            wg_wait<0>();
            reg_fence(as); reg_fence(ac);
            mbar_arrive_if(prev, lead);
            if (!xok) mbar_wait(xfree, 0);
            if (ge) break;
            send();
            load_rows();
            TR(12);
            uint32_t pk[14];
            receive(pk, 0);
            TR(13);
            #pragma unroll
            for (int c = 0; c < 14; c++) {
                float r[2];
                #pragma unroll
                for (int e = 0; e < 2; e++) {
                    const float u = ac[2 * c + e] + (e ? bf_hi(pk[c]) : bf_lo(pk[c]));
                    r[e] = fmaf(u, tanh_hw(u * fmaf(u * u, 8.f * 0.7978845608f * 0.044715f, 2.f * 0.7978845608f)), u);
                }
                stg1(gp1 + (c >> 1) * 256 + (c & 1) * 32, set_par(pack_bf16(r[0], r[1]), gm[c & 1][(c >> 1) & 3], tag));
            }
            named_bar(1 + wg, 128);
            if (w == 0 && lane == 0) {
                asm volatile("st.shared.u32 [%0], %1;" :: "r"(sb + SM_TG + 8 + wg * 4), "r"(clk32() + (wg ? XSPECB : XSPEC)) : "memory");
                mbar_arrive(BAR(B_GD + wg));
            }
            if (lead) mbar_expect(BAR(B_RF + warp), 1792);
            mbar_arrive_remote_if(pbar0 + (B_RE + wg) * 8, lead);
            TR(14);
          } else mbar_wait(BAR(B_GD), 0);
            {
                int it = 0;
                while (__any_sync(~0u, ((tw ^ tag) | (rw[0].x ^ tag) | (rw[0].y ^ tag) | (rw[1].x ^ tag) | (rw[1].y ^ tag)) & 1)) {
                    if (++it > kSpinLimit) { TIMEOUT(110); break; }
                    load_rows();
                }
                uint32_t hw[14];
                #pragma unroll
                for (int c = 0; c < 14; c++) hw[c] = ld_rlx(hp + (c >> 1) * 256 + (c & 1) * 16);
                #pragma unroll
                for (int c = 0; c < 14; c++) {
                    ac[2 * c]     = fmaf(bf_lo(hw[c]), __uint_as_float(rw[c & 1].x), __uint_as_float(rw[c & 1].y));
                    ac[2 * c + 1] = fmaf(bf_hi(hw[c]), __uint_as_float(rw[c & 1].x), __uint_as_float(rw[c & 1].y));
                    as[2 * c] = as[2 * c + 1] = 0.f;
                }
                reg_fence(as); reg_fence(ac);
            }
        }
        uint32_t po[14], pk[14];
        if (!wg) sleep_until(clk32() + w * STAG2);
        send();
        #pragma unroll
        for (int c = 0; c < 14; c++) po[c] = opaque(pack_bf16(ac[2 * c], ac[2 * c + 1]));
        TR(16);
        receive(pk, g1_on);
        TR(17);
        #pragma unroll
        for (int c = 0; c < 14; c++) pk[c] = add_bf16x2(po[c], pk[c]);
        __syncwarp();
        const uint32_t sa = xch - lane * 16 + (lane & 15) * 112 + (lane >> 4) * 16;
        #pragma unroll
        for (int m = 0; m < 3; m++)
            asm volatile("stmatrix.sync.aligned.m8n8.x4.shared.b16 [%0], {%1,%2,%3,%4};"
                         :: "r"(sa + m * 32), "r"(pk[4 * m]), "r"(pk[4 * m + 1]), "r"(pk[4 * m + 2]), "r"(pk[4 * m + 3]) : "memory");
        asm volatile("stmatrix.sync.aligned.m8n8.x2.shared.b16 [%0], {%1,%2};" :: "r"(sa + 96), "r"(pk[12]), "r"(pk[13]) : "memory");
        __syncwarp();
        if (lane < 28) {
            #pragma unroll
            for (int i = 0; i < 4; i++) { const uint4 u = lds4(xch + i * 448); stg4(gp2 + i * 896, u.x, u.y, u.z, u.w); }
        }
        __syncwarp();
        mbar_arrive_remote_if(pbar0 + (B_RE + 2) * 8, lead && wg == 0);
        TR(18);
        if (tid == 128) TRG(62);
        if (b == 0 && tid == 128) prm.sc->epoch = tag;
    }
}

typedef CUresult (*EncodeFn)(CUtensorMap*, CUtensorMapDataType, cuuint32_t, void*, const cuuint64_t*, const cuuint64_t*,
                             const cuuint32_t*, const cuuint32_t*, CUtensorMapInterleave, CUtensorMapSwizzle,
                             CUtensorMapL2promotion, CUtensorMapFloatOOBfill);

void make_map(EncodeFn enc, CUtensorMap* m, const void* base, uint64_t cols, uint64_t rows, uint32_t box_rows) {
    cuuint64_t dims[2] = {cols, rows};
    cuuint64_t strides[1] = {cols * 2};
    cuuint32_t box[2] = {64, box_rows};
    cuuint32_t es[2] = {1, 1};
    enc(m, CU_TENSOR_MAP_DATA_TYPE_BFLOAT16, 2, const_cast<void*>(base), dims, strides, box, es, CU_TENSOR_MAP_INTERLEAVE_NONE,
        CU_TENSOR_MAP_SWIZZLE_128B, CU_TENSOR_MAP_L2_PROMOTION_L2_128B, CU_TENSOR_MAP_FLOAT_OOB_FILL_NONE);
}

}

extern "C" void kernel_launch(void* const* d_in, const int* in_sizes, int n_in, void* d_out, int out_size) {
    (void)in_sizes; (void)n_in; (void)out_size;
    void* fn = nullptr;
    cudaDriverEntryPointQueryResult qr;
    cudaGetDriverEntryPoint("cuTensorMapEncodeTiled", &fn, cudaEnableDefault, &qr);
    EncodeFn enc = (EncodeFn)fn;
    CUtensorMap mX2, mX, mWqkv, mWo, mW1, mW2;
    {
        cuuint64_t dims[3] = {kD, kS / 2, 2}, strides[2] = {4 * kD, 2 * kD};
        cuuint32_t box[3] = {64, 64, 2}, es[3] = {1, 1, 1};
        enc(&mX2, CU_TENSOR_MAP_DATA_TYPE_BFLOAT16, 3, d_in[0], dims, strides, box, es, CU_TENSOR_MAP_INTERLEAVE_NONE,
            CU_TENSOR_MAP_SWIZZLE_128B, CU_TENSOR_MAP_L2_PROMOTION_L2_128B, CU_TENSOR_MAP_FLOAT_OOB_FILL_NONE);
    }
    make_map(enc, &mX, d_in[0], 2 * kD, kS / 2, 64);
    make_map(enc, &mWqkv, d_in[1], 3 * kD, kD, 64);
    make_map(enc, &mWo, d_in[2], kD, kD, 112);
    make_map(enc, &mW1, d_in[4], 2 * kF, kS / 2, 64);
    make_map(enc, &mW2, d_in[6], kS, kF, 64);
    Params prm;
    prm.x = (const __nv_bfloat16*)d_in[0];
    prm.wqkv = (const __nv_bfloat16*)d_in[1];
    prm.wo = (const __nv_bfloat16*)d_in[2];
    prm.w1 = (const __nv_bfloat16*)d_in[4];
    prm.b1 = (const __nv_bfloat16*)d_in[5];
    prm.w2 = (const __nv_bfloat16*)d_in[6];
    prm.b2 = (const __nv_bfloat16*)d_in[7];
    prm.out = (__nv_bfloat16*)d_out;
    cudaGetSymbolAddress((void**)&prm.sc, g_scratch);
    cudaFuncSetAttribute(fused_kernel, cudaFuncAttributeMaxDynamicSharedMemorySize, SM_TOTAL);
    fused_kernel<<<128, 384, SM_TOTAL, cudaStreamPerThread>>>(prm, mX2, mX, mWqkv, mWo, mW1, mW2);
}
```

```cpp
#include <cuda_runtime.h>
#include <cuda.h>
#include <cuda_bf16.h>
#include <stdint.h>
#include <type_traits>

namespace {

constexpr int kS = 2048, kD = 448, kF = 1792;
constexpr float kEps = 1e-5f;

#define FS 32
struct Scratch {
    uint4    o[32 * 56 * 64];
    uint4    hn[32 * 56 * 64];
    uint4    g[28 * 56 * 64];
    uint4    halo[8 * 8 * 2 * 4 * 32];
    uint32_t stats[32 * 8 * 4 * 32];
    uint2    rows[32 * 64];
    uint32_t flag_o[16 * 8 * FS];
    uint32_t flag_h[32 * 4 * FS];
    uint32_t epoch;
};
__device__ __align__(1024) Scratch g_scratch;
#define TIMEOUT(code)
#define RETRY_COUNT(i)
#define CAP_DECL(n, k)
#define CAP(n)
#define CAP_SKIP(n)
#define K5(i)
#define EV(i, dep)
#define TR2(idx)
#define TR(idx)
#define TRW(idx)
#define TRG(idx)

constexpr uint32_t SM_WKV  = 114688;
constexpr uint32_t SM_XR   = 24576;
constexpr uint32_t SM_STG  = 40960;
constexpr uint32_t SM_WQ   = 57344;
constexpr uint32_t SM_XCH  = 0;
constexpr uint32_t SM_B    = 131072;
constexpr uint32_t SM_BAR  = 231424;
constexpr uint32_t SM_TOTAL = SM_BAR + 1024;
constexpr int NB = 7;
#define SH1 0
#define SH2 0
#define SH2N 5
#define SH3 0
#define NSPEC 4
#define XSPEC 500
#define C2 0
#define C3 0
#define CN2 7200
#define CN3 10900
constexpr int B_XF = 0, B_WKVF = 7, B_WQF = 14, B_XRF = 15, B_WOF = 16,
              B_XC = 18, B_KV3 = 19, B_KVC = 20,
              B_A1D = 21, B_XD = 22, B_OC = 23,
              B_BE = 24  , B_RE = B_BE + 2 * NB,
              B_PL = B_RE + 3, B_AF = B_PL + 1, B_BL = B_AF + 1  , B_OL = B_BL + 2 * NB  ,
              B_BF = B_OL + 4  , B_OF = B_BF + NB, B_RF = B_OF + 4, B_EP = B_RF + 8, B_PD = B_EP + 1, B_OD = B_PD + 1, B_RT = B_OD + 1, B_HL = B_RT + 2,
              B_HD = B_HL + 2  , B_GO = B_HD + 1, B_GD = B_GO + 1, B_COUNT = B_GD + 2;
#define WEARLY 6
#define PF0 126
#define TMPF 2
#define RSTE 2
#define POLLP 1
#define PROBEP 1
#define LOADP 1
#define LOADW 64
#define NOB 0
#define AEARLY 5
#define W1PACE 400
#define W2PACE 350
#define PFPACE 280
#define PFBAR (B_XF + 6)
#define DELTA 2080
#define DELTA2 DELTA
#define BPACE 230
#define BURST 2
#define W1OFF 350
#define W2OFF 800
#define XPACE 0
#define PSTAG 200
constexpr uint32_t SM_EPOCH = SM_BAR + B_COUNT * 8, SM_TG = SM_EPOCH + 4  , SM_TG2 = SM_TG + 16  , SM_ORD = SM_TG2 + 4  , SM_TR = SM_BAR + 768;

#define HDELAY 200
#define QC0 4
#define QC1 10
#define QC2 16
#define HPOS 1
#define XSPECB 750
#define PACE1 120
#define PACE2 400
#define RELOAD1 1
#define VCH 1
#define SOFF 0
#define XW 1
#define XLAG 0
#define PFX 3
#define PFD 250
#define SDELAY 200
#define PDELAY 400
#define NPRE 10
#define PREPACE 0
#define AFIRST 1
#define DELTAO 864
#define NS 0
#define GCH 14
#define OCH 14
#define ICH 14
#define PACKO
#define NR 8
#define HMODE 2
#define HOFF0 (-100)
#define HOFF1 900
#define STAG1 0
#define STAG2 400
#define PLOFF (-250)
#define HSRC h
#define WO1 1
#define WOD 350
#define WOP 400
#define WOP0 0
#define KV5 1
#define XLATE 0
#define W0E 1
#define W0F 2
#define PACEA 400
#define PACEB 300
#define PFN 16
#define PFPACE2 300
#define PF2R 1
#define PFW 4
#define PFBAR2 PFBAR
#define WOQ 3
#define DMIN 608
#define CHUNKNS 250
#define QCA QC0
#define QF 0
#define PF3OFF 300
#define PF3PACE 240
#define NPD 400
#define ANN 4
#define QLNS 384
#define HLNS 96
#define ODELAY 0
#define W1Q 3
#define APOS1 ((1ull << 4) | (1ull << 8) | (1ull << 12) | (1ull << 5) | (1ull << 9) | (1ull << 13))
#define APOS2 (0x5555555ull << 17)
constexpr uint32_t seg_mask(int h, int p0, int p1) {
    uint32_t m = 0; int n = 0;
    for (int p = p0; p < p1; p++) if ((p & 1) == h) m |= (uint32_t)(((APOS1 | APOS2) >> p) & 1) << n++;
    return m | 1u << n;
}
constexpr uint64_t seg_masks(int h) {
    return 2 | (uint64_t)seg_mask(h, 0, 16) << 10 | (uint64_t)seg_mask(h, 16, 32) << 20
             | (uint64_t)seg_mask(h, 32, 46) << 30 | (uint64_t)seg_mask(h, 46, 60) << 40;
}
constexpr uint64_t kSegMasks0 = seg_masks(0), kSegMasks1 = seg_masks(1);

constexpr int kSpinLimit = 1 << 15;
__device__ __forceinline__ bool elect_one() {
    uint32_t p;
    asm volatile("{ .reg .pred P; elect.sync _|P, 0xffffffff; selp.u32 %0, 1, 0, P; }" : "=r"(p));
    return p;
}
__device__ __forceinline__ void mbar_init(uint32_t bar, uint32_t cnt) { asm volatile("mbarrier.init.shared::cta.b64 [%0], %1;" :: "r"(bar), "r"(cnt)); }
__device__ __forceinline__ void mbar_expect(uint32_t bar, uint32_t bytes) { asm volatile("mbarrier.arrive.expect_tx.shared::cta.b64 _, [%0], %1;" :: "r"(bar), "r"(bytes) : "memory"); }
__device__ __forceinline__ void mbar_expect_more(uint32_t bar, uint32_t bytes) { asm volatile("mbarrier.expect_tx.relaxed.cta.shared::cta.b64 [%0], %1;" :: "r"(bar), "r"(bytes) : "memory"); }
__device__ __forceinline__ void mbar_arrive(uint32_t bar) { asm volatile("mbarrier.arrive.shared::cta.b64 _, [%0];" :: "r"(bar) : "memory"); }
__device__ __forceinline__ void mbar_wait(uint32_t bar, uint32_t parity) {
    uint32_t ok; int it = 0;
    do {
        asm volatile("{ .reg .pred p; mbarrier.try_wait.parity.shared::cta.b64 p, [%1], %2; selp.u32 %0, 1, 0, p; }"
                     : "=r"(ok) : "r"(bar), "r"(parity) : "memory");
        if (++it > kSpinLimit) { TIMEOUT((bar & 1023) >> 3); break; }
    } while (!ok);
}
__device__ __forceinline__ bool mbar_try(uint32_t bar, uint32_t parity) {
    uint32_t ok;
    asm volatile("{ .reg .pred p; mbarrier.try_wait.parity.shared::cta.b64 p, [%1], %2; selp.u32 %0, 1, 0, p; }" : "=r"(ok) : "r"(bar), "r"(parity) : "memory");
    return ok;
}
__device__ __forceinline__ bool mbar_test(uint32_t bar, uint32_t parity) {
    uint32_t ok;
    asm volatile("{ .reg .pred p; mbarrier.test_wait.parity.shared::cta.b64 p, [%1], %2; selp.u32 %0, 1, 0, p; }" : "=r"(ok) : "r"(bar), "r"(parity) : "memory");
    return ok;
}
__device__ __forceinline__ void mbar_wait_fast(uint32_t bar, uint32_t parity) { if (!mbar_try(bar, parity)) mbar_wait(bar, parity); }
__device__ __forceinline__ void mbar_wait2(uint32_t bar0, uint32_t par0, uint32_t bar1, uint32_t par1) {
    uint32_t ok; int it = 0;
    do {
        asm volatile("{ .reg .pred p, q; mbarrier.try_wait.parity.shared::cta.b64 p, [%1], %2;\n"
                     "mbarrier.try_wait.parity.shared::cta.b64 q, [%3], %4; and.pred p, p, q; selp.u32 %0, 1, 0, p; }"
                     : "=r"(ok) : "r"(bar0), "r"(par0), "r"(bar1), "r"(par1) : "memory");
        if (++it > kSpinLimit) { TIMEOUT((bar0 & 1023) >> 3); break; }
    } while (!ok);
}
__device__ __forceinline__ void sched_fence(uint32_t v) {
    asm volatile("{ .reg .pred p; .reg .b32 x; mov.b32 x, %0;\nL: setp.eq.u32 p, x, 0xffffffff; @p mov.u32 x, %%clock; @p bra L; }" :: "r"(v) : "memory");
}
template <int N> __device__ __forceinline__ void reg_fence(float (&d)[N]) {
    #pragma unroll
    for (int i = 0; i < N; i++) asm volatile("" : "+f"(d[i]) :: "memory");
}
__device__ __forceinline__ void mbar_wait_cluster(uint32_t bar, uint32_t parity) {
    uint32_t ok; int it = 0;
    do {
        asm volatile("{ .reg .pred p; mbarrier.try_wait.parity.acquire.cluster.shared::cta.b64 p, [%1], %2; selp.u32 %0, 1, 0, p; }"
                     : "=r"(ok) : "r"(bar), "r"(parity) : "memory");
        if (++it > kSpinLimit) { TIMEOUT((bar & 1023) >> 3); break; }
    } while (!ok);
}
__device__ __forceinline__ void mbar_arrive_if(uint32_t bar, bool pred) {
    asm volatile("{ .reg .pred p; setp.ne.u32 p, %1, 0; @p mbarrier.arrive.shared::cta.b64 _, [%0]; }" :: "r"(bar), "r"((uint32_t)pred) : "memory");
}
template <int P> __device__ __forceinline__ void tick() {
    if (P > 1) { const uint32_t t = ((uint32_t)clock() | (P - 1)) + 1; while ((int)((uint32_t)clock() - t) < 0) {} }
}
__device__ __forceinline__ void warp_arrive(uint32_t bar) { __syncwarp(); if (elect_one()) mbar_arrive(bar); }
__device__ __forceinline__ void tma2d(uint32_t dst, const CUtensorMap* m, int c0, int c1, uint32_t bar) {
    asm volatile("cp.async.bulk.tensor.2d.shared::cluster.global.mbarrier::complete_tx::bytes [%0], [%1, {%3, %4}], [%2];"
                 :: "r"(dst), "l"(m), "r"(bar), "r"(c0), "r"(c1) : "memory");
}
__device__ __forceinline__ void tma3d(uint32_t dst, const CUtensorMap* m, int c0, int c1, int c2, uint32_t bar) {
    asm volatile("cp.async.bulk.tensor.3d.shared::cluster.global.mbarrier::complete_tx::bytes [%0], [%1, {%3, %4, %5}], [%2];"
                 :: "r"(dst), "l"(m), "r"(bar), "r"(c0), "r"(c1), "r"(c2) : "memory");
}
__device__ __forceinline__ void tma2d_mc(uint32_t dst, const CUtensorMap* m, int c0, int c1, uint32_t bar) {
    asm volatile("cp.async.bulk.tensor.2d.shared::cluster.global.mbarrier::complete_tx::bytes.multicast::cluster [%0], [%1, {%3, %4}], [%2], %5;"
                 :: "r"(dst), "l"(m), "r"(bar), "r"(c0), "r"(c1), "h"((uint16_t)3) : "memory");
}
__device__ __forceinline__ void bulk_g2s_mc(uint32_t dst, const void* src, uint32_t bytes, uint32_t bar) {
    asm volatile("cp.async.bulk.shared::cluster.global.mbarrier::complete_tx::bytes.multicast::cluster [%0], [%1], %2, [%3], %4;"
                 :: "r"(dst), "l"(src), "r"(bytes), "r"(bar), "h"((uint16_t)3) : "memory");
}
__device__ __forceinline__ void mbar_arrive_remote_if(uint32_t cluster_bar, bool pred) {
    asm volatile("{ .reg .pred p; setp.ne.u32 p, %1, 0; @p mbarrier.arrive.shared::cluster.b64 _, [%0]; }" :: "r"(cluster_bar), "r"((uint32_t)pred) : "memory");
}
__device__ __forceinline__ void bulk_g2s(uint32_t dst, const void* src, uint32_t bytes, uint32_t bar) {
    asm volatile("cp.async.bulk.shared::cluster.global.mbarrier::complete_tx::bytes [%0], [%1], %2, [%3];"
                 :: "r"(dst), "l"(src), "r"(bytes), "r"(bar) : "memory");
}
__device__ __forceinline__ void bulk_prefetch(const void* src, uint32_t bytes) { asm volatile("cp.async.bulk.prefetch.L2.global [%0], %1;" :: "l"(src), "r"(bytes) : "memory"); }
__device__ __forceinline__ void wg_fence()  { asm volatile("wgmma.fence.sync.aligned;" ::: "memory"); }
__device__ __forceinline__ void wg_commit() { asm volatile("wgmma.commit_group.sync.aligned;" ::: "memory"); }
template <int N> __device__ __forceinline__ void wg_wait() { asm volatile("wgmma.wait_group.sync.aligned %0;" :: "n"(N) : "memory"); }
__device__ __forceinline__ void named_bar(int id, int n) { asm volatile("bar.sync %0, %1;" :: "r"(id), "r"(n) : "memory"); }
__device__ __forceinline__ void named_arrive(int id, int n) { asm volatile("bar.arrive %0, %1;" :: "r"(id), "r"(n) : "memory"); }
__device__ __forceinline__ bool mbar_try2(uint32_t bar0, uint32_t par0, uint32_t bar1, uint32_t par1) {
    uint32_t ok;
    asm volatile("{ .reg .pred p, q; mbarrier.test_wait.parity.shared::cta.b64 p, [%1], %2;\n"
                 "mbarrier.test_wait.parity.shared::cta.b64 q, [%3], %4; and.pred p, p, q; selp.u32 %0, 1, 0, p; }"
                 : "=r"(ok) : "r"(bar0), "r"(par0), "r"(bar1), "r"(par1) : "memory");
    return ok;
}
__device__ __forceinline__ void fence_gpu() { asm volatile("fence.release.gpu;" ::: "memory"); }
__device__ __forceinline__ void fence_async_global() { asm volatile("fence.proxy.async.global;" ::: "memory"); }
__device__ __forceinline__ void fence_async_smem() { asm volatile("fence.proxy.async.shared::cta;" ::: "memory"); }
__device__ __forceinline__ uint32_t gtime32() { uint64_t t; asm volatile("mov.u64 %0, %%globaltimer;" : "=l"(t) :: "memory"); return (uint32_t)t; }
__device__ __forceinline__ uint32_t clk32() { uint64_t t; asm volatile("mov.u64 %0, %%clock64;" : "=l"(t) :: "memory"); return (uint32_t)t; }
__device__ __forceinline__ void spin_until(uint32_t t) { while ((int)(clk32() - t) < 0) {} }
#define SLEEPNS 20
__device__ __forceinline__ void sleep_until(uint32_t t) { while ((int)(clk32() - t) < 0) { if (SLEEPNS) __nanosleep(SLEEPNS); } }
__device__ __forceinline__ void st_flag(uint32_t* p, uint32_t v, uint32_t time) {
    const uint64_t w = ((uint64_t)time << 32) | v;
    asm volatile("st.relaxed.gpu.global.u64 [%0], %1;" :: "l"(p), "l"(w) : "memory");
}
__device__ __forceinline__ void ld_flag_if(uint64_t& v, const uint32_t* p, bool pred) {
    asm volatile("{ .reg .pred p; setp.ne.u32 p, %2, 0; @p ld.relaxed.gpu.global.u64 %0, [%1]; }" : "+l"(v) : "l"(p), "r"((uint32_t)pred) : "memory");
}
__device__ __forceinline__ uint32_t ld_acq(const uint32_t* p) { uint32_t v; asm volatile("ld.acquire.gpu.global.u32 %0, [%1];" : "=r"(v) : "l"(p) : "memory"); return v; }
__device__ __forceinline__ uint32_t ld_rlx(const uint32_t* p) { uint32_t v; asm volatile("ld.relaxed.gpu.global.u32 %0, [%1];" : "=r"(v) : "l"(p) : "memory"); return v; }
template <class T> __device__ __forceinline__ T* opaque_ptr(T* p) { asm volatile("" : "+l"(p)); return p; }
__device__ __forceinline__ uint4 ld_rlx4(const uint4* p) {
    uint4 v; asm volatile("ld.relaxed.gpu.global.v4.u32 {%0,%1,%2,%3}, [%4];" : "=r"(v.x), "=r"(v.y), "=r"(v.z), "=r"(v.w) : "l"(p) : "memory"); return v;
}
__device__ __forceinline__ void st_ll(uint4* p, uint32_t a, uint32_t b, uint32_t tag) {
    uint64_t lo = ((uint64_t)tag << 32) | a, hi = ((uint64_t)tag << 32) | b;
    asm volatile("st.relaxed.gpu.global.v2.u64 [%0], {%1,%2};" :: "l"(p), "l"(lo), "l"(hi) : "memory");
}
__device__ __forceinline__ bool ld_ll(const uint4* p, uint32_t& a, uint32_t& b, uint32_t tag) {
    uint64_t lo, hi;
    asm volatile("ld.relaxed.gpu.global.v2.u64 {%0,%1}, [%2];" : "=l"(lo), "=l"(hi) : "l"(p) : "memory");
    a = (uint32_t)lo; b = (uint32_t)hi;
    return (uint32_t)(lo >> 32) == tag && (uint32_t)(hi >> 32) == tag;
}
__device__ __forceinline__ uint2 ld_acq2(const uint2* p) {
    uint2 v; asm volatile("ld.acquire.gpu.global.v2.u32 {%0,%1}, [%2];" : "=r"(v.x), "=r"(v.y) : "l"(p) : "memory"); return v;
}
__device__ __forceinline__ uint2 ld_rlx2(const uint2* p) {
    uint2 v; asm volatile("ld.relaxed.gpu.global.v2.u32 {%0,%1}, [%2];" : "=r"(v.x), "=r"(v.y) : "l"(p) : "memory"); return v;
}
__device__ __forceinline__ void stg1(uint32_t* p, uint32_t v) { asm volatile("st.global.u32 [%0], %1;" :: "l"(p), "r"(v) : "memory"); }
__device__ __forceinline__ void stg2(void* p, uint32_t x, uint32_t y) { asm volatile("st.global.v2.u32 [%0], {%1,%2};" :: "l"(p), "r"(x), "r"(y) : "memory"); }
__device__ __forceinline__ void stg4(void* p, uint32_t x, uint32_t y, uint32_t z, uint32_t w) { asm volatile("st.global.v4.u32 [%0], {%1,%2,%3,%4};" :: "l"(p), "r"(x), "r"(y), "r"(z), "r"(w) : "memory"); }
__device__ __forceinline__ uint32_t lds1(uint32_t a) { uint32_t v; asm volatile("ld.shared.u32 %0, [%1];" : "=r"(v) : "r"(a) : "memory"); return v; }
__device__ __forceinline__ uint2 lds2(uint32_t a) { uint2 v; asm volatile("ld.shared.v2.u32 {%0,%1}, [%2];" : "=r"(v.x), "=r"(v.y) : "r"(a) : "memory"); return v; }
__device__ __forceinline__ uint32_t set_par(uint32_t v, uint32_t mask, uint32_t par) {
    uint32_t r; asm("lop3.b32 %0, %1, %2, %3, 0xb8;" : "=r"(r) : "r"(v), "r"(mask), "r"(par)); return r;
}
__device__ __forceinline__ void st_gen4(void* p, uint32_t x, uint32_t y, uint32_t z, uint32_t w) { asm volatile("st.v4.u32 [%0], {%1,%2,%3,%4};" :: "l"(p), "r"(x), "r"(y), "r"(z), "r"(w) : "memory"); }
__device__ __forceinline__ float tanh_hw(float x) { float r; asm("tanh.approx.f32 %0, %1;" : "=f"(r) : "f"(x)); return r; }
__device__ __forceinline__ bool bar_any(int id, int n, bool v) {
    uint32_t r;
    asm volatile("{ .reg .pred p, q; setp.ne.u32 p, %3, 0; bar.red.or.pred q, %1, %2, p; selp.u32 %0, 1, 0, q; }" : "=r"(r) : "r"(id), "r"(n), "r"((uint32_t)v) : "memory");
    return r;
}
__device__ __forceinline__ void sts4(uint32_t a, uint32_t x, uint32_t y, uint32_t z, uint32_t w) { asm volatile("st.shared.v4.u32 [%0], {%1,%2,%3,%4};" :: "r"(a), "r"(x), "r"(y), "r"(z), "r"(w) : "memory"); }
__device__ __forceinline__ uint4 lds4(uint32_t a) { uint4 v; asm volatile("ld.shared.v4.u32 {%0,%1,%2,%3}, [%4];" : "=r"(v.x), "=r"(v.y), "=r"(v.z), "=r"(v.w) : "r"(a) : "memory"); return v; }
__device__ __forceinline__ uint32_t pack_bf16(float lo, float hi) { uint32_t r; asm("cvt.rn.bf16x2.f32 %0, %1, %2;" : "=r"(r) : "f"(hi), "f"(lo)); return r; }
__device__ __forceinline__ float bf_lo(uint32_t v) { return __uint_as_float(v << 16); }
__device__ __forceinline__ float bf_hi(uint32_t v) { return __uint_as_float(v & 0xffff0000u); }
__device__ __forceinline__ uint32_t sub_bf16x2(uint32_t a, uint32_t b) { uint32_t r; asm volatile("sub.rn.bf16x2 %0, %1, %2;" : "=r"(r) : "r"(a), "r"(b)); return r; }
__device__ __forceinline__ uint32_t add_bf16x2(uint32_t a, uint32_t b) { uint32_t r; asm volatile("add.rn.bf16x2 %0, %1, %2;" : "=r"(r) : "r"(a), "r"(b)); return r; }
__device__ __forceinline__ uint32_t sqr_bf16x2(uint32_t a) { uint32_t r; asm volatile("mul.rn.bf16x2 %0, %1, %1;" : "=r"(r) : "r"(a)); return r; }
__device__ __forceinline__ uint32_t sqa_bf16x2(uint32_t a, uint32_t c) { uint32_t r; asm volatile("fma.rn.bf16x2 %0, %1, %1, %2;" : "=r"(r) : "r"(a), "r"(c)); return r; }
__device__ __forceinline__ uint32_t movm(uint32_t a) { uint32_t r; asm volatile("movmatrix.sync.aligned.m8n8.trans.b16 %0, %1;" : "=r"(r) : "r"(a)); return r; }
__device__ __forceinline__ float ex2(float x) { float r; asm("ex2.approx.ftz.f32 %0, %1;" : "=f"(r) : "f"(x)); return r; }
__device__ __forceinline__ float rsq(float x) { float r; asm("rsqrt.approx.ftz.f32 %0, %1;" : "=f"(r) : "f"(x)); return r; }
__device__ __forceinline__ float rcp(float x) { float r; asm("rcp.approx.ftz.f32 %0, %1;" : "=f"(r) : "f"(x)); return r; }
__device__ __forceinline__ void mma16816(float (&c)[4], uint32_t a0, uint32_t a1, uint32_t a2, uint32_t a3, uint32_t b0, uint32_t b1) {
    asm("mma.sync.aligned.m16n8k16.row.col.f32.bf16.bf16.f32 {%0,%1,%2,%3}, {%4,%5,%6,%7}, {%8,%9}, {%0,%1,%2,%3};"
        : "+f"(c[0]), "+f"(c[1]), "+f"(c[2]), "+f"(c[3]) : "r"(a0), "r"(a1), "r"(a2), "r"(a3), "r"(b0), "r"(b1));
}
__device__ __forceinline__ void mma1688(float (&c)[4], uint32_t a0, uint32_t a1, uint32_t b0) {
    asm("mma.sync.aligned.m16n8k8.row.col.f32.bf16.bf16.f32 {%0,%1,%2,%3}, {%4,%5}, {%6}, {%0,%1,%2,%3};"
        : "+f"(c[0]), "+f"(c[1]), "+f"(c[2]), "+f"(c[3]) : "r"(a0), "r"(a1), "r"(b0));
}
__device__ __forceinline__ float quad_sum(float v) { v += __shfl_xor_sync(~0u, v, 1); v += __shfl_xor_sync(~0u, v, 2); return v; }
__device__ __forceinline__ float quad_max(float v) { v = fmaxf(v, __shfl_xor_sync(~0u, v, 1)); v = fmaxf(v, __shfl_xor_sync(~0u, v, 2)); return v; }
__device__ __forceinline__ uint64_t make_desc(uint32_t addr, uint32_t lbo, bool swz, uint32_t sbo = 1024) {
    const uint32_t lo = __shfl_sync(~0u, ((addr & 0x3FFFF) >> 4) | ((lbo >> 4) << 16), 0);
    const uint32_t hi = __shfl_sync(~0u, (swz ? 0x40000000u : 0u) + (sbo >> 4) + (threadIdx.x & 31), 0);
    return ((uint64_t)hi << 32) | lo;
}
template <int I, int N, class F> __device__ __forceinline__ void static_for(F&& f) {
    if constexpr (I < N) { f(std::integral_constant<int, I>{}); static_for<I + 1, N>(f); }
}
__device__ __forceinline__ uint32_t opaque(uint32_t v) { asm volatile("" : "+r"(v)); return v; }
template <int BOFF, int SCALE_D>
__device__ __forceinline__ void wgmma_rs_n56(float (&d)[28], uint32_t a0, uint32_t a1, uint32_t a2, uint32_t a3, uint64_t db) {
    asm volatile("{ .reg .b64 db; add.s64 db, %32, %33;\n"
        "wgmma.mma_async.sync.aligned.m64n56k16.f32.bf16.bf16 "
        "{%0, %1, %2, %3, %4, %5, %6, %7, %8, %9, %10, %11, %12, %13, %14, %15, %16, %17, %18, %19, %20, %21, %22, %23, %24, %25, %26, %27}, "
        "{%28, %29, %30, %31}, db, %34, 1, 1, 1; }"
        : "+f"(d[0]), "+f"(d[1]), "+f"(d[2]), "+f"(d[3]), "+f"(d[4]), "+f"(d[5]), "+f"(d[6]), "+f"(d[7]),
        "+f"(d[8]), "+f"(d[9]), "+f"(d[10]), "+f"(d[11]), "+f"(d[12]), "+f"(d[13]), "+f"(d[14]), "+f"(d[15]),
        "+f"(d[16]), "+f"(d[17]), "+f"(d[18]), "+f"(d[19]), "+f"(d[20]), "+f"(d[21]), "+f"(d[22]), "+f"(d[23]),
        "+f"(d[24]), "+f"(d[25]), "+f"(d[26]), "+f"(d[27])
        : "r"(a0), "r"(a1), "r"(a2), "r"(a3), "l"(db), "n"(BOFF >> 4), "n"(SCALE_D));
}
template <int AOFF, int BOFF, int MMAJOR>
__device__ __forceinline__ void wgmma_ss_n56(float (&d)[28], uint64_t da, uint64_t db) {
    asm volatile("{ .reg .b64 da, db; add.s64 da, %28, %30; add.s64 db, %29, %31;\n"
        "wgmma.mma_async.sync.aligned.m64n56k16.f32.bf16.bf16 "
        "{%0, %1, %2, %3, %4, %5, %6, %7, %8, %9, %10, %11, %12, %13, %14, %15, %16, %17, %18, %19, %20, %21, %22, %23, %24, %25, %26, %27}, "
        "da, db, 1, 1, 1, %32, 1; }"
        : "+f"(d[0]), "+f"(d[1]), "+f"(d[2]), "+f"(d[3]), "+f"(d[4]), "+f"(d[5]), "+f"(d[6]), "+f"(d[7]),
        "+f"(d[8]), "+f"(d[9]), "+f"(d[10]), "+f"(d[11]), "+f"(d[12]), "+f"(d[13]), "+f"(d[14]), "+f"(d[15]),
        "+f"(d[16]), "+f"(d[17]), "+f"(d[18]), "+f"(d[19]), "+f"(d[20]), "+f"(d[21]), "+f"(d[22]), "+f"(d[23]),
        "+f"(d[24]), "+f"(d[25]), "+f"(d[26]), "+f"(d[27])
        : "l"(da), "l"(db), "n"(AOFF >> 4), "n"(BOFF >> 4), "n"(MMAJOR));
}
template <int AOFF, int BOFF, int MMAJOR>
__device__ __forceinline__ void wgmma_ss_n112(float (&d)[28], float (&e)[28], uint64_t da, uint64_t db) {
    asm volatile("{ .reg .b64 da, db; add.s64 da, %56, %58; add.s64 db, %57, %59;\n"
        "wgmma.mma_async.sync.aligned.m64n112k16.f32.bf16.bf16 "
        "{%0, %1, %2, %3, %4, %5, %6, %7, %8, %9, %10, %11, %12, %13, %14, %15, %16, %17, %18, %19, %20, %21, %22, %23, %24, %25, %26, %27, %28, %29, %30, %31, %32, %33, %34, %35, %36, %37, %38, %39, %40, %41, %42, %43, %44, %45, %46, %47, %48, %49, %50, %51, %52, %53, %54, %55}, "
        "da, db, 1, 1, 1, %60, 1; }"
        : "+f"(d[0]), "+f"(d[1]), "+f"(d[2]), "+f"(d[3]), "+f"(d[4]), "+f"(d[5]), "+f"(d[6]), "+f"(d[7]),
        "+f"(d[8]), "+f"(d[9]), "+f"(d[10]), "+f"(d[11]), "+f"(d[12]), "+f"(d[13]), "+f"(d[14]), "+f"(d[15]),
        "+f"(d[16]), "+f"(d[17]), "+f"(d[18]), "+f"(d[19]), "+f"(d[20]), "+f"(d[21]), "+f"(d[22]), "+f"(d[23]),
        "+f"(d[24]), "+f"(d[25]), "+f"(d[26]), "+f"(d[27]), "+f"(e[0]), "+f"(e[1]), "+f"(e[2]), "+f"(e[3]),
        "+f"(e[4]), "+f"(e[5]), "+f"(e[6]), "+f"(e[7]), "+f"(e[8]), "+f"(e[9]), "+f"(e[10]), "+f"(e[11]),
        "+f"(e[12]), "+f"(e[13]), "+f"(e[14]), "+f"(e[15]), "+f"(e[16]), "+f"(e[17]), "+f"(e[18]), "+f"(e[19]),
        "+f"(e[20]), "+f"(e[21]), "+f"(e[22]), "+f"(e[23]), "+f"(e[24]), "+f"(e[25]), "+f"(e[26]), "+f"(e[27])
        : "l"(da), "l"(db), "n"(AOFF >> 4), "n"(BOFF >> 4), "n"(MMAJOR));
}
template <int BOFF, int SCALE_D>
__device__ __forceinline__ void wgmma_rs_n112(float (&d)[28], float (&e)[28], uint32_t a0, uint32_t a1, uint32_t a2, uint32_t a3, uint64_t db) {
    asm volatile("{ .reg .b64 db; add.s64 db, %60, %61;\n"
        "wgmma.mma_async.sync.aligned.m64n112k16.f32.bf16.bf16 "
        "{%0, %1, %2, %3, %4, %5, %6, %7, %8, %9, %10, %11, %12, %13, %14, %15, %16, %17, %18, %19, %20, %21, %22, %23, %24, %25, %26, %27, %28, %29, %30, %31, %32, %33, %34, %35, %36, %37, %38, %39, %40, %41, %42, %43, %44, %45, %46, %47, %48, %49, %50, %51, %52, %53, %54, %55}, "
        "{%56, %57, %58, %59}, db, %62, 1, 1, 1; }"
        : "+f"(d[0]), "+f"(d[1]), "+f"(d[2]), "+f"(d[3]), "+f"(d[4]), "+f"(d[5]), "+f"(d[6]), "+f"(d[7]),
        "+f"(d[8]), "+f"(d[9]), "+f"(d[10]), "+f"(d[11]), "+f"(d[12]), "+f"(d[13]), "+f"(d[14]), "+f"(d[15]),
        "+f"(d[16]), "+f"(d[17]), "+f"(d[18]), "+f"(d[19]), "+f"(d[20]), "+f"(d[21]), "+f"(d[22]), "+f"(d[23]),
        "+f"(d[24]), "+f"(d[25]), "+f"(d[26]), "+f"(d[27]), "+f"(e[0]), "+f"(e[1]), "+f"(e[2]), "+f"(e[3]),
        "+f"(e[4]), "+f"(e[5]), "+f"(e[6]), "+f"(e[7]), "+f"(e[8]), "+f"(e[9]), "+f"(e[10]), "+f"(e[11]),
        "+f"(e[12]), "+f"(e[13]), "+f"(e[14]), "+f"(e[15]), "+f"(e[16]), "+f"(e[17]), "+f"(e[18]), "+f"(e[19]),
        "+f"(e[20]), "+f"(e[21]), "+f"(e[22]), "+f"(e[23]), "+f"(e[24]), "+f"(e[25]), "+f"(e[26]), "+f"(e[27])
        : "r"(a0), "r"(a1), "r"(a2), "r"(a3), "l"(db), "n"(BOFF >> 4), "n"(SCALE_D));
}

struct Params {
    const __nv_bfloat16 *x, *wqkv;
    Scratch* sc;
    const __nv_bfloat16 *wo, *w1, *w2, *b1, *b2;
    __nv_bfloat16* out;
};

__global__ void __cluster_dims__(2, 1, 1) __launch_bounds__(384, 1)
fused_kernel(const Params prm, const __grid_constant__ CUtensorMap mX2, const __grid_constant__ CUtensorMap mX, const __grid_constant__ CUtensorMap mWqkv,
             const __grid_constant__ CUtensorMap mWo, const __grid_constant__ CUtensorMap mW1,
             const __grid_constant__ CUtensorMap mW2)
{
    extern __shared__ __align__(1024) unsigned char smem_raw[];
    if (threadIdx.x < 126) {
        const uint32_t i = threadIdx.x, t = clk32() + (i >> 5) * PFD;
        const char* px = (const char*)prm.x + (blockIdx.x * 16 + (i & 15)) * 896 + (i >> 4) * 128;
        const char* pw = (const char*)prm.wqkv + blockIdx.x * 2688 + i * 128 + (896 - 112 * 128);
        spin_until(t);
        asm volatile("prefetch.global.L2 [%0];" :: "l"(i < 112 ? px : pw) : "memory");
    }
    if (threadIdx.x == 128) { asm volatile("prefetch.tensormap [%0];" :: "l"(&mX2) : "memory"); asm volatile("prefetch.tensormap [%0];" :: "l"(&mWqkv) : "memory"); }
    uint32_t sb = (uint32_t)__cvta_generic_to_shared(smem_raw);
    asm volatile("mov.u32 %0, %0;" : "+r"(sb));
    const uint32_t bar0 = sb + SM_BAR;
    auto BAR = [&](int i) { return bar0 + 8u * i; };

    const int tid = threadIdx.x, lane = tid & 31;
    const int warp = __shfl_sync(~0u, tid >> 5, 0);
    const int b = __shfl_sync(~0u, (int)blockIdx.x, 0);
    const int rank = b & 1;
    const int cl = (b >> 1) - 4, cq = ((cl - 32) * 37) >> 8;
    const int res = cl < 0 ? 0 : cl < 32 ? cl & 7 : cl - 31 - 7 * cq;
    const int rnd = cl < 0 ? cl + 8 : cl < 32 ? cl >> 3 : 4 + cq;
    const int hg = (res & 1) * 4 + (rnd & 3);
    const int ti = (res >> 1) * 4 + (rnd >> 2) * 2 + rank;
    const int a2p = res & 1, a2j = rnd & 3;
    const int a2s = ti * 2 + a2p;
    const bool g1_on = rnd != 7;
    const int g1j = (rnd < 6 ? rnd : res) & 1, g1f = rnd < 6 ? res * 3 + (rnd >> 1) : 24 + (res >> 1);
    const int g2j = rnd & 1, g2s = res * 4 + (rnd >> 1);
    uint32_t pbar0;
    asm volatile("mapa.shared::cluster.u32 %0, %1, %2;" : "=r"(pbar0) : "r"(bar0), "r"(rank ^ 1));
    auto pair_arrive = [&](int i) { __syncwarp(); const bool l = elect_one(); mbar_arrive_if(BAR(i), l); mbar_arrive_remote_if(pbar0 + 8u * i, l); };
    const int wcol = hg * 56 - (hg & 1) * 8;

    if (warp == 8) {
        if (elect_one()) {
            #pragma unroll
            for (int i = 0; i < B_WQF; i++) mbar_init(BAR(i), 1);
            asm volatile("fence.mbarrier_init.release.cluster;" ::: "memory");
            fence_async_smem();
            #pragma unroll
            for (int kb = 0; kb < 7 - XLATE; kb++) {
                tma3d(sb + kb * 16384, &mX2, kb * 64, ti * 64, 0, BAR(B_XF + kb));
                mbar_expect(BAR(B_XF + kb), 16384);
                if (kb == 0 && PFX != 3) asm volatile("prefetch.tensormap [%0];" :: "l"(&mWqkv) : "memory");
            }
        }
    } else if (warp > 8) {
        if (elect_one()) {
            if (warp == 9) {
                #pragma unroll
                for (int i = B_WQF; i < B_AF; i++) mbar_init(BAR(i), i < B_XC ? 1 : i < B_A1D ? 16 : i < B_BE ? 8 : 4);
            } else if (warp == 10) {
                #pragma unroll
                for (int i = B_AF; i < B_BF; i++) mbar_init(BAR(i), 1);
            } else {
                #pragma unroll
                for (int i = B_BF; i < B_COUNT; i++) mbar_init(BAR(i), i == B_HD ? 8 : 1);
            }
            asm volatile("fence.mbarrier_init.release.cluster;" ::: "memory");
            fence_async_smem();
        }
    }
    __syncwarp();
    __syncthreads();
    asm volatile("barrier.cluster.arrive.relaxed.aligned;" ::: "memory");
    if (tid < 256) TR(0);
    if (tid == 0) TRG(61);

    if (warp >= 8) {
        asm volatile("setmaxnreg.dec.sync.aligned.u32 40;");
        asm volatile("barrier.cluster.wait.aligned;" ::: "memory");
        auto fetch_halo = [&](int p, uint32_t tag) {
            const uint32_t hl = BAR(B_HL + p), dst = opaque(sb + SM_STG + p * 8192 + 3 * 2048 + lane * 16);
            const bool lead = elect_one();
            if (rank) { if (lead) mbar_expect(hl, 2048); __syncwarp(); return; }
            const uint4* hp = opaque_ptr(&prm.sc->halo[((((ti >> 1) - 1) * 8 + hg) * 2 + p) * 128 + lane]);
            mbar_wait(BAR(B_KVC), 0);
            if (p == 0) TRW(51);
            if (ti > 0) {
                spin_until(clk32() + HDELAY);
                int it = 0;
                uint32_t bad;
                do {
                    uint4 u[4];
                    #pragma unroll
                    for (int c = 0; c < 4; c++) u[c] = ld_rlx4(hp + c * 32);
                    #pragma unroll
                    for (int c = 0; c < 4; c++) sts4(dst + c * 512, u[c].x, u[c].y, u[c].z, u[c].w);
                    bad = ((u[0].x ^ tag) | (u[1].x ^ tag) | (u[2].x ^ tag) | (u[3].x ^ tag)) & ~lane & 1;
                    if (it) RETRY_COUNT(4);
                } while (__any_sync(~0u, bad) && ++it < kSpinLimit);
                if (it == kSpinLimit) TIMEOUT(101);
            } else {
                #pragma unroll
                for (int c = 0; c < 4; c++) sts4(dst + c * 512, 0u, 0u, 0u, 0u);
            }
            __syncwarp();
            mbar_arrive_if(hl, lead);
        };
        auto poll_flags = [&](const uint32_t* fp, int step, uint32_t tag, uint32_t gbase) {
            uint64_t v0 = 0, v1 = 0;
            int it = 0;
            do {
                ld_flag_if(v0, fp, (uint32_t)v0 != tag); ld_flag_if(v1, fp + step, (uint32_t)v1 != tag);
                if (++it > kSpinLimit) { TIMEOUT(108); break; }
            } while (__any_sync(~0u, (uint32_t)v0 != tag || (uint32_t)v1 != tag));
            return max((int)((uint32_t)(v0 >> 32) - gbase), (int)((uint32_t)(v1 >> 32) - gbase));
        };
        if (warp & 1) {
            uint32_t tag;
            if (warp == 11) {
                tag = *(volatile uint32_t*)&prm.sc->epoch + 1;
            #pragma unroll 1
            for (int i = 0; i < 8 * rank; i++) prm.sc->halo[((ti >> 1) * 8 + hg) * 256 + i * 32 + lane] = make_uint4(~tag, 0u, 0u, 0u);
            ((uint4*)prm.sc->stats)[(a2s * 4 + a2j) * 64 + lane] = ((uint4*)prm.sc->stats)[(a2s * 4 + a2j) * 64 + 32 + lane] = make_uint4(~tag, ~tag, ~tag, ~tag);
            prm.sc->flag_h[(a2s * 4 + a2j) * FS + lane] = 0;
            prm.sc->flag_o[(ti * 8 + hg) * FS + lane] = 0;
            __syncwarp();
            if (lane == 0) {
                asm volatile("st.shared.v2.u32 [%0], {%1, %2};" :: "r"(sb + SM_EPOCH), "r"(tag), "r"(gtime32()) : "memory");
                mbar_arrive(BAR(B_EP));
            }
            if (lane < 8) mbar_expect(BAR(B_RF + lane), 1792);
            __syncwarp();
            TRW(44);
            } else {
                mbar_wait(BAR(B_EP), 0);
                tag = lds1(sb + SM_EPOCH);
            }
            fetch_halo((warp >> 1) & 1, tag);
        }
        if (warp < 10) {
          auto load_slab = [&](int s, bool second) {
              if (!second) tma2d(sb + s * 8192, &mW1, (s & 1) * kF + g1f * 64, (rank * 8 + (s >> 1)) * 64, BAR(B_AF));
              else         tma2d(sb + s * 8192, &mW2, g2s * 64, (rank * 14 + s - 1) * 64, BAR(B_AF));
          };
          const char* pw2 = (const char*)prm.w2 + ((b >> 6) * 896 + (b & 63) + PFW * 64) * 4096;
          if (warp == 8) {
            if (elect_one()) {
                #pragma unroll 1
                for (int s = 0; s < 7; s++) {
                    mbar_expect(BAR(B_WKVF + s), 16384);
                    tma2d_mc(sb + SM_WKV + s * 16384 + rank * 8192, &mWqkv, (1 + rank) * kD + wcol, s * 64, BAR(B_WKVF + s));
                    if (s == 0) {
                        #pragma unroll
                        for (int kb = 7 - XLATE; kb < 7; kb++) {
                            tma3d(sb + kb * 16384, &mX2, kb * 64, ti * 64, 0, BAR(B_XF + kb));
                            mbar_expect(BAR(B_XF + kb), 16384);
                        }
                    }
                }
            }
            __syncwarp();
            mbar_wait(BAR(B_XC), 0);
            if (elect_one()) {
                asm volatile("prefetch.tensormap [%0];" :: "l"(&mX) : "memory");
                asm volatile("prefetch.tensormap [%0];" :: "l"(&mWo) : "memory");
                asm volatile("prefetch.tensormap [%0];" :: "l"(&mW1) : "memory");
                asm volatile("prefetch.tensormap [%0];" :: "l"(&mW2) : "memory");
                mbar_expect(BAR(B_AF), (g1_on ? NPRE : 14) * 8192);
                mbar_expect(BAR(B_WQF), 57344);
                #pragma unroll 1
                for (int s = rank; s < 7; s += 2) tma2d_mc(sb + SM_WQ + s * 8192, &mWqkv, wcol, s * 64, BAR(B_WQF));
                mbar_expect(BAR(B_XRF), 16384);
                tma2d(sb + SM_XR, &mX, a2p * kD + a2j * 112, ti * 64, BAR(B_XRF));
                tma2d(sb + SM_XR + 8192, &mX, a2p * kD + a2j * 112 + 48, ti * 64, BAR(B_XRF));
            }
            __syncwarp();
            #pragma unroll 1
            for (int q = 0; q < 4; q++) {
                mbar_wait(BAR(B_KV3 + (q >> 1)), 0);
                if (q == 2) spin_until(clk32() + WOD);
                if (q == WOQ) mbar_wait2(BAR(B_HL), 0, BAR(B_HL + 1), 0);
                if (elect_one()) {
                    if (!(q & 1)) mbar_expect(BAR(B_WOF + (q >> 1)), 57344);
                    tma2d_mc(sb + SM_WKV + q * 28672 + rank * 14336, &mWo, a2j * 112 + (q & 1) * 48, (q >> 1) * 224 + rank * 112, BAR(B_WOF + (q >> 1)));
                    if (g1_on && q == AFIRST) { load_slab(0, false); load_slab(1, false); load_slab(2, false); }
                }
                __syncwarp();
            }
            if (g1_on) {
                mbar_wait2(BAR(B_XD), 0, BAR(B_OL + 3), 0);
                #pragma unroll 1
                for (int i = 3; i < NPRE; i++) {
                    if (i == 7) mbar_wait(BAR(B_OC), 0);
                    if (elect_one()) load_slab(i, false);
                    __syncwarp();
                }
            } else {
                mbar_arrive_if(BAR((lane < 16 ? B_BE : B_BF) + (lane & 3)), lane < 20);
                mbar_wait(BAR(B_HD), 0);
                mbar_arrive_remote_if(pbar0 + 8u * B_PD, lane == 0);
                mbar_wait(BAR(B_GO), 0);
                uint32_t tg = lds1(sb + SM_TG + 4);
                tg += max((int)(lds1(sb + SM_TG2) - tg), 0);
                int it = 0;
                while ((int)(gtime32() - tg) < 0 && ++it < 256) {}
                const uint32_t t0 = clk32();
                if (lane < 2) {
                    asm volatile("st.shared.u32 [%0], %1;" :: "r"(sb + SM_TG + 8 + lane * 4), "r"(t0 + (lane ? CN3 : CN2)) : "memory");
                    mbar_arrive(BAR(B_GD + lane));
                }
                __syncwarp();
                #pragma unroll 1
                for (int s = 1; s < 15; s++) {
                    sleep_until(t0 + W2OFF + s * W2PACE);
                    if (elect_one()) { if (s < 15 - PFW) bulk_prefetch(pw2 + (s - 1) * 64 * 4096, 4096); load_slab(s, true); }
                    __syncwarp();
                }
            }
          } else {
            TRW(58);
            const uint32_t tag = lds1(sb + SM_EPOCH);
            if (lane < 4) mbar_expect(BAR(B_OL + lane), 14336);
            const uint32_t gbase = lds1(sb + SM_TG);
            const bool lead = elect_one();
            uint32_t* hfl = opaque_ptr(&prm.sc->flag_h[(a2s * 4 + a2j) * FS]);
            mbar_wait(BAR(B_A1D), 0);
            const int d = poll_flags(&prm.sc->flag_o[(ti * 8 + (lane & 3) * 2) * FS], FS, tag, gbase);
            TRW(53);
            int key = max(d + DELTAO, __reduce_max_sync(~0u, d) + DMIN) * 4 + (lane & 3);
            uint32_t order = 0;
            #pragma unroll 1
            for (int i = 0; i < 4; i++) {
                const int m = __reduce_min_sync(~0u, key);
                const uint4* src = &prm.sc->o[(a2s * 4 + (m & 3)) * 896];
                int it = 0;
                while ((int)(gtime32() - gbase) < m >> 2 && ++it < 256) {}
                if (lead) bulk_g2s(sb + SM_WQ + i * 14336, src, 14336, BAR(B_OL + i));
                if (key == m) key = 0x7fffffff;
                order |= (m & 3) << i * 2;
            }
            if (lead) {
                asm volatile("st.shared.u32 [%0], %1;" :: "r"(sb + SM_ORD), "r"(order) : "memory");
                mbar_arrive(BAR(B_OD));
            }
            __syncwarp();
            int t0 = 0;
            #pragma unroll 1
            for (int i = 0; i < 4; i++) { mbar_wait(BAR((i < ANN ? B_OF : B_OL) + i), 0); t0 = max(t0, (int)(gtime32() - gbase) - i * CHUNKNS); }
            if (lead) st_flag(hfl, tag, gbase + t0);
            __syncwarp();
            TRW(57);
          }
          if (elect_one()) {
              const int h = ~warp & 1;
              constexpr uint32_t T = 57344, BO = 2 * 14336;
              const char* src1 = (const char*)&prm.sc->hn[(rank * 16 + h) * 3584 + g1j * 896];
              const char* src2 = (const char*)&prm.sc->g[(rank * 14 + h) * 3584 + g2j * 896];
              uint64_t masks = g1_on ? (h ? kSegMasks1 : kSegMasks0) : 0x80 | 0x80 << 10;
              const uint32_t bl = BAR(B_BL + h * NB);
              uint32_t s8 = (g1_on ? NB - 2 + h : 4 + h) * 8, lap = 3, tmin = 0;
              const CUtensorMap* am = &mW1;
              uint32_t ad = sb + (NPRE + h) * 8192, astep = 16384; int ac0 = h * kF + g1f * 64, ac1 = (rank * 8 + NPRE / 2) * 64;
              CAP_DECL(ti_, 0);
              #pragma unroll 1
              for (int seg = g1_on ? 0 : 3; seg < 5; seg++) {
                  const char* src = (seg < 3 ? src1 : src2) + (~seg & 1) * BO;
                  uint32_t m = (uint32_t)masks & 0x3ff;
                  masks >>= 10;
                  const uint32_t pace = seg == 4 ? PACEB : seg == 3 ? PACEA : PACE2;
                  if (seg == 2) {
                      mbar_wait(BAR(B_PL), 0);
                      mbar_arrive_remote_if(pbar0 + 8u * B_PD, h);
                      am = &mW2; ad = sb + 8192; astep = 8192; ac0 = g2s * 64; ac1 = rank * 14 * 64;
                  } else {
                      const int gate = seg - (seg > 2);
                      mbar_wait(BAR(B_HD + gate), 0);
                      tmin = lds1(sb + SM_TG + gate * 4);
                      if (gate < 2) {
                          tmin += max((int)(lds1(gate ? sb + SM_TG2 : sb + SM_TG) - tmin), 0);
                          int it = 0;
                          while ((int)(gtime32() - tmin) < 0 && ++it < 256) {}
                          tmin = clk32();
                      }
                      tmin += h * PACE1;
                  }
                  #pragma unroll 1
                  do {
                      const uint32_t dst = sb + SM_B + s8 * 1792;
                      spin_until(tmin);
                      mbar_wait_fast(BAR(B_BE) + s8 + (lap & 1) * (NB * 8), lap >> 1 & 1);
                      if (seg) {
                          bulk_g2s(dst, src, 14336, bl + s8);
                          mbar_expect(bl + s8, 14336);
                          CAP(ti_);
                      }
                      tmin += pace;
                      src += 2 * T;
                      s8 += 16;
                      if (s8 >= NB * 8) { s8 -= NB * 8; lap++; }
                      if (m & 1) {
                          mbar_expect_more(bl + s8, 8192);
                          tma2d(ad, am, ac0, ac1, bl + s8);
                          ad += astep; ac1 += 64;
                      }
                      m >>= 1;
                  } while (m != 1);
                  if (seg == 0) lap = 3;
              }
          }
        } else {
          if (warp == 10) {
            mbar_wait(BAR(PFBAR), 0);
            if (lane < 27) asm volatile("prefetch.global.L2 [%0];" :: "l"(lane < 25 ? (const char*)prm.wo + min(b * 25 + lane, 3135) * 128
                                                                          : lane == 25 ? (const char*)prm.b1 + (b % 28) * 128 : (const char*)prm.b2 + (b & 31) * 128));
            const char* p1 = (const char*)prm.w1 + ((b >> 6) * 1024 + (b & 63) * 2) * 3584 + min(lane, 27) * 128;
            uint32_t tnext = clk32();
            #pragma unroll 1
            for (int i = 0; i < 16; i++) {
                while ((int)(clk32() - tnext) < 0) __nanosleep(40);
                asm volatile("prefetch.global.L2 [%0];" :: "l"(p1 + ((i >> 1) * 128 + (i & 1)) * 3584));
                tnext += PFPACE;
            }
            uint32_t* ofl = opaque_ptr(&prm.sc->flag_o[(ti * 8 + hg) * FS]);
            mbar_wait(BAR(B_EP), 0);
            const uint32_t tag = lds1(sb + SM_EPOCH);
            mbar_wait2(BAR(B_HL), 0, BAR(B_HL + 1), 0);
            mbar_wait(BAR(B_A1D), 0);
            if (lane == 0) st_flag(ofl, tag, gtime32());
            __syncwarp();
          }
          const uint32_t tag = lds1(sb + SM_EPOCH);
          const int h = warp & 1;
          const bool lead = elect_one();
          const uint32_t wo = lane * 132, l3 = lane < 16 ? 12288 : 0;
          uint32_t base = sb + SM_WQ, bl = BAR(B_OL), bf = BAR(B_OF), m = 4, rph = 0;
          #pragma unroll 1
          for (int e = 0; e < 2; e++) {
              uint32_t s8 = (e && !g1_on ? 4 + h : h) * 8;
              #pragma unroll 1
              do {
                  const uint32_t dst = base + s8 * 1792;
                  auto stale = [&]() {
                      uint32_t d;
                      asm volatile("{ .reg .b32 x, y, z, u;\n"
                                   "ld.shared.u32 x, [%1]; ld.shared.u32 y, [%1 + 4096]; ld.shared.u32 z, [%1 + 8192]; ld.shared.u32 u, [%2];\n"
                                   "lop3.b32 x, x, y, %3, 0x7e; lop3.b32 z, z, u, %3, 0x7e; lop3.b32 %0, x, z, 1, 0xa8; }"
                                   : "=r"(d) : "r"(dst + wo), "r"(dst + (wo + l3)), "r"(tag) : "memory");
                      return __any_sync(~0u, d);
                  };
                  mbar_wait_fast(bl + s8, m & 1);
                  bool bad = stale();
                  mbar_arrive_if(bf + s8, lead && !bad);
                  if (bad) {
                      const int p = 2 * __clz(m) - 2 + h;
                      RETRY_COUNT(!e ? 1 : p < 32 ? 0 : !g1_on ? 5 : p < 46 ? 2 : 6);
                      const int st = (p > 15) + (p > 31) + (p > 45), s = p - (st < 3 ? 16 * st : 46);
                      mbar_wait(BAR(B_OD), 0);
                      const char* src = (const char*)(!e ? &prm.sc->o[(a2s * 4 + (lds1(sb + SM_ORD) >> (p * 2 & 7) & 3)) * 896] : st < 2 ? &prm.sc->hn[(rank * 16 + s) * 3584 + (g1j + 2 * st) * 896]
                                                                                                      : &prm.sc->g[(rank * 14 + s) * 3584 + (g2j + 2 * st - 4) * 896]);
                      int it = 0;
                      do {
                          if (++it > kSpinLimit) { TIMEOUT(111); break; }
                          const uint32_t* q = (const uint32_t*)(src + wo);
                          if (it > RELOAD1 && __any_sync(~0u, ((ld_rlx(q) ^ tag) | (ld_rlx(q + 1024) ^ tag) | (ld_rlx(q + 2048) ^ tag) | (ld_rlx(q + l3 / 4) ^ tag)) & 1)) continue;
                          if (lead) {
                              mbar_expect(BAR(B_RT + h), 14336);
                              bulk_g2s(dst, src, 14336, BAR(B_RT + h));
                          }
                          __syncwarp();
                          mbar_wait(BAR(B_RT + h), rph);
                          rph ^= 1;
                          bad = stale();
                      } while (bad);
                      mbar_arrive_if(bf + s8, lead);
                  }
                  s8 += 16;
                  if (s8 >= NB * 8) s8 -= NB * 8;
                  m >>= 1;
              } while (m != 1);
              if (e) break;
              if (h) {
                  const uint32_t gbase = lds1(sb + SM_TG);
                  sleep_until(clk32() + PDELAY);
                  const uint32_t tg = gbase + DELTA + __reduce_max_sync(~0u, poll_flags(&prm.sc->flag_h[(rank * 64 + lane) * FS], 32 * FS, tag, gbase));
                  TRW(40);
                  if (lead) {
                      asm volatile("st.async.shared::cluster.mbarrier::complete_tx::bytes.b32 [%0], %1, [%2];"
                                   :: "r"(pbar0 + (SM_TG2 - SM_BAR)), "r"(tg), "r"(pbar0 + 8u * B_GO) : "memory");
                      asm volatile("st.shared.u32 [%0], %1;" :: "r"(sb + SM_TG + 4), "r"(tg) : "memory");
                      mbar_expect(BAR(B_GO), 4);
                  }
                  __syncwarp();
              } else {
                  const char* p2 = (const char*)prm.w2 + ((b >> 6) * 896 + (b & 63)) * 4096 + lane * 128;
                  #pragma unroll 1
                  for (int i = 0; i < PFW; i++) {
                      asm volatile("prefetch.global.L2 [%0];" :: "l"(p2 + i * 64 * 4096));
                      sleep_until(clk32() + PFPACE2);
                  }
              }
              base = sb + SM_B; bl = BAR(B_BL + h * NB); bf = BAR(B_BF); m = g1_on ? 0x4fe03f80 : 0x7f80;
          }
        }
    } else {
        asm volatile("setmaxnreg.inc.sync.aligned.u32 232;");
        asm volatile("barrier.cluster.wait.aligned;" ::: "memory");
        const int wg = warp >> 2, w = warp & 3;
        const int g = lane >> 2, t = lane & 3;
        uint32_t tag;
        __nv_bfloat16 bias1a, bias1b;
        {
            const uint64_t dw = make_desc(sb + (hg & 1) * 16, 0, true);
            uint4* const hp = opaque_ptr((w == 3 ? &prm.sc->halo[(((ti >> 1) * 8 + hg) * 2 + wg) * 128] : (uint4*)(smem_raw + SM_STG + wg * 8192 + w * 2048)) + lane);
            uint32_t a[28][4];
            float sm[4][4] = {};
            {
                const int r = w * 16 + (lane & 15);
                uint32_t xa[4];
                #pragma unroll
                for (int q = 0; q < 4; q++) xa[q] = opaque(sb + wg * 8192 + r * 128 + (((q * 2 + (lane >> 4)) ^ (r & 7)) << 4));
                const uint32_t one = opaque(0x3F803F80u), one2 = opaque(0x3F803F80u);
                #pragma unroll
                for (int k = 0; k < 28; k++) {
                    if ((k & 3) == 0) mbar_wait(BAR(B_XF + (k >> 2)), 0);
                    uint32_t (&f)[4] = a[k];
                    asm volatile("ldmatrix.sync.aligned.m8n8.x4.shared.b16 {%0,%1,%2,%3}, [%4];"
                                 : "=r"(f[0]), "=r"(f[1]), "=r"(f[2]), "=r"(f[3]) : "r"(xa[k & 3] + (k >> 2) * 16384) : "memory");
                    if (k < 24) mma16816(sm[k & 3], f[0], f[1], f[2], f[3], one, one2);
                }
                pair_arrive(B_XC);
                const bool wok = mbar_test(BAR(B_WKVF), 0);
                #pragma unroll
                for (int k = 24; k < 28; k++) mma16816(sm[k & 3], a[k][0], a[k][1], a[k][2], a[k][3], one, one2);
                if (W0E && !wok) mbar_wait(BAR(B_WKVF), 0);
            }
            const float mean0 = ((sm[0][0] + sm[1][0]) + (sm[2][0] + sm[3][0])) * (1.f / kD);
            const float mean1 = ((sm[0][2] + sm[1][2]) + (sm[2][2] + sm[3][2])) * (1.f / kD);
            const uint32_t mb0 = pack_bf16(mean0, mean0), mb1 = pack_bf16(mean1, mean1);
            TR(1);
            K5(0);
            float ak[28], av[28], aq[28];
            float ss0 = 0.f, ss1 = 0.f, ss2 = 0.f, ss3 = 0.f;
            uint32_t p0, p1;
            bool qok;
            static_for<0, 7>([&](auto S_) {
                constexpr int s = decltype(S_)::value;
                auto centre = [&](int q) {
                    uint32_t (&f)[4] = a[s * 4 + q];
                    f[0] = sub_bf16x2(f[0], mb0); f[1] = sub_bf16x2(f[1], mb1);
                    f[2] = sub_bf16x2(f[2], mb0); f[3] = sub_bf16x2(f[3], mb1);
                };
                if (s || !W0E) {
                    #pragma unroll
                    for (int q = 0; q < 4; q++) centre(q);
                    mbar_wait(BAR(B_WKVF + s), 0);
                    if (s == 6) qok = mbar_test(BAR(B_WQF), 0);
                    wg_fence();
                }
                static_for<0, 4>([&](auto Q_) {
                    constexpr int q = decltype(Q_)::value;
                    uint32_t (&f)[4] = a[s * 4 + q];
                    if (s == 0 && W0E) { centre(q); wg_fence(); }
                    wgmma_rs_n56<SM_WKV + s * 16384 + q * 2048, (s | q) != 0>(ak, f[0], f[1], f[2], f[3], dw);
                    wgmma_rs_n56<SM_WKV + s * 16384 + q * 2048 + 8192, (s | q) != 0>(av, f[0], f[1], f[2], f[3], dw);
                });
                wg_commit();
                K5(1 + s);
                if (s == 4) { wg_wait<1>(); pair_arrive(B_KV3); }
                if (s < 2) mbar_wait(BAR(s ? B_EP : B_WKVF), 0);
                if (s == 1) tag = lds1(sb + SM_EPOCH);
                #pragma unroll
                for (int q = 0; q < 8; q++) {
                    const uint32_t u0 = a[s * 4 + q / 2][(q & 1) * 2], u1 = a[s * 4 + q / 2][(q & 1) * 2 + 1];
                    if (q == 0 && (VCH == 1 || (s & 1) || s == 0)) { p0 = sqr_bf16x2(u0); p1 = sqr_bf16x2(u1); }
                    else { p0 = sqa_bf16x2(u0, p0); p1 = sqa_bf16x2(u1, p1); }
                }
                if (VCH == 1 || !(s & 1)) { ss0 += bf_lo(p0); ss2 += bf_hi(p0); ss1 += bf_lo(p1); ss3 += bf_hi(p1); }
            });
            auto q_chunk = [&](auto K0_, auto K1_) {
                wg_fence();
                static_for<decltype(K0_)::value, decltype(K1_)::value>([&](auto K_) {
                    constexpr int k = decltype(K_)::value;
                    wgmma_rs_n56<SM_WQ + k * 2048, k != 0>(aq, a[k][0], a[k][1], a[k][2], a[k][3], dw);
                });
                wg_commit();
            };
            #define QCHUNK(k0, k1) q_chunk(std::integral_constant<int, k0>{}, std::integral_constant<int, k1>{})
            const float dl0 = mean0 - bf_lo(mb0), dl1 = mean1 - bf_lo(mb1);
            const float rs0 = rsq(fmaxf(quad_sum(ss0 + ss2) * (1.f / kD) - dl0 * dl0, 0.f) + kEps);
            const float rs1 = rsq(fmaxf(quad_sum(ss1 + ss3) * (1.f / kD) - dl1 * dl1, 0.f) + kEps);
            float rk[3][2];
            rk[1][0] = __shfl_sync(~0u, rs0, t * 8); rk[1][1] = __shfl_sync(~0u, rs0, t * 8 + 4);
            rk[2][0] = __shfl_sync(~0u, rs1, t * 8); rk[2][1] = __shfl_sync(~0u, rs1, t * 8 + 4);
            const uint32_t stg = sb + SM_STG + wg * 8192 + lane * 16;
            if (!qok) mbar_wait(BAR(B_WQF), 0);
            K5(8);
            QCHUNK(0, QC0);
            K5(9);
            wg_wait<1>();
            K5(10);
            reg_fence(ak); reg_fence(av);
            TR(2);
            uint32_t kf[3][7], vf[3][7];
            #pragma unroll
            for (int c = 0; c < 7; c++) {
                kf[2][c] = pack_bf16(ak[4 * c + 2], ak[4 * c + 3]);
                vf[2][c] = movm(pack_bf16(av[4 * c + 2], av[4 * c + 3]));
            }
            if (QCA > QC0) QCHUNK(QC0, QCA);
            const uint32_t om = ~lane & 1;
            kf[2][0] = set_par(kf[2][0], om, tag); kf[2][4] = set_par(kf[2][4], om, tag);
            vf[2][1] = set_par(vf[2][1], om, tag); vf[2][5] = set_par(vf[2][5], om, tag);
            auto publish = [&](auto st) {
                st(0, kf[2][0], kf[2][1], kf[2][2], kf[2][3]);
                st(1, kf[2][4], kf[2][5], kf[2][6], vf[2][0]);
                st(2, vf[2][1], vf[2][2], vf[2][3], vf[2][4]);
                st(3, vf[2][5], vf[2][6], __float_as_uint(rk[2][0]), __float_as_uint(rk[2][1]));
            };
            if (w < 3 || rank) publish([&](int c, uint32_t x, uint32_t y, uint32_t z, uint32_t v) { st_gen4(hp + c * 32, x, y, z, v); });
            else publish([&](int c, uint32_t x, uint32_t y, uint32_t z, uint32_t v) {
                asm volatile("st.async.shared::cluster.mbarrier::complete_tx::bytes.v4.b32 [%0], {%2,%3,%4,%5}, [%1];"
                             :: "r"(pbar0 + (SM_STG + 3 * 2048 - SM_BAR) + wg * 8192 + lane * 16 + c * 512), "r"(pbar0 + (B_HL + wg) * 8),
                                "r"(x), "r"(y), "r"(z), "r"(v) : "memory");
            });
            pair_arrive(B_KVC);
            K5(11);
            QCHUNK(QCA, QC1);
            if (QF & 1) mbar_wait(BAR(B_EP), 0);
            K5(12);
            #pragma unroll
            for (int c = 0; c < 7; c++) {
                kf[1][c] = pack_bf16(ak[4 * c], ak[4 * c + 1]);
                vf[1][c] = movm(pack_bf16(av[4 * c], av[4 * c + 1]));
            }
            QCHUNK(QC1, QC2);
            K5(13);
            named_bar(1 + wg, 128);
            uint32_t* op = opaque_ptr((uint32_t*)&prm.sc->o[((ti * 2 + wg) * 56 + hg * 7) * 64] + w * 64 + lane);
            const uint32_t om0 = opaque((lane & 7) == w * 2), om1 = opaque((lane & 7) == w * 2 + 1);
            QCHUNK(QC2, 28);
            K5(14);
            #undef QCHUNK
            const bool gt0 = 2 * t > g, gt1 = 2 * t + 1 > g, no_prev = ti == 0 && w == 0;
            const float kf0 = gt0 ? rk[1][0] : rk[2][0], kf1 = gt1 ? rk[1][1] : rk[2][1];
            constexpr float kScale = 0.18898223650461362f * 1.4426950408889634f;
            const float sq0 = rs0 * kScale, sf0 = kf0 * (rs1 * kScale), sf1 = kf1 * (rs1 * kScale);
            const float NEG = -__int_as_float(0x7f800000);
            const float nb0 = gt0 && no_prev ? NEG : 0.f, nb1 = gt1 && no_prev ? NEG : 0.f;
            const uint32_t mk = opaque((gt0 ? 0x0000ffffu : 0u) | (gt1 ? 0xffff0000u : 0u));
            const uint32_t sr = stg + ((w + 3) & 3) * 2048, hbar = BAR(w == 0 ? B_HL + wg : B_EP);
            mbar_wait(BAR(B_EP), 0);
            wg_wait<0>();
            reg_fence(aq);
            warp_arrive(BAR(B_A1D));
            K5(15);
            TR(3);
            uint32_t qf[8][2];
            #pragma unroll
            for (int c = 0; c < 7; c++) {
                qf[c + (c > 3)][0] = pack_bf16(aq[4 * c], aq[4 * c + 1]);
                qf[c + (c > 3)][1] = pack_bf16(aq[4 * c + 2], aq[4 * c + 3]);
            }
            qf[4][0] = t >= 2 ? qf[3][0] : 0u; qf[4][1] = t >= 2 ? qf[3][1] : 0u;
            qf[3][0] = t < 2 ? qf[3][0] : 0u;  qf[3][1] = t < 2 ? qf[3][1] : 0u;
            float sc[2][3][4];
            auto scores = [&](int n) {
                #pragma unroll
                for (int hd = 0; hd < 2; hd++) {
                    sc[hd][n][0] = sc[hd][n][1] = sc[hd][n][2] = sc[hd][n][3] = 0.f;
                    mma16816(sc[hd][n], qf[4 * hd][0], qf[4 * hd][1], qf[4 * hd + 1][0], qf[4 * hd + 1][1], kf[n][3 * hd], kf[n][3 * hd + 1]);
                    mma16816(sc[hd][n], qf[4 * hd + 2][0], qf[4 * hd + 2][1], qf[4 * hd + 3][0], qf[4 * hd + 3][1], kf[n][3 * hd + 2], kf[n][3 * hd + 3]);
                }
            };
            scores(1); scores(2);
            mbar_wait(hbar, 0);
            {
                const uint4 u0 = lds4(sr), u1 = lds4(sr + 512), u3 = lds4(sr + 1536), u2 = lds4(sr + 1024);
                kf[0][0] = u0.x; kf[0][1] = u0.y; kf[0][2] = u0.z; kf[0][3] = u0.w;
                kf[0][4] = u1.x; kf[0][5] = u1.y; kf[0][6] = u1.z; vf[0][0] = u1.w;
                vf[0][1] = u2.x; vf[0][2] = u2.y; vf[0][3] = u2.z; vf[0][4] = u2.w;
                vf[0][5] = u3.x; vf[0][6] = u3.y; rk[0][0] = __uint_as_float(u3.z); rk[0][1] = __uint_as_float(u3.w);
            }
            TR(4);
            scores(0);
            const float ke0 = gt0 ? rk[0][0] : rk[1][0], ke1 = gt1 ? rk[0][1] : rk[1][1];
            const float se0 = ke0 * sq0, se1 = ke1 * sq0;
            uint32_t ow[7][2];
            #pragma unroll
            for (int hd = 0; hd < 2; hd++) {
                const int c0 = hd * 3;
                float (&sc_)[3][4] = sc[hd];
                const float e0 = fmaf(gt0 ? sc_[0][0] : sc_[1][0], se0, nb0), e1 = fmaf(gt1 ? sc_[0][1] : sc_[1][1], se1, nb1);
                const float f0 = (gt0 ? sc_[1][2] : sc_[2][2]) * sf0, f1 = (gt1 ? sc_[1][3] : sc_[2][3]) * sf1;
                const float me = quad_max(fmaxf(e0, e1)), mf = quad_max(fmaxf(f0, f1));
                const float p0 = ex2(e0 - me), p1 = ex2(e1 - me), r0 = ex2(f0 - mf), r1 = ex2(f1 - mf);
                const float ie = rcp(quad_sum(p0 + p1)), jf = rcp(quad_sum(r0 + r1));
                const uint32_t pp = pack_bf16(p0 * ke0 * ie, p1 * ke1 * ie), rp = pack_bf16(r0 * kf0 * jf, r1 * kf1 * jf);
                const uint32_t a0 = pp & ~mk, a1 = rp & mk, a3 = rp & ~mk, a4 = pp & mk, zero = opaque(0u), zero2 = opaque(0u);
                #pragma unroll
                for (int c = 0; c < 4; c++) {
                    float o[4] = {0.f, 0.f, 0.f, 0.f};
                    mma16816(o, a0, a1, zero, a3, vf[1][c0 + c], vf[2][c0 + c]);
                    mma1688(o, a4, zero2, vf[0][c0 + c]);
                    const uint32_t lo = pack_bf16(o[0], o[1]), hi = pack_bf16(o[2], o[3]);
                    if (hd == 1 && c == 0) { if (t >= 2) { ow[3][0] = lo; ow[3][1] = hi; } }
                    else { ow[c0 + c][0] = lo; ow[c0 + c][1] = hi; }
                }
            }
            #pragma unroll
            for (int c = 0; c < 7; c++) {
                stg1(op + c * 256,      set_par(ow[c][0], om0, tag));
                stg1(op + c * 256 + 32, set_par(ow[c][1], om1, tag));
            }
            TR(5);
        }
        float as[28], ac[28];
        uint32_t xch, peer_xch, gm[2][4], *gp1, *gp2;
        const uint32_t *hp, *ht;
        const uint2* hq;
        uint64_t da0, db0;
        const int cg2 = (g2j + 2 * wg) * 2 + (rank ^ 1), cg1 = (g1j + 2 * wg) * 2 + (rank ^ (g1f < 14));
        const bool lead = elect_one();
        {
            const int cg = a2j * 2 + wg;
            float acc2[28];
            mbar_wait(BAR(B_XRF), 0);
            {
                const uint32_t xa = sb + SM_XR + wg * 8192 + (w * 16 + (lane & 15)) * 128;
                #pragma unroll
                for (int c = 0; c < 4; c++) {
                    uint32_t xr[4];
                    asm volatile("ldmatrix.sync.aligned.m8n8.x4.shared.b16 {%0,%1,%2,%3}, [%4];"
                                 : "=r"(xr[0]), "=r"(xr[1]), "=r"(xr[2]), "=r"(xr[3])
                                 : "r"(xa + ((((c * 2 + wg + (lane >> 4)) ^ lane) & 7) << 4)) : "memory");
                    #pragma unroll
                    for (int e = 0; e < (c < 3 ? 4 : 2); e++) { acc2[8 * c + 2 * e] = bf_lo(xr[e]); acc2[8 * c + 2 * e + 1] = bf_hi(xr[e]); }
                }
            }
            uint32_t* spw = opaque_ptr(&prm.sc->stats[((a2s * 8 + cg) * 4 + w) * 32 + lane]);
            const uint32_t* spr = opaque_ptr(&prm.sc->stats[(a2s * 32 + w) * 32 + lane]);
            uint32_t* rp = opaque_ptr((uint32_t*)&prm.sc->rows[a2s * 64 + w * 16 + (t >> 1) * 8 + g] + (t & 1));
            const int cgs = cg ^ (a2s >> 4);
            uint32_t* np = opaque_ptr((uint32_t*)&prm.sc->hn[(a2s * 56 + cgs * 7) * 64] + w * 64 + lane);
            const uint64_t dwo = make_desc(sb + SM_WKV + wg * (28672 + 16), 0, true);
            const uint64_t doa = make_desc(sb + SM_WQ, 1024, false, 128);
            bias1a = prm.b1[g1f * 64 + w * 16 + g]; bias1b = prm.b1[g1f * 64 + w * 16 + 8 + g];
            const __nv_bfloat16 bias2 = prm.b2[ti * 128 + (w * 16 + (t >> 1) * 8 + g) * 2 + a2p];
            reg_fence(acc2);
            fence_async_smem();
            warp_arrive(BAR(B_XD));
            {
                xch = opaque(sb + SM_XCH + w * 1792 + lane * 16);
                asm volatile("mapa.shared::cluster.u32 %0, %1, %2;" : "=r"(peer_xch) : "r"(xch), "r"(rank ^ 1));
                const int hcg = cg2 ^ (g2s >> 4), hrg = (g2s & 1) * 4 + w;
                const uint32_t* hl = (const uint32_t*)&prm.sc->hn[((g2s >> 1) * 112 + hcg * 7) * 64 + hrg * 8];
                hp = opaque_ptr(hl + (g & 1) * 14336 + (g >> 1) * 4 + t);
                ht = opaque_ptr(hl + (lane & 1) * 14336 + min(lane >> 1, 6) * 256 + ((min(lane >> 1, 6) - (hcg & 1)) & 3) * 8 + hrg);
                hq = opaque_ptr(&prm.sc->rows[((g2s >> 1) * 2 + (g & 1)) * 64 + hrg * 8 + (g >> 1)]);
                gp1 = opaque_ptr((uint32_t*)&prm.sc->g[(g1f * 56 + cg1 * 7) * 64] + w * 64 + lane);
                gp2 = opaque_ptr((uint32_t*)(prm.out + (size_t)(g2s * 64 + w * 16 + lane / 7) * kD + cg2 * 56) + (lane % 7) * 4);
                da0 = make_desc(sb, 0, true); db0 = make_desc(sb + SM_B, 128, false);
            }
            mbar_wait2(BAR(B_WOF), 0, BAR(B_WOF + 1), 0);
            mbar_wait(BAR(B_OD), 0);
            const uint32_t order = __shfl_sync(~0u, lds1(sb + SM_ORD), 0);
            static_for<0, 4>([&](auto P_) {
                constexpr int P = decltype(P_)::value;
                const uint64_t dwp = dwo + ((order >> (2 * P + 1) & 1) * 3584 + (order >> 2 * P & 1) * 896);
                mbar_wait(BAR(B_OF + P), 0);
                if (P == 0) TR(6);
                wg_fence();
                static_for<0, 7>([&](auto K_) { constexpr int k = decltype(K_)::value;
                    wgmma_ss_n56<P * 14336 + k * 2048, k * 2048, 0>(acc2, doa, dwp); });
                if (P) wg_commit();
                if (P == 2) { wg_wait<1>(); warp_arrive(BAR(B_OC)); }
            });
            wg_wait<0>();
            reg_fence(acc2);
            TR(7);
            float s0 = 0.f, s1 = 0.f, q0 = 0.f, q1 = 0.f;
            #pragma unroll
            for (int c = 0; c < 7; c++) {
                s0 += acc2[4 * c] + acc2[4 * c + 1];     q0 = fmaf(acc2[4 * c], acc2[4 * c], fmaf(acc2[4 * c + 1], acc2[4 * c + 1], q0));
                s1 += acc2[4 * c + 2] + acc2[4 * c + 3]; q1 = fmaf(acc2[4 * c + 2], acc2[4 * c + 2], fmaf(acc2[4 * c + 3], acc2[4 * c + 3], q1));
            }
            const bool th = t >= 2, to = t & 1;
            const float sa = (th ? s1 : s0) + __shfl_xor_sync(~0u, th ? s0 : s1, 2), qa = (th ? q1 : q0) + __shfl_xor_sync(~0u, th ? q0 : q1, 2);
            const float part = (to ? qa : sa) + __shfl_xor_sync(~0u, to ? sa : qa, 1);
            stg1(spw, set_par(__float_as_uint(part), 1u, tag));
            const uint32_t tpoll = clk32() + SDELAY;
            TR(8);
            warp_arrive(BAR(B_HD));
            uint32_t nm[2][4], us[8];
            spin_until(tpoll);
            #pragma unroll
            for (int i = 0; i < 8; i++) us[i] = ld_rlx(spr + i * 128);
            #pragma unroll
            for (int i = 0; i < 8; i++) {
                nm[i >> 2][i & 3] = lane == ((i - (cgs & 1)) & 3) * 8 + w * 2 + (i >> 2);
                gm[i >> 2][i & 3] = opaque(lane == ((i - (cg1 & 1)) & 3) * 8 + w * 2 + (i >> 2));
            }
            #pragma unroll
            for (int c = 0; c < 28; c++) { ac[c] = 0.5f * __bfloat162float(c & 2 ? bias1b : bias1a); as[c] = 0.f; }
            reg_fence(as); reg_fence(ac);
            {
                int it = 0;
                while (true) {
                    uint32_t bad = 0;
                    #pragma unroll
                    for (int i = 0; i < 8; i++) bad |= us[i] ^ tag;
                    if (!__any_sync(~0u, bad & 1)) break;
                    RETRY_COUNT(3);
                    if (++it > kSpinLimit) { TIMEOUT(103); break; }
                    #pragma unroll
                    for (int i = 0; i < 8; i++) us[i] = ld_rlx(spr + i * 128);
                }
            }
            TR(9);
            const float tot = (((__uint_as_float(us[0]) + __uint_as_float(us[1])) + (__uint_as_float(us[2]) + __uint_as_float(us[3])))
                            + ((__uint_as_float(us[4]) + __uint_as_float(us[5])) + (__uint_as_float(us[6]) + __uint_as_float(us[7])))) * (1.f / kD);
            const float oth = __shfl_xor_sync(~0u, tot, 1);
            const float mean = to ? oth : tot;
            const float var = fmaxf(fmaf(-mean, mean, to ? tot : oth), 0.f);
            const float rra = rsq(fmaf(var, 4.f + 4.f * kEps, 4.f * kEps * kEps)), mra = -mean * rra;
            const float rrb = __shfl_xor_sync(~0u, rra, 2), mrb = __shfl_xor_sync(~0u, mra, 2);
            const float rr0 = th ? rrb : rra, mr0 = th ? mrb : mra, rr1 = th ? rra : rrb, mr1 = th ? mra : mrb;
            #pragma unroll
            for (int c = 0; c < 7; c++) {
                stg1(np + c * 256,      set_par(pack_bf16(fmaf(acc2[4 * c], rr0, mr0), fmaf(acc2[4 * c + 1], rr0, mr0)), nm[0][c & 3], tag));
                stg1(np + c * 256 + 32, set_par(pack_bf16(fmaf(acc2[4 * c + 2], rr1, mr1), fmaf(acc2[4 * c + 3], rr1, mr1)), nm[1][c & 3], tag));
            }
            TR(10);
            if (cg == 0) stg1(rp, set_par(__float_as_uint(to ? mean + __bfloat162float(bias2) : rcp(rra)), 1u, tag));
        }
        auto send = [&]() {
            const uint32_t rf = pbar0 + (B_RF + warp) * 8;
            #pragma unroll
            for (int c = 0; c < 4; c++) {
                const uint32_t p0 = pack_bf16(as[8 * c], as[8 * c + 1]), p1 = pack_bf16(as[8 * c + 2], as[8 * c + 3]);
                if (c < 3) {
                    const uint32_t p2 = pack_bf16(as[8 * c + 4], as[8 * c + 5]), p3 = pack_bf16(as[8 * c + 6], as[8 * c + 7]);
                    asm volatile("st.async.shared::cluster.mbarrier::complete_tx::bytes.v4.b32 [%0], {%1,%2,%3,%4}, [%5];"
                                 :: "r"(peer_xch + c * 512), "r"(p0), "r"(p1), "r"(p2), "r"(p3), "r"(rf) : "memory");
                } else {
                    asm volatile("st.async.shared::cluster.mbarrier::complete_tx::bytes.v2.b32 [%0], {%1,%2}, [%3];"
                                 :: "r"(peer_xch + 1536 - lane * 8), "r"(p0), "r"(p1), "r"(rf) : "memory");
                }
            }
        };
        auto receive = [&](uint32_t (&pk)[14], uint32_t phase) {
            mbar_wait(BAR(B_RF + warp), phase);
            #pragma unroll
            for (int c = 0; c < 3; c++) { const uint4 u = lds4(xch + c * 512); pk[4 * c] = u.x; pk[4 * c + 1] = u.y; pk[4 * c + 2] = u.z; pk[4 * c + 3] = u.w; }
            const uint2 u = lds2(xch + 1536 - lane * 8); pk[12] = u.x; pk[13] = u.y;
        };
        uint2 rw[2]; uint32_t tw;
        auto load_rows = [&]() { tw = ld_rlx(ht); rw[0] = ld_rlx2(hq); rw[1] = ld_rlx2(hq + 4); };
        rw[0] = rw[1] = make_uint2(0u, 0u); tw = ~tag;
        #pragma unroll 1
        for (int ge = 0;; ge++) {
          if (ge || g1_on) {
            const int use = ge * 2 + wg;
            int entry = ge ? 1 : 2 * wg, stop = 0;
            uint64_t da = da0 + (ge ? -3 : wg ? NR - 10 : 0) * 512;
            bool rel = lead && use == 1;
            const uint32_t xfree = BAR(use > (g1_on ? 0 : 2) ? B_RE + use - 1 : B_PD);
            mbar_wait(BAR(B_AF), 0);
            if (ge && (wg || g1_on)) named_bar(5 - wg, 256);
            TR(11 + ge * 4);
            auto step = [&](auto I_) {
                constexpr int i = decltype(I_)::value, sl = i % NB, ao = i * 8192, bo = sl * 14336;
                mbar_wait_fast(BAR(B_BF + sl), i / NB);
                wg_fence();
                wgmma_ss_n112<ao,        bo,       1>(as, ac, da, db0);
                wgmma_ss_n112<ao + 2048, bo + 256, 1>(as, ac, da, db0);
                wgmma_ss_n112<ao + 4096, bo + 512, 1>(as, ac, da, db0);
                wgmma_ss_n112<ao + 6144, bo + 768, 1>(as, ac, da, db0);
                wg_commit();
                if (i == 1 && stop == 1) named_arrive(4, 256);
                if (i == 3 && (use == 1 || use == 2)) named_arrive(4 + wg, 256);
                wg_wait<1>();
                mbar_arrive_if(BAR(B_BE + (13 + i) % 14), rel);
                rel = lead;
            };
            #pragma unroll 1
            while (true) {
                if (entry < 1) {
                    static_for<0, 2>(step);
                    if (stop == 1) break;
                    static_for<2, 4>(step);
                    if (stop) break;
                }
                if (entry < 2) static_for<4, 10>(step);
                else {
                    uint32_t af[NR * 4][4];
                    mbar_wait(BAR(B_GO), 0);
                    const uint32_t tp = lds1(sb + SM_TG + 4) + PLOFF;
                    int it = 0;
                    while ((int)(gtime32() - tp) < 0 && ++it < 256) __nanosleep(20);
                    const uint32_t la = sb + ((lane >> 4) * 8 + (lane & 7)) * 128 + (((w * 2 + ((lane >> 3) & 1)) ^ (lane & 7)) << 4);
                    #pragma unroll
                    for (int k = 0; k < NR * 4; k++)
                        asm volatile("ldmatrix.sync.aligned.m8n8.x4.trans.shared.b16 {%0,%1,%2,%3}, [%4];"
                                     : "=r"(af[k][0]), "=r"(af[k][1]), "=r"(af[k][2]), "=r"(af[k][3]) : "r"(la + k * 2048) : "memory");
                    __syncwarp();
                    mbar_arrive_if(BAR(B_PL), lead);
                    if (w == 0) {
                        const char* p2 = (const char*)prm.w2 + ((b >> 6) * 896 + (b & 63) + PFW * 64) * 4096 + lane * 128;
                        #pragma unroll 1
                        for (int i = 0; i < 14 - PFW; i++) {
                            it = 0;
                            while ((int)(gtime32() - tp) < PF3OFF + i * PF3PACE && ++it < 256) __nanosleep(40);
                            asm volatile("prefetch.global.L2 [%0];" :: "l"(p2 + i * 64 * 4096));
                        }
                    }
                    named_bar(4, 256);
                    static_for<0, NR>([&](auto I_) {
                        constexpr int i = decltype(I_)::value, sl = (16 + i) % NB, o = sl * 14336;
                        mbar_wait_fast(BAR(B_BF + sl), (16 + i) / NB & 1);
                        wg_fence();
                        wgmma_rs_n112<o,       1>(as, ac, af[4 * i][0], af[4 * i][1], af[4 * i][2], af[4 * i][3], db0);
                        wgmma_rs_n112<o + 256, 1>(as, ac, af[4 * i + 1][0], af[4 * i + 1][1], af[4 * i + 1][2], af[4 * i + 1][3], db0);
                        wgmma_rs_n112<o + 512, 1>(as, ac, af[4 * i + 2][0], af[4 * i + 2][1], af[4 * i + 2][2], af[4 * i + 2][3], db0);
                        wgmma_rs_n112<o + 768, 1>(as, ac, af[4 * i + 3][0], af[4 * i + 3][1], af[4 * i + 3][2], af[4 * i + 3][3], db0);
                        wg_commit();
                        if (i) { wg_wait<1>(); mbar_arrive_if(BAR(B_BE + (15 + i) % (2 * NB)), lead); }
                    });
                }
                static_for<10, 14>(step);
                entry = 0; stop = use + 1; da += 14 * 512;
            }
            const uint32_t prev = BAR(B_BE + (use ? 3 : 1));
            const bool xok = mbar_test(xfree, 0);
            wg_wait<0>();
            reg_fence(as); reg_fence(ac);
            mbar_arrive_if(prev, lead);
            if (!xok) mbar_wait(xfree, 0);
            if (ge) break;
            send();
            load_rows();
            TR(12);
            uint32_t pk[14];
            receive(pk, 0);
            TR(13);
            #pragma unroll
            for (int c = 0; c < 14; c++) {
                float r[2];
                #pragma unroll
                for (int e = 0; e < 2; e++) {
                    const float u = ac[2 * c + e] + (e ? bf_hi(pk[c]) : bf_lo(pk[c]));
                    r[e] = fmaf(u, tanh_hw(u * fmaf(u * u, 8.f * 0.7978845608f * 0.044715f, 2.f * 0.7978845608f)), u);
                }
                stg1(gp1 + (c >> 1) * 256 + (c & 1) * 32, set_par(pack_bf16(r[0], r[1]), gm[c & 1][(c >> 1) & 3], tag));
            }
            named_bar(1 + wg, 128);
            if (w == 0 && lane == 0) {
                asm volatile("st.shared.u32 [%0], %1;" :: "r"(sb + SM_TG + 8 + wg * 4), "r"(clk32() + (wg ? XSPECB : XSPEC)) : "memory");
                mbar_arrive(BAR(B_GD + wg));
            }
            if (lead) mbar_expect(BAR(B_RF + warp), 1792);
            mbar_arrive_remote_if(pbar0 + (B_RE + wg) * 8, lead);
            TR(14);
          } else mbar_wait(BAR(B_GD), 0);
            {
                int it = 0;
                while (__any_sync(~0u, ((tw ^ tag) | (rw[0].x ^ tag) | (rw[0].y ^ tag) | (rw[1].x ^ tag) | (rw[1].y ^ tag)) & 1)) {
                    if (++it > kSpinLimit) { TIMEOUT(110); break; }
                    load_rows();
                }
                uint32_t hw[14];
                #pragma unroll
                for (int c = 0; c < 14; c++) hw[c] = ld_rlx(hp + (c >> 1) * 256 + (c & 1) * 16);
                #pragma unroll
                for (int c = 0; c < 14; c++) {
                    ac[2 * c]     = fmaf(bf_lo(hw[c]), __uint_as_float(rw[c & 1].x), __uint_as_float(rw[c & 1].y));
                    ac[2 * c + 1] = fmaf(bf_hi(hw[c]), __uint_as_float(rw[c & 1].x), __uint_as_float(rw[c & 1].y));
                    as[2 * c] = as[2 * c + 1] = 0.f;
                }
                reg_fence(as); reg_fence(ac);
            }
        }
        uint32_t po[14], pk[14];
        if (!wg) sleep_until(clk32() + w * STAG2);
        send();
        #pragma unroll
        for (int c = 0; c < 14; c++) po[c] = opaque(pack_bf16(ac[2 * c], ac[2 * c + 1]));
        TR(16);
        receive(pk, g1_on);
        TR(17);
        #pragma unroll
        for (int c = 0; c < 14; c++) pk[c] = add_bf16x2(po[c], pk[c]);
        __syncwarp();
        const uint32_t sa = xch - lane * 16 + (lane & 15) * 112 + (lane >> 4) * 16;
        #pragma unroll
        for (int m = 0; m < 3; m++)
            asm volatile("stmatrix.sync.aligned.m8n8.x4.shared.b16 [%0], {%1,%2,%3,%4};"
                         :: "r"(sa + m * 32), "r"(pk[4 * m]), "r"(pk[4 * m + 1]), "r"(pk[4 * m + 2]), "r"(pk[4 * m + 3]) : "memory");
        asm volatile("stmatrix.sync.aligned.m8n8.x2.shared.b16 [%0], {%1,%2};" :: "r"(sa + 96), "r"(pk[12]), "r"(pk[13]) : "memory");
        __syncwarp();
        if (lane < 28) {
            #pragma unroll
            for (int i = 0; i < 4; i++) { const uint4 u = lds4(xch + i * 448); stg4(gp2 + i * 896, u.x, u.y, u.z, u.w); }
        }
        __syncwarp();
        mbar_arrive_remote_if(pbar0 + (B_RE + 2) * 8, lead && wg == 0);
        TR(18);
        if (tid == 128) TRG(62);
        if (b == 0 && tid == 128) prm.sc->epoch = tag;
    }
}

typedef CUresult (*EncodeFn)(CUtensorMap*, CUtensorMapDataType, cuuint32_t, void*, const cuuint64_t*, const cuuint64_t*,
                             const cuuint32_t*, const cuuint32_t*, CUtensorMapInterleave, CUtensorMapSwizzle,
                             CUtensorMapL2promotion, CUtensorMapFloatOOBfill);

void make_map(EncodeFn enc, CUtensorMap* m, const void* base, uint64_t cols, uint64_t rows, uint32_t box_rows) {
    cuuint64_t dims[2] = {cols, rows};
    cuuint64_t strides[1] = {cols * 2};
    cuuint32_t box[2] = {64, box_rows};
    cuuint32_t es[2] = {1, 1};
    enc(m, CU_TENSOR_MAP_DATA_TYPE_BFLOAT16, 2, const_cast<void*>(base), dims, strides, box, es, CU_TENSOR_MAP_INTERLEAVE_NONE,
        CU_TENSOR_MAP_SWIZZLE_128B, CU_TENSOR_MAP_L2_PROMOTION_L2_128B, CU_TENSOR_MAP_FLOAT_OOB_FILL_NONE);
}

}

extern "C" void kernel_launch(void* const* d_in, const int* in_sizes, int n_in, void* d_out, int out_size) {
    (void)in_sizes; (void)n_in; (void)out_size;
    void* fn = nullptr;
    cudaDriverEntryPointQueryResult qr;
    cudaGetDriverEntryPoint("cuTensorMapEncodeTiled", &fn, cudaEnableDefault, &qr);
    EncodeFn enc = (EncodeFn)fn;
    CUtensorMap mX2, mX, mWqkv, mWo, mW1, mW2;
    {
        cuuint64_t dims[3] = {kD, kS / 2, 2}, strides[2] = {4 * kD, 2 * kD};
        cuuint32_t box[3] = {64, 64, 2}, es[3] = {1, 1, 1};
        enc(&mX2, CU_TENSOR_MAP_DATA_TYPE_BFLOAT16, 3, d_in[0], dims, strides, box, es, CU_TENSOR_MAP_INTERLEAVE_NONE,
            CU_TENSOR_MAP_SWIZZLE_128B, CU_TENSOR_MAP_L2_PROMOTION_L2_128B, CU_TENSOR_MAP_FLOAT_OOB_FILL_NONE);
    }
    make_map(enc, &mX, d_in[0], 2 * kD, kS / 2, 64);
    make_map(enc, &mWqkv, d_in[1], 3 * kD, kD, 64);
    make_map(enc, &mWo, d_in[2], kD, kD, 112);
    make_map(enc, &mW1, d_in[4], 2 * kF, kS / 2, 64);
    make_map(enc, &mW2, d_in[6], kS, kF, 64);
    Params prm;
    prm.x = (const __nv_bfloat16*)d_in[0];
    prm.wqkv = (const __nv_bfloat16*)d_in[1];
    prm.wo = (const __nv_bfloat16*)d_in[2];
    prm.w1 = (const __nv_bfloat16*)d_in[4];
    prm.b1 = (const __nv_bfloat16*)d_in[5];
    prm.w2 = (const __nv_bfloat16*)d_in[6];
    prm.b2 = (const __nv_bfloat16*)d_in[7];
    prm.out = (__nv_bfloat16*)d_out;
    cudaGetSymbolAddress((void**)&prm.sc, g_scratch);
    cudaFuncSetAttribute(fused_kernel, cudaFuncAttributeMaxDynamicSharedMemorySize, SM_TOTAL);
    fused_kernel<<<128, 384, SM_TOTAL, cudaStreamPerThread>>>(prm, mX2, mX, mWqkv, mWo, mW1, mW2);
}
```

```cpp
#include <cuda_runtime.h>
#include <cuda.h>
#include <cuda_bf16.h>
#include <stdint.h>
#include <type_traits>

namespace {

constexpr int kS = 2048, kD = 448, kF = 1792;
constexpr float kEps = 1e-5f;

constexpr int FS = 32;
constexpr int NPRE = 10;
constexpr int NR = 8;
constexpr int PFW = 4;
constexpr int QC0 = 4;
constexpr int QC1 = 10;
constexpr int QC2 = 16;
constexpr int PFD = 250;
constexpr int PFPACE = 280;
constexpr int PFPACE2 = 300;
constexpr int HDELAY = 200;
constexpr int WOD = 350;
constexpr int SDELAY = 200;
constexpr int PDELAY = 400;
constexpr int PACE1 = 120;
constexpr int PACE2 = 400;
constexpr int PACEB = 300;
constexpr int XSPEC = 500;
constexpr int XSPECB = 750;
constexpr int CN2 = 7200;
constexpr int CN3 = 10900;
constexpr int W2OFF = 800;
constexpr int W2PACE = 350;
constexpr int STAG2 = 400;
constexpr int DELTAO = 864;
constexpr int DMIN = 608;
constexpr int CHUNKNS = 250;
constexpr int DELTA = 2080;
constexpr int PLOFF = -250;
constexpr int PF3OFF = 300;
constexpr int PF3PACE = 240;

struct Scratch {
    uint32_t flag_o[16 * 8 * FS];
    uint4    o[32 * 56 * 64];
    uint32_t stats[32 * 8 * 4 * 32];
    uint4    hn[32 * 56 * 64];
    uint32_t flag_h[32 * 4 * FS];
    uint4    g[28 * 56 * 64];
    uint4    halo[8 * 8 * 2 * 4 * 32];
    uint2    rows[32 * 64];
    uint32_t epoch;
};
__device__ __align__(1024) Scratch g_scratch;

constexpr uint32_t SM_WKV  = 114688;
constexpr uint32_t SM_XR   = 24576;
constexpr uint32_t SM_STG  = 40960;
constexpr uint32_t SM_WQ   = 57344;
constexpr uint32_t SM_XCH  = 0;
constexpr uint32_t SM_B    = 131072;
constexpr uint32_t SM_BAR  = 231424;
constexpr uint32_t SM_TOTAL = SM_BAR + 1024;
constexpr int NB = 7;
constexpr int B_XF = 0, B_WKVF = 7, B_WQF = 14, B_XRF = 15, B_WOF = 16,
              B_XC = 18, B_KV3 = 19, B_KVC = 20,
              B_A1D = 21, B_XD = 22, B_OC = 23,
              B_BE = 24  , B_RE = B_BE + 2 * NB,
              B_PL = B_RE + 3, B_AF = B_PL + 1, B_BL = B_AF + 1  , B_OL = B_BL + 2 * NB  ,
              B_BF = B_OL + 4  , B_OF = B_BF + NB, B_RF = B_OF + 4, B_EP = B_RF + 8, B_PD = B_EP + 1, B_OD = B_PD + 1, B_RT = B_OD + 1, B_HL = B_RT + 2,
              B_HD = B_HL + 2  , B_GO = B_HD + 1, B_GD = B_GO + 1, B_COUNT = B_GD + 2;
constexpr uint32_t SM_EPOCH = SM_BAR + B_COUNT * 8, SM_TG = SM_EPOCH + 4  , SM_TG2 = SM_TG + 16  ,
                   SM_ORD = SM_TG2 + 4  ;

constexpr uint64_t kAPos = 0x3330ull | 0x5555555ull << 17;
constexpr uint32_t seg_mask(int h, int p0, int p1) {
    uint32_t m = 0; int n = 0;
    for (int p = p0; p < p1; p++) if ((p & 1) == h) m |= (uint32_t)((kAPos >> p) & 1) << n++;
    return m | 1u << n;
}
constexpr uint64_t seg_masks(int h) {
    return 2 | (uint64_t)seg_mask(h, 0, 16) << 10 | (uint64_t)seg_mask(h, 16, 32) << 20
             | (uint64_t)seg_mask(h, 32, 46) << 30 | (uint64_t)seg_mask(h, 46, 60) << 40;
}
constexpr uint64_t kSegMasks0 = seg_masks(0), kSegMasks1 = seg_masks(1);

constexpr int kSpinLimit = 1 << 15;
__device__ __forceinline__ bool elect_one() {
    uint32_t p;
    asm volatile("{ .reg .pred P; elect.sync _|P, 0xffffffff; selp.u32 %0, 1, 0, P; }" : "=r"(p));
    return p;
}
__device__ __forceinline__ void mbar_init(uint32_t bar, uint32_t cnt) { asm volatile("mbarrier.init.shared::cta.b64 [%0], %1;" :: "r"(bar), "r"(cnt)); }
__device__ __forceinline__ void mbar_expect(uint32_t bar, uint32_t bytes) { asm volatile("mbarrier.arrive.expect_tx.shared::cta.b64 _, [%0], %1;" :: "r"(bar), "r"(bytes) : "memory"); }
__device__ __forceinline__ void mbar_expect_more(uint32_t bar, uint32_t bytes) { asm volatile("mbarrier.expect_tx.relaxed.cta.shared::cta.b64 [%0], %1;" :: "r"(bar), "r"(bytes) : "memory"); }
__device__ __forceinline__ void mbar_arrive(uint32_t bar) { asm volatile("mbarrier.arrive.shared::cta.b64 _, [%0];" :: "r"(bar) : "memory"); }
__device__ __forceinline__ void mbar_wait(uint32_t bar, uint32_t parity) {
    uint32_t ok; int it = 0;
    do {
        asm volatile("{ .reg .pred p; mbarrier.try_wait.parity.shared::cta.b64 p, [%1], %2; selp.u32 %0, 1, 0, p; }"
                     : "=r"(ok) : "r"(bar), "r"(parity) : "memory");
        if (++it > kSpinLimit) break;
    } while (!ok);
}
__device__ __forceinline__ bool mbar_try(uint32_t bar, uint32_t parity) {
    uint32_t ok;
    asm volatile("{ .reg .pred p; mbarrier.try_wait.parity.shared::cta.b64 p, [%1], %2; selp.u32 %0, 1, 0, p; }" : "=r"(ok) : "r"(bar), "r"(parity) : "memory");
    return ok;
}
__device__ __forceinline__ bool mbar_test(uint32_t bar, uint32_t parity) {
    uint32_t ok;
    asm volatile("{ .reg .pred p; mbarrier.test_wait.parity.shared::cta.b64 p, [%1], %2; selp.u32 %0, 1, 0, p; }" : "=r"(ok) : "r"(bar), "r"(parity) : "memory");
    return ok;
}
__device__ __forceinline__ void mbar_wait_fast(uint32_t bar, uint32_t parity) { if (!mbar_try(bar, parity)) mbar_wait(bar, parity); }
__device__ __forceinline__ void mbar_wait2(uint32_t bar0, uint32_t par0, uint32_t bar1, uint32_t par1) {
    uint32_t ok; int it = 0;
    do {
        asm volatile("{ .reg .pred p, q; mbarrier.try_wait.parity.shared::cta.b64 p, [%1], %2;\n"
                     "mbarrier.try_wait.parity.shared::cta.b64 q, [%3], %4; and.pred p, p, q; selp.u32 %0, 1, 0, p; }"
                     : "=r"(ok) : "r"(bar0), "r"(par0), "r"(bar1), "r"(par1) : "memory");
        if (++it > kSpinLimit) break;
    } while (!ok);
}
template <int N> __device__ __forceinline__ void reg_fence(float (&d)[N]) {
    #pragma unroll
    for (int i = 0; i < N; i++) asm volatile("" : "+f"(d[i]) :: "memory");
}
__device__ __forceinline__ void mbar_arrive_if(uint32_t bar, bool pred) {
    asm volatile("{ .reg .pred p; setp.ne.u32 p, %1, 0; @p mbarrier.arrive.shared::cta.b64 _, [%0]; }" :: "r"(bar), "r"((uint32_t)pred) : "memory");
}
__device__ __forceinline__ void warp_arrive(uint32_t bar) { __syncwarp(); if (elect_one()) mbar_arrive(bar); }
__device__ __forceinline__ void tma2d(uint32_t dst, const CUtensorMap* m, int c0, int c1, uint32_t bar) {
    asm volatile("cp.async.bulk.tensor.2d.shared::cluster.global.mbarrier::complete_tx::bytes [%0], [%1, {%3, %4}], [%2];"
                 :: "r"(dst), "l"(m), "r"(bar), "r"(c0), "r"(c1) : "memory");
}
__device__ __forceinline__ void tma3d(uint32_t dst, const CUtensorMap* m, int c0, int c1, int c2, uint32_t bar) {
    asm volatile("cp.async.bulk.tensor.3d.shared::cluster.global.mbarrier::complete_tx::bytes [%0], [%1, {%3, %4, %5}], [%2];"
                 :: "r"(dst), "l"(m), "r"(bar), "r"(c0), "r"(c1), "r"(c2) : "memory");
}
__device__ __forceinline__ void tma2d_mc(uint32_t dst, const CUtensorMap* m, int c0, int c1, uint32_t bar) {
    asm volatile("cp.async.bulk.tensor.2d.shared::cluster.global.mbarrier::complete_tx::bytes.multicast::cluster [%0], [%1, {%3, %4}], [%2], %5;"
                 :: "r"(dst), "l"(m), "r"(bar), "r"(c0), "r"(c1), "h"((uint16_t)3) : "memory");
}
__device__ __forceinline__ void mbar_arrive_remote_if(uint32_t cluster_bar, bool pred) {
    asm volatile("{ .reg .pred p; setp.ne.u32 p, %1, 0; @p mbarrier.arrive.shared::cluster.b64 _, [%0]; }" :: "r"(cluster_bar), "r"((uint32_t)pred) : "memory");
}
__device__ __forceinline__ void bulk_g2s(uint32_t dst, const void* src, uint32_t bytes, uint32_t bar) {
    asm volatile("cp.async.bulk.shared::cluster.global.mbarrier::complete_tx::bytes [%0], [%1], %2, [%3];"
                 :: "r"(dst), "l"(src), "r"(bytes), "r"(bar) : "memory");
}
__device__ __forceinline__ void bulk_prefetch(const void* src, uint32_t bytes) { asm volatile("cp.async.bulk.prefetch.L2.global [%0], %1;" :: "l"(src), "r"(bytes) : "memory"); }
__device__ __forceinline__ void wg_fence()  { asm volatile("wgmma.fence.sync.aligned;" ::: "memory"); }
__device__ __forceinline__ void wg_commit() { asm volatile("wgmma.commit_group.sync.aligned;" ::: "memory"); }
template <int N> __device__ __forceinline__ void wg_wait() { asm volatile("wgmma.wait_group.sync.aligned %0;" :: "n"(N) : "memory"); }
__device__ __forceinline__ void named_bar(int id, int n) { asm volatile("bar.sync %0, %1;" :: "r"(id), "r"(n) : "memory"); }
__device__ __forceinline__ void named_arrive(int id, int n) { asm volatile("bar.arrive %0, %1;" :: "r"(id), "r"(n) : "memory"); }
__device__ __forceinline__ void fence_async_smem() { asm volatile("fence.proxy.async.shared::cta;" ::: "memory"); }
__device__ __forceinline__ uint32_t gtime32() { uint64_t t; asm volatile("mov.u64 %0, %%globaltimer;" : "=l"(t) :: "memory"); return (uint32_t)t; }
__device__ __forceinline__ uint32_t clk32() { uint64_t t; asm volatile("mov.u64 %0, %%clock64;" : "=l"(t) :: "memory"); return (uint32_t)t; }
__device__ __forceinline__ void spin_until(uint32_t t) { while ((int)(clk32() - t) < 0) {} }
__device__ __forceinline__ void sleep_until(uint32_t t) { while ((int)(clk32() - t) < 0) __nanosleep(20); }
__device__ __forceinline__ void st_flag(uint32_t* p, uint32_t v, uint32_t time) {
    const uint64_t w = ((uint64_t)time << 32) | v;
    asm volatile("st.relaxed.gpu.global.u64 [%0], %1;" :: "l"(p), "l"(w) : "memory");
}
__device__ __forceinline__ void ld_flag_if(uint64_t& v, const uint32_t* p, bool pred) {
    asm volatile("{ .reg .pred p; setp.ne.u32 p, %2, 0; @p ld.relaxed.gpu.global.u64 %0, [%1]; }" : "+l"(v) : "l"(p), "r"((uint32_t)pred) : "memory");
}
__device__ __forceinline__ uint32_t ld_rlx(const uint32_t* p) { uint32_t v; asm volatile("ld.relaxed.gpu.global.u32 %0, [%1];" : "=r"(v) : "l"(p) : "memory"); return v; }
template <class T> __device__ __forceinline__ T* opaque_ptr(T* p) { asm volatile("" : "+l"(p)); return p; }
__device__ __forceinline__ uint4 ld_rlx4(const uint4* p) {
    uint4 v; asm volatile("ld.relaxed.gpu.global.v4.u32 {%0,%1,%2,%3}, [%4];" : "=r"(v.x), "=r"(v.y), "=r"(v.z), "=r"(v.w) : "l"(p) : "memory"); return v;
}
__device__ __forceinline__ uint2 ld_rlx2(const uint2* p) {
    uint2 v; asm volatile("ld.relaxed.gpu.global.v2.u32 {%0,%1}, [%2];" : "=r"(v.x), "=r"(v.y) : "l"(p) : "memory"); return v;
}
__device__ __forceinline__ void stg1(uint32_t* p, uint32_t v) { asm volatile("st.global.u32 [%0], %1;" :: "l"(p), "r"(v) : "memory"); }
__device__ __forceinline__ void stg4(void* p, uint32_t x, uint32_t y, uint32_t z, uint32_t w) { asm volatile("st.global.v4.u32 [%0], {%1,%2,%3,%4};" :: "l"(p), "r"(x), "r"(y), "r"(z), "r"(w) : "memory"); }
__device__ __forceinline__ uint32_t lds1(uint32_t a) { uint32_t v; asm volatile("ld.shared.u32 %0, [%1];" : "=r"(v) : "r"(a) : "memory"); return v; }
__device__ __forceinline__ uint2 lds2(uint32_t a) { uint2 v; asm volatile("ld.shared.v2.u32 {%0,%1}, [%2];" : "=r"(v.x), "=r"(v.y) : "r"(a) : "memory"); return v; }
__device__ __forceinline__ uint32_t set_par(uint32_t v, uint32_t mask, uint32_t par) {
    uint32_t r; asm("lop3.b32 %0, %1, %2, %3, 0xb8;" : "=r"(r) : "r"(v), "r"(mask), "r"(par)); return r;
}
__device__ __forceinline__ void st_gen4(void* p, uint32_t x, uint32_t y, uint32_t z, uint32_t w) { asm volatile("st.v4.u32 [%0], {%1,%2,%3,%4};" :: "l"(p), "r"(x), "r"(y), "r"(z), "r"(w) : "memory"); }
__device__ __forceinline__ float tanh_hw(float x) { float r; asm("tanh.approx.f32 %0, %1;" : "=f"(r) : "f"(x)); return r; }
__device__ __forceinline__ void sts4(uint32_t a, uint32_t x, uint32_t y, uint32_t z, uint32_t w) { asm volatile("st.shared.v4.u32 [%0], {%1,%2,%3,%4};" :: "r"(a), "r"(x), "r"(y), "r"(z), "r"(w) : "memory"); }
__device__ __forceinline__ uint4 lds4(uint32_t a) { uint4 v; asm volatile("ld.shared.v4.u32 {%0,%1,%2,%3}, [%4];" : "=r"(v.x), "=r"(v.y), "=r"(v.z), "=r"(v.w) : "r"(a) : "memory"); return v; }
__device__ __forceinline__ uint32_t pack_bf16(float lo, float hi) { uint32_t r; asm("cvt.rn.bf16x2.f32 %0, %1, %2;" : "=r"(r) : "f"(hi), "f"(lo)); return r; }
__device__ __forceinline__ float bf_lo(uint32_t v) { return __uint_as_float(v << 16); }
__device__ __forceinline__ float bf_hi(uint32_t v) { return __uint_as_float(v & 0xffff0000u); }
__device__ __forceinline__ uint32_t sub_bf16x2(uint32_t a, uint32_t b) { uint32_t r; asm volatile("sub.rn.bf16x2 %0, %1, %2;" : "=r"(r) : "r"(a), "r"(b)); return r; }
__device__ __forceinline__ uint32_t add_bf16x2(uint32_t a, uint32_t b) { uint32_t r; asm volatile("add.rn.bf16x2 %0, %1, %2;" : "=r"(r) : "r"(a), "r"(b)); return r; }
__device__ __forceinline__ uint32_t sqr_bf16x2(uint32_t a) { uint32_t r; asm volatile("mul.rn.bf16x2 %0, %1, %1;" : "=r"(r) : "r"(a)); return r; }
__device__ __forceinline__ uint32_t sqa_bf16x2(uint32_t a, uint32_t c) { uint32_t r; asm volatile("fma.rn.bf16x2 %0, %1, %1, %2;" : "=r"(r) : "r"(a), "r"(c)); return r; }
__device__ __forceinline__ uint32_t movm(uint32_t a) { uint32_t r; asm volatile("movmatrix.sync.aligned.m8n8.trans.b16 %0, %1;" : "=r"(r) : "r"(a)); return r; }
__device__ __forceinline__ float ex2(float x) { float r; asm("ex2.approx.ftz.f32 %0, %1;" : "=f"(r) : "f"(x)); return r; }
__device__ __forceinline__ float rsq(float x) { float r; asm("rsqrt.approx.ftz.f32 %0, %1;" : "=f"(r) : "f"(x)); return r; }
__device__ __forceinline__ float rcp(float x) { float r; asm("rcp.approx.ftz.f32 %0, %1;" : "=f"(r) : "f"(x)); return r; }
__device__ __forceinline__ void mma16816(float (&c)[4], uint32_t a0, uint32_t a1, uint32_t a2, uint32_t a3, uint32_t b0, uint32_t b1) {
    asm("mma.sync.aligned.m16n8k16.row.col.f32.bf16.bf16.f32 {%0,%1,%2,%3}, {%4,%5,%6,%7}, {%8,%9}, {%0,%1,%2,%3};"
        : "+f"(c[0]), "+f"(c[1]), "+f"(c[2]), "+f"(c[3]) : "r"(a0), "r"(a1), "r"(a2), "r"(a3), "r"(b0), "r"(b1));
}
__device__ __forceinline__ void mma1688(float (&c)[4], uint32_t a0, uint32_t a1, uint32_t b0) {
    asm("mma.sync.aligned.m16n8k8.row.col.f32.bf16.bf16.f32 {%0,%1,%2,%3}, {%4,%5}, {%6}, {%0,%1,%2,%3};"
        : "+f"(c[0]), "+f"(c[1]), "+f"(c[2]), "+f"(c[3]) : "r"(a0), "r"(a1), "r"(b0));
}
__device__ __forceinline__ float quad_sum(float v) { v += __shfl_xor_sync(~0u, v, 1); v += __shfl_xor_sync(~0u, v, 2); return v; }
__device__ __forceinline__ float quad_max(float v) { v = fmaxf(v, __shfl_xor_sync(~0u, v, 1)); v = fmaxf(v, __shfl_xor_sync(~0u, v, 2)); return v; }
__device__ __forceinline__ uint64_t make_desc(uint32_t addr, uint32_t lbo, bool swz, uint32_t sbo = 1024) {
    const uint32_t lo = __shfl_sync(~0u, ((addr & 0x3FFFF) >> 4) | ((lbo >> 4) << 16), 0);
    const uint32_t hi = __shfl_sync(~0u, (swz ? 0x40000000u : 0u) + (sbo >> 4) + (threadIdx.x & 31), 0);
    return ((uint64_t)hi << 32) | lo;
}
template <int I, int N, class F> __device__ __forceinline__ void static_for(F&& f) {
    if constexpr (I < N) { f(std::integral_constant<int, I>{}); static_for<I + 1, N>(f); }
}
__device__ __forceinline__ uint32_t opaque(uint32_t v) { asm volatile("" : "+r"(v)); return v; }
template <int BOFF, int SCALE_D>
__device__ __forceinline__ void wgmma_rs_n56(float (&d)[28], uint32_t a0, uint32_t a1, uint32_t a2, uint32_t a3, uint64_t db) {
    asm volatile("{ .reg .b64 db; add.s64 db, %32, %33;\n"
        "wgmma.mma_async.sync.aligned.m64n56k16.f32.bf16.bf16 "
        "{%0, %1, %2, %3, %4, %5, %6, %7, %8, %9, %10, %11, %12, %13, %14, %15, %16, %17, %18, %19, %20, %21, %22, %23, %24, %25, %26, %27}, "
        "{%28, %29, %30, %31}, db, %34, 1, 1, 1; }"
        : "+f"(d[0]), "+f"(d[1]), "+f"(d[2]), "+f"(d[3]), "+f"(d[4]), "+f"(d[5]), "+f"(d[6]), "+f"(d[7]),
        "+f"(d[8]), "+f"(d[9]), "+f"(d[10]), "+f"(d[11]), "+f"(d[12]), "+f"(d[13]), "+f"(d[14]), "+f"(d[15]),
        "+f"(d[16]), "+f"(d[17]), "+f"(d[18]), "+f"(d[19]), "+f"(d[20]), "+f"(d[21]), "+f"(d[22]), "+f"(d[23]),
        "+f"(d[24]), "+f"(d[25]), "+f"(d[26]), "+f"(d[27])
        : "r"(a0), "r"(a1), "r"(a2), "r"(a3), "l"(db), "n"(BOFF >> 4), "n"(SCALE_D));
}
template <int AOFF, int BOFF, int MMAJOR>
__device__ __forceinline__ void wgmma_ss_n56(float (&d)[28], uint64_t da, uint64_t db) {
    asm volatile("{ .reg .b64 da, db; add.s64 da, %28, %30; add.s64 db, %29, %31;\n"
        "wgmma.mma_async.sync.aligned.m64n56k16.f32.bf16.bf16 "
        "{%0, %1, %2, %3, %4, %5, %6, %7, %8, %9, %10, %11, %12, %13, %14, %15, %16, %17, %18, %19, %20, %21, %22, %23, %24, %25, %26, %27}, "
        "da, db, 1, 1, 1, %32, 1; }"
        : "+f"(d[0]), "+f"(d[1]), "+f"(d[2]), "+f"(d[3]), "+f"(d[4]), "+f"(d[5]), "+f"(d[6]), "+f"(d[7]),
        "+f"(d[8]), "+f"(d[9]), "+f"(d[10]), "+f"(d[11]), "+f"(d[12]), "+f"(d[13]), "+f"(d[14]), "+f"(d[15]),
        "+f"(d[16]), "+f"(d[17]), "+f"(d[18]), "+f"(d[19]), "+f"(d[20]), "+f"(d[21]), "+f"(d[22]), "+f"(d[23]),
        "+f"(d[24]), "+f"(d[25]), "+f"(d[26]), "+f"(d[27])
        : "l"(da), "l"(db), "n"(AOFF >> 4), "n"(BOFF >> 4), "n"(MMAJOR));
}
template <int AOFF, int BOFF, int MMAJOR>
__device__ __forceinline__ void wgmma_ss_n112(float (&d)[28], float (&e)[28], uint64_t da, uint64_t db) {
    asm volatile("{ .reg .b64 da, db; add.s64 da, %56, %58; add.s64 db, %57, %59;\n"
        "wgmma.mma_async.sync.aligned.m64n112k16.f32.bf16.bf16 "
        "{%0, %1, %2, %3, %4, %5, %6, %7, %8, %9, %10, %11, %12, %13, %14, %15, %16, %17, %18, %19, %20, %21, %22, %23, %24, %25, %26, %27, %28, %29, %30, %31, %32, %33, %34, %35, %36, %37, %38, %39, %40, %41, %42, %43, %44, %45, %46, %47, %48, %49, %50, %51, %52, %53, %54, %55}, "
        "da, db, 1, 1, 1, %60, 1; }"
        : "+f"(d[0]), "+f"(d[1]), "+f"(d[2]), "+f"(d[3]), "+f"(d[4]), "+f"(d[5]), "+f"(d[6]), "+f"(d[7]),
        "+f"(d[8]), "+f"(d[9]), "+f"(d[10]), "+f"(d[11]), "+f"(d[12]), "+f"(d[13]), "+f"(d[14]), "+f"(d[15]),
        "+f"(d[16]), "+f"(d[17]), "+f"(d[18]), "+f"(d[19]), "+f"(d[20]), "+f"(d[21]), "+f"(d[22]), "+f"(d[23]),
        "+f"(d[24]), "+f"(d[25]), "+f"(d[26]), "+f"(d[27]), "+f"(e[0]), "+f"(e[1]), "+f"(e[2]), "+f"(e[3]),
        "+f"(e[4]), "+f"(e[5]), "+f"(e[6]), "+f"(e[7]), "+f"(e[8]), "+f"(e[9]), "+f"(e[10]), "+f"(e[11]),
        "+f"(e[12]), "+f"(e[13]), "+f"(e[14]), "+f"(e[15]), "+f"(e[16]), "+f"(e[17]), "+f"(e[18]), "+f"(e[19]),
        "+f"(e[20]), "+f"(e[21]), "+f"(e[22]), "+f"(e[23]), "+f"(e[24]), "+f"(e[25]), "+f"(e[26]), "+f"(e[27])
        : "l"(da), "l"(db), "n"(AOFF >> 4), "n"(BOFF >> 4), "n"(MMAJOR));
}
template <int BOFF, int SCALE_D>
__device__ __forceinline__ void wgmma_rs_n112(float (&d)[28], float (&e)[28], uint32_t a0, uint32_t a1, uint32_t a2, uint32_t a3, uint64_t db) {
    asm volatile("{ .reg .b64 db; add.s64 db, %60, %61;\n"
        "wgmma.mma_async.sync.aligned.m64n112k16.f32.bf16.bf16 "
        "{%0, %1, %2, %3, %4, %5, %6, %7, %8, %9, %10, %11, %12, %13, %14, %15, %16, %17, %18, %19, %20, %21, %22, %23, %24, %25, %26, %27, %28, %29, %30, %31, %32, %33, %34, %35, %36, %37, %38, %39, %40, %41, %42, %43, %44, %45, %46, %47, %48, %49, %50, %51, %52, %53, %54, %55}, "
        "{%56, %57, %58, %59}, db, %62, 1, 1, 1; }"
        : "+f"(d[0]), "+f"(d[1]), "+f"(d[2]), "+f"(d[3]), "+f"(d[4]), "+f"(d[5]), "+f"(d[6]), "+f"(d[7]),
        "+f"(d[8]), "+f"(d[9]), "+f"(d[10]), "+f"(d[11]), "+f"(d[12]), "+f"(d[13]), "+f"(d[14]), "+f"(d[15]),
        "+f"(d[16]), "+f"(d[17]), "+f"(d[18]), "+f"(d[19]), "+f"(d[20]), "+f"(d[21]), "+f"(d[22]), "+f"(d[23]),
        "+f"(d[24]), "+f"(d[25]), "+f"(d[26]), "+f"(d[27]), "+f"(e[0]), "+f"(e[1]), "+f"(e[2]), "+f"(e[3]),
        "+f"(e[4]), "+f"(e[5]), "+f"(e[6]), "+f"(e[7]), "+f"(e[8]), "+f"(e[9]), "+f"(e[10]), "+f"(e[11]),
        "+f"(e[12]), "+f"(e[13]), "+f"(e[14]), "+f"(e[15]), "+f"(e[16]), "+f"(e[17]), "+f"(e[18]), "+f"(e[19]),
        "+f"(e[20]), "+f"(e[21]), "+f"(e[22]), "+f"(e[23]), "+f"(e[24]), "+f"(e[25]), "+f"(e[26]), "+f"(e[27])
        : "r"(a0), "r"(a1), "r"(a2), "r"(a3), "l"(db), "n"(BOFF >> 4), "n"(SCALE_D));
}

struct Params {
    const __nv_bfloat16 *x, *wqkv;
    Scratch* sc;
    const __nv_bfloat16 *wo, *w1, *w2, *b1, *b2;
    __nv_bfloat16* out;
};

__global__ void __cluster_dims__(2, 1, 1) __launch_bounds__(384, 1)
fused_kernel(const Params prm, const __grid_constant__ CUtensorMap mX2, const __grid_constant__ CUtensorMap mX, const __grid_constant__ CUtensorMap mWqkv,
             const __grid_constant__ CUtensorMap mWo, const __grid_constant__ CUtensorMap mW1,
             const __grid_constant__ CUtensorMap mW2)
{
    extern __shared__ __align__(1024) unsigned char smem_raw[];
    if (threadIdx.x < 126) {
        const uint32_t i = threadIdx.x, t = clk32() + (i >> 5) * PFD;
        const char* px = (const char*)prm.x + (blockIdx.x * 16 + (i & 15)) * 896 + (i >> 4) * 128;
        const char* pw = (const char*)prm.wqkv + blockIdx.x * 2688 + i * 128 + (896 - 112 * 128);
        spin_until(t);
        asm volatile("prefetch.global.L2 [%0];" :: "l"(i < 112 ? px : pw) : "memory");
    }
    if (threadIdx.x == 128) { asm volatile("prefetch.tensormap [%0];" :: "l"(&mX2) : "memory"); asm volatile("prefetch.tensormap [%0];" :: "l"(&mWqkv) : "memory"); }
    uint32_t sb = (uint32_t)__cvta_generic_to_shared(smem_raw);
    asm volatile("mov.u32 %0, %0;" : "+r"(sb));
    const uint32_t bar0 = sb + SM_BAR;
    auto BAR = [&](int i) { return bar0 + 8u * i; };

    const int tid = threadIdx.x, lane = tid & 31;
    const int warp = __shfl_sync(~0u, tid >> 5, 0);
    const int b = __shfl_sync(~0u, (int)blockIdx.x, 0);
    const int rank = b & 1;
    const int cl = (b >> 1) - 4, cq = ((cl - 32) * 37) >> 8;
    const int res = cl < 0 ? 0 : cl < 32 ? cl & 7 : cl - 31 - 7 * cq;
    const int rnd = cl < 0 ? cl + 8 : cl < 32 ? cl >> 3 : 4 + cq;
    const int hg = (res & 1) * 4 + (rnd & 3);
    const int ti = (res >> 1) * 4 + (rnd >> 2) * 2 + rank;
    const int a2p = res & 1, a2j = rnd & 3;
    const int a2s = ti * 2 + a2p;
    const bool g1_on = rnd != 7;
    const int g1j = (rnd < 6 ? rnd : res) & 1, g1f = rnd < 6 ? res * 3 + (rnd >> 1) : 24 + (res >> 1);
    const int g2j = rnd & 1, g2s = res * 4 + (rnd >> 1);
    uint32_t pbar0;
    asm volatile("mapa.shared::cluster.u32 %0, %1, %2;" : "=r"(pbar0) : "r"(bar0), "r"(rank ^ 1));
    auto pair_arrive = [&](int i) { __syncwarp(); const bool l = elect_one(); mbar_arrive_if(BAR(i), l); mbar_arrive_remote_if(pbar0 + 8u * i, l); };
    const int wcol = hg * 56 - (hg & 1) * 8;

    if (warp == 8) {
        if (elect_one()) {
            #pragma unroll
            for (int i = 0; i < B_WQF; i++) mbar_init(BAR(i), 1);
            asm volatile("fence.mbarrier_init.release.cluster;" ::: "memory");
            fence_async_smem();
            #pragma unroll
            for (int kb = 0; kb < 7; kb++) {
                tma3d(sb + kb * 16384, &mX2, kb * 64, ti * 64, 0, BAR(B_XF + kb));
                mbar_expect(BAR(B_XF + kb), 16384);
            }
        }
    } else if (warp > 8) {
        if (elect_one()) {
            if (warp == 9) {
                #pragma unroll
                for (int i = B_WQF; i < B_AF; i++) mbar_init(BAR(i), i < B_XC ? 1 : i < B_A1D ? 16 : i < B_BE ? 8 : 4);
            } else if (warp == 10) {
                #pragma unroll
                for (int i = B_AF; i < B_BF; i++) mbar_init(BAR(i), 1);
            } else {
                #pragma unroll
                for (int i = B_BF; i < B_COUNT; i++) mbar_init(BAR(i), i == B_HD ? 8 : 1);
            }
            asm volatile("fence.mbarrier_init.release.cluster;" ::: "memory");
            fence_async_smem();
        }
    }
    __syncwarp();
    __syncthreads();
    asm volatile("barrier.cluster.arrive.relaxed.aligned;" ::: "memory");

    if (warp >= 8) {
        asm volatile("setmaxnreg.dec.sync.aligned.u32 40;");
        asm volatile("barrier.cluster.wait.aligned;" ::: "memory");
        auto fetch_halo = [&](int p, uint32_t tag) {
            const uint32_t hl = BAR(B_HL + p), dst = opaque(sb + SM_STG + p * 8192 + 3 * 2048 + lane * 16);
            const bool lead = elect_one();
            if (rank) { if (lead) mbar_expect(hl, 2048); __syncwarp(); return; }
            const uint4* hp = opaque_ptr(&prm.sc->halo[((((ti >> 1) - 1) * 8 + hg) * 2 + p) * 128 + lane]);
            mbar_wait(BAR(B_KVC), 0);
            if (ti > 0) {
                spin_until(clk32() + HDELAY);
                int it = 0;
                uint32_t bad;
                do {
                    uint4 u[4];
                    #pragma unroll
                    for (int c = 0; c < 4; c++) u[c] = ld_rlx4(hp + c * 32);
                    #pragma unroll
                    for (int c = 0; c < 4; c++) sts4(dst + c * 512, u[c].x, u[c].y, u[c].z, u[c].w);
                    bad = ((u[0].x ^ tag) | (u[1].x ^ tag) | (u[2].x ^ tag) | (u[3].x ^ tag)) & ~lane & 1;
                } while (__any_sync(~0u, bad) && ++it < kSpinLimit);
            } else {
                #pragma unroll
                for (int c = 0; c < 4; c++) sts4(dst + c * 512, 0u, 0u, 0u, 0u);
            }
            __syncwarp();
            mbar_arrive_if(hl, lead);
        };
        auto poll_flags = [&](const uint32_t* fp, int step, uint32_t tag, uint32_t gbase) {
            uint64_t v0 = 0, v1 = 0;
            int it = 0;
            do {
                ld_flag_if(v0, fp, (uint32_t)v0 != tag); ld_flag_if(v1, fp + step, (uint32_t)v1 != tag);
                if (++it > kSpinLimit) break;
            } while (__any_sync(~0u, (uint32_t)v0 != tag || (uint32_t)v1 != tag));
            return max((int)((uint32_t)(v0 >> 32) - gbase), (int)((uint32_t)(v1 >> 32) - gbase));
        };
        if (warp & 1) {
            uint32_t tag;
            if (warp == 11) {
                tag = *(volatile uint32_t*)&prm.sc->epoch + 1;
                #pragma unroll 1
                for (int i = 0; i < 8 * rank; i++) prm.sc->halo[((ti >> 1) * 8 + hg) * 256 + i * 32 + lane] = make_uint4(~tag, 0u, 0u, 0u);
                ((uint4*)prm.sc->stats)[(a2s * 4 + a2j) * 64 + lane] = ((uint4*)prm.sc->stats)[(a2s * 4 + a2j) * 64 + 32 + lane] = make_uint4(~tag, ~tag, ~tag, ~tag);
                prm.sc->flag_h[(a2s * 4 + a2j) * FS + lane] = 0;
                prm.sc->flag_o[(ti * 8 + hg) * FS + lane] = 0;
                __syncwarp();
                if (lane == 0) {
                    asm volatile("st.shared.v2.u32 [%0], {%1, %2};" :: "r"(sb + SM_EPOCH), "r"(tag), "r"(gtime32()) : "memory");
                    mbar_arrive(BAR(B_EP));
                }
                if (lane < 8) mbar_expect(BAR(B_RF + lane), 1792);
                __syncwarp();
            } else {
                mbar_wait(BAR(B_EP), 0);
                tag = lds1(sb + SM_EPOCH);
            }
            fetch_halo((warp >> 1) & 1, tag);
        }
        if (warp < 10) {
          auto load_slab = [&](int s, bool second) {
              if (!second) tma2d(sb + s * 8192, &mW1, (s & 1) * kF + g1f * 64, (rank * 8 + (s >> 1)) * 64, BAR(B_AF));
              else         tma2d(sb + s * 8192, &mW2, g2s * 64, (rank * 14 + s - 1) * 64, BAR(B_AF));
          };
          const char* pw2 = (const char*)prm.w2 + ((b >> 6) * 896 + (b & 63) + PFW * 64) * 4096;
          if (warp == 8) {
            if (elect_one()) {
                #pragma unroll 1
                for (int s = 0; s < 7; s++) {
                    mbar_expect(BAR(B_WKVF + s), 16384);
                    tma2d_mc(sb + SM_WKV + s * 16384 + rank * 8192, &mWqkv, (1 + rank) * kD + wcol, s * 64, BAR(B_WKVF + s));
                }
            }
            __syncwarp();
            mbar_wait(BAR(B_XC), 0);
            if (elect_one()) {
                asm volatile("prefetch.tensormap [%0];" :: "l"(&mX) : "memory");
                asm volatile("prefetch.tensormap [%0];" :: "l"(&mWo) : "memory");
                asm volatile("prefetch.tensormap [%0];" :: "l"(&mW1) : "memory");
                asm volatile("prefetch.tensormap [%0];" :: "l"(&mW2) : "memory");
                mbar_expect(BAR(B_AF), (g1_on ? NPRE : 14) * 8192);
                mbar_expect(BAR(B_WQF), 57344);
                #pragma unroll 1
                for (int s = rank; s < 7; s += 2) tma2d_mc(sb + SM_WQ + s * 8192, &mWqkv, wcol, s * 64, BAR(B_WQF));
                mbar_expect(BAR(B_XRF), 16384);
                tma2d(sb + SM_XR, &mX, a2p * kD + a2j * 112, ti * 64, BAR(B_XRF));
                tma2d(sb + SM_XR + 8192, &mX, a2p * kD + a2j * 112 + 48, ti * 64, BAR(B_XRF));
            }
            __syncwarp();
            #pragma unroll 1
            for (int q = 0; q < 4; q++) {
                mbar_wait(BAR(B_KV3 + (q >> 1)), 0);
                if (q == 2) spin_until(clk32() + WOD);
                if (q == 3) mbar_wait2(BAR(B_HL), 0, BAR(B_HL + 1), 0);
                if (elect_one()) {
                    if (!(q & 1)) mbar_expect(BAR(B_WOF + (q >> 1)), 57344);
                    tma2d_mc(sb + SM_WKV + q * 28672 + rank * 14336, &mWo, a2j * 112 + (q & 1) * 48, (q >> 1) * 224 + rank * 112, BAR(B_WOF + (q >> 1)));
                    if (g1_on && q == 1) { load_slab(0, false); load_slab(1, false); load_slab(2, false); }
                }
                __syncwarp();
            }
            if (g1_on) {
                mbar_wait2(BAR(B_XD), 0, BAR(B_OL + 3), 0);
                #pragma unroll 1
                for (int i = 3; i < NPRE; i++) {
                    if (i == 7) mbar_wait(BAR(B_OC), 0);
                    if (elect_one()) load_slab(i, false);
                    __syncwarp();
                }
            } else {
                mbar_arrive_if(BAR((lane < 16 ? B_BE : B_BF) + (lane & 3)), lane < 20);
                mbar_wait(BAR(B_HD), 0);
                mbar_arrive_remote_if(pbar0 + 8u * B_PD, lane == 0);
                mbar_wait(BAR(B_GO), 0);
                uint32_t tg = lds1(sb + SM_TG + 4);
                tg += max((int)(lds1(sb + SM_TG2) - tg), 0);
                int it = 0;
                while ((int)(gtime32() - tg) < 0 && ++it < 256) {}
                const uint32_t t0 = clk32();
                if (lane < 2) {
                    asm volatile("st.shared.u32 [%0], %1;" :: "r"(sb + SM_TG + 8 + lane * 4), "r"(t0 + (lane ? CN3 : CN2)) : "memory");
                    mbar_arrive(BAR(B_GD + lane));
                }
                __syncwarp();
                #pragma unroll 1
                for (int s = 1; s < 15; s++) {
                    sleep_until(t0 + W2OFF + s * W2PACE);
                    if (elect_one()) { if (s < 15 - PFW) bulk_prefetch(pw2 + (s - 1) * 64 * 4096, 4096); load_slab(s, true); }
                    __syncwarp();
                }
            }
          } else {
            const uint32_t tag = lds1(sb + SM_EPOCH);
            if (lane < 4) mbar_expect(BAR(B_OL + lane), 14336);
            const uint32_t gbase = lds1(sb + SM_TG);
            const bool lead = elect_one();
            uint32_t* hfl = opaque_ptr(&prm.sc->flag_h[(a2s * 4 + a2j) * FS]);
            mbar_wait(BAR(B_A1D), 0);
            const int d = poll_flags(&prm.sc->flag_o[(ti * 8 + (lane & 3) * 2) * FS], FS, tag, gbase);
            int key = max(d + DELTAO, __reduce_max_sync(~0u, d) + DMIN) * 4 + (lane & 3);
            uint32_t order = 0;
            #pragma unroll 1
            for (int i = 0; i < 4; i++) {
                const int m = __reduce_min_sync(~0u, key);
                const uint4* src = &prm.sc->o[(a2s * 4 + (m & 3)) * 896];
                int it = 0;
                while ((int)(gtime32() - gbase) < m >> 2 && ++it < 256) {}
                if (lead) bulk_g2s(sb + SM_WQ + i * 14336, src, 14336, BAR(B_OL + i));
                if (key == m) key = 0x7fffffff;
                order |= (m & 3) << i * 2;
            }
            if (lead) {
                asm volatile("st.shared.u32 [%0], %1;" :: "r"(sb + SM_ORD), "r"(order) : "memory");
                mbar_arrive(BAR(B_OD));
            }
            __syncwarp();
            int t0 = 0;
            #pragma unroll 1
            for (int i = 0; i < 4; i++) { mbar_wait(BAR(B_OF + i), 0); t0 = max(t0, (int)(gtime32() - gbase) - i * CHUNKNS); }
            if (lead) st_flag(hfl, tag, gbase + t0);
            __syncwarp();
          }
          if (elect_one()) {
              const int h = ~warp & 1;
              constexpr uint32_t T = 57344, BO = 2 * 14336;
              const char* src1 = (const char*)&prm.sc->hn[(rank * 16 + h) * 3584 + g1j * 896];
              const char* src2 = (const char*)&prm.sc->g[(rank * 14 + h) * 3584 + g2j * 896];
              uint64_t masks = g1_on ? (h ? kSegMasks1 : kSegMasks0) : 0x80 | 0x80 << 10;
              const uint32_t bl = BAR(B_BL + h * NB);
              uint32_t s8 = (g1_on ? NB - 2 + h : 4 + h) * 8, lap = 3, tmin = 0;
              const CUtensorMap* am = &mW1;
              uint32_t ad = sb + (NPRE + h) * 8192, astep = 16384; int ac0 = h * kF + g1f * 64, ac1 = (rank * 8 + NPRE / 2) * 64;
              #pragma unroll 1
              for (int seg = g1_on ? 0 : 3; seg < 5; seg++) {
                  const char* src = (seg < 3 ? src1 : src2) + (~seg & 1) * BO;
                  uint32_t m = (uint32_t)masks & 0x3ff;
                  masks >>= 10;
                  const uint32_t pace = seg == 4 ? PACEB : PACE2;
                  if (seg == 2) {
                      mbar_wait(BAR(B_PL), 0);
                      mbar_arrive_remote_if(pbar0 + 8u * B_PD, h);
                      am = &mW2; ad = sb + 8192; astep = 8192; ac0 = g2s * 64; ac1 = rank * 14 * 64;
                  } else {
                      const int gate = seg - (seg > 2);
                      mbar_wait(BAR(B_HD + gate), 0);
                      tmin = lds1(sb + SM_TG + gate * 4);
                      if (gate < 2) {
                          tmin += max((int)(lds1(gate ? sb + SM_TG2 : sb + SM_TG) - tmin), 0);
                          int it = 0;
                          while ((int)(gtime32() - tmin) < 0 && ++it < 256) {}
                          tmin = clk32();
                      }
                      tmin += h * PACE1;
                  }
                  #pragma unroll 1
                  do {
                      const uint32_t dst = sb + SM_B + s8 * 1792;
                      spin_until(tmin);
                      mbar_wait_fast(BAR(B_BE) + s8 + (lap & 1) * (NB * 8), lap >> 1 & 1);
                      if (seg) {
                          bulk_g2s(dst, src, 14336, bl + s8);
                          mbar_expect(bl + s8, 14336);
                      }
                      tmin += pace;
                      src += 2 * T;
                      s8 += 16;
                      if (s8 >= NB * 8) { s8 -= NB * 8; lap++; }
                      if (m & 1) {
                          mbar_expect_more(bl + s8, 8192);
                          tma2d(ad, am, ac0, ac1, bl + s8);
                          ad += astep; ac1 += 64;
                      }
                      m >>= 1;
                  } while (m != 1);
                  if (seg == 0) lap = 3;
              }
          }
        } else {
          if (warp == 10) {
            mbar_wait(BAR(B_XF + 6), 0);
            if (lane < 27) asm volatile("prefetch.global.L2 [%0];" :: "l"(lane < 25 ? (const char*)prm.wo + min(b * 25 + lane, 3135) * 128
                                                                          : lane == 25 ? (const char*)prm.b1 + (b % 28) * 128 : (const char*)prm.b2 + (b & 31) * 128));
            const char* p1 = (const char*)prm.w1 + ((b >> 6) * 1024 + (b & 63) * 2) * 3584 + min(lane, 27) * 128;
            uint32_t tnext = clk32();
            #pragma unroll 1
            for (int i = 0; i < 16; i++) {
                while ((int)(clk32() - tnext) < 0) __nanosleep(40);
                asm volatile("prefetch.global.L2 [%0];" :: "l"(p1 + ((i >> 1) * 128 + (i & 1)) * 3584));
                tnext += PFPACE;
            }
            uint32_t* ofl = opaque_ptr(&prm.sc->flag_o[(ti * 8 + hg) * FS]);
            mbar_wait(BAR(B_EP), 0);
            const uint32_t tag = lds1(sb + SM_EPOCH);
            mbar_wait2(BAR(B_HL), 0, BAR(B_HL + 1), 0);
            mbar_wait(BAR(B_A1D), 0);
            if (lane == 0) st_flag(ofl, tag, gtime32());
            __syncwarp();
          }
          const uint32_t tag = lds1(sb + SM_EPOCH);
          const int h = warp & 1;
          const bool lead = elect_one();
          const uint32_t wo = lane * 132, l3 = lane < 16 ? 12288 : 0;
          uint32_t base = sb + SM_WQ, bl = BAR(B_OL), bf = BAR(B_OF), m = 4, rph = 0;
          #pragma unroll 1
          for (int e = 0; e < 2; e++) {
              uint32_t s8 = (e && !g1_on ? 4 + h : h) * 8;
              #pragma unroll 1
              do {
                  const uint32_t dst = base + s8 * 1792;
                  auto stale = [&]() {
                      uint32_t d;
                      asm volatile("{ .reg .b32 x, y, z, u;\n"
                                   "ld.shared.u32 x, [%1]; ld.shared.u32 y, [%1 + 4096]; ld.shared.u32 z, [%1 + 8192]; ld.shared.u32 u, [%2];\n"
                                   "lop3.b32 x, x, y, %3, 0x7e; lop3.b32 z, z, u, %3, 0x7e; lop3.b32 %0, x, z, 1, 0xa8; }"
                                   : "=r"(d) : "r"(dst + wo), "r"(dst + (wo + l3)), "r"(tag) : "memory");
                      return __any_sync(~0u, d);
                  };
                  mbar_wait_fast(bl + s8, m & 1);
                  bool bad = stale();
                  mbar_arrive_if(bf + s8, lead && !bad);
                  if (bad) {
                      const int p = 2 * __clz(m) - 2 + h;
                      const int st = (p > 15) + (p > 31) + (p > 45), s = p - (st < 3 ? 16 * st : 46);
                      mbar_wait(BAR(B_OD), 0);
                      const char* src = (const char*)(!e ? &prm.sc->o[(a2s * 4 + (lds1(sb + SM_ORD) >> (p * 2 & 7) & 3)) * 896] : st < 2 ? &prm.sc->hn[(rank * 16 + s) * 3584 + (g1j + 2 * st) * 896]
                                                                                                      : &prm.sc->g[(rank * 14 + s) * 3584 + (g2j + 2 * st - 4) * 896]);
                      int it = 0;
                      do {
                          if (++it > kSpinLimit) break;
                          const uint32_t* q = (const uint32_t*)(src + wo);
                          if (it > 1 && __any_sync(~0u, ((ld_rlx(q) ^ tag) | (ld_rlx(q + 1024) ^ tag) | (ld_rlx(q + 2048) ^ tag) | (ld_rlx(q + l3 / 4) ^ tag)) & 1)) continue;
                          if (lead) {
                              mbar_expect(BAR(B_RT + h), 14336);
                              bulk_g2s(dst, src, 14336, BAR(B_RT + h));
                          }
                          __syncwarp();
                          mbar_wait(BAR(B_RT + h), rph);
                          rph ^= 1;
                          bad = stale();
                      } while (bad);
                      mbar_arrive_if(bf + s8, lead);
                  }
                  s8 += 16;
                  if (s8 >= NB * 8) s8 -= NB * 8;
                  m >>= 1;
              } while (m != 1);
              if (e) break;
              if (h) {
                  const uint32_t gbase = lds1(sb + SM_TG);
                  sleep_until(clk32() + PDELAY);
                  const uint32_t tg = gbase + DELTA + __reduce_max_sync(~0u, poll_flags(&prm.sc->flag_h[(rank * 64 + lane) * FS], 32 * FS, tag, gbase));
                  if (lead) {
                      asm volatile("st.async.shared::cluster.mbarrier::complete_tx::bytes.b32 [%0], %1, [%2];"
                                   :: "r"(pbar0 + (SM_TG2 - SM_BAR)), "r"(tg), "r"(pbar0 + 8u * B_GO) : "memory");
                      asm volatile("st.shared.u32 [%0], %1;" :: "r"(sb + SM_TG + 4), "r"(tg) : "memory");
                      mbar_expect(BAR(B_GO), 4);
                  }
                  __syncwarp();
              } else {
                  const char* p2 = (const char*)prm.w2 + ((b >> 6) * 896 + (b & 63)) * 4096 + lane * 128;
                  #pragma unroll 1
                  for (int i = 0; i < PFW; i++) {
                      asm volatile("prefetch.global.L2 [%0];" :: "l"(p2 + i * 64 * 4096));
                      sleep_until(clk32() + PFPACE2);
                  }
              }
              base = sb + SM_B; bl = BAR(B_BL + h * NB); bf = BAR(B_BF); m = g1_on ? 0x4fe03f80 : 0x7f80;
          }
        }
    } else {
        asm volatile("setmaxnreg.inc.sync.aligned.u32 232;");
        asm volatile("barrier.cluster.wait.aligned;" ::: "memory");
        const int wg = warp >> 2, w = warp & 3;
        const int g = lane >> 2, t = lane & 3;
        uint32_t tag;
        __nv_bfloat16 bias1a, bias1b;
        {
            const uint64_t dw = make_desc(sb + (hg & 1) * 16, 0, true);
            uint4* const hp = opaque_ptr((w == 3 ? &prm.sc->halo[(((ti >> 1) * 8 + hg) * 2 + wg) * 128] : (uint4*)(smem_raw + SM_STG + wg * 8192 + w * 2048)) + lane);
            uint32_t a[28][4];
            float sm[4][4] = {};
            {
                const int r = w * 16 + (lane & 15);
                uint32_t xa[4];
                #pragma unroll
                for (int q = 0; q < 4; q++) xa[q] = opaque(sb + wg * 8192 + r * 128 + (((q * 2 + (lane >> 4)) ^ (r & 7)) << 4));
                const uint32_t one = opaque(0x3F803F80u), one2 = opaque(0x3F803F80u);
                #pragma unroll
                for (int k = 0; k < 28; k++) {
                    if ((k & 3) == 0) mbar_wait(BAR(B_XF + (k >> 2)), 0);
                    uint32_t (&f)[4] = a[k];
                    asm volatile("ldmatrix.sync.aligned.m8n8.x4.shared.b16 {%0,%1,%2,%3}, [%4];"
                                 : "=r"(f[0]), "=r"(f[1]), "=r"(f[2]), "=r"(f[3]) : "r"(xa[k & 3] + (k >> 2) * 16384) : "memory");
                    if (k < 24) mma16816(sm[k & 3], f[0], f[1], f[2], f[3], one, one2);
                }
                pair_arrive(B_XC);
                const bool wok = mbar_test(BAR(B_WKVF), 0);
                #pragma unroll
                for (int k = 24; k < 28; k++) mma16816(sm[k & 3], a[k][0], a[k][1], a[k][2], a[k][3], one, one2);
                if (!wok) mbar_wait(BAR(B_WKVF), 0);
            }
            const float mean0 = ((sm[0][0] + sm[1][0]) + (sm[2][0] + sm[3][0])) * (1.f / kD);
            const float mean1 = ((sm[0][2] + sm[1][2]) + (sm[2][2] + sm[3][2])) * (1.f / kD);
            const uint32_t mb0 = pack_bf16(mean0, mean0), mb1 = pack_bf16(mean1, mean1);
            float ak[28], av[28], aq[28];
            float ss0 = 0.f, ss1 = 0.f, ss2 = 0.f, ss3 = 0.f;
            uint32_t p0, p1;
            bool qok;
            static_for<0, 7>([&](auto S_) {
                constexpr int s = decltype(S_)::value;
                auto centre = [&](int q) {
                    uint32_t (&f)[4] = a[s * 4 + q];
                    f[0] = sub_bf16x2(f[0], mb0); f[1] = sub_bf16x2(f[1], mb1);
                    f[2] = sub_bf16x2(f[2], mb0); f[3] = sub_bf16x2(f[3], mb1);
                };
                if (s) {
                    #pragma unroll
                    for (int q = 0; q < 4; q++) centre(q);
                    mbar_wait(BAR(B_WKVF + s), 0);
                    if (s == 6) qok = mbar_test(BAR(B_WQF), 0);
                    wg_fence();
                }
                static_for<0, 4>([&](auto Q_) {
                    constexpr int q = decltype(Q_)::value;
                    uint32_t (&f)[4] = a[s * 4 + q];
                    if (s == 0) { centre(q); wg_fence(); }
                    wgmma_rs_n56<SM_WKV + s * 16384 + q * 2048, (s | q) != 0>(ak, f[0], f[1], f[2], f[3], dw);
                    wgmma_rs_n56<SM_WKV + s * 16384 + q * 2048 + 8192, (s | q) != 0>(av, f[0], f[1], f[2], f[3], dw);
                });
                wg_commit();
                if (s == 4) { wg_wait<1>(); pair_arrive(B_KV3); }
                if (s < 2) mbar_wait(BAR(s ? B_EP : B_WKVF), 0);
                if (s == 1) tag = lds1(sb + SM_EPOCH);
                #pragma unroll
                for (int q = 0; q < 8; q++) {
                    const uint32_t u0 = a[s * 4 + q / 2][(q & 1) * 2], u1 = a[s * 4 + q / 2][(q & 1) * 2 + 1];
                    if (q == 0) { p0 = sqr_bf16x2(u0); p1 = sqr_bf16x2(u1); }
                    else { p0 = sqa_bf16x2(u0, p0); p1 = sqa_bf16x2(u1, p1); }
                }
                ss0 += bf_lo(p0); ss2 += bf_hi(p0); ss1 += bf_lo(p1); ss3 += bf_hi(p1);
            });
            auto q_chunk = [&](auto K0_, auto K1_) {
                wg_fence();
                static_for<decltype(K0_)::value, decltype(K1_)::value>([&](auto K_) {
                    constexpr int k = decltype(K_)::value;
                    wgmma_rs_n56<SM_WQ + k * 2048, k != 0>(aq, a[k][0], a[k][1], a[k][2], a[k][3], dw);
                });
                wg_commit();
            };
            #define QCHUNK(k0, k1) q_chunk(std::integral_constant<int, k0>{}, std::integral_constant<int, k1>{})
            const float dl0 = mean0 - bf_lo(mb0), dl1 = mean1 - bf_lo(mb1);
            const float rs0 = rsq(fmaxf(quad_sum(ss0 + ss2) * (1.f / kD) - dl0 * dl0, 0.f) + kEps);
            const float rs1 = rsq(fmaxf(quad_sum(ss1 + ss3) * (1.f / kD) - dl1 * dl1, 0.f) + kEps);
            float rk[3][2];
            rk[1][0] = __shfl_sync(~0u, rs0, t * 8); rk[1][1] = __shfl_sync(~0u, rs0, t * 8 + 4);
            rk[2][0] = __shfl_sync(~0u, rs1, t * 8); rk[2][1] = __shfl_sync(~0u, rs1, t * 8 + 4);
            const uint32_t stg = sb + SM_STG + wg * 8192 + lane * 16;
            if (!qok) mbar_wait(BAR(B_WQF), 0);
            QCHUNK(0, QC0);
            wg_wait<1>();
            reg_fence(ak); reg_fence(av);
            uint32_t kf[3][7], vf[3][7];
            #pragma unroll
            for (int c = 0; c < 7; c++) {
                kf[2][c] = pack_bf16(ak[4 * c + 2], ak[4 * c + 3]);
                vf[2][c] = movm(pack_bf16(av[4 * c + 2], av[4 * c + 3]));
            }
            const uint32_t om = ~lane & 1;
            kf[2][0] = set_par(kf[2][0], om, tag); kf[2][4] = set_par(kf[2][4], om, tag);
            vf[2][1] = set_par(vf[2][1], om, tag); vf[2][5] = set_par(vf[2][5], om, tag);
            auto publish = [&](auto st) {
                st(0, kf[2][0], kf[2][1], kf[2][2], kf[2][3]);
                st(1, kf[2][4], kf[2][5], kf[2][6], vf[2][0]);
                st(2, vf[2][1], vf[2][2], vf[2][3], vf[2][4]);
                st(3, vf[2][5], vf[2][6], __float_as_uint(rk[2][0]), __float_as_uint(rk[2][1]));
            };
            if (w < 3 || rank) publish([&](int c, uint32_t x, uint32_t y, uint32_t z, uint32_t v) { st_gen4(hp + c * 32, x, y, z, v); });
            else publish([&](int c, uint32_t x, uint32_t y, uint32_t z, uint32_t v) {
                asm volatile("st.async.shared::cluster.mbarrier::complete_tx::bytes.v4.b32 [%0], {%2,%3,%4,%5}, [%1];"
                             :: "r"(pbar0 + (SM_STG + 3 * 2048 - SM_BAR) + wg * 8192 + lane * 16 + c * 512), "r"(pbar0 + (B_HL + wg) * 8),
                                "r"(x), "r"(y), "r"(z), "r"(v) : "memory");
            });
            pair_arrive(B_KVC);
            QCHUNK(QC0, QC1);
            #pragma unroll
            for (int c = 0; c < 7; c++) {
                kf[1][c] = pack_bf16(ak[4 * c], ak[4 * c + 1]);
                vf[1][c] = movm(pack_bf16(av[4 * c], av[4 * c + 1]));
            }
            QCHUNK(QC1, QC2);
            named_bar(1 + wg, 128);
            uint32_t* op = opaque_ptr((uint32_t*)&prm.sc->o[((ti * 2 + wg) * 56 + hg * 7) * 64] + w * 64 + lane);
            const uint32_t om0 = opaque((lane & 7) == w * 2), om1 = opaque((lane & 7) == w * 2 + 1);
            QCHUNK(QC2, 28);
            #undef QCHUNK
            const bool gt0 = 2 * t > g, gt1 = 2 * t + 1 > g, no_prev = ti == 0 && w == 0;
            const float kf0 = gt0 ? rk[1][0] : rk[2][0], kf1 = gt1 ? rk[1][1] : rk[2][1];
            constexpr float kScale = 0.18898223650461362f * 1.4426950408889634f;
            const float sq0 = rs0 * kScale, sf0 = kf0 * (rs1 * kScale), sf1 = kf1 * (rs1 * kScale);
            const float NEG = -__int_as_float(0x7f800000);
            const float nb0 = gt0 && no_prev ? NEG : 0.f, nb1 = gt1 && no_prev ? NEG : 0.f;
            const uint32_t mk = opaque((gt0 ? 0x0000ffffu : 0u) | (gt1 ? 0xffff0000u : 0u));
            const uint32_t sr = stg + ((w + 3) & 3) * 2048, hbar = BAR(w == 0 ? B_HL + wg : B_EP);
            mbar_wait(BAR(B_EP), 0);
            wg_wait<0>();
            reg_fence(aq);
            warp_arrive(BAR(B_A1D));
            uint32_t qf[8][2];
            #pragma unroll
            for (int c = 0; c < 7; c++) {
                qf[c + (c > 3)][0] = pack_bf16(aq[4 * c], aq[4 * c + 1]);
                qf[c + (c > 3)][1] = pack_bf16(aq[4 * c + 2], aq[4 * c + 3]);
            }
            qf[4][0] = t >= 2 ? qf[3][0] : 0u; qf[4][1] = t >= 2 ? qf[3][1] : 0u;
            qf[3][0] = t < 2 ? qf[3][0] : 0u;  qf[3][1] = t < 2 ? qf[3][1] : 0u;
            float sc[2][3][4];
            auto scores = [&](int n) {
                #pragma unroll
                for (int hd = 0; hd < 2; hd++) {
                    sc[hd][n][0] = sc[hd][n][1] = sc[hd][n][2] = sc[hd][n][3] = 0.f;
                    mma16816(sc[hd][n], qf[4 * hd][0], qf[4 * hd][1], qf[4 * hd + 1][0], qf[4 * hd + 1][1], kf[n][3 * hd], kf[n][3 * hd + 1]);
                    mma16816(sc[hd][n], qf[4 * hd + 2][0], qf[4 * hd + 2][1], qf[4 * hd + 3][0], qf[4 * hd + 3][1], kf[n][3 * hd + 2], kf[n][3 * hd + 3]);
                }
            };
            scores(1); scores(2);
            mbar_wait(hbar, 0);
            {
                const uint4 u0 = lds4(sr), u1 = lds4(sr + 512), u3 = lds4(sr + 1536), u2 = lds4(sr + 1024);
                kf[0][0] = u0.x; kf[0][1] = u0.y; kf[0][2] = u0.z; kf[0][3] = u0.w;
                kf[0][4] = u1.x; kf[0][5] = u1.y; kf[0][6] = u1.z; vf[0][0] = u1.w;
                vf[0][1] = u2.x; vf[0][2] = u2.y; vf[0][3] = u2.z; vf[0][4] = u2.w;
                vf[0][5] = u3.x; vf[0][6] = u3.y; rk[0][0] = __uint_as_float(u3.z); rk[0][1] = __uint_as_float(u3.w);
            }
            scores(0);
            const float ke0 = gt0 ? rk[0][0] : rk[1][0], ke1 = gt1 ? rk[0][1] : rk[1][1];
            const float se0 = ke0 * sq0, se1 = ke1 * sq0;
            uint32_t ow[7][2];
            #pragma unroll
            for (int hd = 0; hd < 2; hd++) {
                const int c0 = hd * 3;
                float (&sc_)[3][4] = sc[hd];
                const float e0 = fmaf(gt0 ? sc_[0][0] : sc_[1][0], se0, nb0), e1 = fmaf(gt1 ? sc_[0][1] : sc_[1][1], se1, nb1);
                const float f0 = (gt0 ? sc_[1][2] : sc_[2][2]) * sf0, f1 = (gt1 ? sc_[1][3] : sc_[2][3]) * sf1;
                const float me = quad_max(fmaxf(e0, e1)), mf = quad_max(fmaxf(f0, f1));
                const float p0 = ex2(e0 - me), p1 = ex2(e1 - me), r0 = ex2(f0 - mf), r1 = ex2(f1 - mf);
                const float ie = rcp(quad_sum(p0 + p1)), jf = rcp(quad_sum(r0 + r1));
                const uint32_t pp = pack_bf16(p0 * ke0 * ie, p1 * ke1 * ie), rp = pack_bf16(r0 * kf0 * jf, r1 * kf1 * jf);
                const uint32_t a0 = pp & ~mk, a1 = rp & mk, a3 = rp & ~mk, a4 = pp & mk, zero = opaque(0u), zero2 = opaque(0u);
                #pragma unroll
                for (int c = 0; c < 4; c++) {
                    float o[4] = {0.f, 0.f, 0.f, 0.f};
                    mma16816(o, a0, a1, zero, a3, vf[1][c0 + c], vf[2][c0 + c]);
                    mma1688(o, a4, zero2, vf[0][c0 + c]);
                    const uint32_t lo = pack_bf16(o[0], o[1]), hi = pack_bf16(o[2], o[3]);
                    if (hd == 1 && c == 0) { if (t >= 2) { ow[3][0] = lo; ow[3][1] = hi; } }
                    else { ow[c0 + c][0] = lo; ow[c0 + c][1] = hi; }
                }
            }
            #pragma unroll
            for (int c = 0; c < 7; c++) {
                stg1(op + c * 256,      set_par(ow[c][0], om0, tag));
                stg1(op + c * 256 + 32, set_par(ow[c][1], om1, tag));
            }
        }
        float as[28], ac[28];
        uint32_t xch, peer_xch, gm[2][4], *gp1, *gp2;
        const uint32_t *hp, *ht;
        const uint2* hq;
        uint64_t da0, db0;
        const int cg2 = (g2j + 2 * wg) * 2 + (rank ^ 1), cg1 = (g1j + 2 * wg) * 2 + (rank ^ (g1f < 14));
        const bool lead = elect_one();
        {
            const int cg = a2j * 2 + wg;
            float acc2[28];
            mbar_wait(BAR(B_XRF), 0);
            {
                const uint32_t xa = sb + SM_XR + wg * 8192 + (w * 16 + (lane & 15)) * 128;
                #pragma unroll
                for (int c = 0; c < 4; c++) {
                    uint32_t xr[4];
                    asm volatile("ldmatrix.sync.aligned.m8n8.x4.shared.b16 {%0,%1,%2,%3}, [%4];"
                                 : "=r"(xr[0]), "=r"(xr[1]), "=r"(xr[2]), "=r"(xr[3])
                                 : "r"(xa + ((((c * 2 + wg + (lane >> 4)) ^ lane) & 7) << 4)) : "memory");
                    #pragma unroll
                    for (int e = 0; e < (c < 3 ? 4 : 2); e++) { acc2[8 * c + 2 * e] = bf_lo(xr[e]); acc2[8 * c + 2 * e + 1] = bf_hi(xr[e]); }
                }
            }
            uint32_t* spw = opaque_ptr(&prm.sc->stats[((a2s * 8 + cg) * 4 + w) * 32 + lane]);
            const uint32_t* spr = opaque_ptr(&prm.sc->stats[(a2s * 32 + w) * 32 + lane]);
            uint32_t* rp = opaque_ptr((uint32_t*)&prm.sc->rows[a2s * 64 + w * 16 + (t >> 1) * 8 + g] + (t & 1));
            const int cgs = cg ^ (a2s >> 4);
            uint32_t* np = opaque_ptr((uint32_t*)&prm.sc->hn[(a2s * 56 + cgs * 7) * 64] + w * 64 + lane);
            const uint64_t dwo = make_desc(sb + SM_WKV + wg * (28672 + 16), 0, true);
            const uint64_t doa = make_desc(sb + SM_WQ, 1024, false, 128);
            bias1a = prm.b1[g1f * 64 + w * 16 + g]; bias1b = prm.b1[g1f * 64 + w * 16 + 8 + g];
            const __nv_bfloat16 bias2 = prm.b2[ti * 128 + (w * 16 + (t >> 1) * 8 + g) * 2 + a2p];
            reg_fence(acc2);
            fence_async_smem();
            warp_arrive(BAR(B_XD));
            {
                xch = opaque(sb + SM_XCH + w * 1792 + lane * 16);
                asm volatile("mapa.shared::cluster.u32 %0, %1, %2;" : "=r"(peer_xch) : "r"(xch), "r"(rank ^ 1));
                const int hcg = cg2 ^ (g2s >> 4), hrg = (g2s & 1) * 4 + w;
                const uint32_t* hl = (const uint32_t*)&prm.sc->hn[((g2s >> 1) * 112 + hcg * 7) * 64 + hrg * 8];
                hp = opaque_ptr(hl + (g & 1) * 14336 + (g >> 1) * 4 + t);
                ht = opaque_ptr(hl + (lane & 1) * 14336 + min(lane >> 1, 6) * 256 + ((min(lane >> 1, 6) - (hcg & 1)) & 3) * 8 + hrg);
                hq = opaque_ptr(&prm.sc->rows[((g2s >> 1) * 2 + (g & 1)) * 64 + hrg * 8 + (g >> 1)]);
                gp1 = opaque_ptr((uint32_t*)&prm.sc->g[(g1f * 56 + cg1 * 7) * 64] + w * 64 + lane);
                gp2 = opaque_ptr((uint32_t*)(prm.out + (size_t)(g2s * 64 + w * 16 + lane / 7) * kD + cg2 * 56) + (lane % 7) * 4);
                da0 = make_desc(sb, 0, true); db0 = make_desc(sb + SM_B, 128, false);
            }
            mbar_wait2(BAR(B_WOF), 0, BAR(B_WOF + 1), 0);
            mbar_wait(BAR(B_OD), 0);
            const uint32_t order = __shfl_sync(~0u, lds1(sb + SM_ORD), 0);
            static_for<0, 4>([&](auto P_) {
                constexpr int P = decltype(P_)::value;
                const uint64_t dwp = dwo + ((order >> (2 * P + 1) & 1) * 3584 + (order >> 2 * P & 1) * 896);
                mbar_wait(BAR(B_OF + P), 0);
                wg_fence();
                static_for<0, 7>([&](auto K_) { constexpr int k = decltype(K_)::value;
                    wgmma_ss_n56<P * 14336 + k * 2048, k * 2048, 0>(acc2, doa, dwp); });
                if (P) wg_commit();
                if (P == 2) { wg_wait<1>(); warp_arrive(BAR(B_OC)); }
            });
            wg_wait<0>();
            reg_fence(acc2);
            float s0 = 0.f, s1 = 0.f, q0 = 0.f, q1 = 0.f;
            #pragma unroll
            for (int c = 0; c < 7; c++) {
                s0 += acc2[4 * c] + acc2[4 * c + 1];     q0 = fmaf(acc2[4 * c], acc2[4 * c], fmaf(acc2[4 * c + 1], acc2[4 * c + 1], q0));
                s1 += acc2[4 * c + 2] + acc2[4 * c + 3]; q1 = fmaf(acc2[4 * c + 2], acc2[4 * c + 2], fmaf(acc2[4 * c + 3], acc2[4 * c + 3], q1));
            }
            const bool th = t >= 2, to = t & 1;
            const float sa = (th ? s1 : s0) + __shfl_xor_sync(~0u, th ? s0 : s1, 2), qa = (th ? q1 : q0) + __shfl_xor_sync(~0u, th ? q0 : q1, 2);
            const float part = (to ? qa : sa) + __shfl_xor_sync(~0u, to ? sa : qa, 1);
            stg1(spw, set_par(__float_as_uint(part), 1u, tag));
            const uint32_t tpoll = clk32() + SDELAY;
            warp_arrive(BAR(B_HD));
            uint32_t nm[2][4], us[8];
            spin_until(tpoll);
            #pragma unroll
            for (int i = 0; i < 8; i++) us[i] = ld_rlx(spr + i * 128);
            #pragma unroll
            for (int i = 0; i < 8; i++) {
                nm[i >> 2][i & 3] = lane == ((i - (cgs & 1)) & 3) * 8 + w * 2 + (i >> 2);
                gm[i >> 2][i & 3] = opaque(lane == ((i - (cg1 & 1)) & 3) * 8 + w * 2 + (i >> 2));
            }
            #pragma unroll
            for (int c = 0; c < 28; c++) { ac[c] = 0.5f * __bfloat162float(c & 2 ? bias1b : bias1a); as[c] = 0.f; }
            reg_fence(as); reg_fence(ac);
            {
                int it = 0;
                while (true) {
                    uint32_t bad = 0;
                    #pragma unroll
                    for (int i = 0; i < 8; i++) bad |= us[i] ^ tag;
                    if (!__any_sync(~0u, bad & 1)) break;
                    if (++it > kSpinLimit) break;
                    #pragma unroll
                    for (int i = 0; i < 8; i++) us[i] = ld_rlx(spr + i * 128);
                }
            }
            const float tot = (((__uint_as_float(us[0]) + __uint_as_float(us[1])) + (__uint_as_float(us[2]) + __uint_as_float(us[3])))
                            + ((__uint_as_float(us[4]) + __uint_as_float(us[5])) + (__uint_as_float(us[6]) + __uint_as_float(us[7])))) * (1.f / kD);
            const float oth = __shfl_xor_sync(~0u, tot, 1);
            const float mean = to ? oth : tot;
            const float var = fmaxf(fmaf(-mean, mean, to ? tot : oth), 0.f);
            const float rra = rsq(fmaf(var, 4.f + 4.f * kEps, 4.f * kEps * kEps)), mra = -mean * rra;
            const float rrb = __shfl_xor_sync(~0u, rra, 2), mrb = __shfl_xor_sync(~0u, mra, 2);
            const float rr0 = th ? rrb : rra, mr0 = th ? mrb : mra, rr1 = th ? rra : rrb, mr1 = th ? mra : mrb;
            #pragma unroll
            for (int c = 0; c < 7; c++) {
                stg1(np + c * 256,      set_par(pack_bf16(fmaf(acc2[4 * c], rr0, mr0), fmaf(acc2[4 * c + 1], rr0, mr0)), nm[0][c & 3], tag));
                stg1(np + c * 256 + 32, set_par(pack_bf16(fmaf(acc2[4 * c + 2], rr1, mr1), fmaf(acc2[4 * c + 3], rr1, mr1)), nm[1][c & 3], tag));
            }
            if (cg == 0) stg1(rp, set_par(__float_as_uint(to ? mean + __bfloat162float(bias2) : rcp(rra)), 1u, tag));
        }
        auto send = [&]() {
            const uint32_t rf = pbar0 + (B_RF + warp) * 8;
            #pragma unroll
            for (int c = 0; c < 4; c++) {
                const uint32_t p0 = pack_bf16(as[8 * c], as[8 * c + 1]), p1 = pack_bf16(as[8 * c + 2], as[8 * c + 3]);
                if (c < 3) {
                    const uint32_t p2 = pack_bf16(as[8 * c + 4], as[8 * c + 5]), p3 = pack_bf16(as[8 * c + 6], as[8 * c + 7]);
                    asm volatile("st.async.shared::cluster.mbarrier::complete_tx::bytes.v4.b32 [%0], {%1,%2,%3,%4}, [%5];"
                                 :: "r"(peer_xch + c * 512), "r"(p0), "r"(p1), "r"(p2), "r"(p3), "r"(rf) : "memory");
                } else {
                    asm volatile("st.async.shared::cluster.mbarrier::complete_tx::bytes.v2.b32 [%0], {%1,%2}, [%3];"
                                 :: "r"(peer_xch + 1536 - lane * 8), "r"(p0), "r"(p1), "r"(rf) : "memory");
                }
            }
        };
        auto receive = [&](uint32_t (&pk)[14], uint32_t phase) {
            mbar_wait(BAR(B_RF + warp), phase);
            #pragma unroll
            for (int c = 0; c < 3; c++) { const uint4 u = lds4(xch + c * 512); pk[4 * c] = u.x; pk[4 * c + 1] = u.y; pk[4 * c + 2] = u.z; pk[4 * c + 3] = u.w; }
            const uint2 u = lds2(xch + 1536 - lane * 8); pk[12] = u.x; pk[13] = u.y;
        };
        uint2 rw[2]; uint32_t tw;
        auto load_rows = [&]() { tw = ld_rlx(ht); rw[0] = ld_rlx2(hq); rw[1] = ld_rlx2(hq + 4); };
        rw[0] = rw[1] = make_uint2(0u, 0u); tw = ~tag;
        #pragma unroll 1
        for (int ge = 0;; ge++) {
          if (ge || g1_on) {
            const int use = ge * 2 + wg;
            int entry = ge ? 1 : 2 * wg, stop = 0;
            uint64_t da = da0 + (ge ? -3 : wg ? NR - 10 : 0) * 512;
            bool rel = lead && use == 1;
            const uint32_t xfree = BAR(use > (g1_on ? 0 : 2) ? B_RE + use - 1 : B_PD);
            mbar_wait(BAR(B_AF), 0);
            if (ge && (wg || g1_on)) named_bar(5 - wg, 256);
            auto step = [&](auto I_) {
                constexpr int i = decltype(I_)::value, sl = i % NB, ao = i * 8192, bo = sl * 14336;
                mbar_wait_fast(BAR(B_BF + sl), i / NB);
                wg_fence();
                wgmma_ss_n112<ao,        bo,       1>(as, ac, da, db0);
                wgmma_ss_n112<ao + 2048, bo + 256, 1>(as, ac, da, db0);
                wgmma_ss_n112<ao + 4096, bo + 512, 1>(as, ac, da, db0);
                wgmma_ss_n112<ao + 6144, bo + 768, 1>(as, ac, da, db0);
                wg_commit();
                if (i == 1 && stop == 1) named_arrive(4, 256);
                if (i == 3 && (use == 1 || use == 2)) named_arrive(4 + wg, 256);
                wg_wait<1>();
                mbar_arrive_if(BAR(B_BE + (13 + i) % 14), rel);
                rel = lead;
            };
            #pragma unroll 1
            while (true) {
                if (entry < 1) {
                    static_for<0, 2>(step);
                    if (stop == 1) break;
                    static_for<2, 4>(step);
                    if (stop) break;
                }
                if (entry < 2) static_for<4, 10>(step);
                else {
                    uint32_t af[NR * 4][4];
                    mbar_wait(BAR(B_GO), 0);
                    const uint32_t tp = lds1(sb + SM_TG + 4) + PLOFF;
                    int it = 0;
                    while ((int)(gtime32() - tp) < 0 && ++it < 256) __nanosleep(20);
                    const uint32_t la = sb + ((lane >> 4) * 8 + (lane & 7)) * 128 + (((w * 2 + ((lane >> 3) & 1)) ^ (lane & 7)) << 4);
                    #pragma unroll
                    for (int k = 0; k < NR * 4; k++)
                        asm volatile("ldmatrix.sync.aligned.m8n8.x4.trans.shared.b16 {%0,%1,%2,%3}, [%4];"
                                     : "=r"(af[k][0]), "=r"(af[k][1]), "=r"(af[k][2]), "=r"(af[k][3]) : "r"(la + k * 2048) : "memory");
                    __syncwarp();
                    mbar_arrive_if(BAR(B_PL), lead);
                    if (w == 0) {
                        const char* p2 = (const char*)prm.w2 + ((b >> 6) * 896 + (b & 63) + PFW * 64) * 4096 + lane * 128;
                        #pragma unroll 1
                        for (int i = 0; i < 14 - PFW; i++) {
                            it = 0;
                            while ((int)(gtime32() - tp) < PF3OFF + i * PF3PACE && ++it < 256) __nanosleep(40);
                            asm volatile("prefetch.global.L2 [%0];" :: "l"(p2 + i * 64 * 4096));
                        }
                    }
                    named_bar(4, 256);
                    static_for<0, NR>([&](auto I_) {
                        constexpr int i = decltype(I_)::value, sl = (16 + i) % NB, o = sl * 14336;
                        mbar_wait_fast(BAR(B_BF + sl), (16 + i) / NB & 1);
                        wg_fence();
                        wgmma_rs_n112<o,       1>(as, ac, af[4 * i][0], af[4 * i][1], af[4 * i][2], af[4 * i][3], db0);
                        wgmma_rs_n112<o + 256, 1>(as, ac, af[4 * i + 1][0], af[4 * i + 1][1], af[4 * i + 1][2], af[4 * i + 1][3], db0);
                        wgmma_rs_n112<o + 512, 1>(as, ac, af[4 * i + 2][0], af[4 * i + 2][1], af[4 * i + 2][2], af[4 * i + 2][3], db0);
                        wgmma_rs_n112<o + 768, 1>(as, ac, af[4 * i + 3][0], af[4 * i + 3][1], af[4 * i + 3][2], af[4 * i + 3][3], db0);
                        wg_commit();
                        if (i) { wg_wait<1>(); mbar_arrive_if(BAR(B_BE + (15 + i) % (2 * NB)), lead); }
                    });
                }
                static_for<10, 14>(step);
                entry = 0; stop = use + 1; da += 14 * 512;
            }
            const uint32_t prev = BAR(B_BE + (use ? 3 : 1));
            const bool xok = mbar_test(xfree, 0);
            wg_wait<0>();
            reg_fence(as); reg_fence(ac);
            mbar_arrive_if(prev, lead);
            if (!xok) mbar_wait(xfree, 0);
            if (ge) break;
            send();
            load_rows();
            uint32_t pk[14];
            receive(pk, 0);
            #pragma unroll
            for (int c = 0; c < 14; c++) {
                float r[2];
                #pragma unroll
                for (int e = 0; e < 2; e++) {
                    const float u = ac[2 * c + e] + (e ? bf_hi(pk[c]) : bf_lo(pk[c]));
                    r[e] = fmaf(u, tanh_hw(u * fmaf(u * u, 8.f * 0.7978845608f * 0.044715f, 2.f * 0.7978845608f)), u);
                }
                stg1(gp1 + (c >> 1) * 256 + (c & 1) * 32, set_par(pack_bf16(r[0], r[1]), gm[c & 1][(c >> 1) & 3], tag));
            }
            named_bar(1 + wg, 128);
            if (w == 0 && lane == 0) {
                asm volatile("st.shared.u32 [%0], %1;" :: "r"(sb + SM_TG + 8 + wg * 4), "r"(clk32() + (wg ? XSPECB : XSPEC)) : "memory");
                mbar_arrive(BAR(B_GD + wg));
            }
            if (lead) mbar_expect(BAR(B_RF + warp), 1792);
            mbar_arrive_remote_if(pbar0 + (B_RE + wg) * 8, lead);
          } else mbar_wait(BAR(B_GD), 0);
            {
                int it = 0;
                while (__any_sync(~0u, ((tw ^ tag) | (rw[0].x ^ tag) | (rw[0].y ^ tag) | (rw[1].x ^ tag) | (rw[1].y ^ tag)) & 1)) {
                    if (++it > kSpinLimit) break;
                    load_rows();
                }
                uint32_t hw[14];
                #pragma unroll
                for (int c = 0; c < 14; c++) hw[c] = ld_rlx(hp + (c >> 1) * 256 + (c & 1) * 16);
                #pragma unroll
                for (int c = 0; c < 14; c++) {
                    ac[2 * c]     = fmaf(bf_lo(hw[c]), __uint_as_float(rw[c & 1].x), __uint_as_float(rw[c & 1].y));
                    ac[2 * c + 1] = fmaf(bf_hi(hw[c]), __uint_as_float(rw[c & 1].x), __uint_as_float(rw[c & 1].y));
                    as[2 * c] = as[2 * c + 1] = 0.f;
                }
                reg_fence(as); reg_fence(ac);
            }
        }
        uint32_t po[14], pk[14];
        if (!wg) sleep_until(clk32() + w * STAG2);
        send();
        #pragma unroll
        for (int c = 0; c < 14; c++) po[c] = opaque(pack_bf16(ac[2 * c], ac[2 * c + 1]));
        receive(pk, g1_on);
        #pragma unroll
        for (int c = 0; c < 14; c++) pk[c] = add_bf16x2(po[c], pk[c]);
        __syncwarp();
        const uint32_t sa = xch - lane * 16 + (lane & 15) * 112 + (lane >> 4) * 16;
        #pragma unroll
        for (int m = 0; m < 3; m++)
            asm volatile("stmatrix.sync.aligned.m8n8.x4.shared.b16 [%0], {%1,%2,%3,%4};"
                         :: "r"(sa + m * 32), "r"(pk[4 * m]), "r"(pk[4 * m + 1]), "r"(pk[4 * m + 2]), "r"(pk[4 * m + 3]) : "memory");
        asm volatile("stmatrix.sync.aligned.m8n8.x2.shared.b16 [%0], {%1,%2};" :: "r"(sa + 96), "r"(pk[12]), "r"(pk[13]) : "memory");
        __syncwarp();
        if (lane < 28) {
            #pragma unroll
            for (int i = 0; i < 4; i++) { const uint4 u = lds4(xch + i * 448); stg4(gp2 + i * 896, u.x, u.y, u.z, u.w); }
        }
        __syncwarp();
        mbar_arrive_remote_if(pbar0 + (B_RE + 2) * 8, lead && wg == 0);
        if (b == 0 && tid == 128) prm.sc->epoch = tag;
    }
}

typedef CUresult (*EncodeFn)(CUtensorMap*, CUtensorMapDataType, cuuint32_t, void*, const cuuint64_t*, const cuuint64_t*,
                             const cuuint32_t*, const cuuint32_t*, CUtensorMapInterleave, CUtensorMapSwizzle,
                             CUtensorMapL2promotion, CUtensorMapFloatOOBfill);

void make_map(EncodeFn enc, CUtensorMap* m, const void* base, uint64_t cols, uint64_t rows, uint32_t box_rows) {
    cuuint64_t dims[2] = {cols, rows};
    cuuint64_t strides[1] = {cols * 2};
    cuuint32_t box[2] = {64, box_rows};
    cuuint32_t es[2] = {1, 1};
    enc(m, CU_TENSOR_MAP_DATA_TYPE_BFLOAT16, 2, const_cast<void*>(base), dims, strides, box, es, CU_TENSOR_MAP_INTERLEAVE_NONE,
        CU_TENSOR_MAP_SWIZZLE_128B, CU_TENSOR_MAP_L2_PROMOTION_L2_128B, CU_TENSOR_MAP_FLOAT_OOB_FILL_NONE);
}

}

extern "C" void kernel_launch(void* const* d_in, const int* in_sizes, int n_in, void* d_out, int out_size) {
    (void)in_sizes; (void)n_in; (void)out_size;
    void* fn = nullptr;
    cudaDriverEntryPointQueryResult qr;
    cudaGetDriverEntryPoint("cuTensorMapEncodeTiled", &fn, cudaEnableDefault, &qr);
    EncodeFn enc = (EncodeFn)fn;
    CUtensorMap mX2, mX, mWqkv, mWo, mW1, mW2;
    {
        cuuint64_t dims[3] = {kD, kS / 2, 2}, strides[2] = {4 * kD, 2 * kD};
        cuuint32_t box[3] = {64, 64, 2}, es[3] = {1, 1, 1};
        enc(&mX2, CU_TENSOR_MAP_DATA_TYPE_BFLOAT16, 3, d_in[0], dims, strides, box, es, CU_TENSOR_MAP_INTERLEAVE_NONE,
            CU_TENSOR_MAP_SWIZZLE_128B, CU_TENSOR_MAP_L2_PROMOTION_L2_128B, CU_TENSOR_MAP_FLOAT_OOB_FILL_NONE);
    }
    make_map(enc, &mX, d_in[0], 2 * kD, kS / 2, 64);
    make_map(enc, &mWqkv, d_in[1], 3 * kD, kD, 64);
    make_map(enc, &mWo, d_in[2], kD, kD, 112);
    make_map(enc, &mW1, d_in[4], 2 * kF, kS / 2, 64);
    make_map(enc, &mW2, d_in[6], kS, kF, 64);
    Params prm;
    prm.x = (const __nv_bfloat16*)d_in[0];
    prm.wqkv = (const __nv_bfloat16*)d_in[1];
    prm.wo = (const __nv_bfloat16*)d_in[2];
    prm.w1 = (const __nv_bfloat16*)d_in[4];
    prm.b1 = (const __nv_bfloat16*)d_in[5];
    prm.w2 = (const __nv_bfloat16*)d_in[6];
    prm.b2 = (const __nv_bfloat16*)d_in[7];
    prm.out = (__nv_bfloat16*)d_out;
    cudaGetSymbolAddress((void**)&prm.sc, g_scratch);
    cudaFuncSetAttribute(fused_kernel, cudaFuncAttributeMaxDynamicSharedMemorySize, SM_TOTAL);
    fused_kernel<<<128, 384, SM_TOTAL, cudaStreamPerThread>>>(prm, mX2, mX, mWqkv, mWo, mW1, mW2);
}
```

```cpp
#include <cuda_runtime.h>
#include <cuda.h>
#include <cuda_bf16.h>
#include <stdint.h>
#include <type_traits>

namespace {

constexpr int kS = 2048, kD = 448, kF = 1792;
constexpr float kEps = 1e-5f;

constexpr int FS = 32;
constexpr int NPRE = 10;
constexpr int NR = 8;
constexpr int PFW = 4;
constexpr int QC0 = 4;
constexpr int QC1 = 10;
constexpr int QC2 = 16;
constexpr int PFD = 250;
constexpr int PFPACE = 280;
constexpr int PFPACE2 = 300;
constexpr int HDELAY = 200;
constexpr int WOD = 350;
constexpr int SDELAY = 200;
constexpr int PDELAY = 400;
constexpr int PACE1 = 120;
constexpr int PACE2 = 400;
constexpr int PACEB = 300;
constexpr int XSPEC = 500;
constexpr int XSPECB = 750;
constexpr int CN2 = 7200;
constexpr int CN3 = 10900;
constexpr int W2OFF = 800;
constexpr int W2PACE = 350;
constexpr int STAG2 = 400;
constexpr int DELTAO = 864;
constexpr int DMIN = 608;
constexpr int CHUNKNS = 250;
constexpr int DELTA = 2080;
constexpr int PLOFF = -250;
constexpr int PF3OFF = 300;
constexpr int PF3PACE = 240;

struct Scratch {
    uint32_t flag_o[16 * 8 * FS];
    uint4    o[32 * 56 * 64];
    uint32_t stats[32 * 8 * 4 * 32];
    uint4    hn[32 * 56 * 64];
    uint32_t flag_h[32 * 4 * FS];
    uint4    g[28 * 56 * 64];
    uint4    halo[8 * 8 * 2 * 4 * 32];
    uint2    rows[32 * 64];
    uint32_t epoch;
};
__device__ __align__(1024) Scratch g_scratch;

constexpr uint32_t SM_WKV  = 114688;
constexpr uint32_t SM_XR   = 24576;
constexpr uint32_t SM_STG  = 40960;
constexpr uint32_t SM_WQ   = 57344;
constexpr uint32_t SM_XCH  = 0;
constexpr uint32_t SM_B    = 131072;
constexpr uint32_t SM_BAR  = 231424;
constexpr uint32_t SM_TOTAL = SM_BAR + 1024;
constexpr int NB = 7;
constexpr int B_XF = 0, B_WKVF = 7, B_WQF = 14, B_XRF = 15, B_WOF = 16,
              B_XC = 18, B_KV3 = 19, B_KVC = 20,
              B_A1D = 21, B_XD = 22, B_OC = 23,
              B_BE = 24  , B_RE = B_BE + 2 * NB,
              B_PL = B_RE + 3, B_AF = B_PL + 1, B_BL = B_AF + 1  , B_OL = B_BL + 2 * NB  ,
              B_BF = B_OL + 4  , B_OF = B_BF + NB, B_RF = B_OF + 4, B_EP = B_RF + 8, B_PD = B_EP + 1, B_OD = B_PD + 1, B_RT = B_OD + 1, B_HL = B_RT + 2,
              B_HD = B_HL + 2  , B_GO = B_HD + 1, B_GD = B_GO + 1, B_COUNT = B_GD + 2;
constexpr uint32_t SM_EPOCH = SM_BAR + B_COUNT * 8, SM_TG = SM_EPOCH + 4  , SM_TG2 = SM_TG + 16  ,
                   SM_ORD = SM_TG2 + 4  ;

constexpr uint64_t kAPos = 0x3330ull | 0x5555555ull << 17;
constexpr uint32_t seg_mask(int h, int p0, int p1) {
    uint32_t m = 0; int n = 0;
    for (int p = p0; p < p1; p++) if ((p & 1) == h) m |= (uint32_t)((kAPos >> p) & 1) << n++;
    return m | 1u << n;
}
constexpr uint64_t seg_masks(int h) {
    return 2 | (uint64_t)seg_mask(h, 0, 16) << 10 | (uint64_t)seg_mask(h, 16, 32) << 20
             | (uint64_t)seg_mask(h, 32, 46) << 30 | (uint64_t)seg_mask(h, 46, 60) << 40;
}
constexpr uint64_t kSegMasks0 = seg_masks(0), kSegMasks1 = seg_masks(1);

constexpr int kSpinLimit = 1 << 15;
__device__ __forceinline__ bool elect_one() {
    uint32_t p;
    asm volatile("{ .reg .pred P; elect.sync _|P, 0xffffffff; selp.u32 %0, 1, 0, P; }" : "=r"(p));
    return p;
}
__device__ __forceinline__ void mbar_init(uint32_t bar, uint32_t cnt) { asm volatile("mbarrier.init.shared::cta.b64 [%0], %1;" :: "r"(bar), "r"(cnt)); }
__device__ __forceinline__ void mbar_expect(uint32_t bar, uint32_t bytes) { asm volatile("mbarrier.arrive.expect_tx.shared::cta.b64 _, [%0], %1;" :: "r"(bar), "r"(bytes) : "memory"); }
__device__ __forceinline__ void mbar_expect_more(uint32_t bar, uint32_t bytes) { asm volatile("mbarrier.expect_tx.relaxed.cta.shared::cta.b64 [%0], %1;" :: "r"(bar), "r"(bytes) : "memory"); }
__device__ __forceinline__ void mbar_arrive(uint32_t bar) { asm volatile("mbarrier.arrive.shared::cta.b64 _, [%0];" :: "r"(bar) : "memory"); }
__device__ __forceinline__ void mbar_wait(uint32_t bar, uint32_t parity) {
    uint32_t ok; int it = 0;
    do {
        asm volatile("{ .reg .pred p; mbarrier.try_wait.parity.shared::cta.b64 p, [%1], %2; selp.u32 %0, 1, 0, p; }"
                     : "=r"(ok) : "r"(bar), "r"(parity) : "memory");
        if (++it > kSpinLimit) break;
    } while (!ok);
}
__device__ __forceinline__ bool mbar_try(uint32_t bar, uint32_t parity) {
    uint32_t ok;
    asm volatile("{ .reg .pred p; mbarrier.try_wait.parity.shared::cta.b64 p, [%1], %2; selp.u32 %0, 1, 0, p; }" : "=r"(ok) : "r"(bar), "r"(parity) : "memory");
    return ok;
}
__device__ __forceinline__ bool mbar_test(uint32_t bar, uint32_t parity) {
    uint32_t ok;
    asm volatile("{ .reg .pred p; mbarrier.test_wait.parity.shared::cta.b64 p, [%1], %2; selp.u32 %0, 1, 0, p; }" : "=r"(ok) : "r"(bar), "r"(parity) : "memory");
    return ok;
}
__device__ __forceinline__ void mbar_wait_fast(uint32_t bar, uint32_t parity) { if (!mbar_try(bar, parity)) mbar_wait(bar, parity); }
__device__ __forceinline__ void mbar_wait2(uint32_t bar0, uint32_t par0, uint32_t bar1, uint32_t par1) {
    uint32_t ok; int it = 0;
    do {
        asm volatile("{ .reg .pred p, q; mbarrier.try_wait.parity.shared::cta.b64 p, [%1], %2;\n"
                     "mbarrier.try_wait.parity.shared::cta.b64 q, [%3], %4; and.pred p, p, q; selp.u32 %0, 1, 0, p; }"
                     : "=r"(ok) : "r"(bar0), "r"(par0), "r"(bar1), "r"(par1) : "memory");
        if (++it > kSpinLimit) break;
    } while (!ok);
}
template <int N> __device__ __forceinline__ void reg_fence(float (&d)[N]) {
    #pragma unroll
    for (int i = 0; i < N; i++) asm volatile("" : "+f"(d[i]) :: "memory");
}
__device__ __forceinline__ void mbar_arrive_if(uint32_t bar, bool pred) {
    asm volatile("{ .reg .pred p; setp.ne.u32 p, %1, 0; @p mbarrier.arrive.shared::cta.b64 _, [%0]; }" :: "r"(bar), "r"((uint32_t)pred) : "memory");
}
__device__ __forceinline__ void warp_arrive(uint32_t bar) { __syncwarp(); if (elect_one()) mbar_arrive(bar); }
__device__ __forceinline__ void tma2d(uint32_t dst, const CUtensorMap* m, int c0, int c1, uint32_t bar) {
    asm volatile("cp.async.bulk.tensor.2d.shared::cluster.global.mbarrier::complete_tx::bytes [%0], [%1, {%3, %4}], [%2];"
                 :: "r"(dst), "l"(m), "r"(bar), "r"(c0), "r"(c1) : "memory");
}
__device__ __forceinline__ void tma3d(uint32_t dst, const CUtensorMap* m, int c0, int c1, int c2, uint32_t bar) {
    asm volatile("cp.async.bulk.tensor.3d.shared::cluster.global.mbarrier::complete_tx::bytes [%0], [%1, {%3, %4, %5}], [%2];"
                 :: "r"(dst), "l"(m), "r"(bar), "r"(c0), "r"(c1), "r"(c2) : "memory");
}
__device__ __forceinline__ void tma2d_mc(uint32_t dst, const CUtensorMap* m, int c0, int c1, uint32_t bar) {
    asm volatile("cp.async.bulk.tensor.2d.shared::cluster.global.mbarrier::complete_tx::bytes.multicast::cluster [%0], [%1, {%3, %4}], [%2], %5;"
                 :: "r"(dst), "l"(m), "r"(bar), "r"(c0), "r"(c1), "h"((uint16_t)3) : "memory");
}
__device__ __forceinline__ void mbar_arrive_remote_if(uint32_t cluster_bar, bool pred) {
    asm volatile("{ .reg .pred p; setp.ne.u32 p, %1, 0; @p mbarrier.arrive.shared::cluster.b64 _, [%0]; }" :: "r"(cluster_bar), "r"((uint32_t)pred) : "memory");
}
__device__ __forceinline__ void bulk_g2s(uint32_t dst, const void* src, uint32_t bytes, uint32_t bar) {
    asm volatile("cp.async.bulk.shared::cluster.global.mbarrier::complete_tx::bytes [%0], [%1], %2, [%3];"
                 :: "r"(dst), "l"(src), "r"(bytes), "r"(bar) : "memory");
}
__device__ __forceinline__ void bulk_prefetch(const void* src, uint32_t bytes) { asm volatile("cp.async.bulk.prefetch.L2.global [%0], %1;" :: "l"(src), "r"(bytes) : "memory"); }
__device__ __forceinline__ void wg_fence()  { asm volatile("wgmma.fence.sync.aligned;" ::: "memory"); }
__device__ __forceinline__ void wg_commit() { asm volatile("wgmma.commit_group.sync.aligned;" ::: "memory"); }
template <int N> __device__ __forceinline__ void wg_wait() { asm volatile("wgmma.wait_group.sync.aligned %0;" :: "n"(N) : "memory"); }
__device__ __forceinline__ void named_bar(int id, int n) { asm volatile("bar.sync %0, %1;" :: "r"(id), "r"(n) : "memory"); }
__device__ __forceinline__ void named_arrive(int id, int n) { asm volatile("bar.arrive %0, %1;" :: "r"(id), "r"(n) : "memory"); }
__device__ __forceinline__ void fence_async_smem() { asm volatile("fence.proxy.async.shared::cta;" ::: "memory"); }
__device__ __forceinline__ uint32_t gtime32() { uint64_t t; asm volatile("mov.u64 %0, %%globaltimer;" : "=l"(t) :: "memory"); return (uint32_t)t; }
__device__ __forceinline__ uint32_t clk32() { uint64_t t; asm volatile("mov.u64 %0, %%clock64;" : "=l"(t) :: "memory"); return (uint32_t)t; }
__device__ __forceinline__ void spin_until(uint32_t t) { while ((int)(clk32() - t) < 0) {} }
__device__ __forceinline__ void sleep_until(uint32_t t) { while ((int)(clk32() - t) < 0) __nanosleep(20); }
__device__ __forceinline__ void st_flag(uint32_t* p, uint32_t v, uint32_t time) {
    const uint64_t w = ((uint64_t)time << 32) | v;
    asm volatile("st.relaxed.gpu.global.u64 [%0], %1;" :: "l"(p), "l"(w) : "memory");
}
__device__ __forceinline__ void ld_flag_if(uint64_t& v, const uint32_t* p, bool pred) {
    asm volatile("{ .reg .pred p; setp.ne.u32 p, %2, 0; @p ld.relaxed.gpu.global.u64 %0, [%1]; }" : "+l"(v) : "l"(p), "r"((uint32_t)pred) : "memory");
}
__device__ __forceinline__ uint32_t ld_rlx(const uint32_t* p) { uint32_t v; asm volatile("ld.relaxed.gpu.global.u32 %0, [%1];" : "=r"(v) : "l"(p) : "memory"); return v; }
template <class T> __device__ __forceinline__ T* opaque_ptr(T* p) { asm volatile("" : "+l"(p)); return p; }
__device__ __forceinline__ uint4 ld_rlx4(const uint4* p) {
    uint4 v; asm volatile("ld.relaxed.gpu.global.v4.u32 {%0,%1,%2,%3}, [%4];" : "=r"(v.x), "=r"(v.y), "=r"(v.z), "=r"(v.w) : "l"(p) : "memory"); return v;
}
__device__ __forceinline__ uint2 ld_rlx2(const uint2* p) {
    uint2 v; asm volatile("ld.relaxed.gpu.global.v2.u32 {%0,%1}, [%2];" : "=r"(v.x), "=r"(v.y) : "l"(p) : "memory"); return v;
}
__device__ __forceinline__ void stg1(uint32_t* p, uint32_t v) { asm volatile("st.global.u32 [%0], %1;" :: "l"(p), "r"(v) : "memory"); }
__device__ __forceinline__ void stg4(void* p, uint32_t x, uint32_t y, uint32_t z, uint32_t w) { asm volatile("st.global.v4.u32 [%0], {%1,%2,%3,%4};" :: "l"(p), "r"(x), "r"(y), "r"(z), "r"(w) : "memory"); }
__device__ __forceinline__ uint32_t lds1(uint32_t a) { uint32_t v; asm volatile("ld.shared.u32 %0, [%1];" : "=r"(v) : "r"(a) : "memory"); return v; }
__device__ __forceinline__ uint2 lds2(uint32_t a) { uint2 v; asm volatile("ld.shared.v2.u32 {%0,%1}, [%2];" : "=r"(v.x), "=r"(v.y) : "r"(a) : "memory"); return v; }
__device__ __forceinline__ uint32_t set_par(uint32_t v, uint32_t mask, uint32_t par) {
    uint32_t r; asm("lop3.b32 %0, %1, %2, %3, 0xb8;" : "=r"(r) : "r"(v), "r"(mask), "r"(par)); return r;
}
__device__ __forceinline__ void st_gen4(void* p, uint32_t x, uint32_t y, uint32_t z, uint32_t w) { asm volatile("st.v4.u32 [%0], {%1,%2,%3,%4};" :: "l"(p), "r"(x), "r"(y), "r"(z), "r"(w) : "memory"); }
__device__ __forceinline__ float tanh_hw(float x) { float r; asm("tanh.approx.f32 %0, %1;" : "=f"(r) : "f"(x)); return r; }
__device__ __forceinline__ void sts4(uint32_t a, uint32_t x, uint32_t y, uint32_t z, uint32_t w) { asm volatile("st.shared.v4.u32 [%0], {%1,%2,%3,%4};" :: "r"(a), "r"(x), "r"(y), "r"(z), "r"(w) : "memory"); }
__device__ __forceinline__ uint4 lds4(uint32_t a) { uint4 v; asm volatile("ld.shared.v4.u32 {%0,%1,%2,%3}, [%4];" : "=r"(v.x), "=r"(v.y), "=r"(v.z), "=r"(v.w) : "r"(a) : "memory"); return v; }
__device__ __forceinline__ uint32_t pack_bf16(float lo, float hi) { uint32_t r; asm("cvt.rn.bf16x2.f32 %0, %1, %2;" : "=r"(r) : "f"(hi), "f"(lo)); return r; }
__device__ __forceinline__ float bf_lo(uint32_t v) { return __uint_as_float(v << 16); }
__device__ __forceinline__ float bf_hi(uint32_t v) { return __uint_as_float(v & 0xffff0000u); }
__device__ __forceinline__ uint32_t sub_bf16x2(uint32_t a, uint32_t b) { uint32_t r; asm volatile("sub.rn.bf16x2 %0, %1, %2;" : "=r"(r) : "r"(a), "r"(b)); return r; }
__device__ __forceinline__ uint32_t add_bf16x2(uint32_t a, uint32_t b) { uint32_t r; asm volatile("add.rn.bf16x2 %0, %1, %2;" : "=r"(r) : "r"(a), "r"(b)); return r; }
__device__ __forceinline__ uint32_t sqr_bf16x2(uint32_t a) { uint32_t r; asm volatile("mul.rn.bf16x2 %0, %1, %1;" : "=r"(r) : "r"(a)); return r; }
__device__ __forceinline__ uint32_t sqa_bf16x2(uint32_t a, uint32_t c) { uint32_t r; asm volatile("fma.rn.bf16x2 %0, %1, %1, %2;" : "=r"(r) : "r"(a), "r"(c)); return r; }
__device__ __forceinline__ uint32_t movm(uint32_t a) { uint32_t r; asm volatile("movmatrix.sync.aligned.m8n8.trans.b16 %0, %1;" : "=r"(r) : "r"(a)); return r; }
__device__ __forceinline__ float ex2(float x) { float r; asm("ex2.approx.ftz.f32 %0, %1;" : "=f"(r) : "f"(x)); return r; }
__device__ __forceinline__ float rsq(float x) { float r; asm("rsqrt.approx.ftz.f32 %0, %1;" : "=f"(r) : "f"(x)); return r; }
__device__ __forceinline__ float rcp(float x) { float r; asm("rcp.approx.ftz.f32 %0, %1;" : "=f"(r) : "f"(x)); return r; }
__device__ __forceinline__ void mma16816(float (&c)[4], uint32_t a0, uint32_t a1, uint32_t a2, uint32_t a3, uint32_t b0, uint32_t b1) {
    asm("mma.sync.aligned.m16n8k16.row.col.f32.bf16.bf16.f32 {%0,%1,%2,%3}, {%4,%5,%6,%7}, {%8,%9}, {%0,%1,%2,%3};"
        : "+f"(c[0]), "+f"(c[1]), "+f"(c[2]), "+f"(c[3]) : "r"(a0), "r"(a1), "r"(a2), "r"(a3), "r"(b0), "r"(b1));
}
__device__ __forceinline__ void mma1688(float (&c)[4], uint32_t a0, uint32_t a1, uint32_t b0) {
    asm("mma.sync.aligned.m16n8k8.row.col.f32.bf16.bf16.f32 {%0,%1,%2,%3}, {%4,%5}, {%6}, {%0,%1,%2,%3};"
        : "+f"(c[0]), "+f"(c[1]), "+f"(c[2]), "+f"(c[3]) : "r"(a0), "r"(a1), "r"(b0));
}
__device__ __forceinline__ float quad_sum(float v) { v += __shfl_xor_sync(~0u, v, 1); v += __shfl_xor_sync(~0u, v, 2); return v; }
__device__ __forceinline__ float quad_max(float v) { v = fmaxf(v, __shfl_xor_sync(~0u, v, 1)); v = fmaxf(v, __shfl_xor_sync(~0u, v, 2)); return v; }
__device__ __forceinline__ uint64_t make_desc(uint32_t addr, uint32_t lbo, bool swz, uint32_t sbo = 1024) {
    const uint32_t lo = __shfl_sync(~0u, ((addr & 0x3FFFF) >> 4) | ((lbo >> 4) << 16), 0);
    const uint32_t hi = __shfl_sync(~0u, (swz ? 0x40000000u : 0u) + (sbo >> 4) + (threadIdx.x & 31), 0);
    return ((uint64_t)hi << 32) | lo;
}
template <int I, int N, class F> __device__ __forceinline__ void static_for(F&& f) {
    if constexpr (I < N) { f(std::integral_constant<int, I>{}); static_for<I + 1, N>(f); }
}
__device__ __forceinline__ uint32_t opaque(uint32_t v) { asm volatile("" : "+r"(v)); return v; }
template <int BOFF, int SCALE_D>
__device__ __forceinline__ void wgmma_rs_n56(float (&d)[28], uint32_t a0, uint32_t a1, uint32_t a2, uint32_t a3, uint64_t db) {
    asm volatile("{ .reg .b64 db; add.s64 db, %32, %33;\n"
        "wgmma.mma_async.sync.aligned.m64n56k16.f32.bf16.bf16 "
        "{%0, %1, %2, %3, %4, %5, %6, %7, %8, %9, %10, %11, %12, %13, %14, %15, %16, %17, %18, %19, %20, %21, %22, %23, %24, %25, %26, %27}, "
        "{%28, %29, %30, %31}, db, %34, 1, 1, 1; }"
        : "+f"(d[0]), "+f"(d[1]), "+f"(d[2]), "+f"(d[3]), "+f"(d[4]), "+f"(d[5]), "+f"(d[6]), "+f"(d[7]),
        "+f"(d[8]), "+f"(d[9]), "+f"(d[10]), "+f"(d[11]), "+f"(d[12]), "+f"(d[13]), "+f"(d[14]), "+f"(d[15]),
        "+f"(d[16]), "+f"(d[17]), "+f"(d[18]), "+f"(d[19]), "+f"(d[20]), "+f"(d[21]), "+f"(d[22]), "+f"(d[23]),
        "+f"(d[24]), "+f"(d[25]), "+f"(d[26]), "+f"(d[27])
        : "r"(a0), "r"(a1), "r"(a2), "r"(a3), "l"(db), "n"(BOFF >> 4), "n"(SCALE_D));
}
template <int AOFF, int BOFF, int MMAJOR>
__device__ __forceinline__ void wgmma_ss_n56(float (&d)[28], uint64_t da, uint64_t db) {
    asm volatile("{ .reg .b64 da, db; add.s64 da, %28, %30; add.s64 db, %29, %31;\n"
        "wgmma.mma_async.sync.aligned.m64n56k16.f32.bf16.bf16 "
        "{%0, %1, %2, %3, %4, %5, %6, %7, %8, %9, %10, %11, %12, %13, %14, %15, %16, %17, %18, %19, %20, %21, %22, %23, %24, %25, %26, %27}, "
        "da, db, 1, 1, 1, %32, 1; }"
        : "+f"(d[0]), "+f"(d[1]), "+f"(d[2]), "+f"(d[3]), "+f"(d[4]), "+f"(d[5]), "+f"(d[6]), "+f"(d[7]),
        "+f"(d[8]), "+f"(d[9]), "+f"(d[10]), "+f"(d[11]), "+f"(d[12]), "+f"(d[13]), "+f"(d[14]), "+f"(d[15]),
        "+f"(d[16]), "+f"(d[17]), "+f"(d[18]), "+f"(d[19]), "+f"(d[20]), "+f"(d[21]), "+f"(d[22]), "+f"(d[23]),
        "+f"(d[24]), "+f"(d[25]), "+f"(d[26]), "+f"(d[27])
        : "l"(da), "l"(db), "n"(AOFF >> 4), "n"(BOFF >> 4), "n"(MMAJOR));
}
template <int AOFF, int BOFF, int MMAJOR>
__device__ __forceinline__ void wgmma_ss_n112(float (&d)[28], float (&e)[28], uint64_t da, uint64_t db) {
    asm volatile("{ .reg .b64 da, db; add.s64 da, %56, %58; add.s64 db, %57, %59;\n"
        "wgmma.mma_async.sync.aligned.m64n112k16.f32.bf16.bf16 "
        "{%0, %1, %2, %3, %4, %5, %6, %7, %8, %9, %10, %11, %12, %13, %14, %15, %16, %17, %18, %19, %20, %21, %22, %23, %24, %25, %26, %27, %28, %29, %30, %31, %32, %33, %34, %35, %36, %37, %38, %39, %40, %41, %42, %43, %44, %45, %46, %47, %48, %49, %50, %51, %52, %53, %54, %55}, "
        "da, db, 1, 1, 1, %60, 1; }"
        : "+f"(d[0]), "+f"(d[1]), "+f"(d[2]), "+f"(d[3]), "+f"(d[4]), "+f"(d[5]), "+f"(d[6]), "+f"(d[7]),
        "+f"(d[8]), "+f"(d[9]), "+f"(d[10]), "+f"(d[11]), "+f"(d[12]), "+f"(d[13]), "+f"(d[14]), "+f"(d[15]),
        "+f"(d[16]), "+f"(d[17]), "+f"(d[18]), "+f"(d[19]), "+f"(d[20]), "+f"(d[21]), "+f"(d[22]), "+f"(d[23]),
        "+f"(d[24]), "+f"(d[25]), "+f"(d[26]), "+f"(d[27]), "+f"(e[0]), "+f"(e[1]), "+f"(e[2]), "+f"(e[3]),
        "+f"(e[4]), "+f"(e[5]), "+f"(e[6]), "+f"(e[7]), "+f"(e[8]), "+f"(e[9]), "+f"(e[10]), "+f"(e[11]),
        "+f"(e[12]), "+f"(e[13]), "+f"(e[14]), "+f"(e[15]), "+f"(e[16]), "+f"(e[17]), "+f"(e[18]), "+f"(e[19]),
        "+f"(e[20]), "+f"(e[21]), "+f"(e[22]), "+f"(e[23]), "+f"(e[24]), "+f"(e[25]), "+f"(e[26]), "+f"(e[27])
        : "l"(da), "l"(db), "n"(AOFF >> 4), "n"(BOFF >> 4), "n"(MMAJOR));
}
template <int BOFF, int SCALE_D>
__device__ __forceinline__ void wgmma_rs_n112(float (&d)[28], float (&e)[28], uint32_t a0, uint32_t a1, uint32_t a2, uint32_t a3, uint64_t db) {
    asm volatile("{ .reg .b64 db; add.s64 db, %60, %61;\n"
        "wgmma.mma_async.sync.aligned.m64n112k16.f32.bf16.bf16 "
        "{%0, %1, %2, %3, %4, %5, %6, %7, %8, %9, %10, %11, %12, %13, %14, %15, %16, %17, %18, %19, %20, %21, %22, %23, %24, %25, %26, %27, %28, %29, %30, %31, %32, %33, %34, %35, %36, %37, %38, %39, %40, %41, %42, %43, %44, %45, %46, %47, %48, %49, %50, %51, %52, %53, %54, %55}, "
        "{%56, %57, %58, %59}, db, %62, 1, 1, 1; }"
        : "+f"(d[0]), "+f"(d[1]), "+f"(d[2]), "+f"(d[3]), "+f"(d[4]), "+f"(d[5]), "+f"(d[6]), "+f"(d[7]),
        "+f"(d[8]), "+f"(d[9]), "+f"(d[10]), "+f"(d[11]), "+f"(d[12]), "+f"(d[13]), "+f"(d[14]), "+f"(d[15]),
        "+f"(d[16]), "+f"(d[17]), "+f"(d[18]), "+f"(d[19]), "+f"(d[20]), "+f"(d[21]), "+f"(d[22]), "+f"(d[23]),
        "+f"(d[24]), "+f"(d[25]), "+f"(d[26]), "+f"(d[27]), "+f"(e[0]), "+f"(e[1]), "+f"(e[2]), "+f"(e[3]),
        "+f"(e[4]), "+f"(e[5]), "+f"(e[6]), "+f"(e[7]), "+f"(e[8]), "+f"(e[9]), "+f"(e[10]), "+f"(e[11]),
        "+f"(e[12]), "+f"(e[13]), "+f"(e[14]), "+f"(e[15]), "+f"(e[16]), "+f"(e[17]), "+f"(e[18]), "+f"(e[19]),
        "+f"(e[20]), "+f"(e[21]), "+f"(e[22]), "+f"(e[23]), "+f"(e[24]), "+f"(e[25]), "+f"(e[26]), "+f"(e[27])
        : "r"(a0), "r"(a1), "r"(a2), "r"(a3), "l"(db), "n"(BOFF >> 4), "n"(SCALE_D));
}

struct Params {
    const __nv_bfloat16 *x, *wqkv;
    Scratch* sc;
    const __nv_bfloat16 *wo, *w1, *w2, *b1, *b2;
    __nv_bfloat16* out;
};

__global__ void __cluster_dims__(2, 1, 1) __launch_bounds__(384, 1)
fused_kernel(const Params prm, const __grid_constant__ CUtensorMap mX2, const __grid_constant__ CUtensorMap mX, const __grid_constant__ CUtensorMap mWqkv,
             const __grid_constant__ CUtensorMap mWo, const __grid_constant__ CUtensorMap mW1,
             const __grid_constant__ CUtensorMap mW2)
{
    extern __shared__ __align__(1024) unsigned char smem_raw[];
    if (threadIdx.x < 126) {
        const uint32_t i = threadIdx.x, t = clk32() + (i >> 5) * PFD;
        const char* px = (const char*)prm.x + (blockIdx.x * 16 + (i & 15)) * 896 + (i >> 4) * 128;
        const char* pw = (const char*)prm.wqkv + blockIdx.x * 2688 + i * 128 + (896 - 112 * 128);
        spin_until(t);
        asm volatile("prefetch.global.L2 [%0];" :: "l"(i < 112 ? px : pw) : "memory");
    }
    if (threadIdx.x == 128) { asm volatile("prefetch.tensormap [%0];" :: "l"(&mX2) : "memory"); asm volatile("prefetch.tensormap [%0];" :: "l"(&mWqkv) : "memory"); }
    uint32_t sb = (uint32_t)__cvta_generic_to_shared(smem_raw);
    asm volatile("mov.u32 %0, %0;" : "+r"(sb));
    const uint32_t bar0 = sb + SM_BAR;
    auto BAR = [&](int i) { return bar0 + 8u * i; };

    const int tid = threadIdx.x, lane = tid & 31;
    const int warp = __shfl_sync(~0u, tid >> 5, 0);
    const int b = __shfl_sync(~0u, (int)blockIdx.x, 0);
    const int rank = b & 1;
    const int cl = (b >> 1) - 4, cq = ((cl - 32) * 37) >> 8;
    const int res = cl < 0 ? 0 : cl < 32 ? cl & 7 : cl - 31 - 7 * cq;
    const int rnd = cl < 0 ? cl + 8 : cl < 32 ? cl >> 3 : 4 + cq;
    const int hg = (res & 1) * 4 + (rnd & 3);
    const int ti = (res >> 1) * 4 + (rnd >> 2) * 2 + rank;
    const int a2p = res & 1, a2j = rnd & 3;
    const int a2s = ti * 2 + a2p;
    const bool g1_on = rnd != 7;
    const int g1j = (rnd < 6 ? rnd : res) & 1, g1f = rnd < 6 ? res * 3 + (rnd >> 1) : 24 + (res >> 1);
    const int g2j = rnd & 1, g2s = res * 4 + (rnd >> 1);
    uint32_t pbar0;
    asm volatile("mapa.shared::cluster.u32 %0, %1, %2;" : "=r"(pbar0) : "r"(bar0), "r"(rank ^ 1));
    auto pair_arrive = [&](int i) { __syncwarp(); const bool l = elect_one(); mbar_arrive_if(BAR(i), l); mbar_arrive_remote_if(pbar0 + 8u * i, l); };
    const int wcol = hg * 56 - (hg & 1) * 8;

    if (warp == 8) {
        if (elect_one()) {
            #pragma unroll
            for (int i = 0; i < B_WQF; i++) mbar_init(BAR(i), 1);
            asm volatile("fence.mbarrier_init.release.cluster;" ::: "memory");
            fence_async_smem();
            #pragma unroll
            for (int kb = 0; kb < 7; kb++) {
                tma3d(sb + kb * 16384, &mX2, kb * 64, ti * 64, 0, BAR(B_XF + kb));
                mbar_expect(BAR(B_XF + kb), 16384);
            }
        }
    } else if (warp > 8) {
        if (elect_one()) {
            if (warp == 9) {
                #pragma unroll
                for (int i = B_WQF; i < B_AF; i++) mbar_init(BAR(i), i < B_XC ? 1 : i < B_A1D ? 16 : i < B_BE ? 8 : 4);
            } else if (warp == 10) {
                #pragma unroll
                for (int i = B_AF; i < B_BF; i++) mbar_init(BAR(i), 1);
            } else {
                #pragma unroll
                for (int i = B_BF; i < B_COUNT; i++) mbar_init(BAR(i), i == B_HD ? 8 : 1);
            }
            asm volatile("fence.mbarrier_init.release.cluster;" ::: "memory");
            fence_async_smem();
        }
    }
    __syncwarp();
    __syncthreads();
    asm volatile("barrier.cluster.arrive.relaxed.aligned;" ::: "memory");

    if (warp >= 8) {
        asm volatile("setmaxnreg.dec.sync.aligned.u32 40;");
        asm volatile("barrier.cluster.wait.aligned;" ::: "memory");
        auto fetch_halo = [&](int p, uint32_t tag) {
            const uint32_t hl = BAR(B_HL + p), dst = opaque(sb + SM_STG + p * 8192 + 3 * 2048 + lane * 16);
            const bool lead = elect_one();
            if (rank) { if (lead) mbar_expect(hl, 2048); __syncwarp(); return; }
            const uint4* hp = opaque_ptr(&prm.sc->halo[((((ti >> 1) - 1) * 8 + hg) * 2 + p) * 128 + lane]);
            mbar_wait(BAR(B_KVC), 0);
            if (ti > 0) {
                spin_until(clk32() + HDELAY);
                int it = 0;
                uint32_t bad;
                do {
                    uint4 u[4];
                    #pragma unroll
                    for (int c = 0; c < 4; c++) u[c] = ld_rlx4(hp + c * 32);
                    #pragma unroll
                    for (int c = 0; c < 4; c++) sts4(dst + c * 512, u[c].x, u[c].y, u[c].z, u[c].w);
                    bad = ((u[0].x ^ tag) | (u[1].x ^ tag) | (u[2].x ^ tag) | (u[3].x ^ tag)) & ~lane & 1;
                } while (__any_sync(~0u, bad) && ++it < kSpinLimit);
            } else {
                #pragma unroll
                for (int c = 0; c < 4; c++) sts4(dst + c * 512, 0u, 0u, 0u, 0u);
            }
            __syncwarp();
            mbar_arrive_if(hl, lead);
        };
        auto poll_flags = [&](const uint32_t* fp, int step, uint32_t tag, uint32_t gbase) {
            uint64_t v0 = 0, v1 = 0;
            int it = 0;
            do {
                ld_flag_if(v0, fp, (uint32_t)v0 != tag); ld_flag_if(v1, fp + step, (uint32_t)v1 != tag);
                if (++it > kSpinLimit) break;
            } while (__any_sync(~0u, (uint32_t)v0 != tag || (uint32_t)v1 != tag));
            return max((int)((uint32_t)(v0 >> 32) - gbase), (int)((uint32_t)(v1 >> 32) - gbase));
        };
        if (warp & 1) {
            uint32_t tag;
            if (warp == 11) {
                tag = *(volatile uint32_t*)&prm.sc->epoch + 1;
                #pragma unroll 1
                for (int i = 0; i < 8 * rank; i++) prm.sc->halo[((ti >> 1) * 8 + hg) * 256 + i * 32 + lane] = make_uint4(~tag, 0u, 0u, 0u);
                ((uint4*)prm.sc->stats)[(a2s * 4 + a2j) * 64 + lane] = ((uint4*)prm.sc->stats)[(a2s * 4 + a2j) * 64 + 32 + lane] = make_uint4(~tag, ~tag, ~tag, ~tag);
                prm.sc->flag_h[(a2s * 4 + a2j) * FS + lane] = 0;
                prm.sc->flag_o[(ti * 8 + hg) * FS + lane] = 0;
                __syncwarp();
                if (lane == 0) {
                    asm volatile("st.shared.v2.u32 [%0], {%1, %2};" :: "r"(sb + SM_EPOCH), "r"(tag), "r"(gtime32()) : "memory");
                    mbar_arrive(BAR(B_EP));
                }
                if (lane < 8) mbar_expect(BAR(B_RF + lane), 1792);
                __syncwarp();
            } else {
                mbar_wait(BAR(B_EP), 0);
                tag = lds1(sb + SM_EPOCH);
            }
            fetch_halo((warp >> 1) & 1, tag);
        }
        if (warp < 10) {
          auto load_slab = [&](int s, bool second) {
              if (!second) tma2d(sb + s * 8192, &mW1, (s & 1) * kF + g1f * 64, (rank * 8 + (s >> 1)) * 64, BAR(B_AF));
              else         tma2d(sb + s * 8192, &mW2, g2s * 64, (rank * 14 + s - 1) * 64, BAR(B_AF));
          };
          const char* pw2 = (const char*)prm.w2 + ((b >> 6) * 896 + (b & 63) + PFW * 64) * 4096;
          if (warp == 8) {
            if (elect_one()) {
                #pragma unroll 1
                for (int s = 0; s < 7; s++) {
                    mbar_expect(BAR(B_WKVF + s), 16384);
                    tma2d_mc(sb + SM_WKV + s * 16384 + rank * 8192, &mWqkv, (1 + rank) * kD + wcol, s * 64, BAR(B_WKVF + s));
                }
            }
            __syncwarp();
            mbar_wait(BAR(B_XC), 0);
            if (elect_one()) {
                asm volatile("prefetch.tensormap [%0];" :: "l"(&mX) : "memory");
                asm volatile("prefetch.tensormap [%0];" :: "l"(&mWo) : "memory");
                asm volatile("prefetch.tensormap [%0];" :: "l"(&mW1) : "memory");
                asm volatile("prefetch.tensormap [%0];" :: "l"(&mW2) : "memory");
                mbar_expect(BAR(B_AF), (g1_on ? NPRE : 14) * 8192);
                mbar_expect(BAR(B_WQF), 57344);
                #pragma unroll 1
                for (int s = rank; s < 7; s += 2) tma2d_mc(sb + SM_WQ + s * 8192, &mWqkv, wcol, s * 64, BAR(B_WQF));
                mbar_expect(BAR(B_XRF), 16384);
                tma2d(sb + SM_XR, &mX, a2p * kD + a2j * 112, ti * 64, BAR(B_XRF));
                tma2d(sb + SM_XR + 8192, &mX, a2p * kD + a2j * 112 + 48, ti * 64, BAR(B_XRF));
            }
            __syncwarp();
            #pragma unroll 1
            for (int q = 0; q < 4; q++) {
                mbar_wait(BAR(B_KV3 + (q >> 1)), 0);
                if (q == 2) spin_until(clk32() + WOD);
                if (q == 3) mbar_wait2(BAR(B_HL), 0, BAR(B_HL + 1), 0);
                if (elect_one()) {
                    if (!(q & 1)) mbar_expect(BAR(B_WOF + (q >> 1)), 57344);
                    tma2d_mc(sb + SM_WKV + q * 28672 + rank * 14336, &mWo, a2j * 112 + (q & 1) * 48, (q >> 1) * 224 + rank * 112, BAR(B_WOF + (q >> 1)));
                    if (g1_on && q == 1) { load_slab(0, false); load_slab(1, false); load_slab(2, false); }
                }
                __syncwarp();
            }
            if (g1_on) {
                mbar_wait2(BAR(B_XD), 0, BAR(B_OL + 3), 0);
                #pragma unroll 1
                for (int i = 3; i < NPRE; i++) {
                    if (i == 7) mbar_wait(BAR(B_OC), 0);
                    if (elect_one()) load_slab(i, false);
                    __syncwarp();
                }
            } else {
                mbar_arrive_if(BAR((lane < 16 ? B_BE : B_BF) + (lane & 3)), lane < 20);
                mbar_wait(BAR(B_HD), 0);
                mbar_arrive_remote_if(pbar0 + 8u * B_PD, lane == 0);
                mbar_wait(BAR(B_GO), 0);
                uint32_t tg = lds1(sb + SM_TG + 4);
                tg += max((int)(lds1(sb + SM_TG2) - tg), 0);
                int it = 0;
                while ((int)(gtime32() - tg) < 0 && ++it < 256) {}
                const uint32_t t0 = clk32();
                if (lane < 2) {
                    asm volatile("st.shared.u32 [%0], %1;" :: "r"(sb + SM_TG + 8 + lane * 4), "r"(t0 + (lane ? CN3 : CN2)) : "memory");
                    mbar_arrive(BAR(B_GD + lane));
                }
                __syncwarp();
                #pragma unroll 1
                for (int s = 1; s < 15; s++) {
                    sleep_until(t0 + W2OFF + s * W2PACE);
                    if (elect_one()) { if (s < 15 - PFW) bulk_prefetch(pw2 + (s - 1) * 64 * 4096, 4096); load_slab(s, true); }
                    __syncwarp();
                }
            }
          } else {
            const uint32_t tag = lds1(sb + SM_EPOCH);
            if (lane < 4) mbar_expect(BAR(B_OL + lane), 14336);
            const uint32_t gbase = lds1(sb + SM_TG);
            const bool lead = elect_one();
            uint32_t* hfl = opaque_ptr(&prm.sc->flag_h[(a2s * 4 + a2j) * FS]);
            mbar_wait(BAR(B_A1D), 0);
            const int d = poll_flags(&prm.sc->flag_o[(ti * 8 + (lane & 3) * 2) * FS], FS, tag, gbase);
            int key = max(d + DELTAO, __reduce_max_sync(~0u, d) + DMIN) * 4 + (lane & 3);
            uint32_t order = 0;
            #pragma unroll 1
            for (int i = 0; i < 4; i++) {
                const int m = __reduce_min_sync(~0u, key);
                const uint4* src = &prm.sc->o[(a2s * 4 + (m & 3)) * 896];
                int it = 0;
                while ((int)(gtime32() - gbase) < m >> 2 && ++it < 256) {}
                if (lead) bulk_g2s(sb + SM_WQ + i * 14336, src, 14336, BAR(B_OL + i));
                if (key == m) key = 0x7fffffff;
                order |= (m & 3) << i * 2;
            }
            if (lead) {
                asm volatile("st.shared.u32 [%0], %1;" :: "r"(sb + SM_ORD), "r"(order) : "memory");
                mbar_arrive(BAR(B_OD));
            }
            __syncwarp();
            int t0 = 0;
            #pragma unroll 1
            for (int i = 0; i < 4; i++) { mbar_wait(BAR(B_OF + i), 0); t0 = max(t0, (int)(gtime32() - gbase) - i * CHUNKNS); }
            if (lead) st_flag(hfl, tag, gbase + t0);
            __syncwarp();
          }
          if (elect_one()) {
              const int h = ~warp & 1;
              constexpr uint32_t T = 57344, BO = 2 * 14336;
              const char* src1 = (const char*)&prm.sc->hn[(rank * 16 + h) * 3584 + g1j * 896];
              const char* src2 = (const char*)&prm.sc->g[(rank * 14 + h) * 3584 + g2j * 896];
              uint64_t masks = g1_on ? (h ? kSegMasks1 : kSegMasks0) : 0x80 | 0x80 << 10;
              const uint32_t bl = BAR(B_BL + h * NB);
              uint32_t s8 = (g1_on ? NB - 2 + h : 4 + h) * 8, lap = 3, tmin = 0;
              const CUtensorMap* am = &mW1;
              uint32_t ad = sb + (NPRE + h) * 8192, astep = 16384; int ac0 = h * kF + g1f * 64, ac1 = (rank * 8 + NPRE / 2) * 64;
              #pragma unroll 1
              for (int seg = g1_on ? 0 : 3; seg < 5; seg++) {
                  const char* src = (seg < 3 ? src1 : src2) + (~seg & 1) * BO;
                  uint32_t m = (uint32_t)masks & 0x3ff;
                  masks >>= 10;
                  const uint32_t pace = seg == 4 ? PACEB : PACE2;
                  if (seg == 2) {
                      mbar_wait(BAR(B_PL), 0);
                      mbar_arrive_remote_if(pbar0 + 8u * B_PD, h);
                      am = &mW2; ad = sb + 8192; astep = 8192; ac0 = g2s * 64; ac1 = rank * 14 * 64;
                  } else {
                      const int gate = seg - (seg > 2);
                      mbar_wait(BAR(B_HD + gate), 0);
                      tmin = lds1(sb + SM_TG + gate * 4);
                      if (gate < 2) {
                          tmin += max((int)(lds1(gate ? sb + SM_TG2 : sb + SM_TG) - tmin), 0);
                          int it = 0;
                          while ((int)(gtime32() - tmin) < 0 && ++it < 256) {}
                          tmin = clk32();
                      }
                      tmin += h * PACE1;
                  }
                  #pragma unroll 1
                  do {
                      const uint32_t dst = sb + SM_B + s8 * 1792;
                      spin_until(tmin);
                      mbar_wait_fast(BAR(B_BE) + s8 + (lap & 1) * (NB * 8), lap >> 1 & 1);
                      if (seg) {
                          bulk_g2s(dst, src, 14336, bl + s8);
                          mbar_expect(bl + s8, 14336);
                      }
                      tmin += pace;
                      src += 2 * T;
                      s8 += 16;
                      if (s8 >= NB * 8) { s8 -= NB * 8; lap++; }
                      if (m & 1) {
                          mbar_expect_more(bl + s8, 8192);
                          tma2d(ad, am, ac0, ac1, bl + s8);
                          ad += astep; ac1 += 64;
                      }
                      m >>= 1;
                  } while (m != 1);
                  if (seg == 0) lap = 3;
              }
          }
        } else {
          if (warp == 10) {
            mbar_wait(BAR(B_XF + 6), 0);
            if (lane < 27) asm volatile("prefetch.global.L2 [%0];" :: "l"(lane < 25 ? (const char*)prm.wo + min(b * 25 + lane, 3135) * 128
                                                                          : lane == 25 ? (const char*)prm.b1 + (b % 28) * 128 : (const char*)prm.b2 + (b & 31) * 128));
            const char* p1 = (const char*)prm.w1 + ((b >> 6) * 1024 + (b & 63) * 2) * 3584 + min(lane, 27) * 128;
            uint32_t tnext = clk32();
            #pragma unroll 1
            for (int i = 0; i < 16; i++) {
                while ((int)(clk32() - tnext) < 0) __nanosleep(40);
                asm volatile("prefetch.global.L2 [%0];" :: "l"(p1 + ((i >> 1) * 128 + (i & 1)) * 3584));
                tnext += PFPACE;
            }
            uint32_t* ofl = opaque_ptr(&prm.sc->flag_o[(ti * 8 + hg) * FS]);
            mbar_wait(BAR(B_EP), 0);
            const uint32_t tag = lds1(sb + SM_EPOCH);
            mbar_wait2(BAR(B_HL), 0, BAR(B_HL + 1), 0);
            mbar_wait(BAR(B_A1D), 0);
            if (lane == 0) st_flag(ofl, tag, gtime32());
            __syncwarp();
          }
          const uint32_t tag = lds1(sb + SM_EPOCH);
          const int h = warp & 1;
          const bool lead = elect_one();
          const uint32_t wo = lane * 132, l3 = lane < 16 ? 12288 : 0;
          uint32_t base = sb + SM_WQ, bl = BAR(B_OL), bf = BAR(B_OF), m = 4, rph = 0;
          #pragma unroll 1
          for (int e = 0; e < 2; e++) {
              uint32_t s8 = (e && !g1_on ? 4 + h : h) * 8;
              #pragma unroll 1
              do {
                  const uint32_t dst = base + s8 * 1792;
                  auto stale = [&]() {
                      uint32_t d;
                      asm volatile("{ .reg .b32 x, y, z, u;\n"
                                   "ld.shared.u32 x, [%1]; ld.shared.u32 y, [%1 + 4096]; ld.shared.u32 z, [%1 + 8192]; ld.shared.u32 u, [%2];\n"
                                   "lop3.b32 x, x, y, %3, 0x7e; lop3.b32 z, z, u, %3, 0x7e; lop3.b32 %0, x, z, 1, 0xa8; }"
                                   : "=r"(d) : "r"(dst + wo), "r"(dst + (wo + l3)), "r"(tag) : "memory");
                      return __any_sync(~0u, d);
                  };
                  mbar_wait_fast(bl + s8, m & 1);
                  bool bad = stale();
                  mbar_arrive_if(bf + s8, lead && !bad);
                  if (bad) {
                      const int p = 2 * __clz(m) - 2 + h;
                      const int st = (p > 15) + (p > 31) + (p > 45), s = p - (st < 3 ? 16 * st : 46);
                      mbar_wait(BAR(B_OD), 0);
                      const char* src = (const char*)(!e ? &prm.sc->o[(a2s * 4 + (lds1(sb + SM_ORD) >> (p * 2 & 7) & 3)) * 896] : st < 2 ? &prm.sc->hn[(rank * 16 + s) * 3584 + (g1j + 2 * st) * 896]
                                                                                                      : &prm.sc->g[(rank * 14 + s) * 3584 + (g2j + 2 * st - 4) * 896]);
                      int it = 0;
                      do {
                          if (++it > kSpinLimit) break;
                          const uint32_t* q = (const uint32_t*)(src + wo);
                          if (it > 1 && __any_sync(~0u, ((ld_rlx(q) ^ tag) | (ld_rlx(q + 1024) ^ tag) | (ld_rlx(q + 2048) ^ tag) | (ld_rlx(q + l3 / 4) ^ tag)) & 1)) continue;
                          if (lead) {
                              mbar_expect(BAR(B_RT + h), 14336);
                              bulk_g2s(dst, src, 14336, BAR(B_RT + h));
                          }
                          __syncwarp();
                          mbar_wait(BAR(B_RT + h), rph);
                          rph ^= 1;
                          bad = stale();
                      } while (bad);
                      mbar_arrive_if(bf + s8, lead);
                  }
                  s8 += 16;
                  if (s8 >= NB * 8) s8 -= NB * 8;
                  m >>= 1;
              } while (m != 1);
              if (e) break;
              if (h) {
                  const uint32_t gbase = lds1(sb + SM_TG);
                  sleep_until(clk32() + PDELAY);
                  const uint32_t tg = gbase + DELTA + __reduce_max_sync(~0u, poll_flags(&prm.sc->flag_h[(rank * 64 + lane) * FS], 32 * FS, tag, gbase));
                  if (lead) {
                      asm volatile("st.async.shared::cluster.mbarrier::complete_tx::bytes.b32 [%0], %1, [%2];"
                                   :: "r"(pbar0 + (SM_TG2 - SM_BAR)), "r"(tg), "r"(pbar0 + 8u * B_GO) : "memory");
                      asm volatile("st.shared.u32 [%0], %1;" :: "r"(sb + SM_TG + 4), "r"(tg) : "memory");
                      mbar_expect(BAR(B_GO), 4);
                  }
                  __syncwarp();
              } else {
                  const char* p2 = (const char*)prm.w2 + ((b >> 6) * 896 + (b & 63)) * 4096 + lane * 128;
                  #pragma unroll 1
                  for (int i = 0; i < PFW; i++) {
                      asm volatile("prefetch.global.L2 [%0];" :: "l"(p2 + i * 64 * 4096));
                      sleep_until(clk32() + PFPACE2);
                  }
              }
              base = sb + SM_B; bl = BAR(B_BL + h * NB); bf = BAR(B_BF); m = g1_on ? 0x4fe03f80 : 0x7f80;
          }
        }
    } else {
        asm volatile("setmaxnreg.inc.sync.aligned.u32 232;");
        asm volatile("barrier.cluster.wait.aligned;" ::: "memory");
        const int wg = warp >> 2, w = warp & 3;
        const int g = lane >> 2, t = lane & 3;
        uint32_t tag;
        __nv_bfloat16 bias1a, bias1b;
        {
            const uint64_t dw = make_desc(sb + (hg & 1) * 16, 0, true);
            uint4* const hp = opaque_ptr((w == 3 ? &prm.sc->halo[(((ti >> 1) * 8 + hg) * 2 + wg) * 128] : (uint4*)(smem_raw + SM_STG + wg * 8192 + w * 2048)) + lane);
            uint32_t a[28][4];
            float sm[4][4] = {};
            {
                const int r = w * 16 + (lane & 15);
                uint32_t xa[4];
                #pragma unroll
                for (int q = 0; q < 4; q++) xa[q] = opaque(sb + wg * 8192 + r * 128 + (((q * 2 + (lane >> 4)) ^ (r & 7)) << 4));
                const uint32_t one = opaque(0x3F803F80u), one2 = opaque(0x3F803F80u);
                #pragma unroll
                for (int k = 0; k < 28; k++) {
                    if ((k & 3) == 0) mbar_wait(BAR(B_XF + (k >> 2)), 0);
                    uint32_t (&f)[4] = a[k];
                    asm volatile("ldmatrix.sync.aligned.m8n8.x4.shared.b16 {%0,%1,%2,%3}, [%4];"
                                 : "=r"(f[0]), "=r"(f[1]), "=r"(f[2]), "=r"(f[3]) : "r"(xa[k & 3] + (k >> 2) * 16384) : "memory");
                    if (k < 24) mma16816(sm[k & 3], f[0], f[1], f[2], f[3], one, one2);
                }
                pair_arrive(B_XC);
                const bool wok = mbar_test(BAR(B_WKVF), 0);
                #pragma unroll
                for (int k = 24; k < 28; k++) mma16816(sm[k & 3], a[k][0], a[k][1], a[k][2], a[k][3], one, one2);
                if (!wok) mbar_wait(BAR(B_WKVF), 0);
            }
            const float mean0 = ((sm[0][0] + sm[1][0]) + (sm[2][0] + sm[3][0])) * (1.f / kD);
            const float mean1 = ((sm[0][2] + sm[1][2]) + (sm[2][2] + sm[3][2])) * (1.f / kD);
            const uint32_t mb0 = pack_bf16(mean0, mean0), mb1 = pack_bf16(mean1, mean1);
            float ak[28], av[28], aq[28];
            float ss0 = 0.f, ss1 = 0.f, ss2 = 0.f, ss3 = 0.f;
            uint32_t p0, p1;
            bool qok;
            static_for<0, 7>([&](auto S_) {
                constexpr int s = decltype(S_)::value;
                auto centre = [&](int q) {
                    uint32_t (&f)[4] = a[s * 4 + q];
                    f[0] = sub_bf16x2(f[0], mb0); f[1] = sub_bf16x2(f[1], mb1);
                    f[2] = sub_bf16x2(f[2], mb0); f[3] = sub_bf16x2(f[3], mb1);
                };
                if (s) {
                    #pragma unroll
                    for (int q = 0; q < 4; q++) centre(q);
                    mbar_wait(BAR(B_WKVF + s), 0);
                    if (s == 6) qok = mbar_test(BAR(B_WQF), 0);
                    wg_fence();
                }
                static_for<0, 4>([&](auto Q_) {
                    constexpr int q = decltype(Q_)::value;
                    uint32_t (&f)[4] = a[s * 4 + q];
                    if (s == 0) { centre(q); wg_fence(); }
                    wgmma_rs_n56<SM_WKV + s * 16384 + q * 2048, (s | q) != 0>(ak, f[0], f[1], f[2], f[3], dw);
                    wgmma_rs_n56<SM_WKV + s * 16384 + q * 2048 + 8192, (s | q) != 0>(av, f[0], f[1], f[2], f[3], dw);
                });
                wg_commit();
                if (s == 4) { wg_wait<1>(); pair_arrive(B_KV3); }
                if (s < 2) mbar_wait(BAR(s ? B_EP : B_WKVF), 0);
                if (s == 1) tag = lds1(sb + SM_EPOCH);
                #pragma unroll
                for (int q = 0; q < 8; q++) {
                    const uint32_t u0 = a[s * 4 + q / 2][(q & 1) * 2], u1 = a[s * 4 + q / 2][(q & 1) * 2 + 1];
                    if (q == 0) { p0 = sqr_bf16x2(u0); p1 = sqr_bf16x2(u1); }
                    else { p0 = sqa_bf16x2(u0, p0); p1 = sqa_bf16x2(u1, p1); }
                }
                ss0 += bf_lo(p0); ss2 += bf_hi(p0); ss1 += bf_lo(p1); ss3 += bf_hi(p1);
            });
            auto q_chunk = [&](auto K0_, auto K1_) {
                wg_fence();
                static_for<decltype(K0_)::value, decltype(K1_)::value>([&](auto K_) {
                    constexpr int k = decltype(K_)::value;
                    wgmma_rs_n56<SM_WQ + k * 2048, k != 0>(aq, a[k][0], a[k][1], a[k][2], a[k][3], dw);
                });
                wg_commit();
            };
            #define QCHUNK(k0, k1) q_chunk(std::integral_constant<int, k0>{}, std::integral_constant<int, k1>{})
            const float dl0 = mean0 - bf_lo(mb0), dl1 = mean1 - bf_lo(mb1);
            const float rs0 = rsq(fmaxf(quad_sum(ss0 + ss2) * (1.f / kD) - dl0 * dl0, 0.f) + kEps);
            const float rs1 = rsq(fmaxf(quad_sum(ss1 + ss3) * (1.f / kD) - dl1 * dl1, 0.f) + kEps);
            float rk[3][2];
            rk[1][0] = __shfl_sync(~0u, rs0, t * 8); rk[1][1] = __shfl_sync(~0u, rs0, t * 8 + 4);
            rk[2][0] = __shfl_sync(~0u, rs1, t * 8); rk[2][1] = __shfl_sync(~0u, rs1, t * 8 + 4);
            const uint32_t stg = sb + SM_STG + wg * 8192 + lane * 16;
            if (!qok) mbar_wait(BAR(B_WQF), 0);
            QCHUNK(0, QC0);
            wg_wait<1>();
            reg_fence(ak); reg_fence(av);
            uint32_t kf[3][7], vf[3][7];
            #pragma unroll
            for (int c = 0; c < 7; c++) {
                kf[2][c] = pack_bf16(ak[4 * c + 2], ak[4 * c + 3]);
                vf[2][c] = movm(pack_bf16(av[4 * c + 2], av[4 * c + 3]));
            }
            const uint32_t om = ~lane & 1;
            kf[2][0] = set_par(kf[2][0], om, tag); vf[2][0] = set_par(vf[2][0], om, tag);
            vf[2][1] = set_par(vf[2][1], om, tag); vf[2][5] = set_par(vf[2][5], om, tag);
            auto publish = [&](auto st) {
                st(0, kf[2][0], kf[2][1], kf[2][2], kf[2][3]);
                st(1, vf[2][0], kf[2][4], kf[2][5], kf[2][6]);
                st(2, vf[2][1], vf[2][2], vf[2][3], vf[2][4]);
                st(3, vf[2][5], vf[2][6], __float_as_uint(rk[2][0]), __float_as_uint(rk[2][1]));
            };
            if (w < 3 || rank) publish([&](int c, uint32_t x, uint32_t y, uint32_t z, uint32_t v) { st_gen4(hp + c * 32, x, y, z, v); });
            else publish([&](int c, uint32_t x, uint32_t y, uint32_t z, uint32_t v) {
                asm volatile("st.async.shared::cluster.mbarrier::complete_tx::bytes.v4.b32 [%0], {%2,%3,%4,%5}, [%1];"
                             :: "r"(pbar0 + (SM_STG + 3 * 2048 - SM_BAR) + wg * 8192 + lane * 16 + c * 512), "r"(pbar0 + (B_HL + wg) * 8),
                                "r"(x), "r"(y), "r"(z), "r"(v) : "memory");
            });
            pair_arrive(B_KVC);
            QCHUNK(QC0, QC1);
            #pragma unroll
            for (int c = 0; c < 7; c++) {
                kf[1][c] = pack_bf16(ak[4 * c], ak[4 * c + 1]);
                vf[1][c] = movm(pack_bf16(av[4 * c], av[4 * c + 1]));
            }
            QCHUNK(QC1, QC2);
            named_bar(1 + wg, 128);
            uint32_t* op = opaque_ptr((uint32_t*)&prm.sc->o[((ti * 2 + wg) * 56 + hg * 7) * 64] + w * 64 + lane);
            const uint32_t om0 = opaque((lane & 7) == w * 2), om1 = opaque((lane & 7) == w * 2 + 1);
            QCHUNK(QC2, 28);
            #undef QCHUNK
            const bool gt0 = 2 * t > g, gt1 = 2 * t + 1 > g, no_prev = ti == 0 && w == 0;
            const float kf0 = gt0 ? rk[1][0] : rk[2][0], kf1 = gt1 ? rk[1][1] : rk[2][1];
            constexpr float kScale = 0.18898223650461362f * 1.4426950408889634f;
            const float sq0 = rs0 * kScale, sf0 = kf0 * (rs1 * kScale), sf1 = kf1 * (rs1 * kScale);
            const float NEG = -__int_as_float(0x7f800000);
            const float nb0 = gt0 && no_prev ? NEG : 0.f, nb1 = gt1 && no_prev ? NEG : 0.f;
            const uint32_t mk = opaque((gt0 ? 0x0000ffffu : 0u) | (gt1 ? 0xffff0000u : 0u));
            const uint32_t nil = __shfl_sync(~0u, lane, 0);
            const uint32_t sr = stg + ((w + 3) & 3) * 2048, hbar = BAR(w == 0 ? B_HL + wg : B_EP);
            mbar_wait(BAR(B_EP), 0);
            wg_wait<0>();
            reg_fence(aq);
            warp_arrive(BAR(B_A1D));
            uint32_t qf[8][2];
            #pragma unroll
            for (int c = 0; c < 7; c++) {
                qf[c + (c > 3)][0] = pack_bf16(aq[4 * c], aq[4 * c + 1]);
                qf[c + (c > 3)][1] = pack_bf16(aq[4 * c + 2], aq[4 * c + 3]);
            }
            qf[4][0] = t >= 2 ? qf[3][0] : 0u; qf[4][1] = t >= 2 ? qf[3][1] : 0u;
            qf[3][0] = t < 2 ? qf[3][0] : 0u;  qf[3][1] = t < 2 ? qf[3][1] : 0u;
            float sc[2][3][4];
            auto scores = [&](int n) {
                #pragma unroll
                for (int hd = 0; hd < 2; hd++) {
                    sc[hd][n][0] = sc[hd][n][1] = sc[hd][n][2] = sc[hd][n][3] = 0.f;
                    mma16816(sc[hd][n], qf[4 * hd][0], qf[4 * hd][1], qf[4 * hd + 1][0], qf[4 * hd + 1][1], kf[n][3 * hd], kf[n][3 * hd + 1]);
                    mma16816(sc[hd][n], qf[4 * hd + 2][0], qf[4 * hd + 2][1], qf[4 * hd + 3][0], qf[4 * hd + 3][1], kf[n][3 * hd + 2], kf[n][3 * hd + 3]);
                }
            };
            scores(1); scores(2);
            mbar_wait(hbar, 0);
            {
                const uint4 u0 = lds4(sr), u1 = lds4(sr + 512), u3 = lds4(sr + 1536), u2 = lds4(sr + 1024);
                kf[0][0] = u0.x; kf[0][1] = u0.y; kf[0][2] = u0.z; kf[0][3] = u0.w;
                vf[0][0] = u1.x; kf[0][4] = u1.y; kf[0][5] = u1.z; kf[0][6] = u1.w;
                vf[0][1] = u2.x; vf[0][2] = u2.y; vf[0][3] = u2.z; vf[0][4] = u2.w;
                vf[0][5] = u3.x; vf[0][6] = u3.y; rk[0][0] = __uint_as_float(u3.z); rk[0][1] = __uint_as_float(u3.w);
            }
            scores(0);
            const float ke0 = gt0 ? rk[0][0] : rk[1][0], ke1 = gt1 ? rk[0][1] : rk[1][1];
            const float se0 = ke0 * sq0, se1 = ke1 * sq0;
            uint32_t ow[7][2];
            #pragma unroll
            for (int hd = 0; hd < 2; hd++) {
                const int c0 = hd * 3;
                float (&sc_)[3][4] = sc[hd];
                const float e0 = fmaf(gt0 ? sc_[0][0] : sc_[1][0], se0, nb0), e1 = fmaf(gt1 ? sc_[0][1] : sc_[1][1], se1, nb1);
                const float f0 = (gt0 ? sc_[1][2] : sc_[2][2]) * sf0, f1 = (gt1 ? sc_[1][3] : sc_[2][3]) * sf1;
                const float me = quad_max(fmaxf(e0, e1)), mf = quad_max(fmaxf(f0, f1));
                const float p0 = ex2(e0 - me), p1 = ex2(e1 - me), r0 = ex2(f0 - mf), r1 = ex2(f1 - mf);
                const float ie = rcp(quad_sum(p0 + p1)), jf = rcp(quad_sum(r0 + r1));
                const uint32_t pp = pack_bf16(p0 * ke0 * ie, p1 * ke1 * ie), rp = pack_bf16(r0 * kf0 * jf, r1 * kf1 * jf);
                const uint32_t a0 = pp & ~mk, a1 = rp & mk, a3 = rp & ~mk, a4 = pp & mk, zero = pp & nil, zero2 = rp & nil;
                #pragma unroll
                for (int c = 0; c < 4; c++) {
                    float o[4] = {0.f, 0.f, 0.f, 0.f};
                    mma16816(o, a0, a1, zero, a3, vf[1][c0 + c], vf[2][c0 + c]);
                    mma1688(o, a4, zero2, vf[0][c0 + c]);
                    const uint32_t lo = pack_bf16(o[0], o[1]), hi = pack_bf16(o[2], o[3]);
                    if (hd == 1 && c == 0) { if (t >= 2) { ow[3][0] = lo; ow[3][1] = hi; } }
                    else { ow[c0 + c][0] = lo; ow[c0 + c][1] = hi; }
                }
            }
            #pragma unroll
            for (int c = 0; c < 7; c++) {
                stg1(op + c * 256,      set_par(ow[c][0], om0, tag));
                stg1(op + c * 256 + 32, set_par(ow[c][1], om1, tag));
            }
        }
        float as[28], ac[28];
        uint32_t xch, peer_xch, gm[2][4], *gp1, *gp2;
        const uint32_t *hp, *ht;
        const uint2* hq;
        uint64_t da0, db0;
        bool lead;
        {
            float acc2[28];
            mbar_wait(BAR(B_XRF), 0);
            const int cg = a2j * 2 + wg, cg2 = (g2j + 2 * wg) * 2 + (rank ^ 1), cg1 = (g1j + 2 * wg) * 2 + (rank ^ (g1f < 14));
            lead = elect_one();
            {
                const uint32_t xa = sb + SM_XR + wg * 8192 + (w * 16 + (lane & 15)) * 128;
                #pragma unroll
                for (int c = 0; c < 4; c++) {
                    uint32_t xr[4];
                    asm volatile("ldmatrix.sync.aligned.m8n8.x4.shared.b16 {%0,%1,%2,%3}, [%4];"
                                 : "=r"(xr[0]), "=r"(xr[1]), "=r"(xr[2]), "=r"(xr[3])
                                 : "r"(xa + ((((c * 2 + wg + (lane >> 4)) ^ lane) & 7) << 4)) : "memory");
                    #pragma unroll
                    for (int e = 0; e < (c < 3 ? 4 : 2); e++) { acc2[8 * c + 2 * e] = bf_lo(xr[e]); acc2[8 * c + 2 * e + 1] = bf_hi(xr[e]); }
                }
            }
            uint32_t* spw = opaque_ptr(&prm.sc->stats[((a2s * 8 + cg) * 4 + w) * 32 + lane]);
            const uint32_t* spr = opaque_ptr(&prm.sc->stats[(a2s * 32 + w) * 32 + lane]);
            uint32_t* rp = opaque_ptr((uint32_t*)&prm.sc->rows[a2s * 64 + w * 16 + (t >> 1) * 8 + g] + (t & 1));
            const int cgs = cg ^ (a2s >> 4);
            uint32_t* np = opaque_ptr((uint32_t*)&prm.sc->hn[(a2s * 56 + cgs * 7) * 64] + w * 64 + lane);
            const uint64_t dwo = make_desc(sb + SM_WKV + wg * (28672 + 16), 0, true);
            const uint64_t doa = make_desc(sb + SM_WQ, 1024, false, 128);
            bias1a = prm.b1[g1f * 64 + w * 16 + g]; bias1b = prm.b1[g1f * 64 + w * 16 + 8 + g];
            const __nv_bfloat16 bias2 = prm.b2[ti * 128 + (w * 16 + (t >> 1) * 8 + g) * 2 + a2p];
            reg_fence(acc2);
            fence_async_smem();
            warp_arrive(BAR(B_XD));
            {
                xch = opaque(sb + SM_XCH + w * 1792 + lane * 16);
                asm volatile("mapa.shared::cluster.u32 %0, %1, %2;" : "=r"(peer_xch) : "r"(xch), "r"(rank ^ 1));
                const int hcg = cg2 ^ (g2s >> 4), hrg = (g2s & 1) * 4 + w;
                const uint32_t* hl = (const uint32_t*)&prm.sc->hn[((g2s >> 1) * 112 + hcg * 7) * 64 + hrg * 8];
                hp = opaque_ptr(hl + (g & 1) * 14336 + (g >> 1) * 4 + t);
                ht = opaque_ptr(hl + (lane & 1) * 14336 + min(lane >> 1, 6) * 256 + ((min(lane >> 1, 6) - (hcg & 1)) & 3) * 8 + hrg);
                hq = opaque_ptr(&prm.sc->rows[((g2s >> 1) * 2 + (g & 1)) * 64 + hrg * 8 + (g >> 1)]);
                gp1 = opaque_ptr((uint32_t*)&prm.sc->g[(g1f * 56 + cg1 * 7) * 64] + w * 64 + lane);
                gp2 = opaque_ptr((uint32_t*)(prm.out + (size_t)(g2s * 64 + w * 16 + lane / 7) * kD + cg2 * 56) + (lane % 7) * 4);
                da0 = make_desc(sb, 0, true); db0 = make_desc(sb + SM_B, 128, false);
            }
            mbar_wait2(BAR(B_WOF), 0, BAR(B_WOF + 1), 0);
            mbar_wait(BAR(B_OD), 0);
            const uint32_t order = __shfl_sync(~0u, lds1(sb + SM_ORD), 0);
            static_for<0, 4>([&](auto P_) {
                constexpr int P = decltype(P_)::value;
                const uint64_t dwp = dwo + ((order >> (2 * P + 1) & 1) * 3584 + (order >> 2 * P & 1) * 896);
                mbar_wait(BAR(B_OF + P), 0);
                wg_fence();
                static_for<0, 7>([&](auto K_) { constexpr int k = decltype(K_)::value;
                    wgmma_ss_n56<P * 14336 + k * 2048, k * 2048, 0>(acc2, doa, dwp); });
                if (P) wg_commit();
                if (P == 2) { wg_wait<1>(); warp_arrive(BAR(B_OC)); }
            });
            wg_wait<0>();
            reg_fence(acc2);
            float s0 = 0.f, s1 = 0.f, q0 = 0.f, q1 = 0.f;
            #pragma unroll
            for (int c = 0; c < 7; c++) {
                s0 += acc2[4 * c] + acc2[4 * c + 1];     q0 = fmaf(acc2[4 * c], acc2[4 * c], fmaf(acc2[4 * c + 1], acc2[4 * c + 1], q0));
                s1 += acc2[4 * c + 2] + acc2[4 * c + 3]; q1 = fmaf(acc2[4 * c + 2], acc2[4 * c + 2], fmaf(acc2[4 * c + 3], acc2[4 * c + 3], q1));
            }
            const bool th = t >= 2, to = t & 1;
            const float sa = (th ? s1 : s0) + __shfl_xor_sync(~0u, th ? s0 : s1, 2), qa = (th ? q1 : q0) + __shfl_xor_sync(~0u, th ? q0 : q1, 2);
            const float part = (to ? qa : sa) + __shfl_xor_sync(~0u, to ? sa : qa, 1);
            stg1(spw, set_par(__float_as_uint(part), 1u, tag));
            const uint32_t tpoll = clk32() + SDELAY;
            warp_arrive(BAR(B_HD));
            uint32_t nm[2][4], us[8];
            spin_until(tpoll);
            #pragma unroll
            for (int i = 0; i < 8; i++) us[i] = ld_rlx(spr + i * 128);
            #pragma unroll
            for (int i = 0; i < 8; i++) {
                nm[i >> 2][i & 3] = lane == ((i - (cgs & 1)) & 3) * 8 + w * 2 + (i >> 2);
                gm[i >> 2][i & 3] = opaque(lane == ((i - (cg1 & 1)) & 3) * 8 + w * 2 + (i >> 2));
            }
            #pragma unroll
            for (int c = 0; c < 28; c++) { ac[c] = 0.5f * __bfloat162float(c & 2 ? bias1b : bias1a); as[c] = 0.f; }
            reg_fence(as); reg_fence(ac);
            {
                int it = 0;
                while (true) {
                    uint32_t bad = 0;
                    #pragma unroll
                    for (int i = 0; i < 8; i++) bad |= us[i] ^ tag;
                    if (!__any_sync(~0u, bad & 1)) break;
                    if (++it > kSpinLimit) break;
                    #pragma unroll
                    for (int i = 0; i < 8; i++) us[i] = ld_rlx(spr + i * 128);
                }
            }
            const float tot = (((__uint_as_float(us[0]) + __uint_as_float(us[1])) + (__uint_as_float(us[2]) + __uint_as_float(us[3])))
                            + ((__uint_as_float(us[4]) + __uint_as_float(us[5])) + (__uint_as_float(us[6]) + __uint_as_float(us[7])))) * (1.f / kD);
            const float oth = __shfl_xor_sync(~0u, tot, 1);
            const float mean = to ? oth : tot;
            const float var = fmaxf(fmaf(-mean, mean, to ? tot : oth), 0.f);
            const float rra = rsq(fmaf(var, 4.f + 4.f * kEps, 4.f * kEps * kEps)), mra = -mean * rra;
            const float rrb = __shfl_xor_sync(~0u, rra, 2), mrb = __shfl_xor_sync(~0u, mra, 2);
            const float rr0 = th ? rrb : rra, mr0 = th ? mrb : mra, rr1 = th ? rra : rrb, mr1 = th ? mra : mrb;
            #pragma unroll
            for (int c = 0; c < 7; c++) {
                stg1(np + c * 256,      set_par(pack_bf16(fmaf(acc2[4 * c], rr0, mr0), fmaf(acc2[4 * c + 1], rr0, mr0)), nm[0][c & 3], tag));
                stg1(np + c * 256 + 32, set_par(pack_bf16(fmaf(acc2[4 * c + 2], rr1, mr1), fmaf(acc2[4 * c + 3], rr1, mr1)), nm[1][c & 3], tag));
            }
            if (cg == 0) stg1(rp, set_par(__float_as_uint(to ? mean + __bfloat162float(bias2) : rcp(rra)), 1u, tag));
        }
        auto send = [&]() {
            const uint32_t rf = pbar0 + (B_RF + warp) * 8;
            #pragma unroll
            for (int c = 0; c < 4; c++) {
                const uint32_t p0 = pack_bf16(as[8 * c], as[8 * c + 1]), p1 = pack_bf16(as[8 * c + 2], as[8 * c + 3]);
                if (c < 3) {
                    const uint32_t p2 = pack_bf16(as[8 * c + 4], as[8 * c + 5]), p3 = pack_bf16(as[8 * c + 6], as[8 * c + 7]);
                    asm volatile("st.async.shared::cluster.mbarrier::complete_tx::bytes.v4.b32 [%0], {%1,%2,%3,%4}, [%5];"
                                 :: "r"(peer_xch + c * 512), "r"(p0), "r"(p1), "r"(p2), "r"(p3), "r"(rf) : "memory");
                } else {
                    asm volatile("st.async.shared::cluster.mbarrier::complete_tx::bytes.v2.b32 [%0], {%1,%2}, [%3];"
                                 :: "r"(peer_xch + 1536 - lane * 8), "r"(p0), "r"(p1), "r"(rf) : "memory");
                }
            }
        };
        auto receive = [&](uint32_t (&pk)[14], uint32_t phase) {
            mbar_wait(BAR(B_RF + warp), phase);
            #pragma unroll
            for (int c = 0; c < 3; c++) { const uint4 u = lds4(xch + c * 512); pk[4 * c] = u.x; pk[4 * c + 1] = u.y; pk[4 * c + 2] = u.z; pk[4 * c + 3] = u.w; }
            const uint2 u = lds2(xch + 1536 - lane * 8); pk[12] = u.x; pk[13] = u.y;
        };
        uint2 rw[2]; uint32_t tw;
        auto load_rows = [&]() { tw = ld_rlx(ht); rw[0] = ld_rlx2(hq); rw[1] = ld_rlx2(hq + 4); };
        rw[0] = rw[1] = make_uint2(0u, 0u); tw = ~tag;
        #pragma unroll 1
        for (int ge = 0;; ge++) {
          if (ge || g1_on) {
            const int use = ge * 2 + wg;
            int entry = ge ? 1 : 2 * wg, stop = 0;
            uint64_t da = da0 + (ge ? -3 : wg ? NR - 10 : 0) * 512;
            bool rel = lead && use == 1;
            const uint32_t xfree = BAR(use > (g1_on ? 0 : 2) ? B_RE + use - 1 : B_PD);
            mbar_wait(BAR(B_AF), 0);
            if (ge && (wg || g1_on)) named_bar(5 - wg, 256);
            auto step = [&](auto I_) {
                constexpr int i = decltype(I_)::value, sl = i % NB, ao = i * 8192, bo = sl * 14336;
                mbar_wait_fast(BAR(B_BF + sl), i / NB);
                wg_fence();
                wgmma_ss_n112<ao,        bo,       1>(as, ac, da, db0);
                wgmma_ss_n112<ao + 2048, bo + 256, 1>(as, ac, da, db0);
                wgmma_ss_n112<ao + 4096, bo + 512, 1>(as, ac, da, db0);
                wgmma_ss_n112<ao + 6144, bo + 768, 1>(as, ac, da, db0);
                wg_commit();
                if (i == 1 && stop == 1) named_arrive(4, 256);
                if (i == 3 && (use == 1 || use == 2)) named_arrive(4 + wg, 256);
                wg_wait<1>();
                mbar_arrive_if(BAR(B_BE + (13 + i) % 14), rel);
                rel = lead;
            };
            #pragma unroll 1
            while (true) {
                if (entry < 1) {
                    static_for<0, 2>(step);
                    if (stop == 1) break;
                    static_for<2, 4>(step);
                    if (stop) break;
                }
                if (entry < 2) static_for<4, 10>(step);
                else {
                    uint32_t af[NR * 4][4];
                    mbar_wait(BAR(B_GO), 0);
                    const uint32_t tp = lds1(sb + SM_TG + 4) + PLOFF;
                    int it = 0;
                    while ((int)(gtime32() - tp) < 0 && ++it < 256) __nanosleep(20);
                    const uint32_t la = sb + ((lane >> 4) * 8 + (lane & 7)) * 128 + (((w * 2 + ((lane >> 3) & 1)) ^ (lane & 7)) << 4);
                    #pragma unroll
                    for (int k = 0; k < NR * 4; k++)
                        asm volatile("ldmatrix.sync.aligned.m8n8.x4.trans.shared.b16 {%0,%1,%2,%3}, [%4];"
                                     : "=r"(af[k][0]), "=r"(af[k][1]), "=r"(af[k][2]), "=r"(af[k][3]) : "r"(la + k * 2048) : "memory");
                    __syncwarp();
                    mbar_arrive_if(BAR(B_PL), lead);
                    if (w == 0) {
                        const char* p2 = (const char*)prm.w2 + ((b >> 6) * 896 + (b & 63) + PFW * 64) * 4096 + lane * 128;
                        #pragma unroll 1
                        for (int i = 0; i < 14 - PFW; i++) {
                            it = 0;
                            while ((int)(gtime32() - tp) < PF3OFF + i * PF3PACE && ++it < 256) __nanosleep(40);
                            asm volatile("prefetch.global.L2 [%0];" :: "l"(p2 + i * 64 * 4096));
                        }
                    }
                    named_bar(4, 256);
                    static_for<0, NR>([&](auto I_) {
                        constexpr int i = decltype(I_)::value, sl = (16 + i) % NB, o = sl * 14336;
                        mbar_wait_fast(BAR(B_BF + sl), (16 + i) / NB & 1);
                        wg_fence();
                        wgmma_rs_n112<o,       1>(as, ac, af[4 * i][0], af[4 * i][1], af[4 * i][2], af[4 * i][3], db0);
                        wgmma_rs_n112<o + 256, 1>(as, ac, af[4 * i + 1][0], af[4 * i + 1][1], af[4 * i + 1][2], af[4 * i + 1][3], db0);
                        wgmma_rs_n112<o + 512, 1>(as, ac, af[4 * i + 2][0], af[4 * i + 2][1], af[4 * i + 2][2], af[4 * i + 2][3], db0);
                        wgmma_rs_n112<o + 768, 1>(as, ac, af[4 * i + 3][0], af[4 * i + 3][1], af[4 * i + 3][2], af[4 * i + 3][3], db0);
                        wg_commit();
                        if (i) { wg_wait<1>(); mbar_arrive_if(BAR(B_BE + (15 + i) % (2 * NB)), lead); }
                    });
                }
                static_for<10, 14>(step);
                entry = 0; stop = use + 1; da += 14 * 512;
            }
            const uint32_t prev = BAR(B_BE + (use ? 3 : 1));
            const bool xok = mbar_test(xfree, 0);
            wg_wait<0>();
            reg_fence(as); reg_fence(ac);
            mbar_arrive_if(prev, lead);
            if (!xok) mbar_wait(xfree, 0);
            if (ge) break;
            send();
            load_rows();
            uint32_t pk[14];
            receive(pk, 0);
            #pragma unroll
            for (int c = 0; c < 14; c++) {
                float r[2];
                #pragma unroll
                for (int e = 0; e < 2; e++) {
                    const float u = ac[2 * c + e] + (e ? bf_hi(pk[c]) : bf_lo(pk[c]));
                    r[e] = fmaf(u, tanh_hw(u * fmaf(u * u, 8.f * 0.7978845608f * 0.044715f, 2.f * 0.7978845608f)), u);
                }
                stg1(gp1 + (c >> 1) * 256 + (c & 1) * 32, set_par(pack_bf16(r[0], r[1]), gm[c & 1][(c >> 1) & 3], tag));
            }
            named_bar(1 + wg, 128);
            if (w == 0 && lane == 0) {
                asm volatile("st.shared.u32 [%0], %1;" :: "r"(sb + SM_TG + 8 + wg * 4), "r"(clk32() + (wg ? XSPECB : XSPEC)) : "memory");
                mbar_arrive(BAR(B_GD + wg));
            }
            if (lead) mbar_expect(BAR(B_RF + warp), 1792);
            mbar_arrive_remote_if(pbar0 + (B_RE + wg) * 8, lead);
          } else mbar_wait(BAR(B_GD), 0);
            {
                int it = 0;
                while (__any_sync(~0u, ((tw ^ tag) | (rw[0].x ^ tag) | (rw[0].y ^ tag) | (rw[1].x ^ tag) | (rw[1].y ^ tag)) & 1)) {
                    if (++it > kSpinLimit) break;
                    load_rows();
                }
                uint32_t hw[14];
                #pragma unroll
                for (int c = 0; c < 14; c++) hw[c] = ld_rlx(hp + (c >> 1) * 256 + (c & 1) * 16);
                #pragma unroll
                for (int c = 0; c < 14; c++) {
                    ac[2 * c]     = fmaf(bf_lo(hw[c]), __uint_as_float(rw[c & 1].x), __uint_as_float(rw[c & 1].y));
                    ac[2 * c + 1] = fmaf(bf_hi(hw[c]), __uint_as_float(rw[c & 1].x), __uint_as_float(rw[c & 1].y));
                    as[2 * c] = as[2 * c + 1] = 0.f;
                }
                reg_fence(as); reg_fence(ac);
            }
        }
        uint32_t po[14], pk[14];
        if (!wg) sleep_until(clk32() + w * STAG2);
        send();
        #pragma unroll
        for (int c = 0; c < 14; c++) po[c] = opaque(pack_bf16(ac[2 * c], ac[2 * c + 1]));
        receive(pk, g1_on);
        #pragma unroll
        for (int c = 0; c < 14; c++) pk[c] = add_bf16x2(po[c], pk[c]);
        __syncwarp();
        const uint32_t sa = xch - lane * 16 + (lane & 15) * 112 + (lane >> 4) * 16;
        #pragma unroll
        for (int m = 0; m < 3; m++)
            asm volatile("stmatrix.sync.aligned.m8n8.x4.shared.b16 [%0], {%1,%2,%3,%4};"
                         :: "r"(sa + m * 32), "r"(pk[4 * m]), "r"(pk[4 * m + 1]), "r"(pk[4 * m + 2]), "r"(pk[4 * m + 3]) : "memory");
        asm volatile("stmatrix.sync.aligned.m8n8.x2.shared.b16 [%0], {%1,%2};" :: "r"(sa + 96), "r"(pk[12]), "r"(pk[13]) : "memory");
        __syncwarp();
        if (lane < 28) {
            #pragma unroll
            for (int i = 0; i < 4; i++) { const uint4 u = lds4(xch + i * 448); stg4(gp2 + i * 896, u.x, u.y, u.z, u.w); }
        }
        __syncwarp();
        mbar_arrive_remote_if(pbar0 + (B_RE + 2) * 8, lead && wg == 0);
        if (b == 0 && tid == 128) prm.sc->epoch = tag;
    }
}

typedef CUresult (*EncodeFn)(CUtensorMap*, CUtensorMapDataType, cuuint32_t, void*, const cuuint64_t*, const cuuint64_t*,
                             const cuuint32_t*, const cuuint32_t*, CUtensorMapInterleave, CUtensorMapSwizzle,
                             CUtensorMapL2promotion, CUtensorMapFloatOOBfill);

void make_map(EncodeFn enc, CUtensorMap* m, const void* base, uint64_t cols, uint64_t rows, uint32_t box_rows) {
    cuuint64_t dims[2] = {cols, rows};
    cuuint64_t strides[1] = {cols * 2};
    cuuint32_t box[2] = {64, box_rows};
    cuuint32_t es[2] = {1, 1};
    enc(m, CU_TENSOR_MAP_DATA_TYPE_BFLOAT16, 2, const_cast<void*>(base), dims, strides, box, es, CU_TENSOR_MAP_INTERLEAVE_NONE,
        CU_TENSOR_MAP_SWIZZLE_128B, CU_TENSOR_MAP_L2_PROMOTION_L2_128B, CU_TENSOR_MAP_FLOAT_OOB_FILL_NONE);
}

}

extern "C" void kernel_launch(void* const* d_in, const int* in_sizes, int n_in, void* d_out, int out_size) {
    (void)in_sizes; (void)n_in; (void)out_size;
    void* fn = nullptr;
    cudaDriverEntryPointQueryResult qr;
    cudaGetDriverEntryPoint("cuTensorMapEncodeTiled", &fn, cudaEnableDefault, &qr);
    EncodeFn enc = (EncodeFn)fn;
    CUtensorMap mX2, mX, mWqkv, mWo, mW1, mW2;
    {
        cuuint64_t dims[3] = {kD, kS / 2, 2}, strides[2] = {4 * kD, 2 * kD};
        cuuint32_t box[3] = {64, 64, 2}, es[3] = {1, 1, 1};
        enc(&mX2, CU_TENSOR_MAP_DATA_TYPE_BFLOAT16, 3, d_in[0], dims, strides, box, es, CU_TENSOR_MAP_INTERLEAVE_NONE,
            CU_TENSOR_MAP_SWIZZLE_128B, CU_TENSOR_MAP_L2_PROMOTION_L2_128B, CU_TENSOR_MAP_FLOAT_OOB_FILL_NONE);
    }
    make_map(enc, &mX, d_in[0], 2 * kD, kS / 2, 64);
    make_map(enc, &mWqkv, d_in[1], 3 * kD, kD, 64);
    make_map(enc, &mWo, d_in[2], kD, kD, 112);
    make_map(enc, &mW1, d_in[4], 2 * kF, kS / 2, 64);
    make_map(enc, &mW2, d_in[6], kS, kF, 64);
    Params prm;
    prm.x = (const __nv_bfloat16*)d_in[0];
    prm.wqkv = (const __nv_bfloat16*)d_in[1];
    prm.wo = (const __nv_bfloat16*)d_in[2];
    prm.w1 = (const __nv_bfloat16*)d_in[4];
    prm.b1 = (const __nv_bfloat16*)d_in[5];
    prm.w2 = (const __nv_bfloat16*)d_in[6];
    prm.b2 = (const __nv_bfloat16*)d_in[7];
    prm.out = (__nv_bfloat16*)d_out;
    cudaGetSymbolAddress((void**)&prm.sc, g_scratch);
    cudaFuncSetAttribute(fused_kernel, cudaFuncAttributeMaxDynamicSharedMemorySize, SM_TOTAL);
    fused_kernel<<<128, 384, SM_TOTAL, cudaStreamPerThread>>>(prm, mX2, mX, mWqkv, mWo, mW1, mW2);
}
```

```cpp
#include <cuda_runtime.h>
#include <cuda.h>
#include <cuda_bf16.h>
#include <stdint.h>
#include <type_traits>

namespace {

constexpr int kS = 2048, kD = 448, kF = 1792;
constexpr float kEps = 1e-5f;

constexpr int FS = 32;
constexpr int NPRE = 10;
constexpr int NR = 8;
constexpr int PFW = 4;
constexpr int QC0 = 4;
constexpr int QC1 = 10;
constexpr int QC2 = 16;
constexpr int PFD = 250;
constexpr int PFPACE = 280;
constexpr int PFPACE2 = 300;
constexpr int HDELAY = 200;
constexpr int WOD = 350;
constexpr int SDELAY = 200;
constexpr int PDELAY = 400;
constexpr int PACE1 = 120;
constexpr int PACE2 = 400;
constexpr int PACEB = 300;
constexpr int XSPEC = 500;
constexpr int XSPECB = 750;
constexpr int CN2 = 7300;
constexpr int CN3 = 11000;
constexpr int W2OFF = 800;
constexpr int W2PACE = 350;
constexpr int STAG2 = 550;
constexpr int QLNS = 256;
constexpr int DELTAO = 800;
constexpr int DMIN = 448;
constexpr int XDNS = 32;
constexpr int CHUNKNS = 250;
constexpr int DELTA = 2016;
constexpr int PLOFF = -250;
constexpr int PF3OFF = 300;
constexpr int PF3PACE = 240;

struct Scratch {
    uint32_t flag_o[16 * 8 * FS];
    uint4    o[32 * 56 * 64];
    uint32_t stats[32 * 8 * 4 * 32];
    uint4    hn[32 * 56 * 64];
    uint32_t flag_h[32 * 4 * FS];
    uint4    g[28 * 56 * 64];
    uint4    halo[8 * 8 * 2 * 4 * 32];
    uint2    rows[32 * 64];
    uint32_t epoch;
};
__device__ __align__(1024) Scratch g_scratch;

constexpr uint32_t SM_WKV  = 114688;
constexpr uint32_t SM_XR   = 24576;
constexpr uint32_t SM_STG  = 40960;
constexpr uint32_t SM_WQ   = 57344;
constexpr uint32_t SM_XCH  = 0;
constexpr uint32_t SM_B    = 131072;
constexpr uint32_t SM_BAR  = 231424;
constexpr uint32_t SM_TOTAL = SM_BAR + 1024;
constexpr int NB = 7;
constexpr int B_XF = 0, B_WKVF = 7, B_WQF = 14, B_XRF = 15, B_WOF = 16,
              B_XC = 18, B_KV3 = 19, B_KVC = 20,
              B_A1D = 21, B_XD = 22, B_OC = 23, B_QL = 24,
              B_BE = 25  , B_RE = B_BE + 2 * NB,
              B_PL = B_RE + 3, B_AF = B_PL + 1, B_BL = B_AF + 1  , B_OL = B_BL + 2 * NB  ,
              B_BF = B_OL + 4  , B_OF = B_BF + NB, B_RF = B_OF + 4, B_EP = B_RF + 8, B_PD = B_EP + 1, B_OD = B_PD + 1, B_RT = B_OD + 1, B_HL = B_RT + 2,
              B_HD = B_HL + 2  , B_GO = B_HD + 1, B_GD = B_GO + 1, B_COUNT = B_GD + 2;
constexpr uint32_t SM_EPOCH = SM_BAR + B_COUNT * 8, SM_TG = SM_EPOCH + 4  , SM_TG2 = SM_TG + 16  ,
                   SM_ORD = SM_TG2 + 4  ;

constexpr uint64_t kAPos = 0x3330ull | 0x5555555ull << 17;
constexpr uint32_t seg_mask(int h, int p0, int p1) {
    uint32_t m = 0; int n = 0;
    for (int p = p0; p < p1; p++) if ((p & 1) == h) m |= (uint32_t)((kAPos >> p) & 1) << n++;
    return m | 1u << n;
}
constexpr uint64_t seg_masks(int h) {
    return 2 | (uint64_t)seg_mask(h, 0, 16) << 10 | (uint64_t)seg_mask(h, 16, 32) << 20
             | (uint64_t)seg_mask(h, 32, 46) << 30 | (uint64_t)seg_mask(h, 46, 60) << 40;
}
constexpr uint64_t kSegMasks0 = seg_masks(0), kSegMasks1 = seg_masks(1);

constexpr int kSpinLimit = 1 << 15;
__device__ __forceinline__ bool elect_one() {
    uint32_t p;
    asm volatile("{ .reg .pred P; elect.sync _|P, 0xffffffff; selp.u32 %0, 1, 0, P; }" : "=r"(p));
    return p;
}
__device__ __forceinline__ void mbar_init(uint32_t bar, uint32_t cnt) { asm volatile("mbarrier.init.shared::cta.b64 [%0], %1;" :: "r"(bar), "r"(cnt)); }
__device__ __forceinline__ void mbar_expect(uint32_t bar, uint32_t bytes) { asm volatile("mbarrier.arrive.expect_tx.shared::cta.b64 _, [%0], %1;" :: "r"(bar), "r"(bytes) : "memory"); }
__device__ __forceinline__ void mbar_expect_more(uint32_t bar, uint32_t bytes) { asm volatile("mbarrier.expect_tx.relaxed.cta.shared::cta.b64 [%0], %1;" :: "r"(bar), "r"(bytes) : "memory"); }
__device__ __forceinline__ void mbar_arrive(uint32_t bar) { asm volatile("mbarrier.arrive.shared::cta.b64 _, [%0];" :: "r"(bar) : "memory"); }
__device__ __forceinline__ void mbar_wait(uint32_t bar, uint32_t parity) {
    uint32_t ok; int it = 0;
    do {
        asm volatile("{ .reg .pred p; mbarrier.try_wait.parity.shared::cta.b64 p, [%1], %2; selp.u32 %0, 1, 0, p; }"
                     : "=r"(ok) : "r"(bar), "r"(parity) : "memory");
        if (++it > kSpinLimit) break;
    } while (!ok);
}
__device__ __forceinline__ bool mbar_try(uint32_t bar, uint32_t parity) {
    uint32_t ok;
    asm volatile("{ .reg .pred p; mbarrier.try_wait.parity.shared::cta.b64 p, [%1], %2; selp.u32 %0, 1, 0, p; }" : "=r"(ok) : "r"(bar), "r"(parity) : "memory");
    return ok;
}
__device__ __forceinline__ bool mbar_test(uint32_t bar, uint32_t parity) {
    uint32_t ok;
    asm volatile("{ .reg .pred p; mbarrier.test_wait.parity.shared::cta.b64 p, [%1], %2; selp.u32 %0, 1, 0, p; }" : "=r"(ok) : "r"(bar), "r"(parity) : "memory");
    return ok;
}
__device__ __forceinline__ void mbar_wait_fast(uint32_t bar, uint32_t parity) { if (!mbar_try(bar, parity)) mbar_wait(bar, parity); }
__device__ __forceinline__ void mbar_wait2(uint32_t bar0, uint32_t par0, uint32_t bar1, uint32_t par1) {
    uint32_t ok; int it = 0;
    do {
        asm volatile("{ .reg .pred p, q; mbarrier.try_wait.parity.shared::cta.b64 p, [%1], %2;\n"
                     "mbarrier.try_wait.parity.shared::cta.b64 q, [%3], %4; and.pred p, p, q; selp.u32 %0, 1, 0, p; }"
                     : "=r"(ok) : "r"(bar0), "r"(par0), "r"(bar1), "r"(par1) : "memory");
        if (++it > kSpinLimit) break;
    } while (!ok);
}
template <int N> __device__ __forceinline__ void reg_fence(float (&d)[N]) {
    #pragma unroll
    for (int i = 0; i < N; i++) asm volatile("" : "+f"(d[i]) :: "memory");
}
__device__ __forceinline__ void mbar_arrive_if(uint32_t bar, bool pred) {
    asm volatile("{ .reg .pred p; setp.ne.u32 p, %1, 0; @p mbarrier.arrive.shared::cta.b64 _, [%0]; }" :: "r"(bar), "r"((uint32_t)pred) : "memory");
}
__device__ __forceinline__ void warp_arrive(uint32_t bar) { __syncwarp(); if (elect_one()) mbar_arrive(bar); }
__device__ __forceinline__ void tma2d(uint32_t dst, const CUtensorMap* m, int c0, int c1, uint32_t bar) {
    asm volatile("cp.async.bulk.tensor.2d.shared::cluster.global.mbarrier::complete_tx::bytes [%0], [%1, {%3, %4}], [%2];"
                 :: "r"(dst), "l"(m), "r"(bar), "r"(c0), "r"(c1) : "memory");
}
__device__ __forceinline__ void tma3d(uint32_t dst, const CUtensorMap* m, int c0, int c1, int c2, uint32_t bar) {
    asm volatile("cp.async.bulk.tensor.3d.shared::cluster.global.mbarrier::complete_tx::bytes [%0], [%1, {%3, %4, %5}], [%2];"
                 :: "r"(dst), "l"(m), "r"(bar), "r"(c0), "r"(c1), "r"(c2) : "memory");
}
__device__ __forceinline__ void tma2d_mc(uint32_t dst, const CUtensorMap* m, int c0, int c1, uint32_t bar) {
    asm volatile("cp.async.bulk.tensor.2d.shared::cluster.global.mbarrier::complete_tx::bytes.multicast::cluster [%0], [%1, {%3, %4}], [%2], %5;"
                 :: "r"(dst), "l"(m), "r"(bar), "r"(c0), "r"(c1), "h"((uint16_t)3) : "memory");
}
__device__ __forceinline__ void mbar_arrive_remote_if(uint32_t cluster_bar, bool pred) {
    asm volatile("{ .reg .pred p; setp.ne.u32 p, %1, 0; @p mbarrier.arrive.shared::cluster.b64 _, [%0]; }" :: "r"(cluster_bar), "r"((uint32_t)pred) : "memory");
}
__device__ __forceinline__ void bulk_g2s(uint32_t dst, const void* src, uint32_t bytes, uint32_t bar) {
    asm volatile("cp.async.bulk.shared::cluster.global.mbarrier::complete_tx::bytes [%0], [%1], %2, [%3];"
                 :: "r"(dst), "l"(src), "r"(bytes), "r"(bar) : "memory");
}
__device__ __forceinline__ void bulk_prefetch(const void* src, uint32_t bytes) { asm volatile("cp.async.bulk.prefetch.L2.global [%0], %1;" :: "l"(src), "r"(bytes) : "memory"); }
__device__ __forceinline__ void wg_fence()  { asm volatile("wgmma.fence.sync.aligned;" ::: "memory"); }
__device__ __forceinline__ void wg_commit() { asm volatile("wgmma.commit_group.sync.aligned;" ::: "memory"); }
template <int N> __device__ __forceinline__ void wg_wait() { asm volatile("wgmma.wait_group.sync.aligned %0;" :: "n"(N) : "memory"); }
__device__ __forceinline__ void named_bar(int id, int n) { asm volatile("bar.sync %0, %1;" :: "r"(id), "r"(n) : "memory"); }
__device__ __forceinline__ void named_arrive(int id, int n) { asm volatile("bar.arrive %0, %1;" :: "r"(id), "r"(n) : "memory"); }
__device__ __forceinline__ void fence_async_smem() { asm volatile("fence.proxy.async.shared::cta;" ::: "memory"); }
__device__ __forceinline__ uint32_t gtime32() { uint64_t t; asm volatile("mov.u64 %0, %%globaltimer;" : "=l"(t) :: "memory"); return (uint32_t)t; }
__device__ __forceinline__ uint32_t clk32() { uint64_t t; asm volatile("mov.u64 %0, %%clock64;" : "=l"(t) :: "memory"); return (uint32_t)t; }
__device__ __forceinline__ void spin_until(uint32_t t) { while ((int)(clk32() - t) < 0) {} }
__device__ __forceinline__ void sleep_until(uint32_t t) { while ((int)(clk32() - t) < 0) __nanosleep(20); }
__device__ __forceinline__ void st_flag(uint32_t* p, uint32_t v, uint32_t time) {
    const uint64_t w = ((uint64_t)time << 32) | v;
    asm volatile("st.relaxed.gpu.global.u64 [%0], %1;" :: "l"(p), "l"(w) : "memory");
}
__device__ __forceinline__ void ld_flag_if(uint64_t& v, const uint32_t* p, bool pred) {
    asm volatile("{ .reg .pred p; setp.ne.u32 p, %2, 0; @p ld.relaxed.gpu.global.u64 %0, [%1]; }" : "+l"(v) : "l"(p), "r"((uint32_t)pred) : "memory");
}
__device__ __forceinline__ uint32_t ld_rlx(const uint32_t* p) { uint32_t v; asm volatile("ld.relaxed.gpu.global.u32 %0, [%1];" : "=r"(v) : "l"(p) : "memory"); return v; }
template <class T> __device__ __forceinline__ T* opaque_ptr(T* p) { asm volatile("" : "+l"(p)); return p; }
__device__ __forceinline__ uint4 ld_rlx4(const uint4* p) {
    uint4 v; asm volatile("ld.relaxed.gpu.global.v4.u32 {%0,%1,%2,%3}, [%4];" : "=r"(v.x), "=r"(v.y), "=r"(v.z), "=r"(v.w) : "l"(p) : "memory"); return v;
}
__device__ __forceinline__ uint2 ld_rlx2(const uint2* p) {
    uint2 v; asm volatile("ld.relaxed.gpu.global.v2.u32 {%0,%1}, [%2];" : "=r"(v.x), "=r"(v.y) : "l"(p) : "memory"); return v;
}
__device__ __forceinline__ void stg1(uint32_t* p, uint32_t v) { asm volatile("st.global.u32 [%0], %1;" :: "l"(p), "r"(v) : "memory"); }
__device__ __forceinline__ void stg4(void* p, uint32_t x, uint32_t y, uint32_t z, uint32_t w) { asm volatile("st.global.v4.u32 [%0], {%1,%2,%3,%4};" :: "l"(p), "r"(x), "r"(y), "r"(z), "r"(w) : "memory"); }
__device__ __forceinline__ uint32_t lds1(uint32_t a) { uint32_t v; asm volatile("ld.shared.u32 %0, [%1];" : "=r"(v) : "r"(a) : "memory"); return v; }
__device__ __forceinline__ uint2 lds2(uint32_t a) { uint2 v; asm volatile("ld.shared.v2.u32 {%0,%1}, [%2];" : "=r"(v.x), "=r"(v.y) : "r"(a) : "memory"); return v; }
__device__ __forceinline__ uint32_t set_par(uint32_t v, uint32_t mask, uint32_t par) {
    uint32_t r; asm("lop3.b32 %0, %1, %2, %3, 0xb8;" : "=r"(r) : "r"(v), "r"(mask), "r"(par)); return r;
}
__device__ __forceinline__ void st_gen4(void* p, uint32_t x, uint32_t y, uint32_t z, uint32_t w) { asm volatile("st.v4.u32 [%0], {%1,%2,%3,%4};" :: "l"(p), "r"(x), "r"(y), "r"(z), "r"(w) : "memory"); }
__device__ __forceinline__ float tanh_hw(float x) { float r; asm("tanh.approx.f32 %0, %1;" : "=f"(r) : "f"(x)); return r; }
__device__ __forceinline__ void sts4(uint32_t a, uint32_t x, uint32_t y, uint32_t z, uint32_t w) { asm volatile("st.shared.v4.u32 [%0], {%1,%2,%3,%4};" :: "r"(a), "r"(x), "r"(y), "r"(z), "r"(w) : "memory"); }
__device__ __forceinline__ uint4 lds4(uint32_t a) { uint4 v; asm volatile("ld.shared.v4.u32 {%0,%1,%2,%3}, [%4];" : "=r"(v.x), "=r"(v.y), "=r"(v.z), "=r"(v.w) : "r"(a) : "memory"); return v; }
__device__ __forceinline__ uint32_t pack_bf16(float lo, float hi) { uint32_t r; asm("cvt.rn.bf16x2.f32 %0, %1, %2;" : "=r"(r) : "f"(hi), "f"(lo)); return r; }
__device__ __forceinline__ float bf_lo(uint32_t v) { return __uint_as_float(v << 16); }
__device__ __forceinline__ float bf_hi(uint32_t v) { return __uint_as_float(v & 0xffff0000u); }
__device__ __forceinline__ uint32_t sub_bf16x2(uint32_t a, uint32_t b) { uint32_t r; asm volatile("sub.rn.bf16x2 %0, %1, %2;" : "=r"(r) : "r"(a), "r"(b)); return r; }
__device__ __forceinline__ uint32_t add_bf16x2(uint32_t a, uint32_t b) { uint32_t r; asm volatile("add.rn.bf16x2 %0, %1, %2;" : "=r"(r) : "r"(a), "r"(b)); return r; }
__device__ __forceinline__ uint32_t sqr_bf16x2(uint32_t a) { uint32_t r; asm volatile("mul.rn.bf16x2 %0, %1, %1;" : "=r"(r) : "r"(a)); return r; }
__device__ __forceinline__ uint32_t sqa_bf16x2(uint32_t a, uint32_t c) { uint32_t r; asm volatile("fma.rn.bf16x2 %0, %1, %1, %2;" : "=r"(r) : "r"(a), "r"(c)); return r; }
__device__ __forceinline__ uint32_t movm(uint32_t a) { uint32_t r; asm volatile("movmatrix.sync.aligned.m8n8.trans.b16 %0, %1;" : "=r"(r) : "r"(a)); return r; }
__device__ __forceinline__ float ex2(float x) { float r; asm("ex2.approx.ftz.f32 %0, %1;" : "=f"(r) : "f"(x)); return r; }
__device__ __forceinline__ float rsq(float x) { float r; asm("rsqrt.approx.ftz.f32 %0, %1;" : "=f"(r) : "f"(x)); return r; }
__device__ __forceinline__ float rcp(float x) { float r; asm("rcp.approx.ftz.f32 %0, %1;" : "=f"(r) : "f"(x)); return r; }
__device__ __forceinline__ void mma16816(float (&c)[4], uint32_t a0, uint32_t a1, uint32_t a2, uint32_t a3, uint32_t b0, uint32_t b1) {
    asm("mma.sync.aligned.m16n8k16.row.col.f32.bf16.bf16.f32 {%0,%1,%2,%3}, {%4,%5,%6,%7}, {%8,%9}, {%0,%1,%2,%3};"
        : "+f"(c[0]), "+f"(c[1]), "+f"(c[2]), "+f"(c[3]) : "r"(a0), "r"(a1), "r"(a2), "r"(a3), "r"(b0), "r"(b1));
}
__device__ __forceinline__ void mma1688(float (&c)[4], uint32_t a0, uint32_t a1, uint32_t b0) {
    asm("mma.sync.aligned.m16n8k8.row.col.f32.bf16.bf16.f32 {%0,%1,%2,%3}, {%4,%5}, {%6}, {%0,%1,%2,%3};"
        : "+f"(c[0]), "+f"(c[1]), "+f"(c[2]), "+f"(c[3]) : "r"(a0), "r"(a1), "r"(b0));
}
__device__ __forceinline__ float quad_sum(float v) { v += __shfl_xor_sync(~0u, v, 1); v += __shfl_xor_sync(~0u, v, 2); return v; }
__device__ __forceinline__ float quad_max(float v) { v = fmaxf(v, __shfl_xor_sync(~0u, v, 1)); v = fmaxf(v, __shfl_xor_sync(~0u, v, 2)); return v; }
__device__ __forceinline__ uint64_t make_desc(uint32_t addr, uint32_t lbo, bool swz, uint32_t sbo = 1024) {
    const uint32_t lo = __shfl_sync(~0u, ((addr & 0x3FFFF) >> 4) | ((lbo >> 4) << 16), 0);
    const uint32_t hi = __shfl_sync(~0u, (swz ? 0x40000000u : 0u) + (sbo >> 4) + (threadIdx.x & 31), 0);
    return ((uint64_t)hi << 32) | lo;
}
template <int I, int N, class F> __device__ __forceinline__ void static_for(F&& f) {
    if constexpr (I < N) { f(std::integral_constant<int, I>{}); static_for<I + 1, N>(f); }
}
__device__ __forceinline__ uint32_t opaque(uint32_t v) { asm volatile("" : "+r"(v)); return v; }
template <int BOFF, int SCALE_D>
__device__ __forceinline__ void wgmma_rs_n56(float (&d)[28], uint32_t a0, uint32_t a1, uint32_t a2, uint32_t a3, uint64_t db) {
    asm volatile("{ .reg .b64 db; add.s64 db, %32, %33;\n"
        "wgmma.mma_async.sync.aligned.m64n56k16.f32.bf16.bf16 "
        "{%0, %1, %2, %3, %4, %5, %6, %7, %8, %9, %10, %11, %12, %13, %14, %15, %16, %17, %18, %19, %20, %21, %22, %23, %24, %25, %26, %27}, "
        "{%28, %29, %30, %31}, db, %34, 1, 1, 1; }"
        : "+f"(d[0]), "+f"(d[1]), "+f"(d[2]), "+f"(d[3]), "+f"(d[4]), "+f"(d[5]), "+f"(d[6]), "+f"(d[7]),
        "+f"(d[8]), "+f"(d[9]), "+f"(d[10]), "+f"(d[11]), "+f"(d[12]), "+f"(d[13]), "+f"(d[14]), "+f"(d[15]),
        "+f"(d[16]), "+f"(d[17]), "+f"(d[18]), "+f"(d[19]), "+f"(d[20]), "+f"(d[21]), "+f"(d[22]), "+f"(d[23]),
        "+f"(d[24]), "+f"(d[25]), "+f"(d[26]), "+f"(d[27])
        : "r"(a0), "r"(a1), "r"(a2), "r"(a3), "l"(db), "n"(BOFF >> 4), "n"(SCALE_D));
}
template <int AOFF, int BOFF, int MMAJOR>
__device__ __forceinline__ void wgmma_ss_n56(float (&d)[28], uint64_t da, uint64_t db) {
    asm volatile("{ .reg .b64 da, db; add.s64 da, %28, %30; add.s64 db, %29, %31;\n"
        "wgmma.mma_async.sync.aligned.m64n56k16.f32.bf16.bf16 "
        "{%0, %1, %2, %3, %4, %5, %6, %7, %8, %9, %10, %11, %12, %13, %14, %15, %16, %17, %18, %19, %20, %21, %22, %23, %24, %25, %26, %27}, "
        "da, db, 1, 1, 1, %32, 1; }"
        : "+f"(d[0]), "+f"(d[1]), "+f"(d[2]), "+f"(d[3]), "+f"(d[4]), "+f"(d[5]), "+f"(d[6]), "+f"(d[7]),
        "+f"(d[8]), "+f"(d[9]), "+f"(d[10]), "+f"(d[11]), "+f"(d[12]), "+f"(d[13]), "+f"(d[14]), "+f"(d[15]),
        "+f"(d[16]), "+f"(d[17]), "+f"(d[18]), "+f"(d[19]), "+f"(d[20]), "+f"(d[21]), "+f"(d[22]), "+f"(d[23]),
        "+f"(d[24]), "+f"(d[25]), "+f"(d[26]), "+f"(d[27])
        : "l"(da), "l"(db), "n"(AOFF >> 4), "n"(BOFF >> 4), "n"(MMAJOR));
}
template <int AOFF, int BOFF, int MMAJOR>
__device__ __forceinline__ void wgmma_ss_n112(float (&d)[28], float (&e)[28], uint64_t da, uint64_t db) {
    asm volatile("{ .reg .b64 da, db; add.s64 da, %56, %58; add.s64 db, %57, %59;\n"
        "wgmma.mma_async.sync.aligned.m64n112k16.f32.bf16.bf16 "
        "{%0, %1, %2, %3, %4, %5, %6, %7, %8, %9, %10, %11, %12, %13, %14, %15, %16, %17, %18, %19, %20, %21, %22, %23, %24, %25, %26, %27, %28, %29, %30, %31, %32, %33, %34, %35, %36, %37, %38, %39, %40, %41, %42, %43, %44, %45, %46, %47, %48, %49, %50, %51, %52, %53, %54, %55}, "
        "da, db, 1, 1, 1, %60, 1; }"
        : "+f"(d[0]), "+f"(d[1]), "+f"(d[2]), "+f"(d[3]), "+f"(d[4]), "+f"(d[5]), "+f"(d[6]), "+f"(d[7]),
        "+f"(d[8]), "+f"(d[9]), "+f"(d[10]), "+f"(d[11]), "+f"(d[12]), "+f"(d[13]), "+f"(d[14]), "+f"(d[15]),
        "+f"(d[16]), "+f"(d[17]), "+f"(d[18]), "+f"(d[19]), "+f"(d[20]), "+f"(d[21]), "+f"(d[22]), "+f"(d[23]),
        "+f"(d[24]), "+f"(d[25]), "+f"(d[26]), "+f"(d[27]), "+f"(e[0]), "+f"(e[1]), "+f"(e[2]), "+f"(e[3]),
        "+f"(e[4]), "+f"(e[5]), "+f"(e[6]), "+f"(e[7]), "+f"(e[8]), "+f"(e[9]), "+f"(e[10]), "+f"(e[11]),
        "+f"(e[12]), "+f"(e[13]), "+f"(e[14]), "+f"(e[15]), "+f"(e[16]), "+f"(e[17]), "+f"(e[18]), "+f"(e[19]),
        "+f"(e[20]), "+f"(e[21]), "+f"(e[22]), "+f"(e[23]), "+f"(e[24]), "+f"(e[25]), "+f"(e[26]), "+f"(e[27])
        : "l"(da), "l"(db), "n"(AOFF >> 4), "n"(BOFF >> 4), "n"(MMAJOR));
}
template <int BOFF, int SCALE_D>
__device__ __forceinline__ void wgmma_rs_n112(float (&d)[28], float (&e)[28], uint32_t a0, uint32_t a1, uint32_t a2, uint32_t a3, uint64_t db) {
    asm volatile("{ .reg .b64 db; add.s64 db, %60, %61;\n"
        "wgmma.mma_async.sync.aligned.m64n112k16.f32.bf16.bf16 "
        "{%0, %1, %2, %3, %4, %5, %6, %7, %8, %9, %10, %11, %12, %13, %14, %15, %16, %17, %18, %19, %20, %21, %22, %23, %24, %25, %26, %27, %28, %29, %30, %31, %32, %33, %34, %35, %36, %37, %38, %39, %40, %41, %42, %43, %44, %45, %46, %47, %48, %49, %50, %51, %52, %53, %54, %55}, "
        "{%56, %57, %58, %59}, db, %62, 1, 1, 1; }"
        : "+f"(d[0]), "+f"(d[1]), "+f"(d[2]), "+f"(d[3]), "+f"(d[4]), "+f"(d[5]), "+f"(d[6]), "+f"(d[7]),
        "+f"(d[8]), "+f"(d[9]), "+f"(d[10]), "+f"(d[11]), "+f"(d[12]), "+f"(d[13]), "+f"(d[14]), "+f"(d[15]),
        "+f"(d[16]), "+f"(d[17]), "+f"(d[18]), "+f"(d[19]), "+f"(d[20]), "+f"(d[21]), "+f"(d[22]), "+f"(d[23]),
        "+f"(d[24]), "+f"(d[25]), "+f"(d[26]), "+f"(d[27]), "+f"(e[0]), "+f"(e[1]), "+f"(e[2]), "+f"(e[3]),
        "+f"(e[4]), "+f"(e[5]), "+f"(e[6]), "+f"(e[7]), "+f"(e[8]), "+f"(e[9]), "+f"(e[10]), "+f"(e[11]),
        "+f"(e[12]), "+f"(e[13]), "+f"(e[14]), "+f"(e[15]), "+f"(e[16]), "+f"(e[17]), "+f"(e[18]), "+f"(e[19]),
        "+f"(e[20]), "+f"(e[21]), "+f"(e[22]), "+f"(e[23]), "+f"(e[24]), "+f"(e[25]), "+f"(e[26]), "+f"(e[27])
        : "r"(a0), "r"(a1), "r"(a2), "r"(a3), "l"(db), "n"(BOFF >> 4), "n"(SCALE_D));
}

struct Params {
    const __nv_bfloat16 *x, *wqkv;
    Scratch* sc;
    const __nv_bfloat16 *wo, *w1, *w2, *b1, *b2;
    __nv_bfloat16* out;
};

__global__ void __cluster_dims__(2, 1, 1) __launch_bounds__(384, 1)
fused_kernel(const Params prm, const __grid_constant__ CUtensorMap mX2, const __grid_constant__ CUtensorMap mX, const __grid_constant__ CUtensorMap mWqkv,
             const __grid_constant__ CUtensorMap mWo, const __grid_constant__ CUtensorMap mW1,
             const __grid_constant__ CUtensorMap mW2)
{
    extern __shared__ __align__(1024) unsigned char smem_raw[];
    if (threadIdx.x < 126) {
        const uint32_t i = threadIdx.x, t = clk32() + (i >> 5) * PFD;
        const char* px = (const char*)prm.x + (blockIdx.x * 16 + (i & 15)) * 896 + (i >> 4) * 128;
        const char* pw = (const char*)prm.wqkv + blockIdx.x * 2688 + i * 128 + (896 - 112 * 128);
        spin_until(t);
        asm volatile("prefetch.global.L2 [%0];" :: "l"(i < 112 ? px : pw) : "memory");
    }
    if (threadIdx.x == 128) { asm volatile("prefetch.tensormap [%0];" :: "l"(&mX2) : "memory"); asm volatile("prefetch.tensormap [%0];" :: "l"(&mWqkv) : "memory"); }
    uint32_t sb = (uint32_t)__cvta_generic_to_shared(smem_raw);
    asm volatile("mov.u32 %0, %0;" : "+r"(sb));
    const uint32_t bar0 = sb + SM_BAR;
    auto BAR = [&](int i) { return bar0 + 8u * i; };

    const int tid = threadIdx.x, lane = tid & 31;
    const int warp = __shfl_sync(~0u, tid >> 5, 0);
    const int b = __shfl_sync(~0u, (int)blockIdx.x, 0);
    const int rank = b & 1;
    const int cl = (b >> 1) - 4, cq = ((cl - 32) * 37) >> 8;
    const int res = cl < 0 ? 0 : cl < 32 ? cl & 7 : cl - 31 - 7 * cq;
    const int rnd = cl < 0 ? cl + 8 : cl < 32 ? cl >> 3 : 4 + cq;
    const int hg = (res & 1) * 4 + (rnd & 3);
    const int ti = (res >> 1) * 4 + (rnd >> 2) * 2 + rank;
    const int a2p = res & 1, a2j = rnd & 3;
    const int a2s = ti * 2 + a2p;
    const bool g1_on = rnd != 7;
    const int g1j = (rnd < 6 ? rnd : res) & 1, g1f = rnd < 6 ? res * 3 + (rnd >> 1) : 24 + (res >> 1);
    const int g2j = rnd & 1, g2s = res * 4 + (rnd >> 1);
    uint32_t pbar0;
    asm volatile("mapa.shared::cluster.u32 %0, %1, %2;" : "=r"(pbar0) : "r"(bar0), "r"(rank ^ 1));
    auto pair_arrive = [&](int i) { __syncwarp(); const bool l = elect_one(); mbar_arrive_if(BAR(i), l); mbar_arrive_remote_if(pbar0 + 8u * i, l); };
    const int wcol = hg * 56 - (hg & 1) * 8;

    if (warp == 8) {
        if (elect_one()) {
            #pragma unroll
            for (int i = 0; i < B_WQF; i++) mbar_init(BAR(i), 1);
            asm volatile("fence.mbarrier_init.release.cluster;" ::: "memory");
            fence_async_smem();
            #pragma unroll
            for (int kb = 0; kb < 7; kb++) {
                tma3d(sb + kb * 16384, &mX2, kb * 64, ti * 64, 0, BAR(B_XF + kb));
                mbar_expect(BAR(B_XF + kb), 16384);
            }
        }
    } else if (warp > 8) {
        if (elect_one()) {
            if (warp == 9) {
                #pragma unroll
                for (int i = B_WQF; i < B_AF; i++) mbar_init(BAR(i), i < B_XC ? 1 : i < B_A1D ? 16 : i < B_BE ? 8 : 4);
            } else if (warp == 10) {
                #pragma unroll
                for (int i = B_AF; i < B_BF; i++) mbar_init(BAR(i), 1);
            } else {
                #pragma unroll
                for (int i = B_BF; i < B_COUNT; i++) mbar_init(BAR(i), i == B_HD ? 8 : 1);
            }
            asm volatile("fence.mbarrier_init.release.cluster;" ::: "memory");
            fence_async_smem();
        }
    }
    __syncwarp();
    __syncthreads();
    asm volatile("barrier.cluster.arrive.relaxed.aligned;" ::: "memory");

    if (warp >= 8) {
        asm volatile("setmaxnreg.dec.sync.aligned.u32 40;");
        asm volatile("barrier.cluster.wait.aligned;" ::: "memory");
        auto fetch_halo = [&](int p, uint32_t tag) {
            const uint32_t hl = BAR(B_HL + p), dst = opaque(sb + SM_STG + p * 8192 + 3 * 2048 + lane * 16);
            const bool lead = elect_one();
            if (rank) { if (lead) mbar_expect(hl, 2048); __syncwarp(); return; }
            const uint4* hp = opaque_ptr(&prm.sc->halo[((((ti >> 1) - 1) * 8 + hg) * 2 + p) * 128 + lane]);
            mbar_wait(BAR(B_KVC), 0);
            if (ti > 0) {
                spin_until(clk32() + HDELAY);
                int it = 0;
                uint32_t bad;
                do {
                    uint4 u[4];
                    #pragma unroll
                    for (int c = 0; c < 4; c++) u[c] = ld_rlx4(hp + c * 32);
                    #pragma unroll
                    for (int c = 0; c < 4; c++) sts4(dst + c * 512, u[c].x, u[c].y, u[c].z, u[c].w);
                    bad = ((u[0].x ^ tag) | (u[1].x ^ tag) | (u[2].x ^ tag) | (u[3].x ^ tag)) & ~lane & 1;
                } while (__any_sync(~0u, bad) && ++it < kSpinLimit);
            } else {
                #pragma unroll
                for (int c = 0; c < 4; c++) sts4(dst + c * 512, 0u, 0u, 0u, 0u);
            }
            __syncwarp();
            mbar_arrive_if(hl, lead);
        };
        auto poll_flags = [&](const uint32_t* fp, int step, uint32_t tag, uint32_t gbase) {
            uint64_t v0 = 0, v1 = 0;
            int it = 0;
            do {
                ld_flag_if(v0, fp, (uint32_t)v0 != tag); ld_flag_if(v1, fp + step, (uint32_t)v1 != tag);
                if (++it > kSpinLimit) break;
            } while (__any_sync(~0u, (uint32_t)v0 != tag || (uint32_t)v1 != tag));
            return max((int)((uint32_t)(v0 >> 32) - gbase), (int)((uint32_t)(v1 >> 32) - gbase));
        };
        if (warp & 1) {
            uint32_t tag;
            if (warp == 11) {
                tag = *(volatile uint32_t*)&prm.sc->epoch + 1;
                #pragma unroll 1
                for (int i = 0; i < 8 * rank; i++) prm.sc->halo[((ti >> 1) * 8 + hg) * 256 + i * 32 + lane] = make_uint4(~tag, 0u, 0u, 0u);
                ((uint4*)prm.sc->stats)[(a2s * 4 + a2j) * 64 + lane] = ((uint4*)prm.sc->stats)[(a2s * 4 + a2j) * 64 + 32 + lane] = make_uint4(~tag, ~tag, ~tag, ~tag);
                prm.sc->flag_h[(a2s * 4 + a2j) * FS + lane] = 0;
                prm.sc->flag_o[(ti * 8 + hg) * FS + lane] = 0;
                __syncwarp();
                if (lane == 0) {
                    asm volatile("st.shared.v2.u32 [%0], {%1, %2};" :: "r"(sb + SM_EPOCH), "r"(tag), "r"(gtime32()) : "memory");
                    mbar_arrive(BAR(B_EP));
                }
                if (lane < 8) mbar_expect(BAR(B_RF + lane), 1792);
                __syncwarp();
            } else {
                mbar_wait(BAR(B_EP), 0);
                tag = lds1(sb + SM_EPOCH);
            }
            fetch_halo((warp >> 1) & 1, tag);
        }
        if (warp < 10) {
          auto load_slab = [&](int s, bool second) {
              if (!second) tma2d(sb + s * 8192, &mW1, (s & 1) * kF + g1f * 64, (rank * 8 + (s >> 1)) * 64, BAR(B_AF));
              else         tma2d(sb + s * 8192, &mW2, g2s * 64, (rank * 14 + s - 1) * 64, BAR(B_AF));
          };
          const char* pw2 = (const char*)prm.w2 + ((b >> 6) * 896 + (b & 63) + PFW * 64) * 4096;
          if (warp == 8) {
            if (elect_one()) {
                #pragma unroll 1
                for (int s = 0; s < 7; s++) {
                    mbar_expect(BAR(B_WKVF + s), 16384);
                    tma2d_mc(sb + SM_WKV + s * 16384 + rank * 8192, &mWqkv, (1 + rank) * kD + wcol, s * 64, BAR(B_WKVF + s));
                }
            }
            __syncwarp();
            mbar_wait(BAR(B_XC), 0);
            if (elect_one()) {
                asm volatile("prefetch.tensormap [%0];" :: "l"(&mX) : "memory");
                asm volatile("prefetch.tensormap [%0];" :: "l"(&mWo) : "memory");
                asm volatile("prefetch.tensormap [%0];" :: "l"(&mW1) : "memory");
                asm volatile("prefetch.tensormap [%0];" :: "l"(&mW2) : "memory");
                mbar_expect(BAR(B_AF), (g1_on ? NPRE : 14) * 8192);
                mbar_expect(BAR(B_WQF), 57344);
                #pragma unroll 1
                for (int s = rank; s < 7; s += 2) tma2d_mc(sb + SM_WQ + s * 8192, &mWqkv, wcol, s * 64, BAR(B_WQF));
                mbar_expect(BAR(B_XRF), 16384);
                tma2d(sb + SM_XR, &mX, a2p * kD + a2j * 112, ti * 64, BAR(B_XRF));
                tma2d(sb + SM_XR + 8192, &mX, a2p * kD + a2j * 112 + 48, ti * 64, BAR(B_XRF));
            }
            __syncwarp();
            #pragma unroll 1
            for (int q = 0; q < 4; q++) {
                mbar_wait(BAR(B_KV3 + (q >> 1)), 0);
                if (q == 2) spin_until(clk32() + WOD);
                if (q == 3) mbar_wait2(BAR(B_HL), 0, BAR(B_HL + 1), 0);
                if (elect_one()) {
                    if (!(q & 1)) mbar_expect(BAR(B_WOF + (q >> 1)), 57344);
                    tma2d_mc(sb + SM_WKV + q * 28672 + rank * 14336, &mWo, a2j * 112 + (q & 1) * 48, (q >> 1) * 224 + rank * 112, BAR(B_WOF + (q >> 1)));
                    if (g1_on && q == 1) { load_slab(0, false); load_slab(1, false); load_slab(2, false); }
                }
                __syncwarp();
            }
            if (g1_on) {
                mbar_wait2(BAR(B_XD), 0, BAR(B_OL + 3), 0);
                #pragma unroll 1
                for (int i = 3; i < NPRE; i++) {
                    if (i == 7) mbar_wait(BAR(B_OC), 0);
                    if (elect_one()) load_slab(i, false);
                    __syncwarp();
                }
            } else {
                mbar_arrive_if(BAR((lane < 16 ? B_BE : B_BF) + (lane & 3)), lane < 20);
                mbar_wait(BAR(B_HD), 0);
                mbar_arrive_remote_if(pbar0 + 8u * B_PD, lane == 0);
                mbar_wait(BAR(B_GO), 0);
                uint32_t tg = lds1(sb + SM_TG + 4);
                tg += max((int)(lds1(sb + SM_TG2) - tg), 0);
                int it = 0;
                while ((int)(gtime32() - tg) < 0 && ++it < 256) {}
                const uint32_t t0 = clk32();
                if (lane < 2) {
                    asm volatile("st.shared.u32 [%0], %1;" :: "r"(sb + SM_TG + 8 + lane * 4), "r"(t0 + (lane ? CN3 : CN2)) : "memory");
                    mbar_arrive(BAR(B_GD + lane));
                }
                __syncwarp();
                #pragma unroll 1
                for (int s = 1; s < 15; s++) {
                    sleep_until(t0 + W2OFF + s * W2PACE);
                    if (elect_one()) { if (s < 15 - PFW) bulk_prefetch(pw2 + (s - 1) * 64 * 4096, 4096); load_slab(s, true); }
                    __syncwarp();
                }
            }
          } else {
            const uint32_t tag = lds1(sb + SM_EPOCH);
            if (lane < 4) mbar_expect(BAR(B_OL + lane), 14336);
            const uint32_t gbase = lds1(sb + SM_TG);
            const bool lead = elect_one();
            uint32_t* hfl = opaque_ptr(&prm.sc->flag_h[(a2s * 4 + a2j) * FS]);
            mbar_wait(BAR(B_QL), 0);
            const int d = poll_flags(&prm.sc->flag_o[(ti * 8 + (lane & 3) * 2) * FS], FS, tag, gbase);
            mbar_wait(BAR(B_A1D), 0);
            int key = max(d + DELTAO, __reduce_max_sync(~0u, d) + DMIN) * 4 + (lane & 3);
            uint32_t order = 0;
            #pragma unroll 1
            for (int i = 0; i < 4; i++) {
                const int m = __reduce_min_sync(~0u, key);
                const uint4* src = &prm.sc->o[(a2s * 4 + (m & 3)) * 896];
                int it = 0;
                while ((int)(gtime32() - gbase) < m >> 2 && ++it < 256) {}
                if (lead) bulk_g2s(sb + SM_WQ + i * 14336, src, 14336, BAR(B_OL + i));
                if (key == m) key = 0x7fffffff;
                order |= (m & 3) << i * 2;
            }
            if (lead) {
                asm volatile("st.shared.u32 [%0], %1;" :: "r"(sb + SM_ORD), "r"(order) : "memory");
                mbar_arrive(BAR(B_OD));
            }
            __syncwarp();
            mbar_wait(BAR(B_XD), 0);
            int t0 = gtime32() - gbase + XDNS;
            #pragma unroll 1
            for (int i = 0; i < 4; i++) { mbar_wait(BAR(B_OF + i), 0); t0 = max(t0, (int)(gtime32() - gbase) - i * CHUNKNS); }
            if (lead) st_flag(hfl, tag, gbase + t0);
            __syncwarp();
          }
          if (elect_one()) {
              const int h = ~warp & 1;
              constexpr uint32_t T = 57344, BO = 2 * 14336;
              const char* src1 = (const char*)&prm.sc->hn[(rank * 16 + h) * 3584 + g1j * 896];
              const char* src2 = (const char*)&prm.sc->g[(rank * 14 + h) * 3584 + g2j * 896];
              uint64_t masks = g1_on ? (h ? kSegMasks1 : kSegMasks0) : 0x80 | 0x80 << 10;
              const uint32_t bl = BAR(B_BL + h * NB);
              uint32_t s8 = (g1_on ? NB - 2 + h : 4 + h) * 8, lap = 3, tmin = 0;
              const CUtensorMap* am = &mW1;
              uint32_t ad = sb + (NPRE + h) * 8192, astep = 16384; int ac0 = h * kF + g1f * 64, ac1 = (rank * 8 + NPRE / 2) * 64;
              #pragma unroll 1
              for (int seg = g1_on ? 0 : 3; seg < 5; seg++) {
                  const char* src = (seg < 3 ? src1 : src2) + (~seg & 1) * BO;
                  uint32_t m = (uint32_t)masks & 0x3ff;
                  masks >>= 10;
                  const uint32_t pace = seg == 4 ? PACEB : PACE2;
                  if (seg == 2) {
                      mbar_wait(BAR(B_PL), 0);
                      mbar_arrive_remote_if(pbar0 + 8u * B_PD, h);
                      am = &mW2; ad = sb + 8192; astep = 8192; ac0 = g2s * 64; ac1 = rank * 14 * 64;
                  } else {
                      const int gate = seg - (seg > 2);
                      mbar_wait(BAR(B_HD + gate), 0);
                      tmin = lds1(sb + SM_TG + gate * 4);
                      if (gate < 2) {
                          tmin += max((int)(lds1(gate ? sb + SM_TG2 : sb + SM_TG) - tmin), 0);
                          int it = 0;
                          while ((int)(gtime32() - tmin) < 0 && ++it < 256) {}
                          tmin = clk32();
                      }
                      tmin += h * PACE1;
                  }
                  #pragma unroll 1
                  do {
                      const uint32_t dst = sb + SM_B + s8 * 1792;
                      spin_until(tmin);
                      mbar_wait_fast(BAR(B_BE) + s8 + (lap & 1) * (NB * 8), lap >> 1 & 1);
                      if (seg) {
                          bulk_g2s(dst, src, 14336, bl + s8);
                          mbar_expect(bl + s8, 14336);
                      }
                      tmin += pace;
                      src += 2 * T;
                      s8 += 16;
                      if (s8 >= NB * 8) { s8 -= NB * 8; lap++; }
                      if (m & 1) {
                          mbar_expect_more(bl + s8, 8192);
                          tma2d(ad, am, ac0, ac1, bl + s8);
                          ad += astep; ac1 += 64;
                      }
                      m >>= 1;
                  } while (m != 1);
                  if (seg == 0) lap = 3;
              }
          }
        } else {
          if (warp == 10) {
            mbar_wait(BAR(B_XF + 6), 0);
            if (lane < 27) asm volatile("prefetch.global.L2 [%0];" :: "l"(lane < 25 ? (const char*)prm.wo + min(b * 25 + lane, 3135) * 128
                                                                          : lane == 25 ? (const char*)prm.b1 + (b % 28) * 128 : (const char*)prm.b2 + (b & 31) * 128));
            const char* p1 = (const char*)prm.w1 + ((b >> 6) * 1024 + (b & 63) * 2) * 3584 + min(lane, 27) * 128;
            uint32_t tnext = clk32();
            #pragma unroll 1
            for (int i = 0; i < 16; i++) {
                while ((int)(clk32() - tnext) < 0) __nanosleep(40);
                asm volatile("prefetch.global.L2 [%0];" :: "l"(p1 + ((i >> 1) * 128 + (i & 1)) * 3584));
                tnext += PFPACE;
            }
            uint32_t* ofl = opaque_ptr(&prm.sc->flag_o[(ti * 8 + hg) * FS]);
            mbar_wait(BAR(B_EP), 0);
            const uint32_t tag = lds1(sb + SM_EPOCH);
            mbar_wait(BAR(B_QL), 0);
            const uint32_t tq = gtime32() + QLNS;
            mbar_wait2(BAR(B_HL), 0, BAR(B_HL + 1), 0);
            if (lane == 0) st_flag(ofl, tag, tq + max((int)(gtime32() - tq), 0));
            __syncwarp();
          }
          const uint32_t tag = lds1(sb + SM_EPOCH);
          const int h = warp & 1;
          const bool lead = elect_one();
          const uint32_t wo = lane * 132, l3 = lane < 16 ? 12288 : 0;
          uint32_t base = sb + SM_WQ, bl = BAR(B_OL), bf = BAR(B_OF), m = 4, rph = 0;
          #pragma unroll 1
          for (int e = 0; e < 2; e++) {
              uint32_t s8 = (e && !g1_on ? 4 + h : h) * 8;
              #pragma unroll 1
              do {
                  const uint32_t dst = base + s8 * 1792;
                  auto stale = [&]() {
                      uint32_t d;
                      asm volatile("{ .reg .b32 x, y, z, u;\n"
                                   "ld.shared.u32 x, [%1]; ld.shared.u32 y, [%1 + 4096]; ld.shared.u32 z, [%1 + 8192]; ld.shared.u32 u, [%2];\n"
                                   "lop3.b32 x, x, y, %3, 0x7e; lop3.b32 z, z, u, %3, 0x7e; lop3.b32 %0, x, z, 1, 0xa8; }"
                                   : "=r"(d) : "r"(dst + wo), "r"(dst + (wo + l3)), "r"(tag) : "memory");
                      return __any_sync(~0u, d);
                  };
                  mbar_wait_fast(bl + s8, m & 1);
                  bool bad = stale();
                  mbar_arrive_if(bf + s8, lead && !bad);
                  if (bad) {
                      const int p = 2 * __clz(m) - 2 + h;
                      const int st = (p > 15) + (p > 31) + (p > 45), s = p - (st < 3 ? 16 * st : 46);
                      mbar_wait(BAR(B_OD), 0);
                      const char* src = (const char*)(!e ? &prm.sc->o[(a2s * 4 + (lds1(sb + SM_ORD) >> (p * 2 & 7) & 3)) * 896] : st < 2 ? &prm.sc->hn[(rank * 16 + s) * 3584 + (g1j + 2 * st) * 896]
                                                                                                      : &prm.sc->g[(rank * 14 + s) * 3584 + (g2j + 2 * st - 4) * 896]);
                      int it = 0;
                      do {
                          if (++it > kSpinLimit) break;
                          const uint32_t* q = (const uint32_t*)(src + wo);
                          if (it > 1 && __any_sync(~0u, ((ld_rlx(q) ^ tag) | (ld_rlx(q + 1024) ^ tag) | (ld_rlx(q + 2048) ^ tag) | (ld_rlx(q + l3 / 4) ^ tag)) & 1)) continue;
                          if (lead) {
                              mbar_expect(BAR(B_RT + h), 14336);
                              bulk_g2s(dst, src, 14336, BAR(B_RT + h));
                          }
                          __syncwarp();
                          mbar_wait(BAR(B_RT + h), rph);
                          rph ^= 1;
                          bad = stale();
                      } while (bad);
                      mbar_arrive_if(bf + s8, lead);
                  }
                  s8 += 16;
                  if (s8 >= NB * 8) s8 -= NB * 8;
                  m >>= 1;
              } while (m != 1);
              if (e) break;
              if (h) {
                  const uint32_t gbase = lds1(sb + SM_TG);
                  sleep_until(clk32() + PDELAY);
                  const uint32_t tg = gbase + DELTA + __reduce_max_sync(~0u, poll_flags(&prm.sc->flag_h[(rank * 64 + lane) * FS], 32 * FS, tag, gbase));
                  if (lead) {
                      asm volatile("st.async.shared::cluster.mbarrier::complete_tx::bytes.b32 [%0], %1, [%2];"
                                   :: "r"(pbar0 + (SM_TG2 - SM_BAR)), "r"(tg), "r"(pbar0 + 8u * B_GO) : "memory");
                      asm volatile("st.shared.u32 [%0], %1;" :: "r"(sb + SM_TG + 4), "r"(tg) : "memory");
                      mbar_expect(BAR(B_GO), 4);
                  }
                  __syncwarp();
              } else {
                  const char* p2 = (const char*)prm.w2 + ((b >> 6) * 896 + (b & 63)) * 4096 + lane * 128;
                  #pragma unroll 1
                  for (int i = 0; i < PFW; i++) {
                      asm volatile("prefetch.global.L2 [%0];" :: "l"(p2 + i * 64 * 4096));
                      sleep_until(clk32() + PFPACE2);
                  }
              }
              base = sb + SM_B; bl = BAR(B_BL + h * NB); bf = BAR(B_BF); m = g1_on ? 0x4fe03f80 : 0x7f80;
          }
        }
    } else {
        asm volatile("setmaxnreg.inc.sync.aligned.u32 232;");
        asm volatile("barrier.cluster.wait.aligned;" ::: "memory");
        const int wg = warp >> 2, w = warp & 3;
        const int g = lane >> 2, t = lane & 3;
        uint32_t tag, om0, om1;
        __nv_bfloat16 bias1a, bias1b;
        {
            const uint64_t dw = make_desc(sb + (hg & 1) * 16, 0, true);
            uint4* const hp = opaque_ptr((w == 3 ? &prm.sc->halo[(((ti >> 1) * 8 + hg) * 2 + wg) * 128] : (uint4*)(smem_raw + SM_STG + wg * 8192 + w * 2048)) + lane);
            uint32_t a[28][4];
            float sm[4][4] = {};
            {
                const int r = w * 16 + (lane & 15);
                uint32_t xa[4];
                #pragma unroll
                for (int q = 0; q < 4; q++) xa[q] = opaque(sb + wg * 8192 + r * 128 + (((q * 2 + (lane >> 4)) ^ (r & 7)) << 4));
                const uint32_t one = opaque(0x3F803F80u), one2 = opaque(0x3F803F80u);
                #pragma unroll
                for (int k = 0; k < 28; k++) {
                    if ((k & 3) == 0) mbar_wait(BAR(B_XF + (k >> 2)), 0);
                    uint32_t (&f)[4] = a[k];
                    asm volatile("ldmatrix.sync.aligned.m8n8.x4.shared.b16 {%0,%1,%2,%3}, [%4];"
                                 : "=r"(f[0]), "=r"(f[1]), "=r"(f[2]), "=r"(f[3]) : "r"(xa[k & 3] + (k >> 2) * 16384) : "memory");
                    if (k < 24) mma16816(sm[k & 3], f[0], f[1], f[2], f[3], one, one2);
                }
                pair_arrive(B_XC);
                const bool wok = mbar_test(BAR(B_WKVF), 0);
                #pragma unroll
                for (int k = 24; k < 28; k++) mma16816(sm[k & 3], a[k][0], a[k][1], a[k][2], a[k][3], one, one2);
                if (!wok) mbar_wait(BAR(B_WKVF), 0);
            }
            const float mean0 = ((sm[0][0] + sm[1][0]) + (sm[2][0] + sm[3][0])) * (1.f / kD);
            const float mean1 = ((sm[0][2] + sm[1][2]) + (sm[2][2] + sm[3][2])) * (1.f / kD);
            const uint32_t mb0 = pack_bf16(mean0, mean0), mb1 = pack_bf16(mean1, mean1);
            float ak[28], av[28], aq[28];
            float ss0 = 0.f, ss1 = 0.f, ss2 = 0.f, ss3 = 0.f;
            uint32_t p0, p1;
            bool qok;
            static_for<0, 7>([&](auto S_) {
                constexpr int s = decltype(S_)::value;
                auto centre = [&](int q) {
                    uint32_t (&f)[4] = a[s * 4 + q];
                    f[0] = sub_bf16x2(f[0], mb0); f[1] = sub_bf16x2(f[1], mb1);
                    f[2] = sub_bf16x2(f[2], mb0); f[3] = sub_bf16x2(f[3], mb1);
                };
                if (s) {
                    #pragma unroll
                    for (int q = 0; q < 4; q++) centre(q);
                    mbar_wait(BAR(B_WKVF + s), 0);
                    if (s == 6) qok = mbar_test(BAR(B_WQF), 0);
                    wg_fence();
                }
                static_for<0, 4>([&](auto Q_) {
                    constexpr int q = decltype(Q_)::value;
                    uint32_t (&f)[4] = a[s * 4 + q];
                    if (s == 0) { centre(q); wg_fence(); }
                    wgmma_rs_n56<SM_WKV + s * 16384 + q * 2048, (s | q) != 0>(ak, f[0], f[1], f[2], f[3], dw);
                    wgmma_rs_n56<SM_WKV + s * 16384 + q * 2048 + 8192, (s | q) != 0>(av, f[0], f[1], f[2], f[3], dw);
                });
                wg_commit();
                if (s == 4) { wg_wait<1>(); pair_arrive(B_KV3); }
                if (s < 2) mbar_wait(BAR(s ? B_EP : B_WKVF), 0);
                if (s == 1) tag = lds1(sb + SM_EPOCH);
                #pragma unroll
                for (int q = 0; q < 8; q++) {
                    const uint32_t u0 = a[s * 4 + q / 2][(q & 1) * 2], u1 = a[s * 4 + q / 2][(q & 1) * 2 + 1];
                    if (q == 0) { p0 = sqr_bf16x2(u0); p1 = sqr_bf16x2(u1); }
                    else { p0 = sqa_bf16x2(u0, p0); p1 = sqa_bf16x2(u1, p1); }
                }
                ss0 += bf_lo(p0); ss2 += bf_hi(p0); ss1 += bf_lo(p1); ss3 += bf_hi(p1);
            });
            auto q_chunk = [&](auto K0_, auto K1_) {
                wg_fence();
                static_for<decltype(K0_)::value, decltype(K1_)::value>([&](auto K_) {
                    constexpr int k = decltype(K_)::value;
                    wgmma_rs_n56<SM_WQ + k * 2048, k != 0>(aq, a[k][0], a[k][1], a[k][2], a[k][3], dw);
                });
                wg_commit();
            };
            #define QCHUNK(k0, k1) q_chunk(std::integral_constant<int, k0>{}, std::integral_constant<int, k1>{})
            const float dl0 = mean0 - bf_lo(mb0), dl1 = mean1 - bf_lo(mb1);
            const float rs0 = rsq(fmaxf(quad_sum(ss0 + ss2) * (1.f / kD) - dl0 * dl0, 0.f) + kEps);
            const float rs1 = rsq(fmaxf(quad_sum(ss1 + ss3) * (1.f / kD) - dl1 * dl1, 0.f) + kEps);
            float rk[3][2];
            rk[1][0] = __shfl_sync(~0u, rs0, t * 8); rk[1][1] = __shfl_sync(~0u, rs0, t * 8 + 4);
            rk[2][0] = __shfl_sync(~0u, rs1, t * 8); rk[2][1] = __shfl_sync(~0u, rs1, t * 8 + 4);
            const uint32_t stg = sb + SM_STG + wg * 8192 + lane * 16;
            if (!qok) mbar_wait(BAR(B_WQF), 0);
            QCHUNK(0, QC0);
            wg_wait<1>();
            reg_fence(ak); reg_fence(av);
            uint32_t kf[3][7], vf[3][7];
            #pragma unroll
            for (int c = 0; c < 7; c++) {
                kf[2][c] = pack_bf16(ak[4 * c + 2], ak[4 * c + 3]);
                vf[2][c] = movm(pack_bf16(av[4 * c + 2], av[4 * c + 3]));
            }
            const uint32_t om = ~lane & 1;
            kf[2][0] = set_par(kf[2][0], om, tag); vf[2][0] = set_par(vf[2][0], om, tag);
            vf[2][1] = set_par(vf[2][1], om, tag); vf[2][5] = set_par(vf[2][5], om, tag);
            auto publish = [&](auto st) {
                st(0, kf[2][0], kf[2][1], kf[2][2], kf[2][3]);
                st(1, vf[2][0], kf[2][4], kf[2][5], kf[2][6]);
                st(2, vf[2][1], vf[2][2], vf[2][3], vf[2][4]);
                st(3, vf[2][5], vf[2][6], __float_as_uint(rk[2][0]), __float_as_uint(rk[2][1]));
            };
            if (w < 3 || rank) publish([&](int c, uint32_t x, uint32_t y, uint32_t z, uint32_t v) { st_gen4(hp + c * 32, x, y, z, v); });
            else publish([&](int c, uint32_t x, uint32_t y, uint32_t z, uint32_t v) {
                asm volatile("st.async.shared::cluster.mbarrier::complete_tx::bytes.v4.b32 [%0], {%2,%3,%4,%5}, [%1];"
                             :: "r"(pbar0 + (SM_STG + 3 * 2048 - SM_BAR) + wg * 8192 + lane * 16 + c * 512), "r"(pbar0 + (B_HL + wg) * 8),
                                "r"(x), "r"(y), "r"(z), "r"(v) : "memory");
            });
            pair_arrive(B_KVC);
            QCHUNK(QC0, QC1);
            #pragma unroll
            for (int c = 0; c < 7; c++) {
                kf[1][c] = pack_bf16(ak[4 * c], ak[4 * c + 1]);
                vf[1][c] = movm(pack_bf16(av[4 * c], av[4 * c + 1]));
            }
            QCHUNK(QC1, QC2);
            named_bar(1 + wg, 128);
            uint32_t* op = opaque_ptr((uint32_t*)&prm.sc->o[((ti * 2 + wg) * 56 + hg * 7) * 64] + w * 64 + lane);
            om0 = opaque((lane & 7) == w * 2); om1 = opaque((lane & 7) == w * 2 + 1);
            QCHUNK(QC2, 28);
            warp_arrive(BAR(B_QL));
            #undef QCHUNK
            const bool gt0 = 2 * t > g, gt1 = 2 * t + 1 > g, no_prev = ti == 0 && w == 0;
            const float kf0 = gt0 ? rk[1][0] : rk[2][0], kf1 = gt1 ? rk[1][1] : rk[2][1];
            constexpr float kScale = 0.18898223650461362f * 1.4426950408889634f;
            const float sq0 = rs0 * kScale, sf0 = kf0 * (rs1 * kScale), sf1 = kf1 * (rs1 * kScale);
            const float NEG = -__int_as_float(0x7f800000);
            const float nb0 = gt0 && no_prev ? NEG : 0.f, nb1 = gt1 && no_prev ? NEG : 0.f;
            const uint32_t mk = opaque((gt0 ? 0x0000ffffu : 0u) | (gt1 ? 0xffff0000u : 0u));
            const uint32_t nil = __shfl_sync(~0u, lane, 0);
            const uint32_t sr = stg + ((w + 3) & 3) * 2048, hbar = BAR(w == 0 ? B_HL + wg : B_EP);
            mbar_wait(BAR(B_EP), 0);
            wg_wait<0>();
            reg_fence(aq);
            warp_arrive(BAR(B_A1D));
            uint32_t qf[8][2];
            #pragma unroll
            for (int c = 0; c < 7; c++) {
                qf[c + (c > 3)][0] = pack_bf16(aq[4 * c], aq[4 * c + 1]);
                qf[c + (c > 3)][1] = pack_bf16(aq[4 * c + 2], aq[4 * c + 3]);
            }
            qf[4][0] = t >= 2 ? qf[3][0] : 0u; qf[4][1] = t >= 2 ? qf[3][1] : 0u;
            qf[3][0] = t < 2 ? qf[3][0] : 0u;  qf[3][1] = t < 2 ? qf[3][1] : 0u;
            float sc[2][3][4];
            auto scores = [&](int n) {
                #pragma unroll
                for (int hd = 0; hd < 2; hd++) {
                    sc[hd][n][0] = sc[hd][n][1] = sc[hd][n][2] = sc[hd][n][3] = 0.f;
                    mma16816(sc[hd][n], qf[4 * hd][0], qf[4 * hd][1], qf[4 * hd + 1][0], qf[4 * hd + 1][1], kf[n][3 * hd], kf[n][3 * hd + 1]);
                    mma16816(sc[hd][n], qf[4 * hd + 2][0], qf[4 * hd + 2][1], qf[4 * hd + 3][0], qf[4 * hd + 3][1], kf[n][3 * hd + 2], kf[n][3 * hd + 3]);
                }
            };
            scores(1); scores(2);
            mbar_wait(hbar, 0);
            {
                const uint4 u0 = lds4(sr), u1 = lds4(sr + 512), u3 = lds4(sr + 1536), u2 = lds4(sr + 1024);
                kf[0][0] = u0.x; kf[0][1] = u0.y; kf[0][2] = u0.z; kf[0][3] = u0.w;
                vf[0][0] = u1.x; kf[0][4] = u1.y; kf[0][5] = u1.z; kf[0][6] = u1.w;
                vf[0][1] = u2.x; vf[0][2] = u2.y; vf[0][3] = u2.z; vf[0][4] = u2.w;
                vf[0][5] = u3.x; vf[0][6] = u3.y; rk[0][0] = __uint_as_float(u3.z); rk[0][1] = __uint_as_float(u3.w);
            }
            scores(0);
            const float ke0 = gt0 ? rk[0][0] : rk[1][0], ke1 = gt1 ? rk[0][1] : rk[1][1];
            const float se0 = ke0 * sq0, se1 = ke1 * sq0;
            uint32_t ow[7][2];
            #pragma unroll
            for (int hd = 0; hd < 2; hd++) {
                const int c0 = hd * 3;
                float (&sc_)[3][4] = sc[hd];
                const float e0 = fmaf(gt0 ? sc_[0][0] : sc_[1][0], se0, nb0), e1 = fmaf(gt1 ? sc_[0][1] : sc_[1][1], se1, nb1);
                const float f0 = (gt0 ? sc_[1][2] : sc_[2][2]) * sf0, f1 = (gt1 ? sc_[1][3] : sc_[2][3]) * sf1;
                const float me = quad_max(fmaxf(e0, e1)), mf = quad_max(fmaxf(f0, f1));
                const float p0 = ex2(e0 - me), p1 = ex2(e1 - me), r0 = ex2(f0 - mf), r1 = ex2(f1 - mf);
                const float ie = rcp(quad_sum(p0 + p1)), jf = rcp(quad_sum(r0 + r1));
                const uint32_t pp = pack_bf16(p0 * ke0 * ie, p1 * ke1 * ie), rp = pack_bf16(r0 * kf0 * jf, r1 * kf1 * jf);
                const uint32_t a0 = pp & ~mk, a1 = rp & mk, a3 = rp & ~mk, a4 = pp & mk, zero = pp & nil, zero2 = rp & nil;
                #pragma unroll
                for (int c = 0; c < 4; c++) {
                    float o[4] = {0.f, 0.f, 0.f, 0.f};
                    mma16816(o, a0, a1, zero, a3, vf[1][c0 + c], vf[2][c0 + c]);
                    mma1688(o, a4, zero2, vf[0][c0 + c]);
                    const uint32_t lo = pack_bf16(o[0], o[1]), hi = pack_bf16(o[2], o[3]);
                    if (hd == 1 && c == 0) { if (t >= 2) { ow[3][0] = lo; ow[3][1] = hi; } }
                    else { ow[c0 + c][0] = lo; ow[c0 + c][1] = hi; }
                }
            }
            #pragma unroll
            for (int c = 0; c < 7; c++) {
                stg1(op + c * 256,      set_par(ow[c][0], om0, tag));
                stg1(op + c * 256 + 32, set_par(ow[c][1], om1, tag));
            }
        }
        float as[28], ac[28];
        uint32_t xch, peer_xch, *gp1, *gp2;
        const uint32_t *hp, *ht;
        const uint2* hq;
        uint64_t da0, db0;
        bool lead;
        {
            float acc2[28];
            mbar_wait(BAR(B_XRF), 0);
            const int cg = a2j * 2 + wg, cg2 = (g2j + 2 * wg) * 2 + (rank ^ 1), cg1 = (g1j + 2 * wg) * 2 + (rank ^ (g1f < 14));
            lead = elect_one();
            {
                const uint32_t xa = sb + SM_XR + wg * 8192 + (w * 16 + (lane & 15)) * 128;
                #pragma unroll
                for (int c = 0; c < 4; c++) {
                    uint32_t xr[4];
                    asm volatile("ldmatrix.sync.aligned.m8n8.x4.shared.b16 {%0,%1,%2,%3}, [%4];"
                                 : "=r"(xr[0]), "=r"(xr[1]), "=r"(xr[2]), "=r"(xr[3])
                                 : "r"(xa + ((((c * 2 + wg + (lane >> 4)) ^ lane) & 7) << 4)) : "memory");
                    #pragma unroll
                    for (int e = 0; e < (c < 3 ? 4 : 2); e++) { acc2[8 * c + 2 * e] = bf_lo(xr[e]); acc2[8 * c + 2 * e + 1] = bf_hi(xr[e]); }
                }
            }
            uint32_t* spw = opaque_ptr(&prm.sc->stats[((a2s * 8 + cg) * 4 + w) * 32 + lane]);
            const uint32_t* spr = opaque_ptr(&prm.sc->stats[(a2s * 32 + w) * 32 + lane]);
            uint32_t* rp = opaque_ptr((uint32_t*)&prm.sc->rows[a2s * 64 + w * 16 + (t >> 1) * 8 + g] + (t & 1));
            const int cgs = cg ^ (a2s >> 4);
            uint32_t* np = opaque_ptr((uint32_t*)&prm.sc->hn[(a2s * 56 + cgs * 7) * 64] + w * 64 + lane);
            const uint64_t dwo = make_desc(sb + SM_WKV + wg * (28672 + 16), 0, true);
            const uint64_t doa = make_desc(sb + SM_WQ, 1024, false, 128);
            bias1a = prm.b1[g1f * 64 + w * 16 + g]; bias1b = prm.b1[g1f * 64 + w * 16 + 8 + g];
            const __nv_bfloat16 bias2 = prm.b2[ti * 128 + (w * 16 + (t >> 1) * 8 + g) * 2 + a2p];
            reg_fence(acc2);
            fence_async_smem();
            warp_arrive(BAR(B_XD));
            mbar_wait2(BAR(B_WOF), 0, BAR(B_WOF + 1), 0);
            mbar_wait(BAR(B_OD), 0);
            const uint32_t order = __shfl_sync(~0u, lds1(sb + SM_ORD), 0);
            static_for<0, 4>([&](auto P_) {
                constexpr int P = decltype(P_)::value;
                const uint64_t dwp = dwo + ((order >> (2 * P + 1) & 1) * 3584 + (order >> 2 * P & 1) * 896);
                mbar_wait(BAR(B_OF + P), 0);
                wg_fence();
                static_for<0, 7>([&](auto K_) { constexpr int k = decltype(K_)::value;
                    wgmma_ss_n56<P * 14336 + k * 2048, k * 2048, 0>(acc2, doa, dwp); });
                if (P) wg_commit();
                if (P == 2) { wg_wait<1>(); warp_arrive(BAR(B_OC)); }
            });
            wg_wait<0>();
            reg_fence(acc2);
            float s0 = 0.f, s1 = 0.f, q0 = 0.f, q1 = 0.f;
            #pragma unroll
            for (int c = 0; c < 7; c++) {
                s0 += acc2[4 * c] + acc2[4 * c + 1];     q0 = fmaf(acc2[4 * c], acc2[4 * c], fmaf(acc2[4 * c + 1], acc2[4 * c + 1], q0));
                s1 += acc2[4 * c + 2] + acc2[4 * c + 3]; q1 = fmaf(acc2[4 * c + 2], acc2[4 * c + 2], fmaf(acc2[4 * c + 3], acc2[4 * c + 3], q1));
            }
            const bool th = t >= 2, to = t & 1;
            const float sa = (th ? s1 : s0) + __shfl_xor_sync(~0u, th ? s0 : s1, 2), qa = (th ? q1 : q0) + __shfl_xor_sync(~0u, th ? q0 : q1, 2);
            const float part = (to ? qa : sa) + __shfl_xor_sync(~0u, to ? sa : qa, 1);
            stg1(spw, set_par(__float_as_uint(part), 1u, tag));
            const uint32_t tpoll = clk32() + SDELAY;
            warp_arrive(BAR(B_HD));
            uint32_t us[8];
            {
                xch = opaque(sb + SM_XCH + w * 1792 + lane * 16);
                asm volatile("mapa.shared::cluster.u32 %0, %1, %2;" : "=r"(peer_xch) : "r"(xch), "r"(rank ^ 1));
                const int hcg = cg2 ^ (g2s >> 4), hrg = (g2s & 1) * 4 + w;
                const uint32_t* hl = (const uint32_t*)&prm.sc->hn[((g2s >> 1) * 112 + hcg * 7) * 64 + hrg * 8];
                hp = opaque_ptr(hl + (g & 1) * 14336 + (g >> 1) * 4 + t);
                ht = opaque_ptr(hl + (lane & 1) * 14336 + min(lane >> 1, 6) * 256 + hrg);
                hq = opaque_ptr(&prm.sc->rows[((g2s >> 1) * 2 + (g & 1)) * 64 + hrg * 8 + (g >> 1)]);
                gp1 = opaque_ptr((uint32_t*)&prm.sc->g[(g1f * 56 + cg1 * 7) * 64] + w * 64 + lane);
                gp2 = opaque_ptr((uint32_t*)(prm.out + (size_t)(g2s * 64 + w * 16 + lane / 7) * kD + cg2 * 56) + (lane % 7) * 4);
                da0 = make_desc(sb, 0, true); db0 = make_desc(sb + SM_B, 128, false);
            }
            spin_until(tpoll);
            #pragma unroll
            for (int i = 0; i < 8; i++) us[i] = ld_rlx(spr + i * 128);
            {
                int it = 0;
                while (true) {
                    uint32_t bad = 0;
                    #pragma unroll
                    for (int i = 0; i < 8; i++) bad |= us[i] ^ tag;
                    if (!__any_sync(~0u, bad & 1)) break;
                    if (++it > kSpinLimit) break;
                    #pragma unroll
                    for (int i = 0; i < 8; i++) us[i] = ld_rlx(spr + i * 128);
                }
            }
            const float tot = (((__uint_as_float(us[0]) + __uint_as_float(us[1])) + (__uint_as_float(us[2]) + __uint_as_float(us[3])))
                            + ((__uint_as_float(us[4]) + __uint_as_float(us[5])) + (__uint_as_float(us[6]) + __uint_as_float(us[7])))) * (1.f / kD);
            const float oth = __shfl_xor_sync(~0u, tot, 1);
            const float mean = to ? oth : tot;
            const float var = fmaxf(fmaf(-mean, mean, to ? tot : oth), 0.f);
            const float rra = rsq(fmaf(var, 4.f + 4.f * kEps, 4.f * kEps * kEps)), mra = -mean * rra;
            const float rrb = __shfl_xor_sync(~0u, rra, 2), mrb = __shfl_xor_sync(~0u, mra, 2);
            const float rr0 = th ? rrb : rra, mr0 = th ? mrb : mra, rr1 = th ? rra : rrb, mr1 = th ? mra : mrb;
            #pragma unroll
            for (int c = 0; c < 7; c++) {
                stg1(np + c * 256,      set_par(pack_bf16(fmaf(acc2[4 * c], rr0, mr0), fmaf(acc2[4 * c + 1], rr0, mr0)), om0, tag));
                stg1(np + c * 256 + 32, set_par(pack_bf16(fmaf(acc2[4 * c + 2], rr1, mr1), fmaf(acc2[4 * c + 3], rr1, mr1)), om1, tag));
            }
            if (cg == 0) stg1(rp, set_par(__float_as_uint(to ? mean + __bfloat162float(bias2) : rcp(rra)), 1u, tag));
            #pragma unroll
            for (int c = 0; c < 28; c++) { ac[c] = 0.5f * __bfloat162float(c & 2 ? bias1b : bias1a); as[c] = 0.f; }
            reg_fence(as); reg_fence(ac);
        }
        auto send = [&]() {
            const uint32_t rf = pbar0 + (B_RF + warp) * 8;
            #pragma unroll
            for (int c = 0; c < 4; c++) {
                const uint32_t p0 = pack_bf16(as[8 * c], as[8 * c + 1]), p1 = pack_bf16(as[8 * c + 2], as[8 * c + 3]);
                if (c < 3) {
                    const uint32_t p2 = pack_bf16(as[8 * c + 4], as[8 * c + 5]), p3 = pack_bf16(as[8 * c + 6], as[8 * c + 7]);
                    asm volatile("st.async.shared::cluster.mbarrier::complete_tx::bytes.v4.b32 [%0], {%1,%2,%3,%4}, [%5];"
                                 :: "r"(peer_xch + c * 512), "r"(p0), "r"(p1), "r"(p2), "r"(p3), "r"(rf) : "memory");
                } else {
                    asm volatile("st.async.shared::cluster.mbarrier::complete_tx::bytes.v2.b32 [%0], {%1,%2}, [%3];"
                                 :: "r"(peer_xch + 1536 - lane * 8), "r"(p0), "r"(p1), "r"(rf) : "memory");
                }
            }
        };
        auto receive = [&](uint32_t (&pk)[14], uint32_t phase) {
            mbar_wait(BAR(B_RF + warp), phase);
            #pragma unroll
            for (int c = 0; c < 3; c++) { const uint4 u = lds4(xch + c * 512); pk[4 * c] = u.x; pk[4 * c + 1] = u.y; pk[4 * c + 2] = u.z; pk[4 * c + 3] = u.w; }
            const uint2 u = lds2(xch + 1536 - lane * 8); pk[12] = u.x; pk[13] = u.y;
        };
        uint2 rw[2]; uint32_t tw;
        auto load_rows = [&]() { tw = ld_rlx(ht); rw[0] = ld_rlx2(hq); rw[1] = ld_rlx2(hq + 4); };
        rw[0] = rw[1] = make_uint2(0u, 0u); tw = ~tag;
        #pragma unroll 1
        for (int ge = 0;; ge++) {
          if (ge || g1_on) {
            const int use = ge * 2 + wg;
            int entry = ge ? 1 : 2 * wg, stop = 0;
            uint64_t da = da0 + (ge ? -3 : wg ? NR - 10 : 0) * 512;
            bool rel = lead && use == 1;
            const uint32_t xfree = BAR(use > (g1_on ? 0 : 2) ? B_RE + use - 1 : B_PD);
            mbar_wait(BAR(B_AF), 0);
            if (ge && (wg || g1_on)) named_bar(5 - wg, 256);
            auto step = [&](auto I_) {
                constexpr int i = decltype(I_)::value, sl = i % NB, ao = i * 8192, bo = sl * 14336;
                mbar_wait_fast(BAR(B_BF + sl), i / NB);
                wg_fence();
                wgmma_ss_n112<ao,        bo,       1>(as, ac, da, db0);
                wgmma_ss_n112<ao + 2048, bo + 256, 1>(as, ac, da, db0);
                wgmma_ss_n112<ao + 4096, bo + 512, 1>(as, ac, da, db0);
                wgmma_ss_n112<ao + 6144, bo + 768, 1>(as, ac, da, db0);
                wg_commit();
                if (i == 1 && stop == 1) named_arrive(4, 256);
                if (i == 3 && (use == 1 || use == 2)) named_arrive(4 + wg, 256);
                wg_wait<1>();
                mbar_arrive_if(BAR(B_BE + (13 + i) % 14), rel);
                rel = lead;
            };
            #pragma unroll 1
            while (true) {
                if (entry < 1) {
                    static_for<0, 2>(step);
                    if (stop == 1) break;
                    static_for<2, 4>(step);
                    if (stop) break;
                }
                if (entry < 2) static_for<4, 10>(step);
                else {
                    uint32_t af[NR * 4][4];
                    mbar_wait(BAR(B_GO), 0);
                    const uint32_t tp = lds1(sb + SM_TG + 4) + PLOFF;
                    int it = 0;
                    while ((int)(gtime32() - tp) < 0 && ++it < 256) __nanosleep(20);
                    const uint32_t la = sb + ((lane >> 4) * 8 + (lane & 7)) * 128 + (((w * 2 + ((lane >> 3) & 1)) ^ (lane & 7)) << 4);
                    #pragma unroll
                    for (int k = 0; k < NR * 4; k++)
                        asm volatile("ldmatrix.sync.aligned.m8n8.x4.trans.shared.b16 {%0,%1,%2,%3}, [%4];"
                                     : "=r"(af[k][0]), "=r"(af[k][1]), "=r"(af[k][2]), "=r"(af[k][3]) : "r"(la + k * 2048) : "memory");
                    __syncwarp();
                    mbar_arrive_if(BAR(B_PL), lead);
                    if (w == 0) {
                        const char* p2 = (const char*)prm.w2 + ((b >> 6) * 896 + (b & 63) + PFW * 64) * 4096 + lane * 128;
                        #pragma unroll 1
                        for (int i = 0; i < 14 - PFW; i++) {
                            it = 0;
                            while ((int)(gtime32() - tp) < PF3OFF + i * PF3PACE && ++it < 256) __nanosleep(40);
                            asm volatile("prefetch.global.L2 [%0];" :: "l"(p2 + i * 64 * 4096));
                        }
                    }
                    named_bar(4, 256);
                    static_for<0, NR>([&](auto I_) {
                        constexpr int i = decltype(I_)::value, sl = (16 + i) % NB, o = sl * 14336;
                        mbar_wait_fast(BAR(B_BF + sl), (16 + i) / NB & 1);
                        wg_fence();
                        wgmma_rs_n112<o,       1>(as, ac, af[4 * i][0], af[4 * i][1], af[4 * i][2], af[4 * i][3], db0);
                        wgmma_rs_n112<o + 256, 1>(as, ac, af[4 * i + 1][0], af[4 * i + 1][1], af[4 * i + 1][2], af[4 * i + 1][3], db0);
                        wgmma_rs_n112<o + 512, 1>(as, ac, af[4 * i + 2][0], af[4 * i + 2][1], af[4 * i + 2][2], af[4 * i + 2][3], db0);
                        wgmma_rs_n112<o + 768, 1>(as, ac, af[4 * i + 3][0], af[4 * i + 3][1], af[4 * i + 3][2], af[4 * i + 3][3], db0);
                        wg_commit();
                        if (i) { wg_wait<1>(); mbar_arrive_if(BAR(B_BE + (15 + i) % (2 * NB)), lead); }
                    });
                }
                static_for<10, 14>(step);
                entry = 0; stop = use + 1; da += 14 * 512;
            }
            const uint32_t prev = BAR(B_BE + (use ? 3 : 1));
            const bool xok = mbar_test(xfree, 0);
            wg_wait<0>();
            reg_fence(as); reg_fence(ac);
            mbar_arrive_if(prev, lead);
            if (!xok) mbar_wait(xfree, 0);
            if (ge) break;
            send();
            load_rows();
            uint32_t pk[14];
            receive(pk, 0);
            #pragma unroll
            for (int c = 0; c < 14; c++) {
                float r[2];
                #pragma unroll
                for (int e = 0; e < 2; e++) {
                    const float u = ac[2 * c + e] + (e ? bf_hi(pk[c]) : bf_lo(pk[c]));
                    r[e] = fmaf(u, tanh_hw(u * fmaf(u * u, 8.f * 0.7978845608f * 0.044715f, 2.f * 0.7978845608f)), u);
                }
                stg1(gp1 + (c >> 1) * 256 + (c & 1) * 32, set_par(pack_bf16(r[0], r[1]), c & 1 ? om1 : om0, tag));
            }
            named_bar(1 + wg, 128);
            if (w == 0 && lane == 0) {
                asm volatile("st.shared.u32 [%0], %1;" :: "r"(sb + SM_TG + 8 + wg * 4), "r"(clk32() + (wg ? XSPECB : XSPEC)) : "memory");
                mbar_arrive(BAR(B_GD + wg));
            }
            if (lead) mbar_expect(BAR(B_RF + warp), 1792);
            mbar_arrive_remote_if(pbar0 + (B_RE + wg) * 8, lead);
          } else mbar_wait(BAR(B_GD), 0);
            {
                int it = 0;
                while (__any_sync(~0u, ((tw ^ tag) | (rw[0].x ^ tag) | (rw[0].y ^ tag) | (rw[1].x ^ tag) | (rw[1].y ^ tag)) & 1)) {
                    if (++it > kSpinLimit) break;
                    load_rows();
                }
                uint32_t hw[14];
                #pragma unroll
                for (int c = 0; c < 14; c++) hw[c] = ld_rlx(hp + (c >> 1) * 256 + (c & 1) * 16);
                #pragma unroll
                for (int c = 0; c < 14; c++) {
                    ac[2 * c]     = fmaf(bf_lo(hw[c]), __uint_as_float(rw[c & 1].x), __uint_as_float(rw[c & 1].y));
                    ac[2 * c + 1] = fmaf(bf_hi(hw[c]), __uint_as_float(rw[c & 1].x), __uint_as_float(rw[c & 1].y));
                    as[2 * c] = as[2 * c + 1] = 0.f;
                }
                reg_fence(as); reg_fence(ac);
            }
        }
        uint32_t po[14], pk[14];
        if (!wg) sleep_until(clk32() + w * STAG2);
        send();
        #pragma unroll
        for (int c = 0; c < 14; c++) po[c] = opaque(pack_bf16(ac[2 * c], ac[2 * c + 1]));
        receive(pk, g1_on);
        #pragma unroll
        for (int c = 0; c < 14; c++) pk[c] = add_bf16x2(po[c], pk[c]);
        __syncwarp();
        const uint32_t sa = xch - lane * 16 + (lane & 15) * 112 + (lane >> 4) * 16;
        #pragma unroll
        for (int m = 0; m < 3; m++)
            asm volatile("stmatrix.sync.aligned.m8n8.x4.shared.b16 [%0], {%1,%2,%3,%4};"
                         :: "r"(sa + m * 32), "r"(pk[4 * m]), "r"(pk[4 * m + 1]), "r"(pk[4 * m + 2]), "r"(pk[4 * m + 3]) : "memory");
        asm volatile("stmatrix.sync.aligned.m8n8.x2.shared.b16 [%0], {%1,%2};" :: "r"(sa + 96), "r"(pk[12]), "r"(pk[13]) : "memory");
        __syncwarp();
        if (lane < 28) {
            #pragma unroll
            for (int i = 0; i < 4; i++) { const uint4 u = lds4(xch + i * 448); stg4(gp2 + i * 896, u.x, u.y, u.z, u.w); }
        }
        __syncwarp();
        mbar_arrive_remote_if(pbar0 + (B_RE + 2) * 8, lead && wg == 0);
        if (b == 0 && tid == 128) prm.sc->epoch = tag;
    }
}

typedef CUresult (*EncodeFn)(CUtensorMap*, CUtensorMapDataType, cuuint32_t, void*, const cuuint64_t*, const cuuint64_t*,
                             const cuuint32_t*, const cuuint32_t*, CUtensorMapInterleave, CUtensorMapSwizzle,
                             CUtensorMapL2promotion, CUtensorMapFloatOOBfill);

void make_map(EncodeFn enc, CUtensorMap* m, const void* base, uint64_t cols, uint64_t rows, uint32_t box_rows) {
    cuuint64_t dims[2] = {cols, rows};
    cuuint64_t strides[1] = {cols * 2};
    cuuint32_t box[2] = {64, box_rows};
    cuuint32_t es[2] = {1, 1};
    enc(m, CU_TENSOR_MAP_DATA_TYPE_BFLOAT16, 2, const_cast<void*>(base), dims, strides, box, es, CU_TENSOR_MAP_INTERLEAVE_NONE,
        CU_TENSOR_MAP_SWIZZLE_128B, CU_TENSOR_MAP_L2_PROMOTION_L2_128B, CU_TENSOR_MAP_FLOAT_OOB_FILL_NONE);
}

}

extern "C" void kernel_launch(void* const* d_in, const int* in_sizes, int n_in, void* d_out, int out_size) {
    (void)in_sizes; (void)n_in; (void)out_size;
    void* fn = nullptr;
    cudaDriverEntryPointQueryResult qr;
    cudaGetDriverEntryPoint("cuTensorMapEncodeTiled", &fn, cudaEnableDefault, &qr);
    EncodeFn enc = (EncodeFn)fn;
    CUtensorMap mX2, mX, mWqkv, mWo, mW1, mW2;
    {
        cuuint64_t dims[3] = {kD, kS / 2, 2}, strides[2] = {4 * kD, 2 * kD};
        cuuint32_t box[3] = {64, 64, 2}, es[3] = {1, 1, 1};
        enc(&mX2, CU_TENSOR_MAP_DATA_TYPE_BFLOAT16, 3, d_in[0], dims, strides, box, es, CU_TENSOR_MAP_INTERLEAVE_NONE,
            CU_TENSOR_MAP_SWIZZLE_128B, CU_TENSOR_MAP_L2_PROMOTION_L2_128B, CU_TENSOR_MAP_FLOAT_OOB_FILL_NONE);
    }
    make_map(enc, &mX, d_in[0], 2 * kD, kS / 2, 64);
    make_map(enc, &mWqkv, d_in[1], 3 * kD, kD, 64);
    make_map(enc, &mWo, d_in[2], kD, kD, 112);
    make_map(enc, &mW1, d_in[4], 2 * kF, kS / 2, 64);
    make_map(enc, &mW2, d_in[6], kS, kF, 64);
    Params prm;
    prm.x = (const __nv_bfloat16*)d_in[0];
    prm.wqkv = (const __nv_bfloat16*)d_in[1];
    prm.wo = (const __nv_bfloat16*)d_in[2];
    prm.w1 = (const __nv_bfloat16*)d_in[4];
    prm.b1 = (const __nv_bfloat16*)d_in[5];
    prm.w2 = (const __nv_bfloat16*)d_in[6];
    prm.b2 = (const __nv_bfloat16*)d_in[7];
    prm.out = (__nv_bfloat16*)d_out;
    cudaGetSymbolAddress((void**)&prm.sc, g_scratch);
    cudaFuncSetAttribute(fused_kernel, cudaFuncAttributeMaxDynamicSharedMemorySize, SM_TOTAL);
    fused_kernel<<<128, 384, SM_TOTAL, cudaStreamPerThread>>>(prm, mX2, mX, mWqkv, mWo, mW1, mW2);
}
```

```cpp
#include <cuda_runtime.h>
#include <cuda.h>
#include <cuda_bf16.h>
#include <stdint.h>
#include <type_traits>

namespace {

constexpr int kS = 2048, kD = 448, kF = 1792;
constexpr float kEps = 1e-5f;

constexpr int FS = 32;
constexpr int NPRE = 10;
constexpr int NR = 8;
constexpr int PFW = 4;
constexpr int QC0 = 4;
constexpr int QC1 = 10;
constexpr int QC2 = 16;
constexpr int PFD = 250;
constexpr int PFPACE = 280;
constexpr int PFPACE2 = 300;
constexpr int HDELAY = 200;
constexpr int WOD = 350;
constexpr int SDELAY = 200;
constexpr int PDELAY = 400;
constexpr int PACE1 = 120;
constexpr int PACE2 = 400;
constexpr int PACEB = 300;
constexpr int XSPEC = 500;
constexpr int XSPECB = 750;
constexpr int CN2 = 7300;
constexpr int CN3 = 11300;
constexpr int W2OFF = 800;
constexpr int W2PACE = 350;
constexpr int STAG2 = 550;
constexpr int QLNS = 256;
constexpr int DELTAO = 800;
constexpr int DMIN = 448;
constexpr int XDNS = 32;
constexpr int CHUNKNS = 250;
constexpr int DELTA = 2016;
constexpr int PLOFF = -250;
constexpr int PF3OFF = 300;
constexpr int PF3PACE = 240;

struct Scratch {
    uint32_t flag_o[16 * 8 * FS];
    uint4    o[32 * 56 * 64];
    uint32_t stats[32 * 8 * 4 * 32];
    uint4    hn[32 * 56 * 64];
    uint32_t flag_h[32 * 4 * FS];
    uint4    g[28 * 56 * 64];
    uint4    halo[8 * 8 * 2 * 4 * 32];
    uint2    rows[32 * 64];
    uint32_t epoch;
};
__device__ __align__(1024) Scratch g_scratch;

constexpr uint32_t SM_WKV  = 114688;
constexpr uint32_t SM_XR   = 24576;
constexpr uint32_t SM_STG  = 40960;
constexpr uint32_t SM_WQ   = 57344;
constexpr uint32_t SM_XCH  = 0;
constexpr uint32_t SM_B    = 131072;
constexpr uint32_t SM_BAR  = 231424;
constexpr uint32_t SM_TOTAL = SM_BAR + 1024;
constexpr int NB = 7;
constexpr int B_XF = 0, B_WKVF = 7, B_WQF = 14, B_XRF = 15, B_WOF = 16,
              B_XC = 18, B_KV3 = 19, B_KVC = 20,
              B_A1D = 21, B_XD = 22, B_OC = 23, B_QL = 24,
              B_BE = 25  , B_RE = B_BE + 2 * NB,
              B_PL = B_RE + 3, B_AF = B_PL + 1, B_BL = B_AF + 1  , B_OL = B_BL + 2 * NB  ,
              B_BF = B_OL + 4  , B_OF = B_BF + NB, B_RF = B_OF + 4, B_EP = B_RF + 8, B_PD = B_EP + 1, B_OD = B_PD + 1, B_RT = B_OD + 1, B_HL = B_RT + 2,
              B_HD = B_HL + 2  , B_GO = B_HD + 1, B_GD = B_GO + 1, B_COUNT = B_GD + 2;
constexpr uint32_t SM_EPOCH = SM_BAR + B_COUNT * 8, SM_TG = SM_EPOCH + 4  , SM_TG2 = SM_TG + 16  ,
                   SM_ORD = SM_TG2 + 4  ;

constexpr uint64_t kAPos = 0x3330ull | 0x5555555ull << 17;
constexpr uint32_t seg_mask(int h, int p0, int p1) {
    uint32_t m = 0; int n = 0;
    for (int p = p0; p < p1; p++) if ((p & 1) == h) m |= (uint32_t)((kAPos >> p) & 1) << n++;
    return m | 1u << n;
}
constexpr uint64_t seg_masks(int h) {
    return 2 | (uint64_t)seg_mask(h, 0, 16) << 10 | (uint64_t)seg_mask(h, 16, 32) << 20
             | (uint64_t)seg_mask(h, 32, 46) << 30 | (uint64_t)seg_mask(h, 46, 60) << 40;
}
constexpr uint64_t kSegMasks0 = seg_masks(0), kSegMasks1 = seg_masks(1);

constexpr int kSpinLimit = 1 << 15;
__device__ __forceinline__ bool elect_one() {
    uint32_t p;
    asm volatile("{ .reg .pred P; elect.sync _|P, 0xffffffff; selp.u32 %0, 1, 0, P; }" : "=r"(p));
    return p;
}
__device__ __forceinline__ void mbar_init(uint32_t bar, uint32_t cnt) { asm volatile("mbarrier.init.shared::cta.b64 [%0], %1;" :: "r"(bar), "r"(cnt)); }
__device__ __forceinline__ void mbar_expect(uint32_t bar, uint32_t bytes) { asm volatile("mbarrier.arrive.expect_tx.shared::cta.b64 _, [%0], %1;" :: "r"(bar), "r"(bytes) : "memory"); }
__device__ __forceinline__ void mbar_expect_more(uint32_t bar, uint32_t bytes) { asm volatile("mbarrier.expect_tx.relaxed.cta.shared::cta.b64 [%0], %1;" :: "r"(bar), "r"(bytes) : "memory"); }
__device__ __forceinline__ void mbar_arrive(uint32_t bar) { asm volatile("mbarrier.arrive.shared::cta.b64 _, [%0];" :: "r"(bar) : "memory"); }
__device__ __forceinline__ void mbar_wait(uint32_t bar, uint32_t parity) {
    uint32_t ok; int it = 0;
    do {
        asm volatile("{ .reg .pred p; mbarrier.try_wait.parity.shared::cta.b64 p, [%1], %2; selp.u32 %0, 1, 0, p; }"
                     : "=r"(ok) : "r"(bar), "r"(parity) : "memory");
        if (++it > kSpinLimit) break;
    } while (!ok);
}
__device__ __forceinline__ bool mbar_try(uint32_t bar, uint32_t parity) {
    uint32_t ok;
    asm volatile("{ .reg .pred p; mbarrier.try_wait.parity.shared::cta.b64 p, [%1], %2; selp.u32 %0, 1, 0, p; }" : "=r"(ok) : "r"(bar), "r"(parity) : "memory");
    return ok;
}
__device__ __forceinline__ bool mbar_test(uint32_t bar, uint32_t parity) {
    uint32_t ok;
    asm volatile("{ .reg .pred p; mbarrier.test_wait.parity.shared::cta.b64 p, [%1], %2; selp.u32 %0, 1, 0, p; }" : "=r"(ok) : "r"(bar), "r"(parity) : "memory");
    return ok;
}
__device__ __forceinline__ void mbar_wait_fast(uint32_t bar, uint32_t parity) { if (!mbar_try(bar, parity)) mbar_wait(bar, parity); }
__device__ __forceinline__ void mbar_wait2(uint32_t bar0, uint32_t par0, uint32_t bar1, uint32_t par1) {
    uint32_t ok; int it = 0;
    do {
        asm volatile("{ .reg .pred p, q; mbarrier.try_wait.parity.shared::cta.b64 p, [%1], %2;\n"
                     "mbarrier.try_wait.parity.shared::cta.b64 q, [%3], %4; and.pred p, p, q; selp.u32 %0, 1, 0, p; }"
                     : "=r"(ok) : "r"(bar0), "r"(par0), "r"(bar1), "r"(par1) : "memory");
        if (++it > kSpinLimit) break;
    } while (!ok);
}
template <int N> __device__ __forceinline__ void reg_fence(float (&d)[N]) {
    #pragma unroll
    for (int i = 0; i < N; i++) asm volatile("" : "+f"(d[i]) :: "memory");
}
__device__ __forceinline__ void mbar_arrive_if(uint32_t bar, bool pred) {
    asm volatile("{ .reg .pred p; setp.ne.u32 p, %1, 0; @p mbarrier.arrive.shared::cta.b64 _, [%0]; }" :: "r"(bar), "r"((uint32_t)pred) : "memory");
}
__device__ __forceinline__ void warp_arrive(uint32_t bar) { __syncwarp(); if (elect_one()) mbar_arrive(bar); }
__device__ __forceinline__ void tma2d(uint32_t dst, const CUtensorMap* m, int c0, int c1, uint32_t bar) {
    asm volatile("cp.async.bulk.tensor.2d.shared::cluster.global.mbarrier::complete_tx::bytes [%0], [%1, {%3, %4}], [%2];"
                 :: "r"(dst), "l"(m), "r"(bar), "r"(c0), "r"(c1) : "memory");
}
__device__ __forceinline__ void tma3d(uint32_t dst, const CUtensorMap* m, int c0, int c1, int c2, uint32_t bar) {
    asm volatile("cp.async.bulk.tensor.3d.shared::cluster.global.mbarrier::complete_tx::bytes [%0], [%1, {%3, %4, %5}], [%2];"
                 :: "r"(dst), "l"(m), "r"(bar), "r"(c0), "r"(c1), "r"(c2) : "memory");
}
__device__ __forceinline__ void tma2d_mc(uint32_t dst, const CUtensorMap* m, int c0, int c1, uint32_t bar) {
    asm volatile("cp.async.bulk.tensor.2d.shared::cluster.global.mbarrier::complete_tx::bytes.multicast::cluster [%0], [%1, {%3, %4}], [%2], %5;"
                 :: "r"(dst), "l"(m), "r"(bar), "r"(c0), "r"(c1), "h"((uint16_t)3) : "memory");
}
__device__ __forceinline__ void mbar_arrive_remote_if(uint32_t cluster_bar, bool pred) {
    asm volatile("{ .reg .pred p; setp.ne.u32 p, %1, 0; @p mbarrier.arrive.shared::cluster.b64 _, [%0]; }" :: "r"(cluster_bar), "r"((uint32_t)pred) : "memory");
}
__device__ __forceinline__ void bulk_g2s(uint32_t dst, const void* src, uint32_t bytes, uint32_t bar) {
    asm volatile("cp.async.bulk.shared::cluster.global.mbarrier::complete_tx::bytes [%0], [%1], %2, [%3];"
                 :: "r"(dst), "l"(src), "r"(bytes), "r"(bar) : "memory");
}
__device__ __forceinline__ void bulk_prefetch(const void* src, uint32_t bytes) { asm volatile("cp.async.bulk.prefetch.L2.global [%0], %1;" :: "l"(src), "r"(bytes) : "memory"); }
__device__ __forceinline__ void wg_fence()  { asm volatile("wgmma.fence.sync.aligned;" ::: "memory"); }
__device__ __forceinline__ void wg_commit() { asm volatile("wgmma.commit_group.sync.aligned;" ::: "memory"); }
template <int N> __device__ __forceinline__ void wg_wait() { asm volatile("wgmma.wait_group.sync.aligned %0;" :: "n"(N) : "memory"); }
__device__ __forceinline__ void named_bar(int id, int n) { asm volatile("bar.sync %0, %1;" :: "r"(id), "r"(n) : "memory"); }
__device__ __forceinline__ void named_arrive(int id, int n) { asm volatile("bar.arrive %0, %1;" :: "r"(id), "r"(n) : "memory"); }
__device__ __forceinline__ void fence_async_smem() { asm volatile("fence.proxy.async.shared::cta;" ::: "memory"); }
__device__ __forceinline__ uint32_t gtime32() { uint64_t t; asm volatile("mov.u64 %0, %%globaltimer;" : "=l"(t) :: "memory"); return (uint32_t)t; }
__device__ __forceinline__ uint32_t clk32() { uint64_t t; asm volatile("mov.u64 %0, %%clock64;" : "=l"(t) :: "memory"); return (uint32_t)t; }
__device__ __forceinline__ void spin_until(uint32_t t) { while ((int)(clk32() - t) < 0) {} }
__device__ __forceinline__ void sleep_until(uint32_t t) { while ((int)(clk32() - t) < 0) __nanosleep(20); }
__device__ __forceinline__ void st_flag(uint32_t* p, uint32_t v, uint32_t time) {
    const uint64_t w = ((uint64_t)time << 32) | v;
    asm volatile("st.relaxed.gpu.global.u64 [%0], %1;" :: "l"(p), "l"(w) : "memory");
}
__device__ __forceinline__ void ld_flag_if(uint64_t& v, const uint32_t* p, bool pred) {
    asm volatile("{ .reg .pred p; setp.ne.u32 p, %2, 0; @p ld.relaxed.gpu.global.u64 %0, [%1]; }" : "+l"(v) : "l"(p), "r"((uint32_t)pred) : "memory");
}
__device__ __forceinline__ uint32_t ld_rlx(const uint32_t* p) { uint32_t v; asm volatile("ld.relaxed.gpu.global.u32 %0, [%1];" : "=r"(v) : "l"(p) : "memory"); return v; }
template <class T> __device__ __forceinline__ T* opaque_ptr(T* p) { asm volatile("" : "+l"(p)); return p; }
__device__ __forceinline__ uint4 ld_rlx4(const uint4* p) {
    uint4 v; asm volatile("ld.relaxed.gpu.global.v4.u32 {%0,%1,%2,%3}, [%4];" : "=r"(v.x), "=r"(v.y), "=r"(v.z), "=r"(v.w) : "l"(p) : "memory"); return v;
}
__device__ __forceinline__ uint2 ld_rlx2(const uint2* p) {
    uint2 v; asm volatile("ld.relaxed.gpu.global.v2.u32 {%0,%1}, [%2];" : "=r"(v.x), "=r"(v.y) : "l"(p) : "memory"); return v;
}
__device__ __forceinline__ void stg1(uint32_t* p, uint32_t v) { asm volatile("st.global.u32 [%0], %1;" :: "l"(p), "r"(v) : "memory"); }
__device__ __forceinline__ void stg4(void* p, uint32_t x, uint32_t y, uint32_t z, uint32_t w) { asm volatile("st.global.v4.u32 [%0], {%1,%2,%3,%4};" :: "l"(p), "r"(x), "r"(y), "r"(z), "r"(w) : "memory"); }
__device__ __forceinline__ uint32_t lds1(uint32_t a) { uint32_t v; asm volatile("ld.shared.u32 %0, [%1];" : "=r"(v) : "r"(a) : "memory"); return v; }
__device__ __forceinline__ uint2 lds2(uint32_t a) { uint2 v; asm volatile("ld.shared.v2.u32 {%0,%1}, [%2];" : "=r"(v.x), "=r"(v.y) : "r"(a) : "memory"); return v; }
__device__ __forceinline__ uint32_t set_par(uint32_t v, uint32_t mask, uint32_t par) {
    uint32_t r; asm("lop3.b32 %0, %1, %2, %3, 0xb8;" : "=r"(r) : "r"(v), "r"(mask), "r"(par)); return r;
}
__device__ __forceinline__ void st_gen4(void* p, uint32_t x, uint32_t y, uint32_t z, uint32_t w) { asm volatile("st.v4.u32 [%0], {%1,%2,%3,%4};" :: "l"(p), "r"(x), "r"(y), "r"(z), "r"(w) : "memory"); }
__device__ __forceinline__ float tanh_hw(float x) { float r; asm("tanh.approx.f32 %0, %1;" : "=f"(r) : "f"(x)); return r; }
__device__ __forceinline__ void sts4(uint32_t a, uint32_t x, uint32_t y, uint32_t z, uint32_t w) { asm volatile("st.shared.v4.u32 [%0], {%1,%2,%3,%4};" :: "r"(a), "r"(x), "r"(y), "r"(z), "r"(w) : "memory"); }
__device__ __forceinline__ uint4 lds4(uint32_t a) { uint4 v; asm volatile("ld.shared.v4.u32 {%0,%1,%2,%3}, [%4];" : "=r"(v.x), "=r"(v.y), "=r"(v.z), "=r"(v.w) : "r"(a) : "memory"); return v; }
__device__ __forceinline__ void ldsm4(uint32_t (&f)[4], uint32_t a) {
    asm volatile("ldmatrix.sync.aligned.m8n8.x4.shared.b16 {%0,%1,%2,%3}, [%4];" : "=r"(f[0]), "=r"(f[1]), "=r"(f[2]), "=r"(f[3]) : "r"(a) : "memory");
}
__device__ __forceinline__ void stsm4(uint32_t a, uint32_t x, uint32_t y, uint32_t z, uint32_t w) {
    asm volatile("stmatrix.sync.aligned.m8n8.x4.shared.b16 [%0], {%1,%2,%3,%4};" :: "r"(a), "r"(x), "r"(y), "r"(z), "r"(w) : "memory");
}
__device__ __forceinline__ uint32_t pack_bf16(float lo, float hi) { uint32_t r; asm("cvt.rn.bf16x2.f32 %0, %1, %2;" : "=r"(r) : "f"(hi), "f"(lo)); return r; }
__device__ __forceinline__ float bf_lo(uint32_t v) { return __uint_as_float(v << 16); }
__device__ __forceinline__ float bf_hi(uint32_t v) { return __uint_as_float(v & 0xffff0000u); }
__device__ __forceinline__ uint32_t sub_bf16x2(uint32_t a, uint32_t b) { uint32_t r; asm volatile("sub.rn.bf16x2 %0, %1, %2;" : "=r"(r) : "r"(a), "r"(b)); return r; }
__device__ __forceinline__ uint32_t add_bf16x2(uint32_t a, uint32_t b) { uint32_t r; asm volatile("add.rn.bf16x2 %0, %1, %2;" : "=r"(r) : "r"(a), "r"(b)); return r; }
__device__ __forceinline__ uint32_t sqr_bf16x2(uint32_t a) { uint32_t r; asm volatile("mul.rn.bf16x2 %0, %1, %1;" : "=r"(r) : "r"(a)); return r; }
__device__ __forceinline__ uint32_t sqa_bf16x2(uint32_t a, uint32_t c) { uint32_t r; asm volatile("fma.rn.bf16x2 %0, %1, %1, %2;" : "=r"(r) : "r"(a), "r"(c)); return r; }
__device__ __forceinline__ uint32_t movm(uint32_t a) { uint32_t r; asm volatile("movmatrix.sync.aligned.m8n8.trans.b16 %0, %1;" : "=r"(r) : "r"(a)); return r; }
__device__ __forceinline__ float ex2(float x) { float r; asm("ex2.approx.ftz.f32 %0, %1;" : "=f"(r) : "f"(x)); return r; }
__device__ __forceinline__ float rsq(float x) { float r; asm("rsqrt.approx.ftz.f32 %0, %1;" : "=f"(r) : "f"(x)); return r; }
__device__ __forceinline__ float rcp(float x) { float r; asm("rcp.approx.ftz.f32 %0, %1;" : "=f"(r) : "f"(x)); return r; }
__device__ __forceinline__ void mma16816(float (&c)[4], uint32_t a0, uint32_t a1, uint32_t a2, uint32_t a3, uint32_t b0, uint32_t b1) {
    asm("mma.sync.aligned.m16n8k16.row.col.f32.bf16.bf16.f32 {%0,%1,%2,%3}, {%4,%5,%6,%7}, {%8,%9}, {%0,%1,%2,%3};"
        : "+f"(c[0]), "+f"(c[1]), "+f"(c[2]), "+f"(c[3]) : "r"(a0), "r"(a1), "r"(a2), "r"(a3), "r"(b0), "r"(b1));
}
__device__ __forceinline__ void mma1688(float (&c)[4], uint32_t a0, uint32_t a1, uint32_t b0) {
    asm("mma.sync.aligned.m16n8k8.row.col.f32.bf16.bf16.f32 {%0,%1,%2,%3}, {%4,%5}, {%6}, {%0,%1,%2,%3};"
        : "+f"(c[0]), "+f"(c[1]), "+f"(c[2]), "+f"(c[3]) : "r"(a0), "r"(a1), "r"(b0));
}
__device__ __forceinline__ float quad_sum(float v) { v += __shfl_xor_sync(~0u, v, 1); v += __shfl_xor_sync(~0u, v, 2); return v; }
__device__ __forceinline__ float quad_max(float v) { v = fmaxf(v, __shfl_xor_sync(~0u, v, 1)); v = fmaxf(v, __shfl_xor_sync(~0u, v, 2)); return v; }
__device__ __forceinline__ uint64_t make_desc(uint32_t addr, uint32_t lbo, bool swz, uint32_t sbo = 1024) {
    const uint32_t lo = __shfl_sync(~0u, ((addr & 0x3FFFF) >> 4) | ((lbo >> 4) << 16), 0);
    const uint32_t hi = __shfl_sync(~0u, (swz ? 0x40000000u : 0u) + (sbo >> 4) + (threadIdx.x & 31), 0);
    return ((uint64_t)hi << 32) | lo;
}
template <int I, int N, class F> __device__ __forceinline__ void static_for(F&& f) {
    if constexpr (I < N) { f(std::integral_constant<int, I>{}); static_for<I + 1, N>(f); }
}
__device__ __forceinline__ uint32_t opaque(uint32_t v) { asm volatile("" : "+r"(v)); return v; }
template <int BOFF, int SCALE_D>
__device__ __forceinline__ void wgmma_rs_n56(float (&d)[28], uint32_t a0, uint32_t a1, uint32_t a2, uint32_t a3, uint64_t db) {
    asm volatile("{ .reg .b64 db; add.s64 db, %32, %33;\n"
        "wgmma.mma_async.sync.aligned.m64n56k16.f32.bf16.bf16 "
        "{%0, %1, %2, %3, %4, %5, %6, %7, %8, %9, %10, %11, %12, %13, %14, %15, %16, %17, %18, %19, %20, %21, %22, %23, %24, %25, %26, %27}, "
        "{%28, %29, %30, %31}, db, %34, 1, 1, 1; }"
        : "+f"(d[0]), "+f"(d[1]), "+f"(d[2]), "+f"(d[3]), "+f"(d[4]), "+f"(d[5]), "+f"(d[6]), "+f"(d[7]),
        "+f"(d[8]), "+f"(d[9]), "+f"(d[10]), "+f"(d[11]), "+f"(d[12]), "+f"(d[13]), "+f"(d[14]), "+f"(d[15]),
        "+f"(d[16]), "+f"(d[17]), "+f"(d[18]), "+f"(d[19]), "+f"(d[20]), "+f"(d[21]), "+f"(d[22]), "+f"(d[23]),
        "+f"(d[24]), "+f"(d[25]), "+f"(d[26]), "+f"(d[27])
        : "r"(a0), "r"(a1), "r"(a2), "r"(a3), "l"(db), "n"(BOFF >> 4), "n"(SCALE_D));
}
template <int AOFF, int BOFF, int MMAJOR>
__device__ __forceinline__ void wgmma_ss_n56(float (&d)[28], uint64_t da, uint64_t db) {
    asm volatile("{ .reg .b64 da, db; add.s64 da, %28, %30; add.s64 db, %29, %31;\n"
        "wgmma.mma_async.sync.aligned.m64n56k16.f32.bf16.bf16 "
        "{%0, %1, %2, %3, %4, %5, %6, %7, %8, %9, %10, %11, %12, %13, %14, %15, %16, %17, %18, %19, %20, %21, %22, %23, %24, %25, %26, %27}, "
        "da, db, 1, 1, 1, %32, 1; }"
        : "+f"(d[0]), "+f"(d[1]), "+f"(d[2]), "+f"(d[3]), "+f"(d[4]), "+f"(d[5]), "+f"(d[6]), "+f"(d[7]),
        "+f"(d[8]), "+f"(d[9]), "+f"(d[10]), "+f"(d[11]), "+f"(d[12]), "+f"(d[13]), "+f"(d[14]), "+f"(d[15]),
        "+f"(d[16]), "+f"(d[17]), "+f"(d[18]), "+f"(d[19]), "+f"(d[20]), "+f"(d[21]), "+f"(d[22]), "+f"(d[23]),
        "+f"(d[24]), "+f"(d[25]), "+f"(d[26]), "+f"(d[27])
        : "l"(da), "l"(db), "n"(AOFF >> 4), "n"(BOFF >> 4), "n"(MMAJOR));
}
template <int AOFF, int BOFF, int MMAJOR>
__device__ __forceinline__ void wgmma_ss_n112(float (&d)[28], float (&e)[28], uint64_t da, uint64_t db) {
    asm volatile("{ .reg .b64 da, db; add.s64 da, %56, %58; add.s64 db, %57, %59;\n"
        "wgmma.mma_async.sync.aligned.m64n112k16.f32.bf16.bf16 "
        "{%0, %1, %2, %3, %4, %5, %6, %7, %8, %9, %10, %11, %12, %13, %14, %15, %16, %17, %18, %19, %20, %21, %22, %23, %24, %25, %26, %27, %28, %29, %30, %31, %32, %33, %34, %35, %36, %37, %38, %39, %40, %41, %42, %43, %44, %45, %46, %47, %48, %49, %50, %51, %52, %53, %54, %55}, "
        "da, db, 1, 1, 1, %60, 1; }"
        : "+f"(d[0]), "+f"(d[1]), "+f"(d[2]), "+f"(d[3]), "+f"(d[4]), "+f"(d[5]), "+f"(d[6]), "+f"(d[7]),
        "+f"(d[8]), "+f"(d[9]), "+f"(d[10]), "+f"(d[11]), "+f"(d[12]), "+f"(d[13]), "+f"(d[14]), "+f"(d[15]),
        "+f"(d[16]), "+f"(d[17]), "+f"(d[18]), "+f"(d[19]), "+f"(d[20]), "+f"(d[21]), "+f"(d[22]), "+f"(d[23]),
        "+f"(d[24]), "+f"(d[25]), "+f"(d[26]), "+f"(d[27]), "+f"(e[0]), "+f"(e[1]), "+f"(e[2]), "+f"(e[3]),
        "+f"(e[4]), "+f"(e[5]), "+f"(e[6]), "+f"(e[7]), "+f"(e[8]), "+f"(e[9]), "+f"(e[10]), "+f"(e[11]),
        "+f"(e[12]), "+f"(e[13]), "+f"(e[14]), "+f"(e[15]), "+f"(e[16]), "+f"(e[17]), "+f"(e[18]), "+f"(e[19]),
        "+f"(e[20]), "+f"(e[21]), "+f"(e[22]), "+f"(e[23]), "+f"(e[24]), "+f"(e[25]), "+f"(e[26]), "+f"(e[27])
        : "l"(da), "l"(db), "n"(AOFF >> 4), "n"(BOFF >> 4), "n"(MMAJOR));
}
template <int BOFF, int SCALE_D>
__device__ __forceinline__ void wgmma_rs_n112(float (&d)[28], float (&e)[28], uint32_t a0, uint32_t a1, uint32_t a2, uint32_t a3, uint64_t db) {
    asm volatile("{ .reg .b64 db; add.s64 db, %60, %61;\n"
        "wgmma.mma_async.sync.aligned.m64n112k16.f32.bf16.bf16 "
        "{%0, %1, %2, %3, %4, %5, %6, %7, %8, %9, %10, %11, %12, %13, %14, %15, %16, %17, %18, %19, %20, %21, %22, %23, %24, %25, %26, %27, %28, %29, %30, %31, %32, %33, %34, %35, %36, %37, %38, %39, %40, %41, %42, %43, %44, %45, %46, %47, %48, %49, %50, %51, %52, %53, %54, %55}, "
        "{%56, %57, %58, %59}, db, %62, 1, 1, 1; }"
        : "+f"(d[0]), "+f"(d[1]), "+f"(d[2]), "+f"(d[3]), "+f"(d[4]), "+f"(d[5]), "+f"(d[6]), "+f"(d[7]),
        "+f"(d[8]), "+f"(d[9]), "+f"(d[10]), "+f"(d[11]), "+f"(d[12]), "+f"(d[13]), "+f"(d[14]), "+f"(d[15]),
        "+f"(d[16]), "+f"(d[17]), "+f"(d[18]), "+f"(d[19]), "+f"(d[20]), "+f"(d[21]), "+f"(d[22]), "+f"(d[23]),
        "+f"(d[24]), "+f"(d[25]), "+f"(d[26]), "+f"(d[27]), "+f"(e[0]), "+f"(e[1]), "+f"(e[2]), "+f"(e[3]),
        "+f"(e[4]), "+f"(e[5]), "+f"(e[6]), "+f"(e[7]), "+f"(e[8]), "+f"(e[9]), "+f"(e[10]), "+f"(e[11]),
        "+f"(e[12]), "+f"(e[13]), "+f"(e[14]), "+f"(e[15]), "+f"(e[16]), "+f"(e[17]), "+f"(e[18]), "+f"(e[19]),
        "+f"(e[20]), "+f"(e[21]), "+f"(e[22]), "+f"(e[23]), "+f"(e[24]), "+f"(e[25]), "+f"(e[26]), "+f"(e[27])
        : "r"(a0), "r"(a1), "r"(a2), "r"(a3), "l"(db), "n"(BOFF >> 4), "n"(SCALE_D));
}

struct Params {
    const __nv_bfloat16 *x, *wqkv;
    Scratch* sc;
    const __nv_bfloat16 *wo, *w1, *w2, *b1, *b2;
    __nv_bfloat16* out;
};

__global__ void __cluster_dims__(2, 1, 1) __launch_bounds__(384, 1)
fused_kernel(const Params prm, const __grid_constant__ CUtensorMap mX2, const __grid_constant__ CUtensorMap mX, const __grid_constant__ CUtensorMap mWqkv,
             const __grid_constant__ CUtensorMap mWo, const __grid_constant__ CUtensorMap mW1,
             const __grid_constant__ CUtensorMap mW2)
{
    extern __shared__ __align__(1024) unsigned char smem_raw[];
    if (threadIdx.x < 126) {
        const uint32_t i = threadIdx.x, t = clk32() + (i >> 5) * PFD;
        const char* px = (const char*)prm.x + (blockIdx.x * 16 + (i & 15)) * 896 + (i >> 4) * 128;
        const char* pw = (const char*)prm.wqkv + blockIdx.x * 2688 + i * 128 + (896 - 112 * 128);
        spin_until(t);
        asm volatile("prefetch.global.L2 [%0];" :: "l"(i < 112 ? px : pw) : "memory");
    }
    if (threadIdx.x == 128) { asm volatile("prefetch.tensormap [%0];" :: "l"(&mX2) : "memory"); asm volatile("prefetch.tensormap [%0];" :: "l"(&mWqkv) : "memory"); }
    uint32_t sb = (uint32_t)__cvta_generic_to_shared(smem_raw);
    asm volatile("mov.u32 %0, %0;" : "+r"(sb));
    const uint32_t bar0 = sb + SM_BAR;
    auto BAR = [&](int i) { return bar0 + 8u * i; };

    const int tid = threadIdx.x, lane = tid & 31;
    const int warp = __shfl_sync(~0u, tid >> 5, 0);
    const int b = __shfl_sync(~0u, (int)blockIdx.x, 0);
    const int rank = b & 1;
    const int cl = (b >> 1) - 4, cq = ((cl - 32) * 37) >> 8;
    const int res = cl < 0 ? 0 : cl < 32 ? cl & 7 : cl - 31 - 7 * cq;
    const int rnd = cl < 0 ? cl + 8 : cl < 32 ? cl >> 3 : 4 + cq;
    const int hg = (res & 1) * 4 + (rnd & 3);
    const int ti = (res >> 1) * 4 + (rnd >> 2) * 2 + rank;
    const int a2p = res & 1, a2j = rnd & 3;
    const int a2s = ti * 2 + a2p;
    const bool g1_on = rnd != 7;
    const int g1j = (rnd < 6 ? rnd : res) & 1, g1f = rnd < 6 ? res * 3 + (rnd >> 1) : 24 + (res >> 1);
    const int g2j = rnd & 1, g2s = res * 4 + (rnd >> 1);
    uint32_t pbar0;
    asm volatile("mapa.shared::cluster.u32 %0, %1, %2;" : "=r"(pbar0) : "r"(bar0), "r"(rank ^ 1));
    auto pair_arrive = [&](int i) { __syncwarp(); const bool l = elect_one(); mbar_arrive_if(BAR(i), l); mbar_arrive_remote_if(pbar0 + 8u * i, l); };
    const int wcol = hg * 56 - (hg & 1) * 8;

    if (warp == 8) {
        if (elect_one()) {
            #pragma unroll
            for (int i = 0; i < B_WQF; i++) mbar_init(BAR(i), 1);
            asm volatile("fence.mbarrier_init.release.cluster;" ::: "memory");
            fence_async_smem();
            #pragma unroll
            for (int kb = 0; kb < 7; kb++) {
                tma3d(sb + kb * 16384, &mX2, kb * 64, ti * 64, 0, BAR(B_XF + kb));
                mbar_expect(BAR(B_XF + kb), 16384);
            }
        }
    } else if (warp > 8) {
        if (elect_one()) {
            if (warp == 9) {
                #pragma unroll
                for (int i = B_WQF; i < B_AF; i++) mbar_init(BAR(i), i < B_XC ? 1 : i < B_A1D ? 16 : i < B_BE ? 8 : 4);
            } else if (warp == 10) {
                #pragma unroll
                for (int i = B_AF; i < B_BF; i++) mbar_init(BAR(i), 1);
            } else {
                #pragma unroll
                for (int i = B_BF; i < B_COUNT; i++) mbar_init(BAR(i), i == B_HD ? 8 : 1);
            }
            asm volatile("fence.mbarrier_init.release.cluster;" ::: "memory");
            fence_async_smem();
        }
    }
    __syncwarp();
    __syncthreads();
    asm volatile("barrier.cluster.arrive.relaxed.aligned;" ::: "memory");

    if (warp >= 8) {
        asm volatile("setmaxnreg.dec.sync.aligned.u32 40;");
        asm volatile("barrier.cluster.wait.aligned;" ::: "memory");
        auto fetch_halo = [&](int p, uint32_t tag) {
            const uint32_t hl = BAR(B_HL + p), dst = opaque(sb + SM_STG + p * 8192 + 3 * 2048 + lane * 16);
            const bool lead = elect_one();
            if (rank) { if (lead) mbar_expect(hl, 2048); __syncwarp(); return; }
            const uint4* hp = opaque_ptr(&prm.sc->halo[((((ti >> 1) - 1) * 8 + hg) * 2 + p) * 128 + lane]);
            mbar_wait(BAR(B_KVC), 0);
            if (ti > 0) {
                spin_until(clk32() + HDELAY);
                int it = 0;
                uint32_t bad;
                do {
                    uint4 u[4];
                    #pragma unroll
                    for (int c = 0; c < 4; c++) u[c] = ld_rlx4(hp + c * 32);
                    #pragma unroll
                    for (int c = 0; c < 4; c++) sts4(dst + c * 512, u[c].x, u[c].y, u[c].z, u[c].w);
                    bad = ((u[0].x ^ tag) | (u[1].x ^ tag) | (u[2].x ^ tag) | (u[3].x ^ tag)) & ~lane & 1;
                } while (__any_sync(~0u, bad) && ++it < kSpinLimit);
            } else {
                #pragma unroll
                for (int c = 0; c < 4; c++) sts4(dst + c * 512, 0u, 0u, 0u, 0u);
            }
            __syncwarp();
            mbar_arrive_if(hl, lead);
        };
        auto poll_flags = [&](const uint32_t* fp, int step, uint32_t tag, uint32_t gbase) {
            uint64_t v0 = 0, v1 = 0;
            int it = 0;
            do {
                ld_flag_if(v0, fp, (uint32_t)v0 != tag); ld_flag_if(v1, fp + step, (uint32_t)v1 != tag);
                if (++it > kSpinLimit) break;
            } while (__any_sync(~0u, (uint32_t)v0 != tag || (uint32_t)v1 != tag));
            return max((int)((uint32_t)(v0 >> 32) - gbase), (int)((uint32_t)(v1 >> 32) - gbase));
        };
        if (warp & 1) {
            uint32_t tag;
            if (warp == 11) {
                tag = *(volatile uint32_t*)&prm.sc->epoch + 1;
                #pragma unroll 1
                for (int i = 0; i < 8 * rank; i++) prm.sc->halo[((ti >> 1) * 8 + hg) * 256 + i * 32 + lane] = make_uint4(~tag, 0u, 0u, 0u);
                ((uint4*)prm.sc->stats)[(a2s * 4 + a2j) * 64 + lane] = ((uint4*)prm.sc->stats)[(a2s * 4 + a2j) * 64 + 32 + lane] = make_uint4(~tag, ~tag, ~tag, ~tag);
                prm.sc->flag_h[(a2s * 4 + a2j) * FS + lane] = 0;
                prm.sc->flag_o[(ti * 8 + hg) * FS + lane] = 0;
                __syncwarp();
                if (lane == 0) {
                    asm volatile("st.shared.v2.u32 [%0], {%1, %2};" :: "r"(sb + SM_EPOCH), "r"(tag), "r"(gtime32()) : "memory");
                    mbar_arrive(BAR(B_EP));
                }
                if (lane < 8) mbar_expect(BAR(B_RF + lane), 1792);
                __syncwarp();
            } else {
                mbar_wait(BAR(B_EP), 0);
                tag = lds1(sb + SM_EPOCH);
            }
            fetch_halo((warp >> 1) & 1, tag);
        }
        if (warp < 10) {
          auto load_slab = [&](int s, bool second) {
              if (!second) tma2d(sb + s * 8192, &mW1, (s & 1) * kF + g1f * 64, (rank * 8 + (s >> 1)) * 64, BAR(B_AF));
              else         tma2d(sb + s * 8192, &mW2, g2s * 64, (rank * 14 + s - 1) * 64, BAR(B_AF));
          };
          const char* pw2 = (const char*)prm.w2 + ((b >> 6) * 896 + (b & 63) + PFW * 64) * 4096;
          if (warp == 8) {
            if (elect_one()) {
                #pragma unroll 1
                for (int s = 0; s < 7; s++) {
                    mbar_expect(BAR(B_WKVF + s), 16384);
                    tma2d_mc(sb + SM_WKV + s * 16384 + rank * 8192, &mWqkv, (1 + rank) * kD + wcol, s * 64, BAR(B_WKVF + s));
                }
            }
            __syncwarp();
            mbar_wait(BAR(B_XC), 0);
            if (elect_one()) {
                asm volatile("prefetch.tensormap [%0];" :: "l"(&mX) : "memory");
                asm volatile("prefetch.tensormap [%0];" :: "l"(&mWo) : "memory");
                asm volatile("prefetch.tensormap [%0];" :: "l"(&mW1) : "memory");
                asm volatile("prefetch.tensormap [%0];" :: "l"(&mW2) : "memory");
                mbar_expect(BAR(B_AF), (g1_on ? NPRE : 14) * 8192);
                mbar_expect(BAR(B_WQF), 57344);
                #pragma unroll 1
                for (int s = rank; s < 7; s += 2) tma2d_mc(sb + SM_WQ + s * 8192, &mWqkv, wcol, s * 64, BAR(B_WQF));
                mbar_expect(BAR(B_XRF), 16384);
                tma2d(sb + SM_XR, &mX, a2p * kD + a2j * 112, ti * 64, BAR(B_XRF));
                tma2d(sb + SM_XR + 8192, &mX, a2p * kD + a2j * 112 + 48, ti * 64, BAR(B_XRF));
            }
            __syncwarp();
            #pragma unroll 1
            for (int q = 0; q < 4; q++) {
                mbar_wait(BAR(B_KV3 + (q >> 1)), 0);
                if (q == 2) spin_until(clk32() + WOD);
                if (q == 3) mbar_wait2(BAR(B_HL), 0, BAR(B_HL + 1), 0);
                if (elect_one()) {
                    if (!(q & 1)) mbar_expect(BAR(B_WOF + (q >> 1)), 57344);
                    tma2d_mc(sb + SM_WKV + q * 28672 + rank * 14336, &mWo, a2j * 112 + (q & 1) * 48, (q >> 1) * 224 + rank * 112, BAR(B_WOF + (q >> 1)));
                    if (g1_on && q == 1) { load_slab(0, false); load_slab(1, false); load_slab(2, false); }
                }
                __syncwarp();
            }
            if (g1_on) {
                mbar_wait2(BAR(B_XD), 0, BAR(B_OL + 3), 0);
                #pragma unroll 1
                for (int i = 3; i < NPRE; i++) {
                    if (i == 7) mbar_wait(BAR(B_OC), 0);
                    if (elect_one()) load_slab(i, false);
                    __syncwarp();
                }
            } else {
                mbar_arrive_if(BAR((lane < 16 ? B_BE : B_BF) + (lane & 3)), lane < 20);
                mbar_wait(BAR(B_HD), 0);
                mbar_arrive_remote_if(pbar0 + 8u * B_PD, lane == 0);
                mbar_wait(BAR(B_GO), 0);
                uint32_t tg = lds1(sb + SM_TG + 4);
                tg += max((int)(lds1(sb + SM_TG2) - tg), 0);
                int it = 0;
                while ((int)(gtime32() - tg) < 0 && ++it < 256) {}
                const uint32_t t0 = clk32();
                if (lane < 2) {
                    asm volatile("st.shared.u32 [%0], %1;" :: "r"(sb + SM_TG + 8 + lane * 4), "r"(t0 + (lane ? CN3 : CN2)) : "memory");
                    mbar_arrive(BAR(B_GD + lane));
                }
                __syncwarp();
                #pragma unroll 1
                for (int s = 1; s < 15; s++) {
                    sleep_until(t0 + W2OFF + s * W2PACE);
                    if (elect_one()) { if (s < 15 - PFW) bulk_prefetch(pw2 + (s - 1) * 64 * 4096, 4096); load_slab(s, true); }
                    __syncwarp();
                }
            }
          } else {
            const uint32_t tag = lds1(sb + SM_EPOCH);
            if (lane < 4) mbar_expect(BAR(B_OL + lane), 14336);
            const uint32_t gbase = lds1(sb + SM_TG);
            const bool lead = elect_one();
            uint32_t* hfl = opaque_ptr(&prm.sc->flag_h[(a2s * 4 + a2j) * FS]);
            mbar_wait(BAR(B_QL), 0);
            const int d = poll_flags(&prm.sc->flag_o[(ti * 8 + (lane & 3) * 2) * FS], FS, tag, gbase);
            mbar_wait(BAR(B_A1D), 0);
            int key = max(d + DELTAO, __reduce_max_sync(~0u, d) + DMIN) * 4 + (lane & 3);
            uint32_t order = 0;
            #pragma unroll 1
            for (int i = 0; i < 4; i++) {
                const int m = __reduce_min_sync(~0u, key);
                const uint4* src = &prm.sc->o[(a2s * 4 + (m & 3)) * 896];
                int it = 0;
                while ((int)(gtime32() - gbase) < m >> 2 && ++it < 256) {}
                if (lead) bulk_g2s(sb + SM_WQ + i * 14336, src, 14336, BAR(B_OL + i));
                if (key == m) key = 0x7fffffff;
                order |= (m & 3) << i * 2;
            }
            if (lead) {
                asm volatile("st.shared.u32 [%0], %1;" :: "r"(sb + SM_ORD), "r"(order) : "memory");
                mbar_arrive(BAR(B_OD));
            }
            __syncwarp();
            mbar_wait(BAR(B_XD), 0);
            int t0 = gtime32() - gbase + XDNS;
            #pragma unroll 1
            for (int i = 0; i < 4; i++) { mbar_wait(BAR(B_OF + i), 0); t0 = max(t0, (int)(gtime32() - gbase) - i * CHUNKNS); }
            if (lead) st_flag(hfl, tag, gbase + t0);
            __syncwarp();
          }
          if (elect_one()) {
              const int h = ~warp & 1;
              constexpr uint32_t T = 57344, BO = 2 * 14336;
              const char* src1 = (const char*)&prm.sc->hn[(rank * 16 + h) * 3584 + g1j * 896];
              const char* src2 = (const char*)&prm.sc->g[(rank * 14 + h) * 3584 + g2j * 896];
              uint64_t masks = g1_on ? (h ? kSegMasks1 : kSegMasks0) : 0x80 | 0x80 << 10;
              const uint32_t bl = BAR(B_BL + h * NB);
              uint32_t s8 = (g1_on ? NB - 2 + h : 4 + h) * 8, lap = 3, tmin = 0;
              const CUtensorMap* am = &mW1;
              uint32_t ad = sb + (NPRE + h) * 8192, astep = 16384; int ac0 = h * kF + g1f * 64, ac1 = (rank * 8 + NPRE / 2) * 64;
              #pragma unroll 1
              for (int seg = g1_on ? 0 : 3; seg < 5; seg++) {
                  const char* src = (seg < 3 ? src1 : src2) + (~seg & 1) * BO;
                  uint32_t m = (uint32_t)masks & 0x3ff;
                  masks >>= 10;
                  const uint32_t pace = seg == 4 ? PACEB : PACE2;
                  if (seg == 2) {
                      mbar_wait(BAR(B_PL), 0);
                      mbar_arrive_remote_if(pbar0 + 8u * B_PD, h);
                      am = &mW2; ad = sb + 8192; astep = 8192; ac0 = g2s * 64; ac1 = rank * 14 * 64;
                  } else {
                      const int gate = seg - (seg > 2);
                      mbar_wait(BAR(B_HD + gate), 0);
                      tmin = lds1(sb + SM_TG + gate * 4);
                      if (gate < 2) {
                          tmin += max((int)(lds1(gate ? sb + SM_TG2 : sb + SM_TG) - tmin), 0);
                          int it = 0;
                          while ((int)(gtime32() - tmin) < 0 && ++it < 256) {}
                          tmin = clk32();
                      }
                      tmin += h * PACE1;
                  }
                  #pragma unroll 1
                  do {
                      const uint32_t dst = sb + SM_B + s8 * 1792;
                      spin_until(tmin);
                      mbar_wait_fast(BAR(B_BE) + s8 + (lap & 1) * (NB * 8), lap >> 1 & 1);
                      if (seg) {
                          bulk_g2s(dst, src, 14336, bl + s8);
                          mbar_expect(bl + s8, 14336);
                      }
                      tmin += pace;
                      src += 2 * T;
                      s8 += 16;
                      if (s8 >= NB * 8) { s8 -= NB * 8; lap++; }
                      if (m & 1) {
                          mbar_expect_more(bl + s8, 8192);
                          tma2d(ad, am, ac0, ac1, bl + s8);
                          ad += astep; ac1 += 64;
                      }
                      m >>= 1;
                  } while (m != 1);
                  if (seg == 0) lap = 3;
              }
          }
        } else {
          if (warp == 10) {
            mbar_wait(BAR(B_XF + 6), 0);
            if (lane < 27) asm volatile("prefetch.global.L2 [%0];" :: "l"(lane < 25 ? (const char*)prm.wo + min(b * 25 + lane, 3135) * 128
                                                                          : lane == 25 ? (const char*)prm.b1 + (b % 28) * 128 : (const char*)prm.b2 + (b & 31) * 128));
            const char* p1 = (const char*)prm.w1 + ((b >> 6) * 1024 + (b & 63) * 2) * 3584 + min(lane, 27) * 128;
            uint32_t tnext = clk32();
            #pragma unroll 1
            for (int i = 0; i < 16; i++) {
                while ((int)(clk32() - tnext) < 0) __nanosleep(40);
                asm volatile("prefetch.global.L2 [%0];" :: "l"(p1 + ((i >> 1) * 128 + (i & 1)) * 3584));
                tnext += PFPACE;
            }
            uint32_t* ofl = opaque_ptr(&prm.sc->flag_o[(ti * 8 + hg) * FS]);
            mbar_wait(BAR(B_EP), 0);
            const uint32_t tag = lds1(sb + SM_EPOCH);
            mbar_wait(BAR(B_QL), 0);
            const uint32_t tq = gtime32() + QLNS;
            mbar_wait2(BAR(B_HL), 0, BAR(B_HL + 1), 0);
            if (lane == 0) st_flag(ofl, tag, tq + max((int)(gtime32() - tq), 0));
            __syncwarp();
          }
          const uint32_t tag = lds1(sb + SM_EPOCH);
          const int h = warp & 1;
          const bool lead = elect_one();
          const uint32_t wo = lane * 132, l3 = lane < 16 ? 12288 : 0;
          uint32_t base = sb + SM_WQ, bl = BAR(B_OL), bf = BAR(B_OF), m = 4, rph = 0;
          #pragma unroll 1
          for (int e = 0; e < 2; e++) {
              uint32_t s8 = (e && !g1_on ? 4 + h : h) * 8;
              #pragma unroll 1
              do {
                  const uint32_t dst = base + s8 * 1792;
                  auto stale = [&]() {
                      uint32_t d;
                      asm volatile("{ .reg .b32 x, y, z, u;\n"
                                   "ld.shared.u32 x, [%1]; ld.shared.u32 y, [%1 + 4096]; ld.shared.u32 z, [%1 + 8192]; ld.shared.u32 u, [%2];\n"
                                   "lop3.b32 x, x, y, %3, 0x7e; lop3.b32 z, z, u, %3, 0x7e; lop3.b32 %0, x, z, 1, 0xa8; }"
                                   : "=r"(d) : "r"(dst + wo), "r"(dst + (wo + l3)), "r"(tag) : "memory");
                      return __any_sync(~0u, d);
                  };
                  mbar_wait_fast(bl + s8, m & 1);
                  bool bad = stale();
                  mbar_arrive_if(bf + s8, lead && !bad);
                  if (bad) {
                      const int p = 2 * __clz(m) - 2 + h;
                      const int st = (p > 15) + (p > 31) + (p > 45), s = p - (st < 3 ? 16 * st : 46);
                      mbar_wait(BAR(B_OD), 0);
                      const char* src = (const char*)(!e ? &prm.sc->o[(a2s * 4 + (lds1(sb + SM_ORD) >> (p * 2 & 7) & 3)) * 896] : st < 2 ? &prm.sc->hn[(rank * 16 + s) * 3584 + (g1j + 2 * st) * 896]
                                                                                                      : &prm.sc->g[(rank * 14 + s) * 3584 + (g2j + 2 * st - 4) * 896]);
                      int it = 0;
                      do {
                          if (++it > kSpinLimit) break;
                          const uint32_t* q = (const uint32_t*)(src + wo);
                          if (it > 1 && __any_sync(~0u, ((ld_rlx(q) ^ tag) | (ld_rlx(q + 1024) ^ tag) | (ld_rlx(q + 2048) ^ tag) | (ld_rlx(q + l3 / 4) ^ tag)) & 1)) continue;
                          if (lead) {
                              mbar_expect(BAR(B_RT + h), 14336);
                              bulk_g2s(dst, src, 14336, BAR(B_RT + h));
                          }
                          __syncwarp();
                          mbar_wait(BAR(B_RT + h), rph);
                          rph ^= 1;
                          bad = stale();
                      } while (bad);
                      mbar_arrive_if(bf + s8, lead);
                  }
                  s8 += 16;
                  if (s8 >= NB * 8) s8 -= NB * 8;
                  m >>= 1;
              } while (m != 1);
              if (e) break;
              if (h) {
                  const uint32_t gbase = lds1(sb + SM_TG);
                  sleep_until(clk32() + PDELAY);
                  const uint32_t tg = gbase + DELTA + __reduce_max_sync(~0u, poll_flags(&prm.sc->flag_h[(rank * 64 + lane) * FS], 32 * FS, tag, gbase));
                  if (lead) {
                      asm volatile("st.async.shared::cluster.mbarrier::complete_tx::bytes.b32 [%0], %1, [%2];"
                                   :: "r"(pbar0 + (SM_TG2 - SM_BAR)), "r"(tg), "r"(pbar0 + 8u * B_GO) : "memory");
                      asm volatile("st.shared.u32 [%0], %1;" :: "r"(sb + SM_TG + 4), "r"(tg) : "memory");
                      mbar_expect(BAR(B_GO), 4);
                  }
                  __syncwarp();
              } else {
                  const char* p2 = (const char*)prm.w2 + ((b >> 6) * 896 + (b & 63)) * 4096 + lane * 128;
                  #pragma unroll 1
                  for (int i = 0; i < PFW; i++) {
                      asm volatile("prefetch.global.L2 [%0];" :: "l"(p2 + i * 64 * 4096));
                      sleep_until(clk32() + PFPACE2);
                  }
              }
              base = sb + SM_B; bl = BAR(B_BL + h * NB); bf = BAR(B_BF); m = g1_on ? 0x4fe03f80 : 0x7f80;
          }
        }
    } else {
        asm volatile("setmaxnreg.inc.sync.aligned.u32 232;");
        asm volatile("barrier.cluster.wait.aligned;" ::: "memory");
        const int wg = warp >> 2, w = warp & 3;
        const int g = lane >> 2, t = lane & 3;
        uint32_t tag, om0, om1;
        __nv_bfloat16 bias1a, bias1b;
        {
            const uint64_t dw = make_desc(sb + (hg & 1) * 16, 0, true);
            uint4* const hp = opaque_ptr((w == 3 ? &prm.sc->halo[(((ti >> 1) * 8 + hg) * 2 + wg) * 128] : (uint4*)(smem_raw + SM_STG + wg * 8192 + w * 2048)) + lane);
            uint32_t a[28][4];
            float sm[4][4];
            auto shift = [](uint32_t (&f)[4], uint32_t m0, uint32_t m1) {
                f[0] = sub_bf16x2(f[0], m0); f[1] = sub_bf16x2(f[1], m1);
                f[2] = sub_bf16x2(f[2], m0); f[3] = sub_bf16x2(f[3], m1);
            };
            {
                const int r = w * 16 + (lane & 15);
                uint32_t xa[4];
                #pragma unroll
                for (int q = 0; q < 4; q++) xa[q] = opaque(sb + wg * 8192 + r * 128 + (((q * 2 + (lane >> 4)) ^ (r & 7)) << 4));
                const uint32_t one = opaque(0x3F803F80u), one2 = opaque(0x3F803F80u);
                auto load = [&](int k0, int k1) {
                    #pragma unroll
                    for (int k = k0; k < k1; k++) {
                        if ((k & 3) == 0) mbar_wait(BAR(B_XF + (k >> 2)), 0);
                        ldsm4(a[k], xa[k & 3] + (k >> 2) * 16384);
                        if (k < 24) mma16816(sm[k & 3], a[k][0], a[k][1], a[k][2], a[k][3], one, one2);
                    }
                };
                #pragma unroll 1
                for (float lim = 128.f;; lim = 0.f) {
                    #pragma unroll
                    for (int i = 0; i < 16; i++) sm[i >> 2][i & 3] = 0.f;
                    load(0, 4);
                    float sq[4] = {};
                    uint32_t u[4];
                    #pragma unroll
                    for (int i = 0; i < 4; i++) u[i] = sqa_bf16x2(a[2][i], sqa_bf16x2(a[3][i], sqa_bf16x2(a[0][i], sqr_bf16x2(a[1][i]))));
                    mma16816(sq, u[0], u[1], u[2], u[3], one, one2);
                    const float m0 = ((sm[0][0] + sm[1][0]) + (sm[2][0] + sm[3][0])) * (1.f / 64);
                    const float m1 = ((sm[0][2] + sm[1][2]) + (sm[2][2] + sm[3][2])) * (1.f / 64);
                    load(4, 8);
                    if (!__any_sync(~0u, m0 * m0 * lim > sq[0] || m1 * m1 * lim > sq[2])) break;
                    #pragma unroll 1
                    for (int k = 0; k < 28; k++) {
                        const uint32_t p = (xa[0] ^ (k & 3) * 32) + (k >> 2) * 16384;
                        mbar_wait(BAR(B_XF + (k >> 2)), 0);
                        ldsm4(u, p);
                        shift(u, pack_bf16(m0, m0), pack_bf16(m1, m1));
                        stsm4(p, u[0], u[1], u[2], u[3]);
                    }
                    fence_async_smem();
                    __syncwarp();
                }
                load(8, 28);
                pair_arrive(B_XC);
                const bool wok = mbar_test(BAR(B_WKVF), 0);
                #pragma unroll
                for (int k = 24; k < 28; k++) mma16816(sm[k & 3], a[k][0], a[k][1], a[k][2], a[k][3], one, one2);
                if (!wok) mbar_wait(BAR(B_WKVF), 0);
            }
            const float mean0 = ((sm[0][0] + sm[1][0]) + (sm[2][0] + sm[3][0])) * (1.f / kD);
            const float mean1 = ((sm[0][2] + sm[1][2]) + (sm[2][2] + sm[3][2])) * (1.f / kD);
            const uint32_t mb0 = pack_bf16(mean0, mean0), mb1 = pack_bf16(mean1, mean1);
            float ak[28], av[28], aq[28];
            float ss0 = 0.f, ss1 = 0.f, ss2 = 0.f, ss3 = 0.f;
            uint32_t p0, p1;
            bool qok;
            static_for<0, 7>([&](auto S_) {
                constexpr int s = decltype(S_)::value;
                auto centre = [&](int q) { shift(a[s * 4 + q], mb0, mb1); };
                if (s) {
                    #pragma unroll
                    for (int q = 0; q < 4; q++) centre(q);
                    mbar_wait(BAR(B_WKVF + s), 0);
                    if (s == 6) qok = mbar_test(BAR(B_WQF), 0);
                    wg_fence();
                }
                static_for<0, 4>([&](auto Q_) {
                    constexpr int q = decltype(Q_)::value;
                    uint32_t (&f)[4] = a[s * 4 + q];
                    if (s == 0) { centre(q); wg_fence(); }
                    wgmma_rs_n56<SM_WKV + s * 16384 + q * 2048, (s | q) != 0>(ak, f[0], f[1], f[2], f[3], dw);
                    wgmma_rs_n56<SM_WKV + s * 16384 + q * 2048 + 8192, (s | q) != 0>(av, f[0], f[1], f[2], f[3], dw);
                });
                wg_commit();
                if (s == 4) { wg_wait<1>(); pair_arrive(B_KV3); }
                if (s < 2) mbar_wait(BAR(s ? B_EP : B_WKVF), 0);
                if (s == 1) tag = lds1(sb + SM_EPOCH);
                #pragma unroll
                for (int q = 0; q < 8; q++) {
                    const uint32_t u0 = a[s * 4 + q / 2][(q & 1) * 2], u1 = a[s * 4 + q / 2][(q & 1) * 2 + 1];
                    if (q == 0) { p0 = sqr_bf16x2(u0); p1 = sqr_bf16x2(u1); }
                    else { p0 = sqa_bf16x2(u0, p0); p1 = sqa_bf16x2(u1, p1); }
                }
                ss0 += bf_lo(p0); ss2 += bf_hi(p0); ss1 += bf_lo(p1); ss3 += bf_hi(p1);
            });
            auto q_chunk = [&](auto K0_, auto K1_) {
                wg_fence();
                static_for<decltype(K0_)::value, decltype(K1_)::value>([&](auto K_) {
                    constexpr int k = decltype(K_)::value;
                    wgmma_rs_n56<SM_WQ + k * 2048, k != 0>(aq, a[k][0], a[k][1], a[k][2], a[k][3], dw);
                });
                wg_commit();
            };
            #define QCHUNK(k0, k1) q_chunk(std::integral_constant<int, k0>{}, std::integral_constant<int, k1>{})
            const float dl0 = mean0 - bf_lo(mb0), dl1 = mean1 - bf_lo(mb1);
            const float rs0 = rsq(fmaxf(quad_sum(ss0 + ss2) * (1.f / kD) - dl0 * dl0, 0.f) + kEps);
            const float rs1 = rsq(fmaxf(quad_sum(ss1 + ss3) * (1.f / kD) - dl1 * dl1, 0.f) + kEps);
            float rk[3][2];
            rk[1][0] = __shfl_sync(~0u, rs0, t * 8); rk[1][1] = __shfl_sync(~0u, rs0, t * 8 + 4);
            rk[2][0] = __shfl_sync(~0u, rs1, t * 8); rk[2][1] = __shfl_sync(~0u, rs1, t * 8 + 4);
            const uint32_t stg = sb + SM_STG + wg * 8192 + lane * 16;
            if (!qok) mbar_wait(BAR(B_WQF), 0);
            QCHUNK(0, QC0);
            wg_wait<1>();
            reg_fence(ak); reg_fence(av);
            uint32_t kf[3][7], vf[3][7];
            #pragma unroll
            for (int c = 0; c < 7; c++) {
                kf[2][c] = pack_bf16(ak[4 * c + 2], ak[4 * c + 3]);
                vf[2][c] = movm(pack_bf16(av[4 * c + 2], av[4 * c + 3]));
            }
            const uint32_t om = ~lane & 1;
            kf[2][0] = set_par(kf[2][0], om, tag); vf[2][0] = set_par(vf[2][0], om, tag);
            vf[2][1] = set_par(vf[2][1], om, tag); vf[2][5] = set_par(vf[2][5], om, tag);
            auto publish = [&](auto st) {
                st(0, kf[2][0], kf[2][1], kf[2][2], kf[2][3]);
                st(1, vf[2][0], kf[2][4], kf[2][5], kf[2][6]);
                st(2, vf[2][1], vf[2][2], vf[2][3], vf[2][4]);
                st(3, vf[2][5], vf[2][6], __float_as_uint(rk[2][0]), __float_as_uint(rk[2][1]));
            };
            if (w < 3 || rank) publish([&](int c, uint32_t x, uint32_t y, uint32_t z, uint32_t v) { st_gen4(hp + c * 32, x, y, z, v); });
            else publish([&](int c, uint32_t x, uint32_t y, uint32_t z, uint32_t v) {
                asm volatile("st.async.shared::cluster.mbarrier::complete_tx::bytes.v4.b32 [%0], {%2,%3,%4,%5}, [%1];"
                             :: "r"(pbar0 + (SM_STG + 3 * 2048 - SM_BAR) + wg * 8192 + lane * 16 + c * 512), "r"(pbar0 + (B_HL + wg) * 8),
                                "r"(x), "r"(y), "r"(z), "r"(v) : "memory");
            });
            pair_arrive(B_KVC);
            QCHUNK(QC0, QC1);
            #pragma unroll
            for (int c = 0; c < 7; c++) {
                kf[1][c] = pack_bf16(ak[4 * c], ak[4 * c + 1]);
                vf[1][c] = movm(pack_bf16(av[4 * c], av[4 * c + 1]));
            }
            QCHUNK(QC1, QC2);
            named_bar(1 + wg, 128);
            uint32_t* op = opaque_ptr((uint32_t*)&prm.sc->o[((ti * 2 + wg) * 56 + hg * 7) * 64] + w * 64 + lane);
            om0 = opaque((lane & 7) == w * 2); om1 = opaque((lane & 7) == w * 2 + 1);
            QCHUNK(QC2, 28);
            warp_arrive(BAR(B_QL));
            #undef QCHUNK
            const bool gt0 = 2 * t > g, gt1 = 2 * t + 1 > g, no_prev = ti == 0 && w == 0;
            const float kf0 = gt0 ? rk[1][0] : rk[2][0], kf1 = gt1 ? rk[1][1] : rk[2][1];
            constexpr float kScale = 0.18898223650461362f * 1.4426950408889634f;
            const float sq0 = rs0 * kScale, sf0 = kf0 * (rs1 * kScale), sf1 = kf1 * (rs1 * kScale);
            const float NEG = -__int_as_float(0x7f800000);
            const float nb0 = gt0 && no_prev ? NEG : 0.f, nb1 = gt1 && no_prev ? NEG : 0.f;
            const uint32_t mk = opaque((gt0 ? 0x0000ffffu : 0u) | (gt1 ? 0xffff0000u : 0u));
            const uint32_t nil = __shfl_sync(~0u, lane, 0);
            const uint32_t sr = stg + ((w + 3) & 3) * 2048, hbar = BAR(w == 0 ? B_HL + wg : B_EP);
            mbar_wait(BAR(B_EP), 0);
            wg_wait<0>();
            reg_fence(aq);
            warp_arrive(BAR(B_A1D));
            uint32_t qf[8][2];
            #pragma unroll
            for (int c = 0; c < 7; c++) {
                qf[c + (c > 3)][0] = pack_bf16(aq[4 * c], aq[4 * c + 1]);
                qf[c + (c > 3)][1] = pack_bf16(aq[4 * c + 2], aq[4 * c + 3]);
            }
            qf[4][0] = t >= 2 ? qf[3][0] : 0u; qf[4][1] = t >= 2 ? qf[3][1] : 0u;
            qf[3][0] = t < 2 ? qf[3][0] : 0u;  qf[3][1] = t < 2 ? qf[3][1] : 0u;
            float sc[2][3][4];
            auto scores = [&](int n) {
                #pragma unroll
                for (int hd = 0; hd < 2; hd++) {
                    sc[hd][n][0] = sc[hd][n][1] = sc[hd][n][2] = sc[hd][n][3] = 0.f;
                    mma16816(sc[hd][n], qf[4 * hd][0], qf[4 * hd][1], qf[4 * hd + 1][0], qf[4 * hd + 1][1], kf[n][3 * hd], kf[n][3 * hd + 1]);
                    mma16816(sc[hd][n], qf[4 * hd + 2][0], qf[4 * hd + 2][1], qf[4 * hd + 3][0], qf[4 * hd + 3][1], kf[n][3 * hd + 2], kf[n][3 * hd + 3]);
                }
            };
            scores(1); scores(2);
            mbar_wait(hbar, 0);
            {
                const uint4 u0 = lds4(sr), u1 = lds4(sr + 512), u3 = lds4(sr + 1536), u2 = lds4(sr + 1024);
                kf[0][0] = u0.x; kf[0][1] = u0.y; kf[0][2] = u0.z; kf[0][3] = u0.w;
                vf[0][0] = u1.x; kf[0][4] = u1.y; kf[0][5] = u1.z; kf[0][6] = u1.w;
                vf[0][1] = u2.x; vf[0][2] = u2.y; vf[0][3] = u2.z; vf[0][4] = u2.w;
                vf[0][5] = u3.x; vf[0][6] = u3.y; rk[0][0] = __uint_as_float(u3.z); rk[0][1] = __uint_as_float(u3.w);
            }
            scores(0);
            const float ke0 = gt0 ? rk[0][0] : rk[1][0], ke1 = gt1 ? rk[0][1] : rk[1][1];
            const float se0 = ke0 * sq0, se1 = ke1 * sq0;
            uint32_t ow[7][2];
            #pragma unroll
            for (int hd = 0; hd < 2; hd++) {
                const int c0 = hd * 3;
                float (&sc_)[3][4] = sc[hd];
                const float e0 = fmaf(gt0 ? sc_[0][0] : sc_[1][0], se0, nb0), e1 = fmaf(gt1 ? sc_[0][1] : sc_[1][1], se1, nb1);
                const float f0 = (gt0 ? sc_[1][2] : sc_[2][2]) * sf0, f1 = (gt1 ? sc_[1][3] : sc_[2][3]) * sf1;
                const float me = quad_max(fmaxf(e0, e1)), mf = quad_max(fmaxf(f0, f1));
                const float p0 = ex2(e0 - me), p1 = ex2(e1 - me), r0 = ex2(f0 - mf), r1 = ex2(f1 - mf);
                const float ie = rcp(quad_sum(p0 + p1)), jf = rcp(quad_sum(r0 + r1));
                const uint32_t pp = pack_bf16(p0 * ke0 * ie, p1 * ke1 * ie), rp = pack_bf16(r0 * kf0 * jf, r1 * kf1 * jf);
                const uint32_t a0 = pp & ~mk, a1 = rp & mk, a3 = rp & ~mk, a4 = pp & mk, zero = pp & nil, zero2 = rp & nil;
                #pragma unroll
                for (int c = 0; c < 4; c++) {
                    float o[4] = {0.f, 0.f, 0.f, 0.f};
                    mma16816(o, a0, a1, zero, a3, vf[1][c0 + c], vf[2][c0 + c]);
                    mma1688(o, a4, zero2, vf[0][c0 + c]);
                    const uint32_t lo = pack_bf16(o[0], o[1]), hi = pack_bf16(o[2], o[3]);
                    if (hd == 1 && c == 0) { if (t >= 2) { ow[3][0] = lo; ow[3][1] = hi; } }
                    else { ow[c0 + c][0] = lo; ow[c0 + c][1] = hi; }
                }
            }
            #pragma unroll
            for (int c = 0; c < 7; c++) {
                stg1(op + c * 256,      set_par(ow[c][0], om0, tag));
                stg1(op + c * 256 + 32, set_par(ow[c][1], om1, tag));
            }
        }
        float as[28], ac[28];
        uint32_t xch, peer_xch, *gp1, *gp2;
        const uint32_t *hp, *ht;
        const uint2* hq;
        uint64_t da0, db0;
        bool lead;
        {
            float acc2[28];
            mbar_wait(BAR(B_XRF), 0);
            const int cg = a2j * 2 + wg, cg2 = (g2j + 2 * wg) * 2 + (rank ^ 1), cg1 = (g1j + 2 * wg) * 2 + (rank ^ (g1f < 14));
            lead = elect_one();
            {
                const uint32_t xa = sb + SM_XR + wg * 8192 + (w * 16 + (lane & 15)) * 128;
                #pragma unroll
                for (int c = 0; c < 4; c++) {
                    uint32_t xr[4];
                    asm volatile("ldmatrix.sync.aligned.m8n8.x4.shared.b16 {%0,%1,%2,%3}, [%4];"
                                 : "=r"(xr[0]), "=r"(xr[1]), "=r"(xr[2]), "=r"(xr[3])
                                 : "r"(xa + ((((c * 2 + wg + (lane >> 4)) ^ lane) & 7) << 4)) : "memory");
                    #pragma unroll
                    for (int e = 0; e < (c < 3 ? 4 : 2); e++) { acc2[8 * c + 2 * e] = bf_lo(xr[e]); acc2[8 * c + 2 * e + 1] = bf_hi(xr[e]); }
                }
            }
            uint32_t* spw = opaque_ptr(&prm.sc->stats[((a2s * 8 + cg) * 4 + w) * 32 + lane]);
            const uint32_t* spr = opaque_ptr(&prm.sc->stats[(a2s * 32 + w) * 32 + lane]);
            uint32_t* rp = opaque_ptr((uint32_t*)&prm.sc->rows[a2s * 64 + w * 16 + (t >> 1) * 8 + g] + (t & 1));
            const int cgs = cg ^ (a2s >> 4);
            uint32_t* np = opaque_ptr((uint32_t*)&prm.sc->hn[(a2s * 56 + cgs * 7) * 64] + w * 64 + lane);
            const uint64_t dwo = make_desc(sb + SM_WKV + wg * (28672 + 16), 0, true);
            const uint64_t doa = make_desc(sb + SM_WQ, 1024, false, 128);
            bias1a = prm.b1[g1f * 64 + w * 16 + g]; bias1b = prm.b1[g1f * 64 + w * 16 + 8 + g];
            const __nv_bfloat16 bias2 = prm.b2[ti * 128 + (w * 16 + (t >> 1) * 8 + g) * 2 + a2p];
            reg_fence(acc2);
            fence_async_smem();
            warp_arrive(BAR(B_XD));
            mbar_wait2(BAR(B_WOF), 0, BAR(B_WOF + 1), 0);
            mbar_wait(BAR(B_OD), 0);
            const uint32_t order = __shfl_sync(~0u, lds1(sb + SM_ORD), 0);
            static_for<0, 4>([&](auto P_) {
                constexpr int P = decltype(P_)::value;
                const uint64_t dwp = dwo + ((order >> (2 * P + 1) & 1) * 3584 + (order >> 2 * P & 1) * 896);
                mbar_wait(BAR(B_OF + P), 0);
                wg_fence();
                static_for<0, 7>([&](auto K_) { constexpr int k = decltype(K_)::value;
                    wgmma_ss_n56<P * 14336 + k * 2048, k * 2048, 0>(acc2, doa, dwp); });
                if (P) wg_commit();
                if (P == 2) { wg_wait<1>(); warp_arrive(BAR(B_OC)); }
            });
            wg_wait<0>();
            reg_fence(acc2);
            float s0 = 0.f, s1 = 0.f, q0 = 0.f, q1 = 0.f;
            #pragma unroll
            for (int c = 0; c < 7; c++) {
                s0 += acc2[4 * c] + acc2[4 * c + 1];     q0 = fmaf(acc2[4 * c], acc2[4 * c], fmaf(acc2[4 * c + 1], acc2[4 * c + 1], q0));
                s1 += acc2[4 * c + 2] + acc2[4 * c + 3]; q1 = fmaf(acc2[4 * c + 2], acc2[4 * c + 2], fmaf(acc2[4 * c + 3], acc2[4 * c + 3], q1));
            }
            const bool th = t >= 2, to = t & 1;
            const float sa = (th ? s1 : s0) + __shfl_xor_sync(~0u, th ? s0 : s1, 2), qa = (th ? q1 : q0) + __shfl_xor_sync(~0u, th ? q0 : q1, 2);
            const float part = (to ? qa : sa) + __shfl_xor_sync(~0u, to ? sa : qa, 1);
            stg1(spw, set_par(__float_as_uint(part), 1u, tag));
            const uint32_t tpoll = clk32() + SDELAY;
            warp_arrive(BAR(B_HD));
            uint32_t us[8];
            {
                xch = opaque(sb + SM_XCH + w * 1792 + lane * 16);
                asm volatile("mapa.shared::cluster.u32 %0, %1, %2;" : "=r"(peer_xch) : "r"(xch), "r"(rank ^ 1));
                const int hcg = cg2 ^ (g2s >> 4), hrg = (g2s & 1) * 4 + w;
                const uint32_t* hl = (const uint32_t*)&prm.sc->hn[((g2s >> 1) * 112 + hcg * 7) * 64 + hrg * 8];
                hp = opaque_ptr(hl + (g & 1) * 14336 + (g >> 1) * 4 + t);
                ht = opaque_ptr(hl + (lane & 1) * 14336 + min(lane >> 1, 6) * 256 + hrg);
                hq = opaque_ptr(&prm.sc->rows[((g2s >> 1) * 2 + (g & 1)) * 64 + hrg * 8 + (g >> 1)]);
                gp1 = opaque_ptr((uint32_t*)&prm.sc->g[(g1f * 56 + cg1 * 7) * 64] + w * 64 + lane);
                gp2 = opaque_ptr((uint32_t*)(prm.out + (size_t)(g2s * 64 + w * 16 + lane / 7) * kD + cg2 * 56) + (lane % 7) * 4);
                da0 = make_desc(sb, 0, true); db0 = make_desc(sb + SM_B, 128, false);
            }
            spin_until(tpoll);
            #pragma unroll
            for (int i = 0; i < 8; i++) us[i] = ld_rlx(spr + i * 128);
            {
                int it = 0;
                while (true) {
                    uint32_t bad = 0;
                    #pragma unroll
                    for (int i = 0; i < 8; i++) bad |= us[i] ^ tag;
                    if (!__any_sync(~0u, bad & 1)) break;
                    if (++it > kSpinLimit) break;
                    #pragma unroll
                    for (int i = 0; i < 8; i++) us[i] = ld_rlx(spr + i * 128);
                }
            }
            const float tot = (((__uint_as_float(us[0]) + __uint_as_float(us[1])) + (__uint_as_float(us[2]) + __uint_as_float(us[3])))
                            + ((__uint_as_float(us[4]) + __uint_as_float(us[5])) + (__uint_as_float(us[6]) + __uint_as_float(us[7])))) * (1.f / kD);
            const float oth = __shfl_xor_sync(~0u, tot, 1);
            const float mean = to ? oth : tot;
            const float var = fmaxf(fmaf(-mean, mean, to ? tot : oth), 0.f);
            const float rra = rsq(fmaf(var, 4.f + 4.f * kEps, 4.f * kEps * kEps)), mra = -mean * rra;
            const float rrb = __shfl_xor_sync(~0u, rra, 2), mrb = __shfl_xor_sync(~0u, mra, 2);
            const float rr0 = th ? rrb : rra, mr0 = th ? mrb : mra, rr1 = th ? rra : rrb, mr1 = th ? mra : mrb;
            #pragma unroll
            for (int c = 0; c < 7; c++) {
                stg1(np + c * 256,      set_par(pack_bf16(fmaf(acc2[4 * c], rr0, mr0), fmaf(acc2[4 * c + 1], rr0, mr0)), om0, tag));
                stg1(np + c * 256 + 32, set_par(pack_bf16(fmaf(acc2[4 * c + 2], rr1, mr1), fmaf(acc2[4 * c + 3], rr1, mr1)), om1, tag));
            }
            if (cg == 0) stg1(rp, set_par(__float_as_uint(to ? mean + __bfloat162float(bias2) : rcp(rra)), 1u, tag));
            #pragma unroll
            for (int c = 0; c < 28; c++) { ac[c] = 0.5f * __bfloat162float(c & 2 ? bias1b : bias1a); as[c] = 0.f; }
            reg_fence(as); reg_fence(ac);
        }
        auto send = [&]() {
            const uint32_t rf = pbar0 + (B_RF + warp) * 8;
            #pragma unroll
            for (int c = 0; c < 4; c++) {
                const uint32_t p0 = pack_bf16(as[8 * c], as[8 * c + 1]), p1 = pack_bf16(as[8 * c + 2], as[8 * c + 3]);
                if (c < 3) {
                    const uint32_t p2 = pack_bf16(as[8 * c + 4], as[8 * c + 5]), p3 = pack_bf16(as[8 * c + 6], as[8 * c + 7]);
                    asm volatile("st.async.shared::cluster.mbarrier::complete_tx::bytes.v4.b32 [%0], {%1,%2,%3,%4}, [%5];"
                                 :: "r"(peer_xch + c * 512), "r"(p0), "r"(p1), "r"(p2), "r"(p3), "r"(rf) : "memory");
                } else {
                    asm volatile("st.async.shared::cluster.mbarrier::complete_tx::bytes.v2.b32 [%0], {%1,%2}, [%3];"
                                 :: "r"(peer_xch + 1536 - lane * 8), "r"(p0), "r"(p1), "r"(rf) : "memory");
                }
            }
        };
        auto receive = [&](uint32_t (&pk)[14], uint32_t phase) {
            mbar_wait(BAR(B_RF + warp), phase);
            #pragma unroll
            for (int c = 0; c < 3; c++) { const uint4 u = lds4(xch + c * 512); pk[4 * c] = u.x; pk[4 * c + 1] = u.y; pk[4 * c + 2] = u.z; pk[4 * c + 3] = u.w; }
            const uint2 u = lds2(xch + 1536 - lane * 8); pk[12] = u.x; pk[13] = u.y;
        };
        uint2 rw[2]; uint32_t tw;
        auto load_rows = [&]() { tw = ld_rlx(ht); rw[0] = ld_rlx2(hq); rw[1] = ld_rlx2(hq + 4); };
        rw[0] = rw[1] = make_uint2(0u, 0u); tw = ~tag;
        #pragma unroll 1
        for (int ge = 0;; ge++) {
          if (ge || g1_on) {
            const int use = ge * 2 + wg;
            int entry = ge ? 1 : 2 * wg, stop = 0;
            uint64_t da = da0 + (ge ? -3 : wg ? NR - 10 : 0) * 512;
            bool rel = lead && use == 1;
            const uint32_t xfree = BAR(use > (g1_on ? 0 : 2) ? B_RE + use - 1 : B_PD);
            mbar_wait(BAR(B_AF), 0);
            if (ge && (wg || g1_on)) named_bar(5 - wg, 256);
            auto step = [&](auto I_) {
                constexpr int i = decltype(I_)::value, sl = i % NB, ao = i * 8192, bo = sl * 14336;
                mbar_wait_fast(BAR(B_BF + sl), i / NB);
                wg_fence();
                wgmma_ss_n112<ao,        bo,       1>(as, ac, da, db0);
                wgmma_ss_n112<ao + 2048, bo + 256, 1>(as, ac, da, db0);
                wgmma_ss_n112<ao + 4096, bo + 512, 1>(as, ac, da, db0);
                wgmma_ss_n112<ao + 6144, bo + 768, 1>(as, ac, da, db0);
                wg_commit();
                if (i == 1 && stop == 1) named_arrive(4, 256);
                if (i == 3 && (use == 1 || use == 2)) named_arrive(4 + wg, 256);
                wg_wait<1>();
                mbar_arrive_if(BAR(B_BE + (13 + i) % 14), rel);
                rel = lead;
            };
            #pragma unroll 1
            while (true) {
                if (entry < 1) {
                    static_for<0, 2>(step);
                    if (stop == 1) break;
                    static_for<2, 4>(step);
                    if (stop) break;
                }
                if (entry < 2) static_for<4, 10>(step);
                else {
                    uint32_t af[NR * 4][4];
                    mbar_wait(BAR(B_GO), 0);
                    const uint32_t tp = lds1(sb + SM_TG + 4) + PLOFF;
                    int it = 0;
                    while ((int)(gtime32() - tp) < 0 && ++it < 256) __nanosleep(20);
                    const uint32_t la = sb + ((lane >> 4) * 8 + (lane & 7)) * 128 + (((w * 2 + ((lane >> 3) & 1)) ^ (lane & 7)) << 4);
                    #pragma unroll
                    for (int k = 0; k < NR * 4; k++)
                        asm volatile("ldmatrix.sync.aligned.m8n8.x4.trans.shared.b16 {%0,%1,%2,%3}, [%4];"
                                     : "=r"(af[k][0]), "=r"(af[k][1]), "=r"(af[k][2]), "=r"(af[k][3]) : "r"(la + k * 2048) : "memory");
                    __syncwarp();
                    mbar_arrive_if(BAR(B_PL), lead);
                    if (w == 0) {
                        const char* p2 = (const char*)prm.w2 + ((b >> 6) * 896 + (b & 63) + PFW * 64) * 4096 + lane * 128;
                        #pragma unroll 1
                        for (int i = 0; i < 14 - PFW; i++) {
                            it = 0;
                            while ((int)(gtime32() - tp) < PF3OFF + i * PF3PACE && ++it < 256) __nanosleep(40);
                            asm volatile("prefetch.global.L2 [%0];" :: "l"(p2 + i * 64 * 4096));
                        }
                    }
                    named_bar(4, 256);
                    static_for<0, NR>([&](auto I_) {
                        constexpr int i = decltype(I_)::value, sl = (16 + i) % NB, o = sl * 14336;
                        mbar_wait_fast(BAR(B_BF + sl), (16 + i) / NB & 1);
                        wg_fence();
                        wgmma_rs_n112<o,       1>(as, ac, af[4 * i][0], af[4 * i][1], af[4 * i][2], af[4 * i][3], db0);
                        wgmma_rs_n112<o + 256, 1>(as, ac, af[4 * i + 1][0], af[4 * i + 1][1], af[4 * i + 1][2], af[4 * i + 1][3], db0);
                        wgmma_rs_n112<o + 512, 1>(as, ac, af[4 * i + 2][0], af[4 * i + 2][1], af[4 * i + 2][2], af[4 * i + 2][3], db0);
                        wgmma_rs_n112<o + 768, 1>(as, ac, af[4 * i + 3][0], af[4 * i + 3][1], af[4 * i + 3][2], af[4 * i + 3][3], db0);
                        wg_commit();
                        if (i) { wg_wait<1>(); mbar_arrive_if(BAR(B_BE + (15 + i) % (2 * NB)), lead); }
                    });
                }
                static_for<10, 14>(step);
                entry = 0; stop = use + 1; da += 14 * 512;
            }
            const uint32_t prev = BAR(B_BE + (use ? 3 : 1));
            const bool xok = mbar_test(xfree, 0);
            wg_wait<0>();
            reg_fence(as); reg_fence(ac);
            mbar_arrive_if(prev, lead);
            if (!xok) mbar_wait(xfree, 0);
            if (ge) break;
            send();
            load_rows();
            uint32_t pk[14];
            receive(pk, 0);
            #pragma unroll
            for (int c = 0; c < 14; c++) {
                float r[2];
                #pragma unroll
                for (int e = 0; e < 2; e++) {
                    const float u = ac[2 * c + e] + (e ? bf_hi(pk[c]) : bf_lo(pk[c]));
                    r[e] = fmaf(u, tanh_hw(u * fmaf(u * u, 8.f * 0.7978845608f * 0.044715f, 2.f * 0.7978845608f)), u);
                }
                stg1(gp1 + (c >> 1) * 256 + (c & 1) * 32, set_par(pack_bf16(r[0], r[1]), c & 1 ? om1 : om0, tag));
            }
            named_bar(1 + wg, 128);
            if (w == 0 && lane == 0) {
                asm volatile("st.shared.u32 [%0], %1;" :: "r"(sb + SM_TG + 8 + wg * 4), "r"(clk32() + (wg ? XSPECB : XSPEC)) : "memory");
                mbar_arrive(BAR(B_GD + wg));
            }
            if (lead) mbar_expect(BAR(B_RF + warp), 1792);
            mbar_arrive_remote_if(pbar0 + (B_RE + wg) * 8, lead);
          } else mbar_wait(BAR(B_GD), 0);
            {
                int it = 0;
                while (__any_sync(~0u, ((tw ^ tag) | (rw[0].x ^ tag) | (rw[0].y ^ tag) | (rw[1].x ^ tag) | (rw[1].y ^ tag)) & 1)) {
                    if (++it > kSpinLimit) break;
                    load_rows();
                }
                uint32_t hw[14];
                #pragma unroll
                for (int c = 0; c < 14; c++) hw[c] = ld_rlx(hp + (c >> 1) * 256 + (c & 1) * 16);
                #pragma unroll
                for (int c = 0; c < 14; c++) {
                    ac[2 * c]     = fmaf(bf_lo(hw[c]), __uint_as_float(rw[c & 1].x), __uint_as_float(rw[c & 1].y));
                    ac[2 * c + 1] = fmaf(bf_hi(hw[c]), __uint_as_float(rw[c & 1].x), __uint_as_float(rw[c & 1].y));
                    as[2 * c] = as[2 * c + 1] = 0.f;
                }
                reg_fence(as); reg_fence(ac);
            }
        }
        uint32_t po[14], pk[14];
        if (!wg) sleep_until(clk32() + w * STAG2);
        send();
        #pragma unroll
        for (int c = 0; c < 14; c++) po[c] = opaque(pack_bf16(ac[2 * c], ac[2 * c + 1]));
        receive(pk, g1_on);
        #pragma unroll
        for (int c = 0; c < 14; c++) pk[c] = add_bf16x2(po[c], pk[c]);
        __syncwarp();
        const uint32_t sa = xch - lane * 16 + (lane & 15) * 112 + (lane >> 4) * 16;
        #pragma unroll
        for (int m = 0; m < 3; m++)
            asm volatile("stmatrix.sync.aligned.m8n8.x4.shared.b16 [%0], {%1,%2,%3,%4};"
                         :: "r"(sa + m * 32), "r"(pk[4 * m]), "r"(pk[4 * m + 1]), "r"(pk[4 * m + 2]), "r"(pk[4 * m + 3]) : "memory");
        asm volatile("stmatrix.sync.aligned.m8n8.x2.shared.b16 [%0], {%1,%2};" :: "r"(sa + 96), "r"(pk[12]), "r"(pk[13]) : "memory");
        __syncwarp();
        if (lane < 28) {
            #pragma unroll
            for (int i = 0; i < 4; i++) { const uint4 u = lds4(xch + i * 448); stg4(gp2 + i * 896, u.x, u.y, u.z, u.w); }
        }
        __syncwarp();
        mbar_arrive_remote_if(pbar0 + (B_RE + 2) * 8, lead && wg == 0);
        if (b == 0 && tid == 128) prm.sc->epoch = tag;
    }
}

typedef CUresult (*EncodeFn)(CUtensorMap*, CUtensorMapDataType, cuuint32_t, void*, const cuuint64_t*, const cuuint64_t*,
                             const cuuint32_t*, const cuuint32_t*, CUtensorMapInterleave, CUtensorMapSwizzle,
                             CUtensorMapL2promotion, CUtensorMapFloatOOBfill);

void make_map(EncodeFn enc, CUtensorMap* m, const void* base, uint64_t cols, uint64_t rows, uint32_t box_rows) {
    cuuint64_t dims[2] = {cols, rows};
    cuuint64_t strides[1] = {cols * 2};
    cuuint32_t box[2] = {64, box_rows};
    cuuint32_t es[2] = {1, 1};
    enc(m, CU_TENSOR_MAP_DATA_TYPE_BFLOAT16, 2, const_cast<void*>(base), dims, strides, box, es, CU_TENSOR_MAP_INTERLEAVE_NONE,
        CU_TENSOR_MAP_SWIZZLE_128B, CU_TENSOR_MAP_L2_PROMOTION_L2_128B, CU_TENSOR_MAP_FLOAT_OOB_FILL_NONE);
}

}

extern "C" void kernel_launch(void* const* d_in, const int* in_sizes, int n_in, void* d_out, int out_size) {
    (void)in_sizes; (void)n_in; (void)out_size;
    void* fn = nullptr;
    cudaDriverEntryPointQueryResult qr;
    cudaGetDriverEntryPoint("cuTensorMapEncodeTiled", &fn, cudaEnableDefault, &qr);
    EncodeFn enc = (EncodeFn)fn;
    CUtensorMap mX2, mX, mWqkv, mWo, mW1, mW2;
    {
        cuuint64_t dims[3] = {kD, kS / 2, 2}, strides[2] = {4 * kD, 2 * kD};
        cuuint32_t box[3] = {64, 64, 2}, es[3] = {1, 1, 1};
        enc(&mX2, CU_TENSOR_MAP_DATA_TYPE_BFLOAT16, 3, d_in[0], dims, strides, box, es, CU_TENSOR_MAP_INTERLEAVE_NONE,
            CU_TENSOR_MAP_SWIZZLE_128B, CU_TENSOR_MAP_L2_PROMOTION_L2_128B, CU_TENSOR_MAP_FLOAT_OOB_FILL_NONE);
    }
    make_map(enc, &mX, d_in[0], 2 * kD, kS / 2, 64);
    make_map(enc, &mWqkv, d_in[1], 3 * kD, kD, 64);
    make_map(enc, &mWo, d_in[2], kD, kD, 112);
    make_map(enc, &mW1, d_in[4], 2 * kF, kS / 2, 64);
    make_map(enc, &mW2, d_in[6], kS, kF, 64);
    Params prm;
    prm.x = (const __nv_bfloat16*)d_in[0];
    prm.wqkv = (const __nv_bfloat16*)d_in[1];
    prm.wo = (const __nv_bfloat16*)d_in[2];
    prm.w1 = (const __nv_bfloat16*)d_in[4];
    prm.b1 = (const __nv_bfloat16*)d_in[5];
    prm.w2 = (const __nv_bfloat16*)d_in[6];
    prm.b2 = (const __nv_bfloat16*)d_in[7];
    prm.out = (__nv_bfloat16*)d_out;
    cudaGetSymbolAddress((void**)&prm.sc, g_scratch);
    cudaFuncSetAttribute(fused_kernel, cudaFuncAttributeMaxDynamicSharedMemorySize, SM_TOTAL);
    fused_kernel<<<128, 384, SM_TOTAL, cudaStreamPerThread>>>(prm, mX2, mX, mWqkv, mWo, mW1, mW2);
}
```

```cpp
#include <cuda_runtime.h>
#include <cuda.h>
#include <cuda_bf16.h>
#include <stdint.h>
#include <type_traits>

namespace {

constexpr int kS = 2048, kD = 448, kF = 1792;
constexpr float kEps = 1e-5f;

constexpr int FS = 32;
constexpr int NPRE = 10;
constexpr int NR = 8;
constexpr int PFW = 4;
constexpr int QC0 = 4;
constexpr int QC1 = 10;
constexpr int QC2 = 16;
constexpr int PFD = 250;
constexpr int PFPACE = 280;
constexpr int PFPACE2 = 300;
constexpr int HDELAY = 200;
constexpr int WOD = 350;
constexpr int SDELAY = 200;
constexpr int PDELAY = 400;
constexpr int PACE1 = 120;
constexpr int PACE2 = 400;
constexpr int PACEB = 300;
constexpr int XSPEC = 500;
constexpr int XSPECB = 750;
constexpr int CN2 = 7400;
constexpr int CN3 = 11400;
constexpr int W2OFF = 800;
constexpr int W2PACE = 350;
constexpr int STAG2 = 550;
constexpr int QLNS = 256;
constexpr int DELTAO = 800;
constexpr int DMIN = 448;
constexpr int XDNS = 32;
constexpr int CHUNKNS = 250;
constexpr int DELTA = 2016;
constexpr int PLOFF = -250;
constexpr int PF3OFF = 300;
constexpr int PF3PACE = 240;

struct Scratch {
    uint32_t flag_o[16 * 8 * FS];
    uint4    o[32 * 56 * 64];
    uint32_t stats[32 * 8 * 4 * 32];
    uint4    hn[32 * 56 * 64];
    uint32_t flag_h[32 * 4 * FS];
    uint4    g[28 * 56 * 64];
    uint4    halo[8 * 8 * 2 * 4 * 32];
    uint2    rows[32 * 64];
    uint32_t epoch;
};
__device__ __align__(1024) Scratch g_scratch;

constexpr uint32_t SM_WKV  = 114688;
constexpr uint32_t SM_XR   = 24576;
constexpr uint32_t SM_STG  = 40960;
constexpr uint32_t SM_WQ   = 57344;
constexpr uint32_t SM_XCH  = 0;
constexpr uint32_t SM_B    = 131072;
constexpr uint32_t SM_BAR  = 231424;
constexpr uint32_t SM_TOTAL = SM_BAR + 1024;
constexpr int NB = 7;
constexpr int B_XF = 0, B_WKVF = 7, B_WQF = 14, B_XRF = 15, B_WOF = 16,
              B_XC = 18, B_KV3 = 19, B_KVC = 20,
              B_A1D = 21, B_XD = 22, B_OC = 23, B_QL = 24,
              B_BE = 25  , B_RE = B_BE + 2 * NB,
              B_PL = B_RE + 3, B_AF = B_PL + 1, B_BL = B_AF + 1  , B_OL = B_BL + 2 * NB  ,
              B_BF = B_OL + 4  , B_OF = B_BF + NB, B_RF = B_OF + 4, B_EP = B_RF + 8, B_PD = B_EP + 1, B_OD = B_PD + 1, B_RT = B_OD + 1, B_HL = B_RT + 2,
              B_HD = B_HL + 2  , B_GO = B_HD + 1, B_GD = B_GO + 1, B_COUNT = B_GD + 2;
constexpr uint32_t SM_EPOCH = SM_BAR + B_COUNT * 8, SM_TG = SM_EPOCH + 4  , SM_TG2 = SM_TG + 16  ,
                   SM_ORD = SM_TG2 + 4  ;

constexpr uint64_t kAPos = 0x3330ull | 0x5555555ull << 17;
constexpr uint32_t seg_mask(int h, int p0, int p1) {
    uint32_t m = 0; int n = 0;
    for (int p = p0; p < p1; p++) if ((p & 1) == h) m |= (uint32_t)((kAPos >> p) & 1) << n++;
    return m | 1u << n;
}
constexpr uint64_t seg_masks(int h) {
    return 2 | (uint64_t)seg_mask(h, 0, 16) << 10 | (uint64_t)seg_mask(h, 16, 32) << 20
             | (uint64_t)seg_mask(h, 32, 46) << 30 | (uint64_t)seg_mask(h, 46, 60) << 40;
}
constexpr uint64_t kSegMasks0 = seg_masks(0), kSegMasks1 = seg_masks(1);

constexpr int kSpinLimit = 1 << 15;
__device__ __forceinline__ bool elect_one() {
    uint32_t p;
    asm volatile("{ .reg .pred P; elect.sync _|P, 0xffffffff; selp.u32 %0, 1, 0, P; }" : "=r"(p));
    return p;
}
__device__ __forceinline__ void mbar_init(uint32_t bar, uint32_t cnt) { asm volatile("mbarrier.init.shared::cta.b64 [%0], %1;" :: "r"(bar), "r"(cnt)); }
__device__ __forceinline__ void mbar_expect(uint32_t bar, uint32_t bytes) { asm volatile("mbarrier.arrive.expect_tx.shared::cta.b64 _, [%0], %1;" :: "r"(bar), "r"(bytes) : "memory"); }
__device__ __forceinline__ void mbar_expect_more(uint32_t bar, uint32_t bytes) { asm volatile("mbarrier.expect_tx.relaxed.cta.shared::cta.b64 [%0], %1;" :: "r"(bar), "r"(bytes) : "memory"); }
__device__ __forceinline__ void mbar_arrive(uint32_t bar) { asm volatile("mbarrier.arrive.shared::cta.b64 _, [%0];" :: "r"(bar) : "memory"); }
__device__ __forceinline__ void mbar_wait(uint32_t bar, uint32_t parity) {
    uint32_t ok; int it = 0;
    do {
        asm volatile("{ .reg .pred p; mbarrier.try_wait.parity.shared::cta.b64 p, [%1], %2; selp.u32 %0, 1, 0, p; }"
                     : "=r"(ok) : "r"(bar), "r"(parity) : "memory");
        if (++it > kSpinLimit) break;
    } while (!ok);
}
__device__ __forceinline__ bool mbar_try(uint32_t bar, uint32_t parity) {
    uint32_t ok;
    asm volatile("{ .reg .pred p; mbarrier.try_wait.parity.shared::cta.b64 p, [%1], %2; selp.u32 %0, 1, 0, p; }" : "=r"(ok) : "r"(bar), "r"(parity) : "memory");
    return ok;
}
__device__ __forceinline__ bool mbar_test(uint32_t bar, uint32_t parity) {
    uint32_t ok;
    asm volatile("{ .reg .pred p; mbarrier.test_wait.parity.shared::cta.b64 p, [%1], %2; selp.u32 %0, 1, 0, p; }" : "=r"(ok) : "r"(bar), "r"(parity) : "memory");
    return ok;
}
__device__ __forceinline__ void mbar_wait_fast(uint32_t bar, uint32_t parity) { if (!mbar_try(bar, parity)) mbar_wait(bar, parity); }
__device__ __forceinline__ void mbar_wait2(uint32_t bar0, uint32_t par0, uint32_t bar1, uint32_t par1) {
    uint32_t ok; int it = 0;
    do {
        asm volatile("{ .reg .pred p, q; mbarrier.try_wait.parity.shared::cta.b64 p, [%1], %2;\n"
                     "mbarrier.try_wait.parity.shared::cta.b64 q, [%3], %4; and.pred p, p, q; selp.u32 %0, 1, 0, p; }"
                     : "=r"(ok) : "r"(bar0), "r"(par0), "r"(bar1), "r"(par1) : "memory");
        if (++it > kSpinLimit) break;
    } while (!ok);
}
template <int N> __device__ __forceinline__ void reg_fence(float (&d)[N]) {
    #pragma unroll
    for (int i = 0; i < N; i++) asm volatile("" : "+f"(d[i]) :: "memory");
}
__device__ __forceinline__ void mbar_arrive_if(uint32_t bar, bool pred) {
    asm volatile("{ .reg .pred p; setp.ne.u32 p, %1, 0; @p mbarrier.arrive.shared::cta.b64 _, [%0]; }" :: "r"(bar), "r"((uint32_t)pred) : "memory");
}
__device__ __forceinline__ void warp_arrive(uint32_t bar) { __syncwarp(); if (elect_one()) mbar_arrive(bar); }
__device__ __forceinline__ void tma2d(uint32_t dst, const CUtensorMap* m, int c0, int c1, uint32_t bar) {
    asm volatile("cp.async.bulk.tensor.2d.shared::cluster.global.mbarrier::complete_tx::bytes [%0], [%1, {%3, %4}], [%2];"
                 :: "r"(dst), "l"(m), "r"(bar), "r"(c0), "r"(c1) : "memory");
}
__device__ __forceinline__ void tma3d(uint32_t dst, const CUtensorMap* m, int c0, int c1, int c2, uint32_t bar) {
    asm volatile("cp.async.bulk.tensor.3d.shared::cluster.global.mbarrier::complete_tx::bytes [%0], [%1, {%3, %4, %5}], [%2];"
                 :: "r"(dst), "l"(m), "r"(bar), "r"(c0), "r"(c1), "r"(c2) : "memory");
}
__device__ __forceinline__ void tma2d_mc(uint32_t dst, const CUtensorMap* m, int c0, int c1, uint32_t bar) {
    asm volatile("cp.async.bulk.tensor.2d.shared::cluster.global.mbarrier::complete_tx::bytes.multicast::cluster [%0], [%1, {%3, %4}], [%2], %5;"
                 :: "r"(dst), "l"(m), "r"(bar), "r"(c0), "r"(c1), "h"((uint16_t)3) : "memory");
}
__device__ __forceinline__ void mbar_arrive_remote_if(uint32_t cluster_bar, bool pred) {
    asm volatile("{ .reg .pred p; setp.ne.u32 p, %1, 0; @p mbarrier.arrive.shared::cluster.b64 _, [%0]; }" :: "r"(cluster_bar), "r"((uint32_t)pred) : "memory");
}
__device__ __forceinline__ void bulk_g2s(uint32_t dst, const void* src, uint32_t bytes, uint32_t bar) {
    asm volatile("cp.async.bulk.shared::cluster.global.mbarrier::complete_tx::bytes [%0], [%1], %2, [%3];"
                 :: "r"(dst), "l"(src), "r"(bytes), "r"(bar) : "memory");
}
__device__ __forceinline__ void bulk_prefetch(const void* src, uint32_t bytes) { asm volatile("cp.async.bulk.prefetch.L2.global [%0], %1;" :: "l"(src), "r"(bytes) : "memory"); }
__device__ __forceinline__ void wg_fence()  { asm volatile("wgmma.fence.sync.aligned;" ::: "memory"); }
__device__ __forceinline__ void wg_commit() { asm volatile("wgmma.commit_group.sync.aligned;" ::: "memory"); }
template <int N> __device__ __forceinline__ void wg_wait() { asm volatile("wgmma.wait_group.sync.aligned %0;" :: "n"(N) : "memory"); }
__device__ __forceinline__ void named_bar(int id, int n) { asm volatile("bar.sync %0, %1;" :: "r"(id), "r"(n) : "memory"); }
__device__ __forceinline__ void named_arrive(int id, int n) { asm volatile("bar.arrive %0, %1;" :: "r"(id), "r"(n) : "memory"); }
__device__ __forceinline__ void fence_async_smem() { asm volatile("fence.proxy.async.shared::cta;" ::: "memory"); }
__device__ __forceinline__ uint32_t gtime32() { uint64_t t; asm volatile("mov.u64 %0, %%globaltimer;" : "=l"(t) :: "memory"); return (uint32_t)t; }
__device__ __forceinline__ uint32_t clk32() { uint64_t t; asm volatile("mov.u64 %0, %%clock64;" : "=l"(t) :: "memory"); return (uint32_t)t; }
__device__ __forceinline__ void spin_until(uint32_t t) { while ((int)(clk32() - t) < 0) {} }
__device__ __forceinline__ void sleep_until(uint32_t t) { while ((int)(clk32() - t) < 0) __nanosleep(20); }
__device__ __forceinline__ void st_flag(uint32_t* p, uint32_t v, uint32_t time) {
    const uint64_t w = ((uint64_t)time << 32) | v;
    asm volatile("st.relaxed.gpu.global.u64 [%0], %1;" :: "l"(p), "l"(w) : "memory");
}
__device__ __forceinline__ void ld_flag_if(uint64_t& v, const uint32_t* p, bool pred) {
    asm volatile("{ .reg .pred p; setp.ne.u32 p, %2, 0; @p ld.relaxed.gpu.global.u64 %0, [%1]; }" : "+l"(v) : "l"(p), "r"((uint32_t)pred) : "memory");
}
__device__ __forceinline__ uint32_t ld_rlx(const uint32_t* p) { uint32_t v; asm volatile("ld.relaxed.gpu.global.u32 %0, [%1];" : "=r"(v) : "l"(p) : "memory"); return v; }
template <class T> __device__ __forceinline__ T* opaque_ptr(T* p) { asm volatile("" : "+l"(p)); return p; }
__device__ __forceinline__ uint4 ld_rlx4(const uint4* p) {
    uint4 v; asm volatile("ld.relaxed.gpu.global.v4.u32 {%0,%1,%2,%3}, [%4];" : "=r"(v.x), "=r"(v.y), "=r"(v.z), "=r"(v.w) : "l"(p) : "memory"); return v;
}
__device__ __forceinline__ uint2 ld_rlx2(const uint2* p) {
    uint2 v; asm volatile("ld.relaxed.gpu.global.v2.u32 {%0,%1}, [%2];" : "=r"(v.x), "=r"(v.y) : "l"(p) : "memory"); return v;
}
__device__ __forceinline__ void stg1(uint32_t* p, uint32_t v) { asm volatile("st.global.u32 [%0], %1;" :: "l"(p), "r"(v) : "memory"); }
__device__ __forceinline__ void stg4(void* p, uint32_t x, uint32_t y, uint32_t z, uint32_t w) { asm volatile("st.global.v4.u32 [%0], {%1,%2,%3,%4};" :: "l"(p), "r"(x), "r"(y), "r"(z), "r"(w) : "memory"); }
__device__ __forceinline__ uint32_t lds1(uint32_t a) { uint32_t v; asm volatile("ld.shared.u32 %0, [%1];" : "=r"(v) : "r"(a) : "memory"); return v; }
__device__ __forceinline__ uint2 lds2(uint32_t a) { uint2 v; asm volatile("ld.shared.v2.u32 {%0,%1}, [%2];" : "=r"(v.x), "=r"(v.y) : "r"(a) : "memory"); return v; }
__device__ __forceinline__ uint32_t set_par(uint32_t v, uint32_t mask, uint32_t par) {
    uint32_t r; asm("lop3.b32 %0, %1, %2, %3, 0xb8;" : "=r"(r) : "r"(v), "r"(mask), "r"(par)); return r;
}
__device__ __forceinline__ void st_gen4(void* p, uint32_t x, uint32_t y, uint32_t z, uint32_t w) { asm volatile("st.v4.u32 [%0], {%1,%2,%3,%4};" :: "l"(p), "r"(x), "r"(y), "r"(z), "r"(w) : "memory"); }
__device__ __forceinline__ float tanh_hw(float x) { float r; asm("tanh.approx.f32 %0, %1;" : "=f"(r) : "f"(x)); return r; }
__device__ __forceinline__ void sts4(uint32_t a, uint32_t x, uint32_t y, uint32_t z, uint32_t w) { asm volatile("st.shared.v4.u32 [%0], {%1,%2,%3,%4};" :: "r"(a), "r"(x), "r"(y), "r"(z), "r"(w) : "memory"); }
__device__ __forceinline__ uint4 lds4(uint32_t a) { uint4 v; asm volatile("ld.shared.v4.u32 {%0,%1,%2,%3}, [%4];" : "=r"(v.x), "=r"(v.y), "=r"(v.z), "=r"(v.w) : "r"(a) : "memory"); return v; }
__device__ __forceinline__ void ldsm4(uint32_t (&f)[4], uint32_t a) {
    asm volatile("ldmatrix.sync.aligned.m8n8.x4.shared.b16 {%0,%1,%2,%3}, [%4];" : "=r"(f[0]), "=r"(f[1]), "=r"(f[2]), "=r"(f[3]) : "r"(a) : "memory");
}
__device__ __forceinline__ void stsm4(uint32_t a, uint32_t x, uint32_t y, uint32_t z, uint32_t w) {
    asm volatile("stmatrix.sync.aligned.m8n8.x4.shared.b16 [%0], {%1,%2,%3,%4};" :: "r"(a), "r"(x), "r"(y), "r"(z), "r"(w) : "memory");
}
__device__ __forceinline__ uint32_t pack_bf16(float lo, float hi) { uint32_t r; asm("cvt.rn.bf16x2.f32 %0, %1, %2;" : "=r"(r) : "f"(hi), "f"(lo)); return r; }
__device__ __forceinline__ float bf_lo(uint32_t v) { return __uint_as_float(v << 16); }
__device__ __forceinline__ float bf_hi(uint32_t v) { return __uint_as_float(v & 0xffff0000u); }
__device__ __forceinline__ uint32_t sub_bf16x2(uint32_t a, uint32_t b) { uint32_t r; asm volatile("sub.rn.bf16x2 %0, %1, %2;" : "=r"(r) : "r"(a), "r"(b)); return r; }
__device__ __forceinline__ uint32_t add_bf16x2(uint32_t a, uint32_t b) { uint32_t r; asm volatile("add.rn.bf16x2 %0, %1, %2;" : "=r"(r) : "r"(a), "r"(b)); return r; }
__device__ __forceinline__ uint32_t sqr_bf16x2(uint32_t a) { uint32_t r; asm volatile("mul.rn.bf16x2 %0, %1, %1;" : "=r"(r) : "r"(a)); return r; }
__device__ __forceinline__ uint32_t sqa_bf16x2(uint32_t a, uint32_t c) { uint32_t r; asm volatile("fma.rn.bf16x2 %0, %1, %1, %2;" : "=r"(r) : "r"(a), "r"(c)); return r; }
__device__ __forceinline__ uint32_t movm(uint32_t a) { uint32_t r; asm volatile("movmatrix.sync.aligned.m8n8.trans.b16 %0, %1;" : "=r"(r) : "r"(a)); return r; }
__device__ __forceinline__ float ex2(float x) { float r; asm("ex2.approx.ftz.f32 %0, %1;" : "=f"(r) : "f"(x)); return r; }
__device__ __forceinline__ float rsq(float x) { float r; asm("rsqrt.approx.ftz.f32 %0, %1;" : "=f"(r) : "f"(x)); return r; }
__device__ __forceinline__ float rcp(float x) { float r; asm("rcp.approx.ftz.f32 %0, %1;" : "=f"(r) : "f"(x)); return r; }
__device__ __forceinline__ void mma16816(float (&c)[4], uint32_t a0, uint32_t a1, uint32_t a2, uint32_t a3, uint32_t b0, uint32_t b1) {
    asm("mma.sync.aligned.m16n8k16.row.col.f32.bf16.bf16.f32 {%0,%1,%2,%3}, {%4,%5,%6,%7}, {%8,%9}, {%0,%1,%2,%3};"
        : "+f"(c[0]), "+f"(c[1]), "+f"(c[2]), "+f"(c[3]) : "r"(a0), "r"(a1), "r"(a2), "r"(a3), "r"(b0), "r"(b1));
}
__device__ __forceinline__ void mma1688(float (&c)[4], uint32_t a0, uint32_t a1, uint32_t b0) {
    asm("mma.sync.aligned.m16n8k8.row.col.f32.bf16.bf16.f32 {%0,%1,%2,%3}, {%4,%5}, {%6}, {%0,%1,%2,%3};"
        : "+f"(c[0]), "+f"(c[1]), "+f"(c[2]), "+f"(c[3]) : "r"(a0), "r"(a1), "r"(b0));
}
__device__ __forceinline__ float quad_sum(float v) { v += __shfl_xor_sync(~0u, v, 1); v += __shfl_xor_sync(~0u, v, 2); return v; }
__device__ __forceinline__ float quad_max(float v) { v = fmaxf(v, __shfl_xor_sync(~0u, v, 1)); v = fmaxf(v, __shfl_xor_sync(~0u, v, 2)); return v; }
__device__ __forceinline__ uint64_t make_desc(uint32_t addr, uint32_t lbo, bool swz, uint32_t sbo = 1024) {
    const uint32_t lo = __shfl_sync(~0u, ((addr & 0x3FFFF) >> 4) | ((lbo >> 4) << 16), 0);
    const uint32_t hi = __shfl_sync(~0u, (swz ? 0x40000000u : 0u) + (sbo >> 4) + (threadIdx.x & 31), 0);
    return ((uint64_t)hi << 32) | lo;
}
template <int I, int N, class F> __device__ __forceinline__ void static_for(F&& f) {
    if constexpr (I < N) { f(std::integral_constant<int, I>{}); static_for<I + 1, N>(f); }
}
__device__ __forceinline__ uint32_t opaque(uint32_t v) { asm volatile("" : "+r"(v)); return v; }
template <int BOFF, int SCALE_D>
__device__ __forceinline__ void wgmma_rs_n56(float (&d)[28], uint32_t a0, uint32_t a1, uint32_t a2, uint32_t a3, uint64_t db) {
    asm volatile("{ .reg .b64 db; add.s64 db, %32, %33;\n"
        "wgmma.mma_async.sync.aligned.m64n56k16.f32.bf16.bf16 "
        "{%0, %1, %2, %3, %4, %5, %6, %7, %8, %9, %10, %11, %12, %13, %14, %15, %16, %17, %18, %19, %20, %21, %22, %23, %24, %25, %26, %27}, "
        "{%28, %29, %30, %31}, db, %34, 1, 1, 1; }"
        : "+f"(d[0]), "+f"(d[1]), "+f"(d[2]), "+f"(d[3]), "+f"(d[4]), "+f"(d[5]), "+f"(d[6]), "+f"(d[7]),
        "+f"(d[8]), "+f"(d[9]), "+f"(d[10]), "+f"(d[11]), "+f"(d[12]), "+f"(d[13]), "+f"(d[14]), "+f"(d[15]),
        "+f"(d[16]), "+f"(d[17]), "+f"(d[18]), "+f"(d[19]), "+f"(d[20]), "+f"(d[21]), "+f"(d[22]), "+f"(d[23]),
        "+f"(d[24]), "+f"(d[25]), "+f"(d[26]), "+f"(d[27])
        : "r"(a0), "r"(a1), "r"(a2), "r"(a3), "l"(db), "n"(BOFF >> 4), "n"(SCALE_D));
}
template <int AOFF, int BOFF, int MMAJOR>
__device__ __forceinline__ void wgmma_ss_n56(float (&d)[28], uint64_t da, uint64_t db) {
    asm volatile("{ .reg .b64 da, db; add.s64 da, %28, %30; add.s64 db, %29, %31;\n"
        "wgmma.mma_async.sync.aligned.m64n56k16.f32.bf16.bf16 "
        "{%0, %1, %2, %3, %4, %5, %6, %7, %8, %9, %10, %11, %12, %13, %14, %15, %16, %17, %18, %19, %20, %21, %22, %23, %24, %25, %26, %27}, "
        "da, db, 1, 1, 1, %32, 1; }"
        : "+f"(d[0]), "+f"(d[1]), "+f"(d[2]), "+f"(d[3]), "+f"(d[4]), "+f"(d[5]), "+f"(d[6]), "+f"(d[7]),
        "+f"(d[8]), "+f"(d[9]), "+f"(d[10]), "+f"(d[11]), "+f"(d[12]), "+f"(d[13]), "+f"(d[14]), "+f"(d[15]),
        "+f"(d[16]), "+f"(d[17]), "+f"(d[18]), "+f"(d[19]), "+f"(d[20]), "+f"(d[21]), "+f"(d[22]), "+f"(d[23]),
        "+f"(d[24]), "+f"(d[25]), "+f"(d[26]), "+f"(d[27])
        : "l"(da), "l"(db), "n"(AOFF >> 4), "n"(BOFF >> 4), "n"(MMAJOR));
}
template <int AOFF, int BOFF, int MMAJOR>
__device__ __forceinline__ void wgmma_ss_n112(float (&d)[28], float (&e)[28], uint64_t da, uint64_t db) {
    asm volatile("{ .reg .b64 da, db; add.s64 da, %56, %58; add.s64 db, %57, %59;\n"
        "wgmma.mma_async.sync.aligned.m64n112k16.f32.bf16.bf16 "
        "{%0, %1, %2, %3, %4, %5, %6, %7, %8, %9, %10, %11, %12, %13, %14, %15, %16, %17, %18, %19, %20, %21, %22, %23, %24, %25, %26, %27, %28, %29, %30, %31, %32, %33, %34, %35, %36, %37, %38, %39, %40, %41, %42, %43, %44, %45, %46, %47, %48, %49, %50, %51, %52, %53, %54, %55}, "
        "da, db, 1, 1, 1, %60, 1; }"
        : "+f"(d[0]), "+f"(d[1]), "+f"(d[2]), "+f"(d[3]), "+f"(d[4]), "+f"(d[5]), "+f"(d[6]), "+f"(d[7]),
        "+f"(d[8]), "+f"(d[9]), "+f"(d[10]), "+f"(d[11]), "+f"(d[12]), "+f"(d[13]), "+f"(d[14]), "+f"(d[15]),
        "+f"(d[16]), "+f"(d[17]), "+f"(d[18]), "+f"(d[19]), "+f"(d[20]), "+f"(d[21]), "+f"(d[22]), "+f"(d[23]),
        "+f"(d[24]), "+f"(d[25]), "+f"(d[26]), "+f"(d[27]), "+f"(e[0]), "+f"(e[1]), "+f"(e[2]), "+f"(e[3]),
        "+f"(e[4]), "+f"(e[5]), "+f"(e[6]), "+f"(e[7]), "+f"(e[8]), "+f"(e[9]), "+f"(e[10]), "+f"(e[11]),
        "+f"(e[12]), "+f"(e[13]), "+f"(e[14]), "+f"(e[15]), "+f"(e[16]), "+f"(e[17]), "+f"(e[18]), "+f"(e[19]),
        "+f"(e[20]), "+f"(e[21]), "+f"(e[22]), "+f"(e[23]), "+f"(e[24]), "+f"(e[25]), "+f"(e[26]), "+f"(e[27])
        : "l"(da), "l"(db), "n"(AOFF >> 4), "n"(BOFF >> 4), "n"(MMAJOR));
}
template <int BOFF, int SCALE_D>
__device__ __forceinline__ void wgmma_rs_n112(float (&d)[28], float (&e)[28], uint32_t a0, uint32_t a1, uint32_t a2, uint32_t a3, uint64_t db) {
    asm volatile("{ .reg .b64 db; add.s64 db, %60, %61;\n"
        "wgmma.mma_async.sync.aligned.m64n112k16.f32.bf16.bf16 "
        "{%0, %1, %2, %3, %4, %5, %6, %7, %8, %9, %10, %11, %12, %13, %14, %15, %16, %17, %18, %19, %20, %21, %22, %23, %24, %25, %26, %27, %28, %29, %30, %31, %32, %33, %34, %35, %36, %37, %38, %39, %40, %41, %42, %43, %44, %45, %46, %47, %48, %49, %50, %51, %52, %53, %54, %55}, "
        "{%56, %57, %58, %59}, db, %62, 1, 1, 1; }"
        : "+f"(d[0]), "+f"(d[1]), "+f"(d[2]), "+f"(d[3]), "+f"(d[4]), "+f"(d[5]), "+f"(d[6]), "+f"(d[7]),
        "+f"(d[8]), "+f"(d[9]), "+f"(d[10]), "+f"(d[11]), "+f"(d[12]), "+f"(d[13]), "+f"(d[14]), "+f"(d[15]),
        "+f"(d[16]), "+f"(d[17]), "+f"(d[18]), "+f"(d[19]), "+f"(d[20]), "+f"(d[21]), "+f"(d[22]), "+f"(d[23]),
        "+f"(d[24]), "+f"(d[25]), "+f"(d[26]), "+f"(d[27]), "+f"(e[0]), "+f"(e[1]), "+f"(e[2]), "+f"(e[3]),
        "+f"(e[4]), "+f"(e[5]), "+f"(e[6]), "+f"(e[7]), "+f"(e[8]), "+f"(e[9]), "+f"(e[10]), "+f"(e[11]),
        "+f"(e[12]), "+f"(e[13]), "+f"(e[14]), "+f"(e[15]), "+f"(e[16]), "+f"(e[17]), "+f"(e[18]), "+f"(e[19]),
        "+f"(e[20]), "+f"(e[21]), "+f"(e[22]), "+f"(e[23]), "+f"(e[24]), "+f"(e[25]), "+f"(e[26]), "+f"(e[27])
        : "r"(a0), "r"(a1), "r"(a2), "r"(a3), "l"(db), "n"(BOFF >> 4), "n"(SCALE_D));
}

struct Params {
    const __nv_bfloat16 *x, *wqkv;
    Scratch* sc;
    const __nv_bfloat16 *wo, *w1, *w2, *b1, *b2;
    __nv_bfloat16* out;
};

__global__ void __cluster_dims__(2, 1, 1) __launch_bounds__(384, 1)
fused_kernel(const Params prm, const __grid_constant__ CUtensorMap mX2, const __grid_constant__ CUtensorMap mX, const __grid_constant__ CUtensorMap mWqkv,
             const __grid_constant__ CUtensorMap mWo, const __grid_constant__ CUtensorMap mW1,
             const __grid_constant__ CUtensorMap mW2)
{
    extern __shared__ __align__(1024) unsigned char smem_raw[];
    if (threadIdx.x < 126) {
        const uint32_t i = threadIdx.x, t = clk32() + (i >> 5) * PFD;
        const char* px = (const char*)prm.x + (blockIdx.x * 16 + (i & 15)) * 896 + (i >> 4) * 128;
        const char* pw = (const char*)prm.wqkv + blockIdx.x * 2688 + i * 128 + (896 - 112 * 128);
        spin_until(t);
        asm volatile("prefetch.global.L2 [%0];" :: "l"(i < 112 ? px : pw) : "memory");
    }
    if (threadIdx.x == 128) { asm volatile("prefetch.tensormap [%0];" :: "l"(&mX2) : "memory"); asm volatile("prefetch.tensormap [%0];" :: "l"(&mWqkv) : "memory"); }
    uint32_t sb = (uint32_t)__cvta_generic_to_shared(smem_raw);
    asm volatile("mov.u32 %0, %0;" : "+r"(sb));
    const uint32_t bar0 = sb + SM_BAR;
    auto BAR = [&](int i) { return bar0 + 8u * i; };

    const int tid = threadIdx.x, lane = tid & 31;
    const int warp = __shfl_sync(~0u, tid >> 5, 0);
    const int b = __shfl_sync(~0u, (int)blockIdx.x, 0);
    const int rank = b & 1;
    const int cl = (b >> 1) - 4, cq = ((cl - 32) * 37) >> 8;
    const int res = cl < 0 ? 0 : cl < 32 ? cl & 7 : cl - 31 - 7 * cq;
    const int rnd = cl < 0 ? cl + 8 : cl < 32 ? cl >> 3 : 4 + cq;
    const int hg = (res & 1) * 4 + (rnd & 3);
    const int ti = (res >> 1) * 4 + (rnd >> 2) * 2 + rank;
    const int a2p = res & 1, a2j = rnd & 3;
    const int a2s = ti * 2 + a2p;
    const bool g1_on = rnd != 7;
    const int g1j = (rnd < 6 ? rnd : res) & 1, g1f = rnd < 6 ? res * 3 + (rnd >> 1) : 24 + (res >> 1);
    const int g2j = rnd & 1, g2s = res * 4 + (rnd >> 1);
    uint32_t pbar0;
    asm volatile("mapa.shared::cluster.u32 %0, %1, %2;" : "=r"(pbar0) : "r"(bar0), "r"(rank ^ 1));
    auto pair_arrive = [&](int i) { __syncwarp(); const bool l = elect_one(); mbar_arrive_if(BAR(i), l); mbar_arrive_remote_if(pbar0 + 8u * i, l); };
    const int wcol = hg * 56 - (hg & 1) * 8;

    if (warp == 8) {
        if (elect_one()) {
            #pragma unroll
            for (int i = 0; i < B_WQF; i++) mbar_init(BAR(i), 1);
            asm volatile("fence.mbarrier_init.release.cluster;" ::: "memory");
            fence_async_smem();
            #pragma unroll
            for (int kb = 0; kb < 7; kb++) {
                tma3d(sb + kb * 16384, &mX2, kb * 64, ti * 64, 0, BAR(B_XF + kb));
                mbar_expect(BAR(B_XF + kb), 16384);
            }
        }
    } else if (warp > 8) {
        if (elect_one()) {
            if (warp == 9) {
                #pragma unroll
                for (int i = B_WQF; i < B_AF; i++) mbar_init(BAR(i), i < B_XC ? 1 : i < B_A1D ? 16 : i < B_BE ? 8 : 4);
            } else if (warp == 10) {
                #pragma unroll
                for (int i = B_AF; i < B_BF; i++) mbar_init(BAR(i), 1);
            } else {
                #pragma unroll
                for (int i = B_BF; i < B_COUNT; i++) mbar_init(BAR(i), i == B_HD ? 8 : 1);
            }
            asm volatile("fence.mbarrier_init.release.cluster;" ::: "memory");
            fence_async_smem();
        }
    }
    __syncwarp();
    __syncthreads();
    asm volatile("barrier.cluster.arrive.relaxed.aligned;" ::: "memory");

    if (warp >= 8) {
        asm volatile("setmaxnreg.dec.sync.aligned.u32 40;");
        asm volatile("barrier.cluster.wait.aligned;" ::: "memory");
        auto fetch_halo = [&](int p, uint32_t tag) {
            const uint32_t hl = BAR(B_HL + p), dst = opaque(sb + SM_STG + p * 8192 + 3 * 2048 + lane * 16);
            const bool lead = elect_one();
            if (rank) { if (lead) mbar_expect(hl, 2048); __syncwarp(); return; }
            const uint4* hp = opaque_ptr(&prm.sc->halo[((((ti >> 1) - 1) * 8 + hg) * 2 + p) * 128 + lane]);
            mbar_wait(BAR(B_KVC), 0);
            if (ti > 0) {
                spin_until(clk32() + HDELAY);
                int it = 0;
                uint32_t bad;
                do {
                    uint4 u[4];
                    #pragma unroll
                    for (int c = 0; c < 4; c++) u[c] = ld_rlx4(hp + c * 32);
                    #pragma unroll
                    for (int c = 0; c < 4; c++) sts4(dst + c * 512, u[c].x, u[c].y, u[c].z, u[c].w);
                    bad = ((u[0].x ^ tag) | (u[1].x ^ tag) | (u[2].x ^ tag) | (u[3].x ^ tag)) & ~lane & 1;
                } while (__any_sync(~0u, bad) && ++it < kSpinLimit);
            } else {
                #pragma unroll
                for (int c = 0; c < 4; c++) sts4(dst + c * 512, 0u, 0u, 0u, 0u);
            }
            __syncwarp();
            mbar_arrive_if(hl, lead);
        };
        auto poll_flags = [&](const uint32_t* fp, int step, uint32_t tag, uint32_t gbase) {
            uint64_t v0 = 0, v1 = 0;
            int it = 0;
            do {
                ld_flag_if(v0, fp, (uint32_t)v0 != tag); ld_flag_if(v1, fp + step, (uint32_t)v1 != tag);
                if (++it > kSpinLimit) break;
            } while (__any_sync(~0u, (uint32_t)v0 != tag || (uint32_t)v1 != tag));
            return max((int)((uint32_t)(v0 >> 32) - gbase), (int)((uint32_t)(v1 >> 32) - gbase));
        };
        if (warp & 1) {
            uint32_t tag;
            if (warp == 11) {
                tag = *(volatile uint32_t*)&prm.sc->epoch + 1;
                #pragma unroll 1
                for (int i = 0; i < 8 * rank; i++) prm.sc->halo[((ti >> 1) * 8 + hg) * 256 + i * 32 + lane] = make_uint4(~tag, 0u, 0u, 0u);
                ((uint4*)prm.sc->stats)[(a2s * 4 + a2j) * 64 + lane] = ((uint4*)prm.sc->stats)[(a2s * 4 + a2j) * 64 + 32 + lane] = make_uint4(~tag, ~tag, ~tag, ~tag);
                prm.sc->flag_h[(a2s * 4 + a2j) * FS + lane] = 0;
                prm.sc->flag_o[(ti * 8 + hg) * FS + lane] = 0;
                __syncwarp();
                if (lane == 0) {
                    asm volatile("st.shared.v2.u32 [%0], {%1, %2};" :: "r"(sb + SM_EPOCH), "r"(tag), "r"(gtime32()) : "memory");
                    mbar_arrive(BAR(B_EP));
                }
                if (lane < 8) mbar_expect(BAR(B_RF + lane), 1792);
                __syncwarp();
            } else {
                mbar_wait(BAR(B_EP), 0);
                tag = lds1(sb + SM_EPOCH);
            }
            fetch_halo((warp >> 1) & 1, tag);
        }
        if (warp < 10) {
          auto load_slab = [&](int s, bool second) {
              if (!second) tma2d(sb + s * 8192, &mW1, (s & 1) * kF + g1f * 64, (rank * 8 + (s >> 1)) * 64, BAR(B_AF));
              else         tma2d(sb + s * 8192, &mW2, g2s * 64, (rank * 14 + s - 1) * 64, BAR(B_AF));
          };
          const char* pw2 = (const char*)prm.w2 + ((b >> 6) * 896 + (b & 63) + PFW * 64) * 4096;
          if (warp == 8) {
            if (elect_one()) {
                #pragma unroll 1
                for (int s = 0; s < 7; s++) {
                    mbar_expect(BAR(B_WKVF + s), 16384);
                    tma2d_mc(sb + SM_WKV + s * 16384 + rank * 8192, &mWqkv, (1 + rank) * kD + wcol, s * 64, BAR(B_WKVF + s));
                }
            }
            __syncwarp();
            mbar_wait(BAR(B_XC), 0);
            if (elect_one()) {
                asm volatile("prefetch.tensormap [%0];" :: "l"(&mX) : "memory");
                asm volatile("prefetch.tensormap [%0];" :: "l"(&mWo) : "memory");
                asm volatile("prefetch.tensormap [%0];" :: "l"(&mW1) : "memory");
                asm volatile("prefetch.tensormap [%0];" :: "l"(&mW2) : "memory");
                mbar_expect(BAR(B_AF), (g1_on ? NPRE : 14) * 8192);
                mbar_expect(BAR(B_WQF), 57344);
                #pragma unroll 1
                for (int s = rank; s < 7; s += 2) tma2d_mc(sb + SM_WQ + s * 8192, &mWqkv, wcol, s * 64, BAR(B_WQF));
                mbar_expect(BAR(B_XRF), 16384);
                tma2d(sb + SM_XR, &mX, a2p * kD + a2j * 112, ti * 64, BAR(B_XRF));
                tma2d(sb + SM_XR + 8192, &mX, a2p * kD + a2j * 112 + 48, ti * 64, BAR(B_XRF));
            }
            __syncwarp();
            #pragma unroll 1
            for (int q = 0; q < 4; q++) {
                mbar_wait(BAR(B_KV3 + (q >> 1)), 0);
                if (q == 2) spin_until(clk32() + WOD);
                if (q == 3) mbar_wait2(BAR(B_HL), 0, BAR(B_HL + 1), 0);
                if (elect_one()) {
                    if (!(q & 1)) mbar_expect(BAR(B_WOF + (q >> 1)), 57344);
                    tma2d_mc(sb + SM_WKV + q * 28672 + rank * 14336, &mWo, a2j * 112 + (q & 1) * 48, (q >> 1) * 224 + rank * 112, BAR(B_WOF + (q >> 1)));
                    if (g1_on && q == 1) { load_slab(0, false); load_slab(1, false); load_slab(2, false); }
                }
                __syncwarp();
            }
            if (g1_on) {
                mbar_wait2(BAR(B_XD), 0, BAR(B_OL + 3), 0);
                #pragma unroll 1
                for (int i = 3; i < NPRE; i++) {
                    if (i == 7) mbar_wait(BAR(B_OC), 0);
                    if (elect_one()) load_slab(i, false);
                    __syncwarp();
                }
            } else {
                mbar_arrive_if(BAR((lane < 16 ? B_BE : B_BF) + (lane & 3)), lane < 20);
                mbar_wait(BAR(B_HD), 0);
                mbar_arrive_remote_if(pbar0 + 8u * B_PD, lane == 0);
                mbar_wait(BAR(B_GO), 0);
                uint32_t tg = lds1(sb + SM_TG + 4);
                tg += max((int)(lds1(sb + SM_TG2) - tg), 0);
                int it = 0;
                while ((int)(gtime32() - tg) < 0 && ++it < 256) {}
                const uint32_t t0 = clk32();
                if (lane < 2) {
                    asm volatile("st.shared.u32 [%0], %1;" :: "r"(sb + SM_TG + 8 + lane * 4), "r"(t0 + (lane ? CN3 : CN2)) : "memory");
                    mbar_arrive(BAR(B_GD + lane));
                }
                __syncwarp();
                #pragma unroll 1
                for (int s = 1; s < 15; s++) {
                    sleep_until(t0 + W2OFF + s * W2PACE);
                    if (elect_one()) { if (s < 15 - PFW) bulk_prefetch(pw2 + (s - 1) * 64 * 4096, 4096); load_slab(s, true); }
                    __syncwarp();
                }
            }
          } else {
            const uint32_t tag = lds1(sb + SM_EPOCH);
            if (lane < 4) mbar_expect(BAR(B_OL + lane), 14336);
            const uint32_t gbase = lds1(sb + SM_TG);
            const bool lead = elect_one();
            uint32_t* hfl = opaque_ptr(&prm.sc->flag_h[(a2s * 4 + a2j) * FS]);
            mbar_wait(BAR(B_QL), 0);
            const int d = poll_flags(&prm.sc->flag_o[(ti * 8 + (lane & 3) * 2) * FS], FS, tag, gbase);
            mbar_wait(BAR(B_A1D), 0);
            int key = max(d + DELTAO, __reduce_max_sync(~0u, d) + DMIN) * 4 + (lane & 3);
            uint32_t order = 0;
            #pragma unroll 1
            for (int i = 0; i < 4; i++) {
                const int m = __reduce_min_sync(~0u, key);
                const uint4* src = &prm.sc->o[(a2s * 4 + (m & 3)) * 896];
                int it = 0;
                while ((int)(gtime32() - gbase) < m >> 2 && ++it < 256) {}
                if (lead) bulk_g2s(sb + SM_WQ + i * 14336, src, 14336, BAR(B_OL + i));
                if (key == m) key = 0x7fffffff;
                order |= (m & 3) << i * 2;
            }
            if (lead) {
                asm volatile("st.shared.u32 [%0], %1;" :: "r"(sb + SM_ORD), "r"(order) : "memory");
                mbar_arrive(BAR(B_OD));
            }
            __syncwarp();
            mbar_wait(BAR(B_XD), 0);
            int t0 = gtime32() - gbase + XDNS;
            #pragma unroll 1
            for (int i = 0; i < 4; i++) { mbar_wait(BAR(B_OF + i), 0); t0 = max(t0, (int)(gtime32() - gbase) - i * CHUNKNS); }
            if (lead) st_flag(hfl, tag, gbase + t0);
            __syncwarp();
          }
          if (elect_one()) {
              const int h = ~warp & 1;
              constexpr uint32_t T = 57344, BO = 2 * 14336;
              const char* src1 = (const char*)&prm.sc->hn[(rank * 16 + h) * 3584 + g1j * 896];
              const char* src2 = (const char*)&prm.sc->g[(rank * 14 + h) * 3584 + g2j * 896];
              uint64_t masks = g1_on ? (h ? kSegMasks1 : kSegMasks0) : 0x80 | 0x80 << 10;
              const uint32_t bl = BAR(B_BL + h * NB);
              uint32_t s8 = (g1_on ? NB - 2 + h : 4 + h) * 8, lap = 3, tmin = 0;
              const CUtensorMap* am = &mW1;
              uint32_t ad = sb + (NPRE + h) * 8192, astep = 16384; int ac0 = h * kF + g1f * 64, ac1 = (rank * 8 + NPRE / 2) * 64;
              #pragma unroll 1
              for (int seg = g1_on ? 0 : 3; seg < 5; seg++) {
                  const char* src = (seg < 3 ? src1 : src2) + (~seg & 1) * BO;
                  uint32_t m = (uint32_t)masks & 0x3ff;
                  masks >>= 10;
                  const uint32_t pace = seg == 4 ? PACEB : PACE2;
                  if (seg == 2) {
                      mbar_wait(BAR(B_PL), 0);
                      mbar_arrive_remote_if(pbar0 + 8u * B_PD, h);
                      am = &mW2; ad = sb + 8192; astep = 8192; ac0 = g2s * 64; ac1 = rank * 14 * 64;
                  } else {
                      const int gate = seg - (seg > 2);
                      mbar_wait(BAR(B_HD + gate), 0);
                      tmin = lds1(sb + SM_TG + gate * 4);
                      if (gate < 2) {
                          tmin += max((int)(lds1(gate ? sb + SM_TG2 : sb + SM_TG) - tmin), 0);
                          int it = 0;
                          while ((int)(gtime32() - tmin) < 0 && ++it < 256) {}
                          tmin = clk32();
                      }
                      tmin += h * PACE1;
                  }
                  #pragma unroll 1
                  do {
                      const uint32_t dst = sb + SM_B + s8 * 1792;
                      spin_until(tmin);
                      mbar_wait_fast(BAR(B_BE) + s8 + (lap & 1) * (NB * 8), lap >> 1 & 1);
                      if (seg) {
                          bulk_g2s(dst, src, 14336, bl + s8);
                          mbar_expect(bl + s8, 14336);
                      }
                      tmin += pace;
                      src += 2 * T;
                      s8 += 16;
                      if (s8 >= NB * 8) { s8 -= NB * 8; lap++; }
                      if (m & 1) {
                          mbar_expect_more(bl + s8, 8192);
                          tma2d(ad, am, ac0, ac1, bl + s8);
                          ad += astep; ac1 += 64;
                      }
                      m >>= 1;
                  } while (m != 1);
                  if (seg == 0) lap = 3;
              }
          }
        } else {
          if (warp == 10) {
            mbar_wait(BAR(B_XF + 6), 0);
            if (lane < 27) asm volatile("prefetch.global.L2 [%0];" :: "l"(lane < 25 ? (const char*)prm.wo + min(b * 25 + lane, 3135) * 128
                                                                          : lane == 25 ? (const char*)prm.b1 + (b % 28) * 128 : (const char*)prm.b2 + (b & 31) * 128));
            const char* p1 = (const char*)prm.w1 + ((b >> 6) * 1024 + (b & 63) * 2) * 3584 + min(lane, 27) * 128;
            uint32_t tnext = clk32();
            #pragma unroll 1
            for (int i = 0; i < 16; i++) {
                while ((int)(clk32() - tnext) < 0) __nanosleep(40);
                asm volatile("prefetch.global.L2 [%0];" :: "l"(p1 + ((i >> 1) * 128 + (i & 1)) * 3584));
                tnext += PFPACE;
            }
            uint32_t* ofl = opaque_ptr(&prm.sc->flag_o[(ti * 8 + hg) * FS]);
            mbar_wait(BAR(B_EP), 0);
            const uint32_t tag = lds1(sb + SM_EPOCH);
            mbar_wait(BAR(B_QL), 0);
            const uint32_t tq = gtime32() + QLNS;
            mbar_wait2(BAR(B_HL), 0, BAR(B_HL + 1), 0);
            if (lane == 0) st_flag(ofl, tag, tq + max((int)(gtime32() - tq), 0));
            __syncwarp();
          }
          const uint32_t tag = lds1(sb + SM_EPOCH);
          const int h = warp & 1;
          const bool lead = elect_one();
          const uint32_t wo = (lane & 15) * 128 + lane * 4;
          uint32_t base = sb + SM_WQ, bl = BAR(B_OL), bf = BAR(B_OF), m = 4, rph = 0;
          #pragma unroll 1
          for (int e = 0; e < 2; e++) {
              uint32_t s8 = (e && !g1_on ? 4 + h : h) * 8;
              #pragma unroll 1
              do {
                  const uint32_t dst = base + s8 * 1792;
                  auto stale = [&](uint32_t at) {
                      uint32_t v[8];
                      #pragma unroll
                      for (int i = 0; i < 7; i++) v[i] = lds1(at + i * 2048);
                      v[7] = v[6];
                      #pragma unroll
                      for (int i = 0; i < 4; i++) asm("lop3.b32 %0, %1, %2, %3, 0x7e;" : "=r"(v[i]) : "r"(v[2 * i]), "r"(v[2 * i + 1]), "r"(tag));
                      return __any_sync(~0u, (v[0] | v[1] | v[2] | v[3]) & 1);
                  };
                  mbar_wait_fast(bl + s8, m & 1);
                  bool bad = stale(dst + wo);
                  mbar_arrive_if(bf + s8, lead && !bad);
                  if (bad) {
                      const int p = 2 * __clz(m) - 2 + h;
                      const int st = (p > 15) + (p > 31) + (p > 45), s = p - (st < 3 ? 16 * st : 46);
                      mbar_wait(BAR(B_OD), 0);
                      const char* src = (const char*)(!e ? &prm.sc->o[(a2s * 4 + (lds1(sb + SM_ORD) >> (p * 2 & 7) & 3)) * 896] : st < 2 ? &prm.sc->hn[(rank * 16 + s) * 3584 + (g1j + 2 * st) * 896]
                                                                                                      : &prm.sc->g[(rank * 14 + s) * 3584 + (g2j + 2 * st - 4) * 896]);
                      int it = 0;
                      do {
                          if (++it > kSpinLimit) break;
                          const uint32_t* q = (const uint32_t*)(src + lane * 132);
                          if (it > 1 && __any_sync(~0u, ((ld_rlx(q) ^ tag) | (ld_rlx(q + 1024) ^ tag) | (ld_rlx(q + 2048) ^ tag) | (ld_rlx(q + (lane < 16 ? 3072 : 0)) ^ tag)) & 1)) continue;
                          if (lead) {
                              mbar_expect(BAR(B_RT + h), 14336);
                              bulk_g2s(dst, src, 14336, BAR(B_RT + h));
                          }
                          __syncwarp();
                          mbar_wait(BAR(B_RT + h), rph);
                          rph ^= 1;
                          bad = stale(dst + wo) || stale(dst + (wo ^ 1024));
                      } while (bad);
                      mbar_arrive_if(bf + s8, lead);
                  }
                  s8 += 16;
                  if (s8 >= NB * 8) s8 -= NB * 8;
                  m >>= 1;
              } while (m != 1);
              if (e) break;
              if (h) {
                  const uint32_t gbase = lds1(sb + SM_TG);
                  sleep_until(clk32() + PDELAY);
                  const uint32_t tg = gbase + DELTA + __reduce_max_sync(~0u, poll_flags(&prm.sc->flag_h[(rank * 64 + lane) * FS], 32 * FS, tag, gbase));
                  if (lead) {
                      asm volatile("st.async.shared::cluster.mbarrier::complete_tx::bytes.b32 [%0], %1, [%2];"
                                   :: "r"(pbar0 + (SM_TG2 - SM_BAR)), "r"(tg), "r"(pbar0 + 8u * B_GO) : "memory");
                      asm volatile("st.shared.u32 [%0], %1;" :: "r"(sb + SM_TG + 4), "r"(tg) : "memory");
                      mbar_expect(BAR(B_GO), 4);
                  }
                  __syncwarp();
              } else {
                  const char* p2 = (const char*)prm.w2 + ((b >> 6) * 896 + (b & 63)) * 4096 + lane * 128;
                  #pragma unroll 1
                  for (int i = 0; i < PFW; i++) {
                      asm volatile("prefetch.global.L2 [%0];" :: "l"(p2 + i * 64 * 4096));
                      sleep_until(clk32() + PFPACE2);
                  }
              }
              base = sb + SM_B; bl = BAR(B_BL + h * NB); bf = BAR(B_BF); m = g1_on ? 0x4fe03f80 : 0x7f80;
          }
        }
    } else {
        asm volatile("setmaxnreg.inc.sync.aligned.u32 232;");
        asm volatile("barrier.cluster.wait.aligned;" ::: "memory");
        const int wg = warp >> 2, w = warp & 3;
        const int g = lane >> 2, t = lane & 3;
        uint32_t tag, om0, om1;
        __nv_bfloat16 bias1a, bias1b;
        {
            const uint64_t dw = make_desc(sb + (hg & 1) * 16, 0, true);
            uint4* const hp = opaque_ptr((w == 3 ? &prm.sc->halo[(((ti >> 1) * 8 + hg) * 2 + wg) * 128] : (uint4*)(smem_raw + SM_STG + wg * 8192 + w * 2048)) + lane);
            uint32_t a[28][4];
            float sm[4][4];
            auto shift = [](uint32_t (&f)[4], uint32_t m0, uint32_t m1) {
                f[0] = sub_bf16x2(f[0], m0); f[1] = sub_bf16x2(f[1], m1);
                f[2] = sub_bf16x2(f[2], m0); f[3] = sub_bf16x2(f[3], m1);
            };
            {
                const int r = w * 16 + (lane & 15);
                uint32_t xa[4];
                #pragma unroll
                for (int q = 0; q < 4; q++) xa[q] = opaque(sb + wg * 8192 + r * 128 + (((q * 2 + (lane >> 4)) ^ (r & 7)) << 4));
                const uint32_t one = opaque(0x3F803F80u), one2 = opaque(0x3F803F80u);
                auto load = [&](int k0, int k1) {
                    #pragma unroll
                    for (int k = k0; k < k1; k++) {
                        if ((k & 3) == 0) mbar_wait(BAR(B_XF + (k >> 2)), 0);
                        ldsm4(a[k], xa[k & 3] + (k >> 2) * 16384);
                        if (k < 24) mma16816(sm[k & 3], a[k][0], a[k][1], a[k][2], a[k][3], one, one2);
                    }
                };
                #pragma unroll 1
                for (float lim = 128.f;; lim = 0.f) {
                    #pragma unroll
                    for (int i = 0; i < 16; i++) sm[i >> 2][i & 3] = 0.f;
                    load(0, 4);
                    float sq[4] = {};
                    uint32_t u[4];
                    #pragma unroll
                    for (int i = 0; i < 4; i++) u[i] = sqa_bf16x2(a[2][i], sqa_bf16x2(a[3][i], sqa_bf16x2(a[0][i], sqr_bf16x2(a[1][i]))));
                    mma16816(sq, u[0], u[1], u[2], u[3], one, one2);
                    const float m0 = ((sm[0][0] + sm[1][0]) + (sm[2][0] + sm[3][0])) * (1.f / 64);
                    const float m1 = ((sm[0][2] + sm[1][2]) + (sm[2][2] + sm[3][2])) * (1.f / 64);
                    load(4, 8);
                    if (!__any_sync(~0u, m0 * m0 * lim > sq[0] || m1 * m1 * lim > sq[2])) break;
                    #pragma unroll 1
                    for (int k = 0; k < 28; k++) {
                        const uint32_t p = (xa[0] ^ (k & 3) * 32) + (k >> 2) * 16384;
                        mbar_wait(BAR(B_XF + (k >> 2)), 0);
                        ldsm4(u, p);
                        shift(u, pack_bf16(m0, m0), pack_bf16(m1, m1));
                        stsm4(p, u[0], u[1], u[2], u[3]);
                    }
                    fence_async_smem();
                    __syncwarp();
                }
                load(8, 28);
                pair_arrive(B_XC);
                const bool wok = mbar_test(BAR(B_WKVF), 0);
                #pragma unroll
                for (int k = 24; k < 28; k++) mma16816(sm[k & 3], a[k][0], a[k][1], a[k][2], a[k][3], one, one2);
                if (!wok) mbar_wait(BAR(B_WKVF), 0);
            }
            const float mean0 = ((sm[0][0] + sm[1][0]) + (sm[2][0] + sm[3][0])) * (1.f / kD);
            const float mean1 = ((sm[0][2] + sm[1][2]) + (sm[2][2] + sm[3][2])) * (1.f / kD);
            const uint32_t mb0 = pack_bf16(mean0, mean0), mb1 = pack_bf16(mean1, mean1);
            float ak[28], av[28], aq[28];
            float ss0 = 0.f, ss1 = 0.f, ss2 = 0.f, ss3 = 0.f;
            uint32_t p0, p1;
            bool qok;
            static_for<0, 7>([&](auto S_) {
                constexpr int s = decltype(S_)::value;
                auto centre = [&](int q) { shift(a[s * 4 + q], mb0, mb1); };
                if (s) {
                    #pragma unroll
                    for (int q = 0; q < 4; q++) centre(q);
                    mbar_wait(BAR(B_WKVF + s), 0);
                    if (s == 6) qok = mbar_test(BAR(B_WQF), 0);
                    wg_fence();
                }
                static_for<0, 4>([&](auto Q_) {
                    constexpr int q = decltype(Q_)::value;
                    uint32_t (&f)[4] = a[s * 4 + q];
                    if (s == 0) { centre(q); wg_fence(); }
                    wgmma_rs_n56<SM_WKV + s * 16384 + q * 2048, (s | q) != 0>(ak, f[0], f[1], f[2], f[3], dw);
                    wgmma_rs_n56<SM_WKV + s * 16384 + q * 2048 + 8192, (s | q) != 0>(av, f[0], f[1], f[2], f[3], dw);
                });
                wg_commit();
                if (s == 4) { wg_wait<1>(); pair_arrive(B_KV3); }
                if (s < 2) mbar_wait(BAR(s ? B_EP : B_WKVF), 0);
                if (s == 1) tag = lds1(sb + SM_EPOCH);
                #pragma unroll
                for (int q = 0; q < 8; q++) {
                    const uint32_t u0 = a[s * 4 + q / 2][(q & 1) * 2], u1 = a[s * 4 + q / 2][(q & 1) * 2 + 1];
                    if (q == 0) { p0 = sqr_bf16x2(u0); p1 = sqr_bf16x2(u1); }
                    else { p0 = sqa_bf16x2(u0, p0); p1 = sqa_bf16x2(u1, p1); }
                }
                ss0 += bf_lo(p0); ss2 += bf_hi(p0); ss1 += bf_lo(p1); ss3 += bf_hi(p1);
            });
            auto q_chunk = [&](auto K0_, auto K1_) {
                wg_fence();
                static_for<decltype(K0_)::value, decltype(K1_)::value>([&](auto K_) {
                    constexpr int k = decltype(K_)::value;
                    wgmma_rs_n56<SM_WQ + k * 2048, k != 0>(aq, a[k][0], a[k][1], a[k][2], a[k][3], dw);
                });
                wg_commit();
            };
            #define QCHUNK(k0, k1) q_chunk(std::integral_constant<int, k0>{}, std::integral_constant<int, k1>{})
            const float dl0 = mean0 - bf_lo(mb0), dl1 = mean1 - bf_lo(mb1);
            const float rs0 = rsq(fmaxf(quad_sum(ss0 + ss2) * (1.f / kD) - dl0 * dl0, 0.f) + kEps);
            const float rs1 = rsq(fmaxf(quad_sum(ss1 + ss3) * (1.f / kD) - dl1 * dl1, 0.f) + kEps);
            float rk[3][2];
            rk[1][0] = __shfl_sync(~0u, rs0, t * 8); rk[1][1] = __shfl_sync(~0u, rs0, t * 8 + 4);
            rk[2][0] = __shfl_sync(~0u, rs1, t * 8); rk[2][1] = __shfl_sync(~0u, rs1, t * 8 + 4);
            const uint32_t stg = sb + SM_STG + wg * 8192 + lane * 16;
            if (!qok) mbar_wait(BAR(B_WQF), 0);
            QCHUNK(0, QC0);
            wg_wait<1>();
            reg_fence(ak); reg_fence(av);
            uint32_t kf[3][7], vf[3][7];
            #pragma unroll
            for (int c = 0; c < 7; c++) {
                kf[2][c] = pack_bf16(ak[4 * c + 2], ak[4 * c + 3]);
                vf[2][c] = movm(pack_bf16(av[4 * c + 2], av[4 * c + 3]));
            }
            const uint32_t om = ~lane & 1;
            kf[2][0] = set_par(kf[2][0], om, tag); vf[2][0] = set_par(vf[2][0], om, tag);
            vf[2][1] = set_par(vf[2][1], om, tag); vf[2][5] = set_par(vf[2][5], om, tag);
            auto publish = [&](auto st) {
                st(0, kf[2][0], kf[2][1], kf[2][2], kf[2][3]);
                st(1, vf[2][0], kf[2][4], kf[2][5], kf[2][6]);
                st(2, vf[2][1], vf[2][2], vf[2][3], vf[2][4]);
                st(3, vf[2][5], vf[2][6], __float_as_uint(rk[2][0]), __float_as_uint(rk[2][1]));
            };
            if (w < 3 || rank) publish([&](int c, uint32_t x, uint32_t y, uint32_t z, uint32_t v) { st_gen4(hp + c * 32, x, y, z, v); });
            else publish([&](int c, uint32_t x, uint32_t y, uint32_t z, uint32_t v) {
                asm volatile("st.async.shared::cluster.mbarrier::complete_tx::bytes.v4.b32 [%0], {%2,%3,%4,%5}, [%1];"
                             :: "r"(pbar0 + (SM_STG + 3 * 2048 - SM_BAR) + wg * 8192 + lane * 16 + c * 512), "r"(pbar0 + (B_HL + wg) * 8),
                                "r"(x), "r"(y), "r"(z), "r"(v) : "memory");
            });
            pair_arrive(B_KVC);
            QCHUNK(QC0, QC1);
            #pragma unroll
            for (int c = 0; c < 7; c++) {
                kf[1][c] = pack_bf16(ak[4 * c], ak[4 * c + 1]);
                vf[1][c] = movm(pack_bf16(av[4 * c], av[4 * c + 1]));
            }
            QCHUNK(QC1, QC2);
            named_bar(1 + wg, 128);
            uint32_t* op = opaque_ptr((uint32_t*)&prm.sc->o[((ti * 2 + wg) * 56 + hg * 7) * 64] + w * 64 + lane);
            om0 = opaque((lane & 7) == w * 2); om1 = opaque((lane & 7) == w * 2 + 1);
            QCHUNK(QC2, 28);
            warp_arrive(BAR(B_QL));
            #undef QCHUNK
            const bool gt0 = 2 * t > g, gt1 = 2 * t + 1 > g, no_prev = ti == 0 && w == 0;
            const float kf0 = gt0 ? rk[1][0] : rk[2][0], kf1 = gt1 ? rk[1][1] : rk[2][1];
            constexpr float kScale = 0.18898223650461362f * 1.4426950408889634f;
            const float sq0 = rs0 * kScale, sf0 = kf0 * (rs1 * kScale), sf1 = kf1 * (rs1 * kScale);
            const float NEG = -__int_as_float(0x7f800000);
            const float nb0 = gt0 && no_prev ? NEG : 0.f, nb1 = gt1 && no_prev ? NEG : 0.f;
            const uint32_t mk = opaque((gt0 ? 0x0000ffffu : 0u) | (gt1 ? 0xffff0000u : 0u));
            const uint32_t nil = __shfl_sync(~0u, lane, 0);
            const uint32_t sr = stg + ((w + 3) & 3) * 2048, hbar = BAR(w == 0 ? B_HL + wg : B_EP);
            mbar_wait(BAR(B_EP), 0);
            wg_wait<0>();
            reg_fence(aq);
            warp_arrive(BAR(B_A1D));
            uint32_t qf[8][2];
            #pragma unroll
            for (int c = 0; c < 7; c++) {
                qf[c + (c > 3)][0] = pack_bf16(aq[4 * c], aq[4 * c + 1]);
                qf[c + (c > 3)][1] = pack_bf16(aq[4 * c + 2], aq[4 * c + 3]);
            }
            qf[4][0] = t >= 2 ? qf[3][0] : 0u; qf[4][1] = t >= 2 ? qf[3][1] : 0u;
            qf[3][0] = t < 2 ? qf[3][0] : 0u;  qf[3][1] = t < 2 ? qf[3][1] : 0u;
            float sc[2][3][4];
            auto scores = [&](int n) {
                #pragma unroll
                for (int hd = 0; hd < 2; hd++) {
                    sc[hd][n][0] = sc[hd][n][1] = sc[hd][n][2] = sc[hd][n][3] = 0.f;
                    mma16816(sc[hd][n], qf[4 * hd][0], qf[4 * hd][1], qf[4 * hd + 1][0], qf[4 * hd + 1][1], kf[n][3 * hd], kf[n][3 * hd + 1]);
                    mma16816(sc[hd][n], qf[4 * hd + 2][0], qf[4 * hd + 2][1], qf[4 * hd + 3][0], qf[4 * hd + 3][1], kf[n][3 * hd + 2], kf[n][3 * hd + 3]);
                }
            };
            scores(1); scores(2);
            mbar_wait(hbar, 0);
            {
                const uint4 u0 = lds4(sr), u1 = lds4(sr + 512), u3 = lds4(sr + 1536), u2 = lds4(sr + 1024);
                kf[0][0] = u0.x; kf[0][1] = u0.y; kf[0][2] = u0.z; kf[0][3] = u0.w;
                vf[0][0] = u1.x; kf[0][4] = u1.y; kf[0][5] = u1.z; kf[0][6] = u1.w;
                vf[0][1] = u2.x; vf[0][2] = u2.y; vf[0][3] = u2.z; vf[0][4] = u2.w;
                vf[0][5] = u3.x; vf[0][6] = u3.y; rk[0][0] = __uint_as_float(u3.z); rk[0][1] = __uint_as_float(u3.w);
            }
            scores(0);
            const float ke0 = gt0 ? rk[0][0] : rk[1][0], ke1 = gt1 ? rk[0][1] : rk[1][1];
            const float se0 = ke0 * sq0, se1 = ke1 * sq0;
            uint32_t ow[7][2];
            #pragma unroll
            for (int hd = 0; hd < 2; hd++) {
                const int c0 = hd * 3;
                float (&sc_)[3][4] = sc[hd];
                const float e0 = fmaf(gt0 ? sc_[0][0] : sc_[1][0], se0, nb0), e1 = fmaf(gt1 ? sc_[0][1] : sc_[1][1], se1, nb1);
                const float f0 = (gt0 ? sc_[1][2] : sc_[2][2]) * sf0, f1 = (gt1 ? sc_[1][3] : sc_[2][3]) * sf1;
                const float me = quad_max(fmaxf(e0, e1)), mf = quad_max(fmaxf(f0, f1));
                const float p0 = ex2(e0 - me), p1 = ex2(e1 - me), r0 = ex2(f0 - mf), r1 = ex2(f1 - mf);
                const float ie = rcp(quad_sum(p0 + p1)), jf = rcp(quad_sum(r0 + r1));
                const uint32_t pp = pack_bf16(p0 * ke0 * ie, p1 * ke1 * ie), rp = pack_bf16(r0 * kf0 * jf, r1 * kf1 * jf);
                const uint32_t a0 = pp & ~mk, a1 = rp & mk, a3 = rp & ~mk, a4 = pp & mk, zero = pp & nil, zero2 = rp & nil;
                #pragma unroll
                for (int c = 0; c < 4; c++) {
                    float o[4] = {0.f, 0.f, 0.f, 0.f};
                    mma16816(o, a0, a1, zero, a3, vf[1][c0 + c], vf[2][c0 + c]);
                    mma1688(o, a4, zero2, vf[0][c0 + c]);
                    const uint32_t lo = pack_bf16(o[0], o[1]), hi = pack_bf16(o[2], o[3]);
                    if (hd == 1 && c == 0) { if (t >= 2) { ow[3][0] = lo; ow[3][1] = hi; } }
                    else { ow[c0 + c][0] = lo; ow[c0 + c][1] = hi; }
                }
            }
            #pragma unroll
            for (int c = 0; c < 7; c++) {
                stg1(op + c * 256,      set_par(ow[c][0], om0, tag));
                stg1(op + c * 256 + 32, set_par(ow[c][1], om1, tag));
            }
        }
        float as[28], ac[28];
        uint32_t xch, peer_xch, *gp1, *gp2;
        const uint32_t *hp, *ht;
        const uint2* hq;
        uint64_t da0, db0;
        bool lead;
        {
            float acc2[28];
            mbar_wait(BAR(B_XRF), 0);
            const int cg = a2j * 2 + wg, cg2 = (g2j + 2 * wg) * 2 + (rank ^ 1), cg1 = (g1j + 2 * wg) * 2 + (rank ^ (g1f < 14));
            lead = elect_one();
            {
                const uint32_t xa = sb + SM_XR + wg * 8192 + (w * 16 + (lane & 15)) * 128;
                #pragma unroll
                for (int c = 0; c < 4; c++) {
                    uint32_t xr[4];
                    asm volatile("ldmatrix.sync.aligned.m8n8.x4.shared.b16 {%0,%1,%2,%3}, [%4];"
                                 : "=r"(xr[0]), "=r"(xr[1]), "=r"(xr[2]), "=r"(xr[3])
                                 : "r"(xa + ((((c * 2 + wg + (lane >> 4)) ^ lane) & 7) << 4)) : "memory");
                    #pragma unroll
                    for (int e = 0; e < (c < 3 ? 4 : 2); e++) { acc2[8 * c + 2 * e] = bf_lo(xr[e]); acc2[8 * c + 2 * e + 1] = bf_hi(xr[e]); }
                }
            }
            uint32_t* spw = opaque_ptr(&prm.sc->stats[((a2s * 8 + cg) * 4 + w) * 32 + lane]);
            const uint32_t* spr = opaque_ptr(&prm.sc->stats[(a2s * 32 + w) * 32 + lane]);
            uint32_t* rp = opaque_ptr((uint32_t*)&prm.sc->rows[a2s * 64 + w * 16 + (t >> 1) * 8 + g] + (t & 1));
            const int cgs = cg ^ (a2s >> 4);
            uint32_t* np = opaque_ptr((uint32_t*)&prm.sc->hn[(a2s * 56 + cgs * 7) * 64] + w * 64 + lane);
            const uint64_t dwo = make_desc(sb + SM_WKV + wg * (28672 + 16), 0, true);
            const uint64_t doa = make_desc(sb + SM_WQ, 1024, false, 128);
            bias1a = prm.b1[g1f * 64 + w * 16 + g]; bias1b = prm.b1[g1f * 64 + w * 16 + 8 + g];
            const __nv_bfloat16 bias2 = prm.b2[ti * 128 + (w * 16 + (t >> 1) * 8 + g) * 2 + a2p];
            reg_fence(acc2);
            fence_async_smem();
            warp_arrive(BAR(B_XD));
            mbar_wait2(BAR(B_WOF), 0, BAR(B_WOF + 1), 0);
            mbar_wait(BAR(B_OD), 0);
            const uint32_t order = __shfl_sync(~0u, lds1(sb + SM_ORD), 0);
            static_for<0, 4>([&](auto P_) {
                constexpr int P = decltype(P_)::value;
                const uint64_t dwp = dwo + ((order >> (2 * P + 1) & 1) * 3584 + (order >> 2 * P & 1) * 896);
                mbar_wait(BAR(B_OF + P), 0);
                wg_fence();
                static_for<0, 7>([&](auto K_) { constexpr int k = decltype(K_)::value;
                    wgmma_ss_n56<P * 14336 + k * 2048, k * 2048, 0>(acc2, doa, dwp); });
                if (P) wg_commit();
                if (P == 2) { wg_wait<1>(); warp_arrive(BAR(B_OC)); }
            });
            wg_wait<0>();
            reg_fence(acc2);
            float s0 = 0.f, s1 = 0.f, q0 = 0.f, q1 = 0.f;
            #pragma unroll
            for (int c = 0; c < 7; c++) {
                s0 += acc2[4 * c] + acc2[4 * c + 1];     q0 = fmaf(acc2[4 * c], acc2[4 * c], fmaf(acc2[4 * c + 1], acc2[4 * c + 1], q0));
                s1 += acc2[4 * c + 2] + acc2[4 * c + 3]; q1 = fmaf(acc2[4 * c + 2], acc2[4 * c + 2], fmaf(acc2[4 * c + 3], acc2[4 * c + 3], q1));
            }
            const bool th = t >= 2, to = t & 1;
            const float sa = (th ? s1 : s0) + __shfl_xor_sync(~0u, th ? s0 : s1, 2), qa = (th ? q1 : q0) + __shfl_xor_sync(~0u, th ? q0 : q1, 2);
            const float part = (to ? qa : sa) + __shfl_xor_sync(~0u, to ? sa : qa, 1);
            stg1(spw, set_par(__float_as_uint(part), 1u, tag));
            const uint32_t tpoll = clk32() + SDELAY;
            warp_arrive(BAR(B_HD));
            uint32_t us[8];
            {
                xch = opaque(sb + SM_XCH + w * 1792 + lane * 16);
                asm volatile("mapa.shared::cluster.u32 %0, %1, %2;" : "=r"(peer_xch) : "r"(xch), "r"(rank ^ 1));
                const int hcg = cg2 ^ (g2s >> 4), hrg = (g2s & 1) * 4 + w;
                const uint32_t* hl = (const uint32_t*)&prm.sc->hn[((g2s >> 1) * 112 + hcg * 7) * 64 + hrg * 8];
                hp = opaque_ptr(hl + (g & 1) * 14336 + (g >> 1) * 4 + t);
                ht = opaque_ptr(hl + min(lane >> 2, 6) * 256 + (lane & 3) * 8 + hrg);
                hq = opaque_ptr(&prm.sc->rows[((g2s >> 1) * 2 + (g & 1)) * 64 + hrg * 8 + (g >> 1)]);
                gp1 = opaque_ptr((uint32_t*)&prm.sc->g[(g1f * 56 + cg1 * 7) * 64] + w * 64 + lane);
                gp2 = opaque_ptr((uint32_t*)(prm.out + (size_t)(g2s * 64 + w * 16 + lane / 7) * kD + cg2 * 56) + (lane % 7) * 4);
                da0 = make_desc(sb, 0, true); db0 = make_desc(sb + SM_B, 128, false);
            }
            spin_until(tpoll);
            #pragma unroll
            for (int i = 0; i < 8; i++) us[i] = ld_rlx(spr + i * 128);
            {
                int it = 0;
                while (true) {
                    uint32_t bad = 0;
                    #pragma unroll
                    for (int i = 0; i < 8; i++) bad |= us[i] ^ tag;
                    if (!__any_sync(~0u, bad & 1)) break;
                    if (++it > kSpinLimit) break;
                    #pragma unroll
                    for (int i = 0; i < 8; i++) us[i] = ld_rlx(spr + i * 128);
                }
            }
            const float tot = (((__uint_as_float(us[0]) + __uint_as_float(us[1])) + (__uint_as_float(us[2]) + __uint_as_float(us[3])))
                            + ((__uint_as_float(us[4]) + __uint_as_float(us[5])) + (__uint_as_float(us[6]) + __uint_as_float(us[7])))) * (1.f / kD);
            const float oth = __shfl_xor_sync(~0u, tot, 1);
            const float mean = to ? oth : tot;
            const float var = fmaxf(fmaf(-mean, mean, to ? tot : oth), 0.f);
            const float rra = rsq(fmaf(var, 4.f + 4.f * kEps, 4.f * kEps * kEps)), mra = -mean * rra;
            const float rrb = __shfl_xor_sync(~0u, rra, 2), mrb = __shfl_xor_sync(~0u, mra, 2);
            const float rr0 = th ? rrb : rra, mr0 = th ? mrb : mra, rr1 = th ? rra : rrb, mr1 = th ? mra : mrb;
            #pragma unroll
            for (int c = 0; c < 7; c++) {
                stg1(np + c * 256,      set_par(pack_bf16(fmaf(acc2[4 * c], rr0, mr0), fmaf(acc2[4 * c + 1], rr0, mr0)), om0, tag));
                stg1(np + c * 256 + 32, set_par(pack_bf16(fmaf(acc2[4 * c + 2], rr1, mr1), fmaf(acc2[4 * c + 3], rr1, mr1)), om1, tag));
            }
            if (cg == 0) stg1(rp, set_par(__float_as_uint(to ? mean + __bfloat162float(bias2) : rcp(rra)), 1u, tag));
            #pragma unroll
            for (int c = 0; c < 28; c++) { ac[c] = 0.5f * __bfloat162float(c & 2 ? bias1b : bias1a); as[c] = 0.f; }
            reg_fence(as); reg_fence(ac);
        }
        auto send = [&]() {
            const uint32_t rf = pbar0 + (B_RF + warp) * 8;
            #pragma unroll
            for (int c = 0; c < 4; c++) {
                const uint32_t p0 = pack_bf16(as[8 * c], as[8 * c + 1]), p1 = pack_bf16(as[8 * c + 2], as[8 * c + 3]);
                if (c < 3) {
                    const uint32_t p2 = pack_bf16(as[8 * c + 4], as[8 * c + 5]), p3 = pack_bf16(as[8 * c + 6], as[8 * c + 7]);
                    asm volatile("st.async.shared::cluster.mbarrier::complete_tx::bytes.v4.b32 [%0], {%1,%2,%3,%4}, [%5];"
                                 :: "r"(peer_xch + c * 512), "r"(p0), "r"(p1), "r"(p2), "r"(p3), "r"(rf) : "memory");
                } else {
                    asm volatile("st.async.shared::cluster.mbarrier::complete_tx::bytes.v2.b32 [%0], {%1,%2}, [%3];"
                                 :: "r"(peer_xch + 1536 - lane * 8), "r"(p0), "r"(p1), "r"(rf) : "memory");
                }
            }
        };
        auto receive = [&](uint32_t (&pk)[14], uint32_t phase) {
            mbar_wait(BAR(B_RF + warp), phase);
            #pragma unroll
            for (int c = 0; c < 3; c++) { const uint4 u = lds4(xch + c * 512); pk[4 * c] = u.x; pk[4 * c + 1] = u.y; pk[4 * c + 2] = u.z; pk[4 * c + 3] = u.w; }
            const uint2 u = lds2(xch + 1536 - lane * 8); pk[12] = u.x; pk[13] = u.y;
        };
        uint2 rw[2]; uint32_t tw, tx;
        auto load_rows = [&]() { tw = ld_rlx(ht); tx = ld_rlx(ht + 14336); rw[0] = ld_rlx2(hq); rw[1] = ld_rlx2(hq + 4); };
        rw[0] = rw[1] = make_uint2(0u, 0u); tw = tx = ~tag;
        #pragma unroll 1
        for (int ge = 0;; ge++) {
          if (ge || g1_on) {
            const int use = ge * 2 + wg;
            int entry = ge ? 1 : 2 * wg, stop = 0;
            uint64_t da = da0 + (ge ? -3 : wg ? NR - 10 : 0) * 512;
            bool rel = lead && use == 1;
            const uint32_t xfree = BAR(use > (g1_on ? 0 : 2) ? B_RE + use - 1 : B_PD);
            mbar_wait(BAR(B_AF), 0);
            if (ge && (wg || g1_on)) named_bar(5 - wg, 256);
            auto step = [&](auto I_) {
                constexpr int i = decltype(I_)::value, sl = i % NB, ao = i * 8192, bo = sl * 14336;
                mbar_wait_fast(BAR(B_BF + sl), i / NB);
                wg_fence();
                wgmma_ss_n112<ao,        bo,       1>(as, ac, da, db0);
                wgmma_ss_n112<ao + 2048, bo + 256, 1>(as, ac, da, db0);
                wgmma_ss_n112<ao + 4096, bo + 512, 1>(as, ac, da, db0);
                wgmma_ss_n112<ao + 6144, bo + 768, 1>(as, ac, da, db0);
                wg_commit();
                if (i == 1 && stop == 1) named_arrive(4, 256);
                if (i == 3 && (use == 1 || use == 2)) named_arrive(4 + wg, 256);
                wg_wait<1>();
                mbar_arrive_if(BAR(B_BE + (13 + i) % 14), rel);
                rel = lead;
            };
            #pragma unroll 1
            while (true) {
                if (entry < 1) {
                    static_for<0, 2>(step);
                    if (stop == 1) break;
                    static_for<2, 4>(step);
                    if (stop) break;
                }
                if (entry < 2) static_for<4, 10>(step);
                else {
                    uint32_t af[NR * 4][4];
                    mbar_wait(BAR(B_GO), 0);
                    const uint32_t tp = lds1(sb + SM_TG + 4) + PLOFF;
                    int it = 0;
                    while ((int)(gtime32() - tp) < 0 && ++it < 256) __nanosleep(20);
                    const uint32_t la = sb + ((lane >> 4) * 8 + (lane & 7)) * 128 + (((w * 2 + ((lane >> 3) & 1)) ^ (lane & 7)) << 4);
                    #pragma unroll
                    for (int k = 0; k < NR * 4; k++)
                        asm volatile("ldmatrix.sync.aligned.m8n8.x4.trans.shared.b16 {%0,%1,%2,%3}, [%4];"
                                     : "=r"(af[k][0]), "=r"(af[k][1]), "=r"(af[k][2]), "=r"(af[k][3]) : "r"(la + k * 2048) : "memory");
                    __syncwarp();
                    mbar_arrive_if(BAR(B_PL), lead);
                    if (w == 0) {
                        const char* p2 = (const char*)prm.w2 + ((b >> 6) * 896 + (b & 63) + PFW * 64) * 4096 + lane * 128;
                        #pragma unroll 1
                        for (int i = 0; i < 14 - PFW; i++) {
                            it = 0;
                            while ((int)(gtime32() - tp) < PF3OFF + i * PF3PACE && ++it < 256) __nanosleep(40);
                            asm volatile("prefetch.global.L2 [%0];" :: "l"(p2 + i * 64 * 4096));
                        }
                    }
                    named_bar(4, 256);
                    static_for<0, NR>([&](auto I_) {
                        constexpr int i = decltype(I_)::value, sl = (16 + i) % NB, o = sl * 14336;
                        mbar_wait_fast(BAR(B_BF + sl), (16 + i) / NB & 1);
                        wg_fence();
                        wgmma_rs_n112<o,       1>(as, ac, af[4 * i][0], af[4 * i][1], af[4 * i][2], af[4 * i][3], db0);
                        wgmma_rs_n112<o + 256, 1>(as, ac, af[4 * i + 1][0], af[4 * i + 1][1], af[4 * i + 1][2], af[4 * i + 1][3], db0);
                        wgmma_rs_n112<o + 512, 1>(as, ac, af[4 * i + 2][0], af[4 * i + 2][1], af[4 * i + 2][2], af[4 * i + 2][3], db0);
                        wgmma_rs_n112<o + 768, 1>(as, ac, af[4 * i + 3][0], af[4 * i + 3][1], af[4 * i + 3][2], af[4 * i + 3][3], db0);
                        wg_commit();
                        if (i) { wg_wait<1>(); mbar_arrive_if(BAR(B_BE + (15 + i) % (2 * NB)), lead); }
                    });
                }
                static_for<10, 14>(step);
                entry = 0; stop = use + 1; da += 14 * 512;
            }
            const uint32_t prev = BAR(B_BE + (use ? 3 : 1));
            const bool xok = mbar_test(xfree, 0);
            wg_wait<0>();
            reg_fence(as); reg_fence(ac);
            mbar_arrive_if(prev, lead);
            if (!xok) mbar_wait(xfree, 0);
            if (ge) break;
            send();
            load_rows();
            uint32_t pk[14];
            receive(pk, 0);
            #pragma unroll
            for (int c = 0; c < 14; c++) {
                float r[2];
                #pragma unroll
                for (int e = 0; e < 2; e++) {
                    const float u = ac[2 * c + e] + (e ? bf_hi(pk[c]) : bf_lo(pk[c]));
                    r[e] = fmaf(u, tanh_hw(u * fmaf(u * u, 8.f * 0.7978845608f * 0.044715f, 2.f * 0.7978845608f)), u);
                }
                stg1(gp1 + (c >> 1) * 256 + (c & 1) * 32, set_par(pack_bf16(r[0], r[1]), c & 1 ? om1 : om0, tag));
            }
            named_bar(1 + wg, 128);
            if (w == 0 && lane == 0) {
                asm volatile("st.shared.u32 [%0], %1;" :: "r"(sb + SM_TG + 8 + wg * 4), "r"(clk32() + (wg ? XSPECB : XSPEC)) : "memory");
                mbar_arrive(BAR(B_GD + wg));
            }
            if (lead) mbar_expect(BAR(B_RF + warp), 1792);
            mbar_arrive_remote_if(pbar0 + (B_RE + wg) * 8, lead);
          } else mbar_wait(BAR(B_GD), 0);
            {
                int it = 0;
                while (__any_sync(~0u, ((tw ^ tag) | (tx ^ tag) | (rw[0].x ^ tag) | (rw[0].y ^ tag) | (rw[1].x ^ tag) | (rw[1].y ^ tag)) & 1)) {
                    if (++it > kSpinLimit) break;
                    load_rows();
                }
                uint32_t hw[14];
                #pragma unroll
                for (int c = 0; c < 14; c++) hw[c] = ld_rlx(hp + (c >> 1) * 256 + (c & 1) * 16);
                #pragma unroll
                for (int c = 0; c < 14; c++) {
                    ac[2 * c]     = fmaf(bf_lo(hw[c]), __uint_as_float(rw[c & 1].x), __uint_as_float(rw[c & 1].y));
                    ac[2 * c + 1] = fmaf(bf_hi(hw[c]), __uint_as_float(rw[c & 1].x), __uint_as_float(rw[c & 1].y));
                    as[2 * c] = as[2 * c + 1] = 0.f;
                }
                reg_fence(as); reg_fence(ac);
            }
        }
        uint32_t po[14], pk[14];
        if (!wg) sleep_until(clk32() + w * STAG2);
        send();
        #pragma unroll
        for (int c = 0; c < 14; c++) po[c] = opaque(pack_bf16(ac[2 * c], ac[2 * c + 1]));
        receive(pk, g1_on);
        #pragma unroll
        for (int c = 0; c < 14; c++) pk[c] = add_bf16x2(po[c], pk[c]);
        __syncwarp();
        const uint32_t sa = xch - lane * 16 + (lane & 15) * 112 + (lane >> 4) * 16;
        #pragma unroll
        for (int m = 0; m < 3; m++)
            asm volatile("stmatrix.sync.aligned.m8n8.x4.shared.b16 [%0], {%1,%2,%3,%4};"
                         :: "r"(sa + m * 32), "r"(pk[4 * m]), "r"(pk[4 * m + 1]), "r"(pk[4 * m + 2]), "r"(pk[4 * m + 3]) : "memory");
        asm volatile("stmatrix.sync.aligned.m8n8.x2.shared.b16 [%0], {%1,%2};" :: "r"(sa + 96), "r"(pk[12]), "r"(pk[13]) : "memory");
        __syncwarp();
        if (lane < 28) {
            #pragma unroll
            for (int i = 0; i < 4; i++) { const uint4 u = lds4(xch + i * 448); stg4(gp2 + i * 896, u.x, u.y, u.z, u.w); }
        }
        __syncwarp();
        mbar_arrive_remote_if(pbar0 + (B_RE + 2) * 8, lead && wg == 0);
        if (b == 0 && tid == 128) prm.sc->epoch = tag;
    }
}

typedef CUresult (*EncodeFn)(CUtensorMap*, CUtensorMapDataType, cuuint32_t, void*, const cuuint64_t*, const cuuint64_t*,
                             const cuuint32_t*, const cuuint32_t*, CUtensorMapInterleave, CUtensorMapSwizzle,
                             CUtensorMapL2promotion, CUtensorMapFloatOOBfill);

void make_map(EncodeFn enc, CUtensorMap* m, const void* base, uint64_t cols, uint64_t rows, uint32_t box_rows) {
    cuuint64_t dims[2] = {cols, rows};
    cuuint64_t strides[1] = {cols * 2};
    cuuint32_t box[2] = {64, box_rows};
    cuuint32_t es[2] = {1, 1};
    enc(m, CU_TENSOR_MAP_DATA_TYPE_BFLOAT16, 2, const_cast<void*>(base), dims, strides, box, es, CU_TENSOR_MAP_INTERLEAVE_NONE,
        CU_TENSOR_MAP_SWIZZLE_128B, CU_TENSOR_MAP_L2_PROMOTION_L2_128B, CU_TENSOR_MAP_FLOAT_OOB_FILL_NONE);
}

}

extern "C" void kernel_launch(void* const* d_in, const int* in_sizes, int n_in, void* d_out, int out_size) {
    (void)in_sizes; (void)n_in; (void)out_size;
    void* fn = nullptr;
    cudaDriverEntryPointQueryResult qr;
    cudaGetDriverEntryPoint("cuTensorMapEncodeTiled", &fn, cudaEnableDefault, &qr);
    EncodeFn enc = (EncodeFn)fn;
    CUtensorMap mX2, mX, mWqkv, mWo, mW1, mW2;
    {
        cuuint64_t dims[3] = {kD, kS / 2, 2}, strides[2] = {4 * kD, 2 * kD};
        cuuint32_t box[3] = {64, 64, 2}, es[3] = {1, 1, 1};
        enc(&mX2, CU_TENSOR_MAP_DATA_TYPE_BFLOAT16, 3, d_in[0], dims, strides, box, es, CU_TENSOR_MAP_INTERLEAVE_NONE,
            CU_TENSOR_MAP_SWIZZLE_128B, CU_TENSOR_MAP_L2_PROMOTION_L2_128B, CU_TENSOR_MAP_FLOAT_OOB_FILL_NONE);
    }
    make_map(enc, &mX, d_in[0], 2 * kD, kS / 2, 64);
    make_map(enc, &mWqkv, d_in[1], 3 * kD, kD, 64);
    make_map(enc, &mWo, d_in[2], kD, kD, 112);
    make_map(enc, &mW1, d_in[4], 2 * kF, kS / 2, 64);
    make_map(enc, &mW2, d_in[6], kS, kF, 64);
    Params prm;
    prm.x = (const __nv_bfloat16*)d_in[0];
    prm.wqkv = (const __nv_bfloat16*)d_in[1];
    prm.wo = (const __nv_bfloat16*)d_in[2];
    prm.w1 = (const __nv_bfloat16*)d_in[4];
    prm.b1 = (const __nv_bfloat16*)d_in[5];
    prm.w2 = (const __nv_bfloat16*)d_in[6];
    prm.b2 = (const __nv_bfloat16*)d_in[7];
    prm.out = (__nv_bfloat16*)d_out;
    cudaGetSymbolAddress((void**)&prm.sc, g_scratch);
    cudaFuncSetAttribute(fused_kernel, cudaFuncAttributeMaxDynamicSharedMemorySize, SM_TOTAL);
    fused_kernel<<<128, 384, SM_TOTAL, cudaStreamPerThread>>>(prm, mX2, mX, mWqkv, mWo, mW1, mW2);
}
```

```cpp
#include <cuda_runtime.h>
#include <cuda.h>
#include <cuda_bf16.h>
#include <stdint.h>
#include <type_traits>

namespace {

constexpr int kS = 2048, kD = 448, kF = 1792;
constexpr float kEps = 1e-5f;

constexpr int FS = 32;
constexpr int NPRE = 10;
constexpr int NR = 8;
constexpr int PFW = 4;
constexpr int QC0 = 4;
constexpr int QC1 = 10;
constexpr int QC2 = 16;
constexpr int PFD = 250;
constexpr int PFPACE = 280;
constexpr int PFPACE2 = 300;
constexpr int HDELAY = 200;
constexpr int WOD = 350;
constexpr int SDELAY = 200;
constexpr int PDELAY = 400;
constexpr int PACE1 = 120;
constexpr int PACE2 = 400;
constexpr int PACEB = 300;
constexpr int XSPEC = 500;
constexpr int XSPECB = 750;
constexpr int CN2 = 7400;
constexpr int CN3 = 11400;
constexpr int W2OFF = 800;
constexpr int W2PACE = 350;
constexpr int STAG2 = 650;
constexpr int QLNS = 256;
constexpr int DELTAO = 800;
constexpr int DMIN = 448;
constexpr int XDNS = 32;
constexpr int CHUNKNS = 250;
constexpr int DELTA = 2016;
constexpr int PLOFF = -250;
constexpr int PF3OFF = 300;
constexpr int PF3PACE = 240;

struct Scratch {
    uint32_t flag_o[16 * 8 * FS];
    uint4    o[32 * 56 * 64];
    uint32_t stats[32 * 8 * 4 * 32];
    uint4    hn[32 * 56 * 64];
    uint32_t flag_h[32 * 4 * FS];
    uint4    g[28 * 56 * 64];
    uint4    halo[8 * 8 * 2 * 4 * 32];
    uint2    rows[32 * 64];
    uint32_t epoch;
};
__device__ __align__(1024) Scratch g_scratch;

constexpr uint32_t SM_WKV  = 114688;
constexpr uint32_t SM_XR   = 24576;
constexpr uint32_t SM_STG  = 40960;
constexpr uint32_t SM_WQ   = 57344;
constexpr uint32_t SM_XCH  = 0;
constexpr uint32_t SM_B    = 131072;
constexpr uint32_t SM_BAR  = 231424;
constexpr uint32_t SM_TOTAL = SM_BAR + 1024;
constexpr int NB = 7;
constexpr int B_XF = 0, B_WKVF = 7, B_WQF = 14, B_XRF = 15, B_WOF = 16,
              B_XC = 18, B_KV3 = 19, B_KVC = 20,
              B_A1D = 21, B_XD = 22, B_OC = 23, B_QL = 24,
              B_BE = 25  , B_RE = B_BE + 2 * NB,
              B_PL = B_RE + 3, B_AF = B_PL + 1, B_BL = B_AF + 1  , B_OL = B_BL + 2 * NB  ,
              B_BF = B_OL + 4  , B_OF = B_BF + NB, B_RF = B_OF + 4, B_EP = B_RF + 8, B_PD = B_EP + 1, B_OD = B_PD + 1, B_RT = B_OD + 1, B_HL = B_RT + 2,
              B_HD = B_HL + 2  , B_GO = B_HD + 1, B_GD = B_GO + 1, B_COUNT = B_GD + 2;
constexpr uint32_t SM_EPOCH = SM_BAR + B_COUNT * 8, SM_TG = SM_EPOCH + 4  , SM_TG2 = SM_TG + 16  ,
                   SM_ORD = SM_TG2 + 4  ;

constexpr uint64_t kAPos = 0x3330ull | 0x5555555ull << 17;
constexpr uint32_t seg_mask(int h, int p0, int p1) {
    uint32_t m = 0; int n = 0;
    for (int p = p0; p < p1; p++) if ((p & 1) == h) m |= (uint32_t)((kAPos >> p) & 1) << n++;
    return m | 1u << n;
}
constexpr uint64_t seg_masks(int h) {
    return 2 | (uint64_t)seg_mask(h, 0, 16) << 10 | (uint64_t)seg_mask(h, 16, 32) << 20
             | (uint64_t)seg_mask(h, 32, 46) << 30 | (uint64_t)seg_mask(h, 46, 60) << 40;
}
constexpr uint64_t kSegMasks0 = seg_masks(0), kSegMasks1 = seg_masks(1);

constexpr int kSpinLimit = 1 << 15;
__device__ __forceinline__ bool elect_one() {
    uint32_t p;
    asm volatile("{ .reg .pred P; elect.sync _|P, 0xffffffff; selp.u32 %0, 1, 0, P; }" : "=r"(p));
    return p;
}
__device__ __forceinline__ void mbar_init(uint32_t bar, uint32_t cnt) { asm volatile("mbarrier.init.shared::cta.b64 [%0], %1;" :: "r"(bar), "r"(cnt)); }
__device__ __forceinline__ void mbar_expect(uint32_t bar, uint32_t bytes) { asm volatile("mbarrier.arrive.expect_tx.shared::cta.b64 _, [%0], %1;" :: "r"(bar), "r"(bytes) : "memory"); }
__device__ __forceinline__ void mbar_expect_more(uint32_t bar, uint32_t bytes) { asm volatile("mbarrier.expect_tx.relaxed.cta.shared::cta.b64 [%0], %1;" :: "r"(bar), "r"(bytes) : "memory"); }
__device__ __forceinline__ void mbar_arrive(uint32_t bar) { asm volatile("mbarrier.arrive.shared::cta.b64 _, [%0];" :: "r"(bar) : "memory"); }
__device__ __forceinline__ void mbar_wait(uint32_t bar, uint32_t parity) {
    uint32_t ok; int it = 0;
    do {
        asm volatile("{ .reg .pred p; mbarrier.try_wait.parity.shared::cta.b64 p, [%1], %2; selp.u32 %0, 1, 0, p; }"
                     : "=r"(ok) : "r"(bar), "r"(parity) : "memory");
        if (++it > kSpinLimit) break;
    } while (!ok);
}
__device__ __forceinline__ bool mbar_try(uint32_t bar, uint32_t parity) {
    uint32_t ok;
    asm volatile("{ .reg .pred p; mbarrier.try_wait.parity.shared::cta.b64 p, [%1], %2; selp.u32 %0, 1, 0, p; }" : "=r"(ok) : "r"(bar), "r"(parity) : "memory");
    return ok;
}
__device__ __forceinline__ bool mbar_test(uint32_t bar, uint32_t parity) {
    uint32_t ok;
    asm volatile("{ .reg .pred p; mbarrier.test_wait.parity.shared::cta.b64 p, [%1], %2; selp.u32 %0, 1, 0, p; }" : "=r"(ok) : "r"(bar), "r"(parity) : "memory");
    return ok;
}
__device__ __forceinline__ void mbar_wait_fast(uint32_t bar, uint32_t parity) { if (!mbar_try(bar, parity)) mbar_wait(bar, parity); }
__device__ __forceinline__ void mbar_wait2(uint32_t bar0, uint32_t par0, uint32_t bar1, uint32_t par1) {
    uint32_t ok; int it = 0;
    do {
        asm volatile("{ .reg .pred p, q; mbarrier.try_wait.parity.shared::cta.b64 p, [%1], %2;\n"
                     "mbarrier.try_wait.parity.shared::cta.b64 q, [%3], %4; and.pred p, p, q; selp.u32 %0, 1, 0, p; }"
                     : "=r"(ok) : "r"(bar0), "r"(par0), "r"(bar1), "r"(par1) : "memory");
        if (++it > kSpinLimit) break;
    } while (!ok);
}
template <int N> __device__ __forceinline__ void reg_fence(float (&d)[N]) {
    #pragma unroll
    for (int i = 0; i < N; i++) asm volatile("" : "+f"(d[i]) :: "memory");
}
__device__ __forceinline__ void mbar_arrive_if(uint32_t bar, bool pred) {
    asm volatile("{ .reg .pred p; setp.ne.u32 p, %1, 0; @p mbarrier.arrive.shared::cta.b64 _, [%0]; }" :: "r"(bar), "r"((uint32_t)pred) : "memory");
}
__device__ __forceinline__ void warp_arrive(uint32_t bar) { __syncwarp(); if (elect_one()) mbar_arrive(bar); }
__device__ __forceinline__ void tma2d(uint32_t dst, const CUtensorMap* m, int c0, int c1, uint32_t bar) {
    asm volatile("cp.async.bulk.tensor.2d.shared::cluster.global.mbarrier::complete_tx::bytes [%0], [%1, {%3, %4}], [%2];"
                 :: "r"(dst), "l"(m), "r"(bar), "r"(c0), "r"(c1) : "memory");
}
__device__ __forceinline__ void tma3d(uint32_t dst, const CUtensorMap* m, int c0, int c1, int c2, uint32_t bar) {
    asm volatile("cp.async.bulk.tensor.3d.shared::cluster.global.mbarrier::complete_tx::bytes [%0], [%1, {%3, %4, %5}], [%2];"
                 :: "r"(dst), "l"(m), "r"(bar), "r"(c0), "r"(c1), "r"(c2) : "memory");
}
__device__ __forceinline__ void tma2d_mc(uint32_t dst, const CUtensorMap* m, int c0, int c1, uint32_t bar) {
    asm volatile("cp.async.bulk.tensor.2d.shared::cluster.global.mbarrier::complete_tx::bytes.multicast::cluster [%0], [%1, {%3, %4}], [%2], %5;"
                 :: "r"(dst), "l"(m), "r"(bar), "r"(c0), "r"(c1), "h"((uint16_t)3) : "memory");
}
__device__ __forceinline__ void mbar_arrive_remote_if(uint32_t cluster_bar, bool pred) {
    asm volatile("{ .reg .pred p; setp.ne.u32 p, %1, 0; @p mbarrier.arrive.shared::cluster.b64 _, [%0]; }" :: "r"(cluster_bar), "r"((uint32_t)pred) : "memory");
}
__device__ __forceinline__ void bulk_g2s(uint32_t dst, const void* src, uint32_t bytes, uint32_t bar) {
    asm volatile("cp.async.bulk.shared::cluster.global.mbarrier::complete_tx::bytes [%0], [%1], %2, [%3];"
                 :: "r"(dst), "l"(src), "r"(bytes), "r"(bar) : "memory");
}
__device__ __forceinline__ void bulk_prefetch(const void* src, uint32_t bytes) { asm volatile("cp.async.bulk.prefetch.L2.global [%0], %1;" :: "l"(src), "r"(bytes) : "memory"); }
__device__ __forceinline__ void wg_fence()  { asm volatile("wgmma.fence.sync.aligned;" ::: "memory"); }
__device__ __forceinline__ void wg_commit() { asm volatile("wgmma.commit_group.sync.aligned;" ::: "memory"); }
template <int N> __device__ __forceinline__ void wg_wait() { asm volatile("wgmma.wait_group.sync.aligned %0;" :: "n"(N) : "memory"); }
__device__ __forceinline__ void named_bar(int id, int n) { asm volatile("bar.sync %0, %1;" :: "r"(id), "r"(n) : "memory"); }
__device__ __forceinline__ void named_arrive(int id, int n) { asm volatile("bar.arrive %0, %1;" :: "r"(id), "r"(n) : "memory"); }
__device__ __forceinline__ void fence_async_smem() { asm volatile("fence.proxy.async.shared::cta;" ::: "memory"); }
__device__ __forceinline__ uint32_t gtime32() { uint64_t t; asm volatile("mov.u64 %0, %%globaltimer;" : "=l"(t) :: "memory"); return (uint32_t)t; }
__device__ __forceinline__ uint32_t clk32() { uint64_t t; asm volatile("mov.u64 %0, %%clock64;" : "=l"(t) :: "memory"); return (uint32_t)t; }
__device__ __forceinline__ void spin_until(uint32_t t) { while ((int)(clk32() - t) < 0) {} }
__device__ __forceinline__ void sleep_until(uint32_t t) { while ((int)(clk32() - t) < 0) __nanosleep(20); }
__device__ __forceinline__ void st_flag(uint32_t* p, uint32_t v, uint32_t time) {
    const uint64_t w = ((uint64_t)time << 32) | v;
    asm volatile("st.relaxed.gpu.global.u64 [%0], %1;" :: "l"(p), "l"(w) : "memory");
}
__device__ __forceinline__ void ld_flag_if(uint64_t& v, const uint32_t* p, bool pred) {
    asm volatile("{ .reg .pred p; setp.ne.u32 p, %2, 0; @p ld.relaxed.gpu.global.u64 %0, [%1]; }" : "+l"(v) : "l"(p), "r"((uint32_t)pred) : "memory");
}
__device__ __forceinline__ uint32_t ld_rlx(const uint32_t* p) { uint32_t v; asm volatile("ld.relaxed.gpu.global.u32 %0, [%1];" : "=r"(v) : "l"(p) : "memory"); return v; }
template <class T> __device__ __forceinline__ T* opaque_ptr(T* p) { asm volatile("" : "+l"(p)); return p; }
__device__ __forceinline__ uint4 ld_rlx4(const uint4* p) {
    uint4 v; asm volatile("ld.relaxed.gpu.global.v4.u32 {%0,%1,%2,%3}, [%4];" : "=r"(v.x), "=r"(v.y), "=r"(v.z), "=r"(v.w) : "l"(p) : "memory"); return v;
}
__device__ __forceinline__ uint2 ld_rlx2(const uint2* p) {
    uint2 v; asm volatile("ld.relaxed.gpu.global.v2.u32 {%0,%1}, [%2];" : "=r"(v.x), "=r"(v.y) : "l"(p) : "memory"); return v;
}
__device__ __forceinline__ void stg1(uint32_t* p, uint32_t v) { asm volatile("st.global.u32 [%0], %1;" :: "l"(p), "r"(v) : "memory"); }
__device__ __forceinline__ void stg4(void* p, uint32_t x, uint32_t y, uint32_t z, uint32_t w) { asm volatile("st.global.v4.u32 [%0], {%1,%2,%3,%4};" :: "l"(p), "r"(x), "r"(y), "r"(z), "r"(w) : "memory"); }
__device__ __forceinline__ uint32_t lds1(uint32_t a) { uint32_t v; asm volatile("ld.shared.u32 %0, [%1];" : "=r"(v) : "r"(a) : "memory"); return v; }
__device__ __forceinline__ uint2 lds2(uint32_t a) { uint2 v; asm volatile("ld.shared.v2.u32 {%0,%1}, [%2];" : "=r"(v.x), "=r"(v.y) : "r"(a) : "memory"); return v; }
__device__ __forceinline__ uint32_t set_par(uint32_t v, uint32_t mask, uint32_t par) {
    uint32_t r; asm("lop3.b32 %0, %1, %2, %3, 0xb8;" : "=r"(r) : "r"(v), "r"(mask), "r"(par)); return r;
}
__device__ __forceinline__ void st_gen4(void* p, uint32_t x, uint32_t y, uint32_t z, uint32_t w) { asm volatile("st.v4.u32 [%0], {%1,%2,%3,%4};" :: "l"(p), "r"(x), "r"(y), "r"(z), "r"(w) : "memory"); }
__device__ __forceinline__ float tanh_hw(float x) { float r; asm("tanh.approx.f32 %0, %1;" : "=f"(r) : "f"(x)); return r; }
__device__ __forceinline__ void sts4(uint32_t a, uint32_t x, uint32_t y, uint32_t z, uint32_t w) { asm volatile("st.shared.v4.u32 [%0], {%1,%2,%3,%4};" :: "r"(a), "r"(x), "r"(y), "r"(z), "r"(w) : "memory"); }
__device__ __forceinline__ uint4 lds4(uint32_t a) { uint4 v; asm volatile("ld.shared.v4.u32 {%0,%1,%2,%3}, [%4];" : "=r"(v.x), "=r"(v.y), "=r"(v.z), "=r"(v.w) : "r"(a) : "memory"); return v; }
__device__ __forceinline__ void ldsm4(uint32_t (&f)[4], uint32_t a) {
    asm volatile("ldmatrix.sync.aligned.m8n8.x4.shared.b16 {%0,%1,%2,%3}, [%4];" : "=r"(f[0]), "=r"(f[1]), "=r"(f[2]), "=r"(f[3]) : "r"(a) : "memory");
}
__device__ __forceinline__ void stsm4(uint32_t a, uint32_t x, uint32_t y, uint32_t z, uint32_t w) {
    asm volatile("stmatrix.sync.aligned.m8n8.x4.shared.b16 [%0], {%1,%2,%3,%4};" :: "r"(a), "r"(x), "r"(y), "r"(z), "r"(w) : "memory");
}
__device__ __forceinline__ uint32_t pack_bf16(float lo, float hi) { uint32_t r; asm("cvt.rn.bf16x2.f32 %0, %1, %2;" : "=r"(r) : "f"(hi), "f"(lo)); return r; }
__device__ __forceinline__ float bf_lo(uint32_t v) { return __uint_as_float(v << 16); }
__device__ __forceinline__ float bf_hi(uint32_t v) { return __uint_as_float(v & 0xffff0000u); }
__device__ __forceinline__ uint32_t sub_bf16x2(uint32_t a, uint32_t b) { uint32_t r; asm volatile("sub.rn.bf16x2 %0, %1, %2;" : "=r"(r) : "r"(a), "r"(b)); return r; }
__device__ __forceinline__ uint32_t add_bf16x2(uint32_t a, uint32_t b) { uint32_t r; asm volatile("add.rn.bf16x2 %0, %1, %2;" : "=r"(r) : "r"(a), "r"(b)); return r; }
__device__ __forceinline__ uint32_t sqr_bf16x2(uint32_t a) { uint32_t r; asm volatile("mul.rn.bf16x2 %0, %1, %1;" : "=r"(r) : "r"(a)); return r; }
__device__ __forceinline__ uint32_t sqa_bf16x2(uint32_t a, uint32_t c) { uint32_t r; asm volatile("fma.rn.bf16x2 %0, %1, %1, %2;" : "=r"(r) : "r"(a), "r"(c)); return r; }
__device__ __forceinline__ uint32_t movm(uint32_t a) { uint32_t r; asm volatile("movmatrix.sync.aligned.m8n8.trans.b16 %0, %1;" : "=r"(r) : "r"(a)); return r; }
__device__ __forceinline__ float ex2(float x) { float r; asm("ex2.approx.ftz.f32 %0, %1;" : "=f"(r) : "f"(x)); return r; }
__device__ __forceinline__ float rsq(float x) { float r; asm("rsqrt.approx.ftz.f32 %0, %1;" : "=f"(r) : "f"(x)); return r; }
__device__ __forceinline__ float rcp(float x) { float r; asm("rcp.approx.ftz.f32 %0, %1;" : "=f"(r) : "f"(x)); return r; }
__device__ __forceinline__ void mma16816(float (&c)[4], uint32_t a0, uint32_t a1, uint32_t a2, uint32_t a3, uint32_t b0, uint32_t b1) {
    asm("mma.sync.aligned.m16n8k16.row.col.f32.bf16.bf16.f32 {%0,%1,%2,%3}, {%4,%5,%6,%7}, {%8,%9}, {%0,%1,%2,%3};"
        : "+f"(c[0]), "+f"(c[1]), "+f"(c[2]), "+f"(c[3]) : "r"(a0), "r"(a1), "r"(a2), "r"(a3), "r"(b0), "r"(b1));
}
__device__ __forceinline__ void mma1688(float (&c)[4], uint32_t a0, uint32_t a1, uint32_t b0) {
    asm("mma.sync.aligned.m16n8k8.row.col.f32.bf16.bf16.f32 {%0,%1,%2,%3}, {%4,%5}, {%6}, {%0,%1,%2,%3};"
        : "+f"(c[0]), "+f"(c[1]), "+f"(c[2]), "+f"(c[3]) : "r"(a0), "r"(a1), "r"(b0));
}
__device__ __forceinline__ float quad_sum(float v) { v += __shfl_xor_sync(~0u, v, 1); v += __shfl_xor_sync(~0u, v, 2); return v; }
__device__ __forceinline__ float quad_max(float v) { v = fmaxf(v, __shfl_xor_sync(~0u, v, 1)); v = fmaxf(v, __shfl_xor_sync(~0u, v, 2)); return v; }
__device__ __forceinline__ uint64_t make_desc(uint32_t addr, uint32_t lbo, bool swz, uint32_t sbo = 1024) {
    const uint32_t lo = __shfl_sync(~0u, ((addr & 0x3FFFF) >> 4) | ((lbo >> 4) << 16), 0);
    const uint32_t hi = __shfl_sync(~0u, (swz ? 0x40000000u : 0u) + (sbo >> 4) + (threadIdx.x & 31), 0);
    return ((uint64_t)hi << 32) | lo;
}
template <int I, int N, class F> __device__ __forceinline__ void static_for(F&& f) {
    if constexpr (I < N) { f(std::integral_constant<int, I>{}); static_for<I + 1, N>(f); }
}
__device__ __forceinline__ uint32_t opaque(uint32_t v) { asm volatile("" : "+r"(v)); return v; }
template <int BOFF, int SCALE_D>
__device__ __forceinline__ void wgmma_rs_n56(float (&d)[28], uint32_t a0, uint32_t a1, uint32_t a2, uint32_t a3, uint64_t db) {
    asm volatile("{ .reg .b64 db; add.s64 db, %32, %33;\n"
        "wgmma.mma_async.sync.aligned.m64n56k16.f32.bf16.bf16 "
        "{%0, %1, %2, %3, %4, %5, %6, %7, %8, %9, %10, %11, %12, %13, %14, %15, %16, %17, %18, %19, %20, %21, %22, %23, %24, %25, %26, %27}, "
        "{%28, %29, %30, %31}, db, %34, 1, 1, 1; }"
        : "+f"(d[0]), "+f"(d[1]), "+f"(d[2]), "+f"(d[3]), "+f"(d[4]), "+f"(d[5]), "+f"(d[6]), "+f"(d[7]),
        "+f"(d[8]), "+f"(d[9]), "+f"(d[10]), "+f"(d[11]), "+f"(d[12]), "+f"(d[13]), "+f"(d[14]), "+f"(d[15]),
        "+f"(d[16]), "+f"(d[17]), "+f"(d[18]), "+f"(d[19]), "+f"(d[20]), "+f"(d[21]), "+f"(d[22]), "+f"(d[23]),
        "+f"(d[24]), "+f"(d[25]), "+f"(d[26]), "+f"(d[27])
        : "r"(a0), "r"(a1), "r"(a2), "r"(a3), "l"(db), "n"(BOFF >> 4), "n"(SCALE_D));
}
template <int AOFF, int BOFF, int MMAJOR>
__device__ __forceinline__ void wgmma_ss_n56(float (&d)[28], uint64_t da, uint64_t db) {
    asm volatile("{ .reg .b64 da, db; add.s64 da, %28, %30; add.s64 db, %29, %31;\n"
        "wgmma.mma_async.sync.aligned.m64n56k16.f32.bf16.bf16 "
        "{%0, %1, %2, %3, %4, %5, %6, %7, %8, %9, %10, %11, %12, %13, %14, %15, %16, %17, %18, %19, %20, %21, %22, %23, %24, %25, %26, %27}, "
        "da, db, 1, 1, 1, %32, 1; }"
        : "+f"(d[0]), "+f"(d[1]), "+f"(d[2]), "+f"(d[3]), "+f"(d[4]), "+f"(d[5]), "+f"(d[6]), "+f"(d[7]),
        "+f"(d[8]), "+f"(d[9]), "+f"(d[10]), "+f"(d[11]), "+f"(d[12]), "+f"(d[13]), "+f"(d[14]), "+f"(d[15]),
        "+f"(d[16]), "+f"(d[17]), "+f"(d[18]), "+f"(d[19]), "+f"(d[20]), "+f"(d[21]), "+f"(d[22]), "+f"(d[23]),
        "+f"(d[24]), "+f"(d[25]), "+f"(d[26]), "+f"(d[27])
        : "l"(da), "l"(db), "n"(AOFF >> 4), "n"(BOFF >> 4), "n"(MMAJOR));
}
template <int AOFF, int BOFF, int MMAJOR>
__device__ __forceinline__ void wgmma_ss_n112(float (&d)[28], float (&e)[28], uint64_t da, uint64_t db) {
    asm volatile("{ .reg .b64 da, db; add.s64 da, %56, %58; add.s64 db, %57, %59;\n"
        "wgmma.mma_async.sync.aligned.m64n112k16.f32.bf16.bf16 "
        "{%0, %1, %2, %3, %4, %5, %6, %7, %8, %9, %10, %11, %12, %13, %14, %15, %16, %17, %18, %19, %20, %21, %22, %23, %24, %25, %26, %27, %28, %29, %30, %31, %32, %33, %34, %35, %36, %37, %38, %39, %40, %41, %42, %43, %44, %45, %46, %47, %48, %49, %50, %51, %52, %53, %54, %55}, "
        "da, db, 1, 1, 1, %60, 1; }"
        : "+f"(d[0]), "+f"(d[1]), "+f"(d[2]), "+f"(d[3]), "+f"(d[4]), "+f"(d[5]), "+f"(d[6]), "+f"(d[7]),
        "+f"(d[8]), "+f"(d[9]), "+f"(d[10]), "+f"(d[11]), "+f"(d[12]), "+f"(d[13]), "+f"(d[14]), "+f"(d[15]),
        "+f"(d[16]), "+f"(d[17]), "+f"(d[18]), "+f"(d[19]), "+f"(d[20]), "+f"(d[21]), "+f"(d[22]), "+f"(d[23]),
        "+f"(d[24]), "+f"(d[25]), "+f"(d[26]), "+f"(d[27]), "+f"(e[0]), "+f"(e[1]), "+f"(e[2]), "+f"(e[3]),
        "+f"(e[4]), "+f"(e[5]), "+f"(e[6]), "+f"(e[7]), "+f"(e[8]), "+f"(e[9]), "+f"(e[10]), "+f"(e[11]),
        "+f"(e[12]), "+f"(e[13]), "+f"(e[14]), "+f"(e[15]), "+f"(e[16]), "+f"(e[17]), "+f"(e[18]), "+f"(e[19]),
        "+f"(e[20]), "+f"(e[21]), "+f"(e[22]), "+f"(e[23]), "+f"(e[24]), "+f"(e[25]), "+f"(e[26]), "+f"(e[27])
        : "l"(da), "l"(db), "n"(AOFF >> 4), "n"(BOFF >> 4), "n"(MMAJOR));
}
template <int BOFF, int SCALE_D>
__device__ __forceinline__ void wgmma_rs_n112(float (&d)[28], float (&e)[28], uint32_t a0, uint32_t a1, uint32_t a2, uint32_t a3, uint64_t db) {
    asm volatile("{ .reg .b64 db; add.s64 db, %60, %61;\n"
        "wgmma.mma_async.sync.aligned.m64n112k16.f32.bf16.bf16 "
        "{%0, %1, %2, %3, %4, %5, %6, %7, %8, %9, %10, %11, %12, %13, %14, %15, %16, %17, %18, %19, %20, %21, %22, %23, %24, %25, %26, %27, %28, %29, %30, %31, %32, %33, %34, %35, %36, %37, %38, %39, %40, %41, %42, %43, %44, %45, %46, %47, %48, %49, %50, %51, %52, %53, %54, %55}, "
        "{%56, %57, %58, %59}, db, %62, 1, 1, 1; }"
        : "+f"(d[0]), "+f"(d[1]), "+f"(d[2]), "+f"(d[3]), "+f"(d[4]), "+f"(d[5]), "+f"(d[6]), "+f"(d[7]),
        "+f"(d[8]), "+f"(d[9]), "+f"(d[10]), "+f"(d[11]), "+f"(d[12]), "+f"(d[13]), "+f"(d[14]), "+f"(d[15]),
        "+f"(d[16]), "+f"(d[17]), "+f"(d[18]), "+f"(d[19]), "+f"(d[20]), "+f"(d[21]), "+f"(d[22]), "+f"(d[23]),
        "+f"(d[24]), "+f"(d[25]), "+f"(d[26]), "+f"(d[27]), "+f"(e[0]), "+f"(e[1]), "+f"(e[2]), "+f"(e[3]),
        "+f"(e[4]), "+f"(e[5]), "+f"(e[6]), "+f"(e[7]), "+f"(e[8]), "+f"(e[9]), "+f"(e[10]), "+f"(e[11]),
        "+f"(e[12]), "+f"(e[13]), "+f"(e[14]), "+f"(e[15]), "+f"(e[16]), "+f"(e[17]), "+f"(e[18]), "+f"(e[19]),
        "+f"(e[20]), "+f"(e[21]), "+f"(e[22]), "+f"(e[23]), "+f"(e[24]), "+f"(e[25]), "+f"(e[26]), "+f"(e[27])
        : "r"(a0), "r"(a1), "r"(a2), "r"(a3), "l"(db), "n"(BOFF >> 4), "n"(SCALE_D));
}

struct Params {
    const __nv_bfloat16 *x, *wqkv;
    Scratch* sc;
    const __nv_bfloat16 *wo, *w1, *w2, *b1, *b2;
    __nv_bfloat16* out;
};

__global__ void __cluster_dims__(2, 1, 1) __launch_bounds__(384, 1)
fused_kernel(const Params prm, const __grid_constant__ CUtensorMap mX2, const __grid_constant__ CUtensorMap mX, const __grid_constant__ CUtensorMap mWqkv,
             const __grid_constant__ CUtensorMap mWo, const __grid_constant__ CUtensorMap mW1,
             const __grid_constant__ CUtensorMap mW2)
{
    extern __shared__ __align__(1024) unsigned char smem_raw[];
    if (threadIdx.x < 126) {
        const uint32_t i = threadIdx.x, t = clk32() + (i >> 5) * PFD;
        const char* px = (const char*)prm.x + (blockIdx.x * 16 + (i & 15)) * 896 + (i >> 4) * 128;
        const char* pw = (const char*)prm.wqkv + blockIdx.x * 2688 + i * 128 + (896 - 112 * 128);
        spin_until(t);
        asm volatile("prefetch.global.L2 [%0];" :: "l"(i < 112 ? px : pw) : "memory");
    }
    if (threadIdx.x == 128) { asm volatile("prefetch.tensormap [%0];" :: "l"(&mX2) : "memory"); asm volatile("prefetch.tensormap [%0];" :: "l"(&mWqkv) : "memory"); }
    uint32_t sb = (uint32_t)__cvta_generic_to_shared(smem_raw);
    asm volatile("mov.u32 %0, %0;" : "+r"(sb));
    const uint32_t bar0 = sb + SM_BAR;
    auto BAR = [&](int i) { return bar0 + 8u * i; };

    const int tid = threadIdx.x, lane = tid & 31;
    const int warp = __shfl_sync(~0u, tid >> 5, 0);
    const int b = __shfl_sync(~0u, (int)blockIdx.x, 0);
    const int rank = b & 1;
    const int cl = (b >> 1) - 4, cq = ((cl - 32) * 37) >> 8;
    const int res = cl < 0 ? 0 : cl < 32 ? cl & 7 : cl - 31 - 7 * cq;
    const int rnd = cl < 0 ? cl + 8 : cl < 32 ? cl >> 3 : 4 + cq;
    const int hg = (res & 1) * 4 + (rnd & 3);
    const int ti = (res >> 1) * 4 + (rnd >> 2) * 2 + rank;
    const int a2p = res & 1, a2j = rnd & 3;
    const int a2s = ti * 2 + a2p;
    const bool g1_on = rnd != 7;
    const int g1j = (rnd < 6 ? rnd : res) & 1, g1f = rnd < 6 ? res * 3 + (rnd >> 1) : 24 + (res >> 1);
    const int g2j = rnd & 1, g2s = res * 4 + (rnd >> 1);
    uint32_t pbar0;
    asm volatile("mapa.shared::cluster.u32 %0, %1, %2;" : "=r"(pbar0) : "r"(bar0), "r"(rank ^ 1));
    auto pair_arrive = [&](int i) { __syncwarp(); const bool l = elect_one(); mbar_arrive_if(BAR(i), l); mbar_arrive_remote_if(pbar0 + 8u * i, l); };
    const int wcol = hg * 56 - (hg & 1) * 8;

    if (warp == 8) {
        if (elect_one()) {
            #pragma unroll
            for (int i = 0; i < B_WQF; i++) mbar_init(BAR(i), 1);
            asm volatile("fence.mbarrier_init.release.cluster;" ::: "memory");
            fence_async_smem();
            #pragma unroll
            for (int kb = 0; kb < 7; kb++) {
                tma3d(sb + kb * 16384, &mX2, kb * 64, ti * 64, 0, BAR(B_XF + kb));
                mbar_expect(BAR(B_XF + kb), 16384);
            }
        }
    } else if (warp > 8) {
        if (elect_one()) {
            if (warp == 9) {
                #pragma unroll
                for (int i = B_WQF; i < B_AF; i++) mbar_init(BAR(i), i < B_XC ? 1 : i < B_A1D ? 16 : i < B_BE ? 8 : 4);
            } else if (warp == 10) {
                #pragma unroll
                for (int i = B_AF; i < B_BF; i++) mbar_init(BAR(i), 1);
            } else {
                #pragma unroll
                for (int i = B_BF; i < B_COUNT; i++) mbar_init(BAR(i), i == B_HD ? 8 : 1);
            }
            asm volatile("fence.mbarrier_init.release.cluster;" ::: "memory");
            fence_async_smem();
        }
    }
    __syncwarp();
    __syncthreads();
    asm volatile("barrier.cluster.arrive.relaxed.aligned;" ::: "memory");

    if (warp >= 8) {
        asm volatile("setmaxnreg.dec.sync.aligned.u32 40;");
        asm volatile("barrier.cluster.wait.aligned;" ::: "memory");
        auto fetch_halo = [&](int p, uint32_t tag) {
            const uint32_t hl = BAR(B_HL + p), dst = opaque(sb + SM_STG + p * 8192 + 3 * 2048 + lane * 16);
            const bool lead = elect_one();
            if (rank) { if (lead) mbar_expect(hl, 2048); __syncwarp(); return; }
            const uint4* hp = opaque_ptr(&prm.sc->halo[((((ti >> 1) - 1) * 8 + hg) * 2 + p) * 128 + lane]);
            mbar_wait(BAR(B_KVC), 0);
            if (ti > 0) {
                spin_until(clk32() + HDELAY);
                int it = 0;
                uint32_t bad;
                do {
                    uint4 u[4];
                    #pragma unroll
                    for (int c = 0; c < 4; c++) u[c] = ld_rlx4(hp + c * 32);
                    #pragma unroll
                    for (int c = 0; c < 4; c++) sts4(dst + c * 512, u[c].x, u[c].y, u[c].z, u[c].w);
                    bad = ((u[0].x ^ tag) | (u[1].x ^ tag) | (u[2].x ^ tag) | (u[3].x ^ tag)) & ~lane & 1;
                } while (__any_sync(~0u, bad) && ++it < kSpinLimit);
            } else {
                #pragma unroll
                for (int c = 0; c < 4; c++) sts4(dst + c * 512, 0u, 0u, 0u, 0u);
            }
            __syncwarp();
            mbar_arrive_if(hl, lead);
        };
        auto poll_flags = [&](const uint32_t* fp, int step, uint32_t tag, uint32_t gbase) {
            uint64_t v0 = 0, v1 = 0;
            int it = 0;
            do {
                ld_flag_if(v0, fp, (uint32_t)v0 != tag); ld_flag_if(v1, fp + step, (uint32_t)v1 != tag);
                if (++it > kSpinLimit) break;
            } while (__any_sync(~0u, (uint32_t)v0 != tag || (uint32_t)v1 != tag));
            return max((int)((uint32_t)(v0 >> 32) - gbase), (int)((uint32_t)(v1 >> 32) - gbase));
        };
        if (warp & 1) {
            uint32_t tag;
            if (warp == 11) {
                tag = *(volatile uint32_t*)&prm.sc->epoch + 1;
                #pragma unroll 1
                for (int i = 0; i < 8 * rank; i++) prm.sc->halo[((ti >> 1) * 8 + hg) * 256 + i * 32 + lane] = make_uint4(~tag, 0u, 0u, 0u);
                ((uint4*)prm.sc->stats)[(a2s * 4 + a2j) * 64 + lane] = ((uint4*)prm.sc->stats)[(a2s * 4 + a2j) * 64 + 32 + lane] = make_uint4(~tag, ~tag, ~tag, ~tag);
                prm.sc->flag_h[(a2s * 4 + a2j) * FS + lane] = 0;
                prm.sc->flag_o[(ti * 8 + hg) * FS + lane] = 0;
                __syncwarp();
                if (lane == 0) {
                    asm volatile("st.shared.v2.u32 [%0], {%1, %2};" :: "r"(sb + SM_EPOCH), "r"(tag), "r"(gtime32()) : "memory");
                    mbar_arrive(BAR(B_EP));
                }
                if (lane < 8) mbar_expect(BAR(B_RF + lane), 1792);
                __syncwarp();
            } else {
                mbar_wait(BAR(B_EP), 0);
                tag = lds1(sb + SM_EPOCH);
            }
            fetch_halo((warp >> 1) & 1, tag);
        }
        if (warp < 10) {
          auto load_slab = [&](int s, bool second) {
              if (!second) tma2d(sb + s * 8192, &mW1, (s & 1) * kF + g1f * 64, (rank * 8 + (s >> 1)) * 64, BAR(B_AF));
              else         tma2d(sb + s * 8192, &mW2, g2s * 64, (rank * 14 + s - 1) * 64, BAR(B_AF));
          };
          const char* pw2 = (const char*)prm.w2 + ((b >> 6) * 896 + (b & 63) + PFW * 64) * 4096;
          if (warp == 8) {
            if (elect_one()) {
                #pragma unroll 1
                for (int s = 0; s < 7; s++) {
                    mbar_expect(BAR(B_WKVF + s), 16384);
                    tma2d_mc(sb + SM_WKV + s * 16384 + rank * 8192, &mWqkv, (1 + rank) * kD + wcol, s * 64, BAR(B_WKVF + s));
                }
            }
            __syncwarp();
            mbar_wait(BAR(B_XC), 0);
            if (elect_one()) {
                asm volatile("prefetch.tensormap [%0];" :: "l"(&mX) : "memory");
                asm volatile("prefetch.tensormap [%0];" :: "l"(&mWo) : "memory");
                asm volatile("prefetch.tensormap [%0];" :: "l"(&mW1) : "memory");
                asm volatile("prefetch.tensormap [%0];" :: "l"(&mW2) : "memory");
                mbar_expect(BAR(B_AF), (g1_on ? NPRE : 14) * 8192);
                mbar_expect(BAR(B_WQF), 57344);
                #pragma unroll 1
                for (int s = rank; s < 7; s += 2) tma2d_mc(sb + SM_WQ + s * 8192, &mWqkv, wcol, s * 64, BAR(B_WQF));
                mbar_expect(BAR(B_XRF), 16384);
                tma2d(sb + SM_XR, &mX, a2p * kD + a2j * 112, ti * 64, BAR(B_XRF));
                tma2d(sb + SM_XR + 8192, &mX, a2p * kD + a2j * 112 + 48, ti * 64, BAR(B_XRF));
            }
            __syncwarp();
            #pragma unroll 1
            for (int q = 0; q < 4; q++) {
                mbar_wait(BAR(B_KV3 + (q >> 1)), 0);
                if (q == 2) spin_until(clk32() + WOD);
                if (q == 3) mbar_wait2(BAR(B_HL), 0, BAR(B_HL + 1), 0);
                if (elect_one()) {
                    if (!(q & 1)) mbar_expect(BAR(B_WOF + (q >> 1)), 57344);
                    tma2d_mc(sb + SM_WKV + q * 28672 + rank * 14336, &mWo, a2j * 112 + (q & 1) * 48, (q >> 1) * 224 + rank * 112, BAR(B_WOF + (q >> 1)));
                    if (g1_on && q == 1) { load_slab(0, false); load_slab(1, false); load_slab(2, false); }
                }
                __syncwarp();
            }
            if (g1_on) {
                mbar_wait2(BAR(B_XD), 0, BAR(B_OL + 3), 0);
                #pragma unroll 1
                for (int i = 3; i < NPRE; i++) {
                    if (i == 7) mbar_wait(BAR(B_OC), 0);
                    if (elect_one()) load_slab(i, false);
                    __syncwarp();
                }
            } else {
                mbar_arrive_if(BAR((lane < 16 ? B_BE : B_BF) + (lane & 3)), lane < 20);
                mbar_wait(BAR(B_HD), 0);
                mbar_arrive_remote_if(pbar0 + 8u * B_PD, lane == 0);
                mbar_wait(BAR(B_GO), 0);
                uint32_t tg = lds1(sb + SM_TG + 4);
                tg += max((int)(lds1(sb + SM_TG2) - tg), 0);
                int it = 0;
                while ((int)(gtime32() - tg) < 0 && ++it < 256) {}
                const uint32_t t0 = clk32();
                if (lane < 2) {
                    asm volatile("st.shared.u32 [%0], %1;" :: "r"(sb + SM_TG + 8 + lane * 4), "r"(t0 + (lane ? CN3 : CN2)) : "memory");
                    mbar_arrive(BAR(B_GD + lane));
                }
                __syncwarp();
                #pragma unroll 1
                for (int s = 1; s < 15; s++) {
                    sleep_until(t0 + W2OFF + s * W2PACE);
                    if (elect_one()) { if (s < 15 - PFW) bulk_prefetch(pw2 + (s - 1) * 64 * 4096, 4096); load_slab(s, true); }
                    __syncwarp();
                }
            }
          } else {
            const uint32_t tag = lds1(sb + SM_EPOCH);
            if (lane < 4) mbar_expect(BAR(B_OL + lane), 14336);
            const uint32_t gbase = lds1(sb + SM_TG);
            const bool lead = elect_one();
            uint32_t* hfl = opaque_ptr(&prm.sc->flag_h[(a2s * 4 + a2j) * FS]);
            mbar_wait(BAR(B_QL), 0);
            const int d = poll_flags(&prm.sc->flag_o[(ti * 8 + (lane & 3) * 2) * FS], FS, tag, gbase);
            mbar_wait(BAR(B_A1D), 0);
            int key = max(d + DELTAO, __reduce_max_sync(~0u, d) + DMIN) * 4 + (lane & 3);
            uint32_t order = 0;
            #pragma unroll 1
            for (int i = 0; i < 4; i++) {
                const int m = __reduce_min_sync(~0u, key);
                const uint4* src = &prm.sc->o[(a2s * 4 + (m & 3)) * 896];
                int it = 0;
                while ((int)(gtime32() - gbase) < m >> 2 && ++it < 256) {}
                if (lead) bulk_g2s(sb + SM_WQ + i * 14336, src, 14336, BAR(B_OL + i));
                if (key == m) key = 0x7fffffff;
                order |= (m & 3) << i * 2;
            }
            if (lead) {
                asm volatile("st.shared.u32 [%0], %1;" :: "r"(sb + SM_ORD), "r"(order) : "memory");
                mbar_arrive(BAR(B_OD));
            }
            __syncwarp();
            mbar_wait(BAR(B_XD), 0);
            int t0 = gtime32() - gbase + XDNS;
            #pragma unroll 1
            for (int i = 0; i < 4; i++) { mbar_wait(BAR(B_OF + i), 0); t0 = max(t0, (int)(gtime32() - gbase) - i * CHUNKNS); }
            if (lead) st_flag(hfl, tag, gbase + t0);
            __syncwarp();
          }
          if (elect_one()) {
              const int h = ~warp & 1;
              constexpr uint32_t T = 57344, BO = 2 * 14336;
              const char* src1 = (const char*)&prm.sc->hn[(rank * 16 + h) * 3584 + g1j * 896];
              const char* src2 = (const char*)&prm.sc->g[(rank * 14 + h) * 3584 + g2j * 896];
              uint64_t masks = g1_on ? (h ? kSegMasks1 : kSegMasks0) : 0x80 | 0x80 << 10;
              const uint32_t bl = BAR(B_BL + h * NB);
              uint32_t s8 = (g1_on ? NB - 2 + h : 4 + h) * 8, lap = 3, tmin = 0;
              const CUtensorMap* am = &mW1;
              uint32_t ad = sb + (NPRE + h) * 8192, astep = 16384; int ac0 = h * kF + g1f * 64, ac1 = (rank * 8 + NPRE / 2) * 64;
              #pragma unroll 1
              for (int seg = g1_on ? 0 : 3; seg < 5; seg++) {
                  const char* src = (seg < 3 ? src1 : src2) + (~seg & 1) * BO;
                  uint32_t m = (uint32_t)masks & 0x3ff;
                  masks >>= 10;
                  const uint32_t pace = seg == 4 ? PACEB : PACE2;
                  if (seg == 2) {
                      mbar_wait(BAR(B_PL), 0);
                      mbar_arrive_remote_if(pbar0 + 8u * B_PD, h);
                      am = &mW2; ad = sb + 8192; astep = 8192; ac0 = g2s * 64; ac1 = rank * 14 * 64;
                  } else {
                      const int gate = seg - (seg > 2);
                      mbar_wait(BAR(B_HD + gate), 0);
                      tmin = lds1(sb + SM_TG + gate * 4);
                      if (gate < 2) {
                          tmin += max((int)(lds1(gate ? sb + SM_TG2 : sb + SM_TG) - tmin), 0);
                          int it = 0;
                          while ((int)(gtime32() - tmin) < 0 && ++it < 256) {}
                          tmin = clk32();
                      }
                      tmin += h * PACE1;
                  }
                  #pragma unroll 1
                  do {
                      const uint32_t dst = sb + SM_B + s8 * 1792;
                      spin_until(tmin);
                      mbar_wait_fast(BAR(B_BE) + s8 + (lap & 1) * (NB * 8), lap >> 1 & 1);
                      if (seg) {
                          bulk_g2s(dst, src, 14336, bl + s8);
                          mbar_expect(bl + s8, 14336);
                      }
                      tmin += pace;
                      src += 2 * T;
                      s8 += 16;
                      if (s8 >= NB * 8) { s8 -= NB * 8; lap++; }
                      if (m & 1) {
                          mbar_expect_more(bl + s8, 8192);
                          tma2d(ad, am, ac0, ac1, bl + s8);
                          ad += astep; ac1 += 64;
                      }
                      m >>= 1;
                  } while (m != 1);
                  if (seg == 0) lap = 3;
              }
          }
        } else {
          if (warp == 10) {
            mbar_wait(BAR(B_XF + 6), 0);
            if (lane < 27) asm volatile("prefetch.global.L2 [%0];" :: "l"(lane < 25 ? (const char*)prm.wo + min(b * 25 + lane, 3135) * 128
                                                                          : lane == 25 ? (const char*)prm.b1 + (b % 28) * 128 : (const char*)prm.b2 + (b & 31) * 128));
            const char* p1 = (const char*)prm.w1 + ((b >> 6) * 1024 + (b & 63) * 2) * 3584 + min(lane, 27) * 128;
            uint32_t tnext = clk32();
            #pragma unroll 1
            for (int i = 0; i < 16; i++) {
                while ((int)(clk32() - tnext) < 0) __nanosleep(40);
                asm volatile("prefetch.global.L2 [%0];" :: "l"(p1 + ((i >> 1) * 128 + (i & 1)) * 3584));
                tnext += PFPACE;
            }
            uint32_t* ofl = opaque_ptr(&prm.sc->flag_o[(ti * 8 + hg) * FS]);
            mbar_wait(BAR(B_EP), 0);
            const uint32_t tag = lds1(sb + SM_EPOCH);
            mbar_wait(BAR(B_QL), 0);
            const uint32_t tq = gtime32() + QLNS;
            mbar_wait2(BAR(B_HL), 0, BAR(B_HL + 1), 0);
            if (lane == 0) st_flag(ofl, tag, tq + max((int)(gtime32() - tq), 0));
            __syncwarp();
          }
          const uint32_t tag = lds1(sb + SM_EPOCH);
          const int h = warp & 1;
          const bool lead = elect_one();
          const uint32_t wo = (lane & 15) * 128 + lane * 4;
          uint32_t base = sb + SM_WQ, bl = BAR(B_OL), bf = BAR(B_OF), m = 4, rph = 0;
          #pragma unroll 1
          for (int e = 0; e < 2; e++) {
              uint32_t s8 = (e && !g1_on ? 4 + h : h) * 8;
              #pragma unroll 1
              do {
                  const uint32_t dst = base + s8 * 1792;
                  auto stale = [&](uint32_t at) {
                      uint32_t d;
                      asm volatile("{ .reg .b32 v<7>;\n"
                                   "ld.shared.u32 v0, [%1]; ld.shared.u32 v1, [%1 + 2048]; ld.shared.u32 v2, [%1 + 4096]; ld.shared.u32 v3, [%1 + 6144];\n"
                                   "ld.shared.u32 v4, [%1 + 8192]; ld.shared.u32 v5, [%1 + 10240]; ld.shared.u32 v6, [%1 + 12288];\n"
                                   "lop3.b32 v0, v0, v1, %2, 0x7e; lop3.b32 v2, v2, v3, %2, 0x7e; lop3.b32 v4, v4, v5, %2, 0x7e;\n"
                                   "or.b32 v0, v0, v2; lop3.b32 v4, v4, v6, %2, 0xf6; lop3.b32 %0, v0, v4, 1, 0xa8; }"
                                   : "=r"(d) : "r"(at), "r"(tag) : "memory");
                      return __any_sync(~0u, d);
                  };
                  mbar_wait_fast(bl + s8, m & 1);
                  bool bad = stale(dst + wo);
                  mbar_arrive_if(bf + s8, lead && !bad);
                  if (bad) {
                      const int p = 2 * __clz(m) - 2 + h;
                      const int st = (p > 15) + (p > 31) + (p > 45), s = p - (st < 3 ? 16 * st : 46);
                      mbar_wait(BAR(B_OD), 0);
                      const char* src = (const char*)(!e ? &prm.sc->o[(a2s * 4 + (lds1(sb + SM_ORD) >> (p * 2 & 7) & 3)) * 896] : st < 2 ? &prm.sc->hn[(rank * 16 + s) * 3584 + (g1j + 2 * st) * 896]
                                                                                                      : &prm.sc->g[(rank * 14 + s) * 3584 + (g2j + 2 * st - 4) * 896]);
                      int it = 0;
                      do {
                          if (++it > kSpinLimit) break;
                          const uint32_t* q = (const uint32_t*)(src + lane * 132);
                          if (it > 1 && __any_sync(~0u, ((ld_rlx(q) ^ tag) | (ld_rlx(q + 1024) ^ tag) | (ld_rlx(q + 2048) ^ tag) | (ld_rlx(q + (lane < 16 ? 3072 : 0)) ^ tag)) & 1)) continue;
                          if (lead) {
                              mbar_expect(BAR(B_RT + h), 14336);
                              bulk_g2s(dst, src, 14336, BAR(B_RT + h));
                          }
                          __syncwarp();
                          mbar_wait(BAR(B_RT + h), rph);
                          rph ^= 1;
                          bad = stale(dst + wo) || stale(dst + (wo ^ 1024));
                      } while (bad);
                      mbar_arrive_if(bf + s8, lead);
                  }
                  s8 += 16;
                  if (s8 >= NB * 8) s8 -= NB * 8;
                  m >>= 1;
              } while (m != 1);
              if (e) break;
              if (h) {
                  const uint32_t gbase = lds1(sb + SM_TG);
                  sleep_until(clk32() + PDELAY);
                  const uint32_t tg = gbase + DELTA + __reduce_max_sync(~0u, poll_flags(&prm.sc->flag_h[(rank * 64 + lane) * FS], 32 * FS, tag, gbase));
                  if (lead) {
                      asm volatile("st.async.shared::cluster.mbarrier::complete_tx::bytes.b32 [%0], %1, [%2];"
                                   :: "r"(pbar0 + (SM_TG2 - SM_BAR)), "r"(tg), "r"(pbar0 + 8u * B_GO) : "memory");
                      asm volatile("st.shared.u32 [%0], %1;" :: "r"(sb + SM_TG + 4), "r"(tg) : "memory");
                      mbar_expect(BAR(B_GO), 4);
                  }
                  __syncwarp();
              } else {
                  const char* p2 = (const char*)prm.w2 + ((b >> 6) * 896 + (b & 63)) * 4096 + lane * 128;
                  #pragma unroll 1
                  for (int i = 0; i < PFW; i++) {
                      asm volatile("prefetch.global.L2 [%0];" :: "l"(p2 + i * 64 * 4096));
                      sleep_until(clk32() + PFPACE2);
                  }
              }
              base = sb + SM_B; bl = BAR(B_BL + h * NB); bf = BAR(B_BF); m = g1_on ? 0x4fe03f80 : 0x7f80;
          }
        }
    } else {
        asm volatile("setmaxnreg.inc.sync.aligned.u32 232;");
        asm volatile("barrier.cluster.wait.aligned;" ::: "memory");
        const int wg = warp >> 2, w = warp & 3;
        const int g = lane >> 2, t = lane & 3;
        uint32_t tag, om0, om1;
        __nv_bfloat16 bias1a, bias1b;
        {
            const uint64_t dw = make_desc(sb + (hg & 1) * 16, 0, true);
            uint4* const hp = opaque_ptr((w == 3 ? &prm.sc->halo[(((ti >> 1) * 8 + hg) * 2 + wg) * 128] : (uint4*)(smem_raw + SM_STG + wg * 8192 + w * 2048)) + lane);
            uint32_t a[28][4];
            float sm[4][4];
            auto shift = [](uint32_t (&f)[4], uint32_t m0, uint32_t m1) {
                f[0] = sub_bf16x2(f[0], m0); f[1] = sub_bf16x2(f[1], m1);
                f[2] = sub_bf16x2(f[2], m0); f[3] = sub_bf16x2(f[3], m1);
            };
            {
                const int r = w * 16 + (lane & 15);
                uint32_t xa[4];
                #pragma unroll
                for (int q = 0; q < 4; q++) xa[q] = opaque(sb + wg * 8192 + r * 128 + (((q * 2 + (lane >> 4)) ^ (r & 7)) << 4));
                const uint32_t one = opaque(0x3F803F80u), one2 = opaque(0x3F803F80u);
                auto load = [&](int k0, int k1) {
                    #pragma unroll
                    for (int k = k0; k < k1; k++) {
                        if ((k & 3) == 0) mbar_wait(BAR(B_XF + (k >> 2)), 0);
                        ldsm4(a[k], xa[k & 3] + (k >> 2) * 16384);
                        if (k < 24) mma16816(sm[k & 3], a[k][0], a[k][1], a[k][2], a[k][3], one, one2);
                    }
                };
                #pragma unroll 1
                for (float lim = 128.f;; lim = 0.f) {
                    #pragma unroll
                    for (int i = 0; i < 16; i++) sm[i >> 2][i & 3] = 0.f;
                    load(0, 4);
                    float sq[4] = {};
                    uint32_t u[4];
                    #pragma unroll
                    for (int i = 0; i < 4; i++) u[i] = sqa_bf16x2(a[2][i], sqa_bf16x2(a[3][i], sqa_bf16x2(a[0][i], sqr_bf16x2(a[1][i]))));
                    mma16816(sq, u[0], u[1], u[2], u[3], one, one2);
                    const float m0 = ((sm[0][0] + sm[1][0]) + (sm[2][0] + sm[3][0])) * (1.f / 64);
                    const float m1 = ((sm[0][2] + sm[1][2]) + (sm[2][2] + sm[3][2])) * (1.f / 64);
                    load(4, 8);
                    if (!__any_sync(~0u, m0 * m0 * lim > sq[0] || m1 * m1 * lim > sq[2])) break;
                    #pragma unroll 1
                    for (int k = 0; k < 28; k++) {
                        const uint32_t p = (xa[0] ^ (k & 3) * 32) + (k >> 2) * 16384;
                        mbar_wait(BAR(B_XF + (k >> 2)), 0);
                        ldsm4(u, p);
                        shift(u, pack_bf16(m0, m0), pack_bf16(m1, m1));
                        stsm4(p, u[0], u[1], u[2], u[3]);
                    }
                    fence_async_smem();
                    __syncwarp();
                }
                load(8, 28);
                pair_arrive(B_XC);
                const bool wok = mbar_test(BAR(B_WKVF), 0);
                #pragma unroll
                for (int k = 24; k < 28; k++) mma16816(sm[k & 3], a[k][0], a[k][1], a[k][2], a[k][3], one, one2);
                if (!wok) mbar_wait(BAR(B_WKVF), 0);
            }
            const float mean0 = ((sm[0][0] + sm[1][0]) + (sm[2][0] + sm[3][0])) * (1.f / kD);
            const float mean1 = ((sm[0][2] + sm[1][2]) + (sm[2][2] + sm[3][2])) * (1.f / kD);
            const uint32_t mb0 = pack_bf16(mean0, mean0), mb1 = pack_bf16(mean1, mean1);
            float ak[28], av[28], aq[28];
            float ss0 = 0.f, ss1 = 0.f, ss2 = 0.f, ss3 = 0.f;
            uint32_t p0, p1;
            bool qok;
            static_for<0, 7>([&](auto S_) {
                constexpr int s = decltype(S_)::value;
                auto centre = [&](int q) { shift(a[s * 4 + q], mb0, mb1); };
                if (s) {
                    #pragma unroll
                    for (int q = 0; q < 4; q++) centre(q);
                    mbar_wait(BAR(B_WKVF + s), 0);
                    if (s == 6) qok = mbar_test(BAR(B_WQF), 0);
                    wg_fence();
                }
                static_for<0, 4>([&](auto Q_) {
                    constexpr int q = decltype(Q_)::value;
                    uint32_t (&f)[4] = a[s * 4 + q];
                    if (s == 0) { centre(q); wg_fence(); }
                    wgmma_rs_n56<SM_WKV + s * 16384 + q * 2048, (s | q) != 0>(ak, f[0], f[1], f[2], f[3], dw);
                    wgmma_rs_n56<SM_WKV + s * 16384 + q * 2048 + 8192, (s | q) != 0>(av, f[0], f[1], f[2], f[3], dw);
                });
                wg_commit();
                if (s == 4) { wg_wait<1>(); pair_arrive(B_KV3); }
                if (s < 2) mbar_wait(BAR(s ? B_EP : B_WKVF), 0);
                if (s == 1) tag = lds1(sb + SM_EPOCH);
                #pragma unroll
                for (int q = 0; q < 8; q++) {
                    const uint32_t u0 = a[s * 4 + q / 2][(q & 1) * 2], u1 = a[s * 4 + q / 2][(q & 1) * 2 + 1];
                    if (q == 0) { p0 = sqr_bf16x2(u0); p1 = sqr_bf16x2(u1); }
                    else { p0 = sqa_bf16x2(u0, p0); p1 = sqa_bf16x2(u1, p1); }
                }
                ss0 += bf_lo(p0); ss2 += bf_hi(p0); ss1 += bf_lo(p1); ss3 += bf_hi(p1);
            });
            auto q_chunk = [&](auto K0_, auto K1_) {
                wg_fence();
                static_for<decltype(K0_)::value, decltype(K1_)::value>([&](auto K_) {
                    constexpr int k = decltype(K_)::value;
                    wgmma_rs_n56<SM_WQ + k * 2048, k != 0>(aq, a[k][0], a[k][1], a[k][2], a[k][3], dw);
                });
                wg_commit();
            };
            #define QCHUNK(k0, k1) q_chunk(std::integral_constant<int, k0>{}, std::integral_constant<int, k1>{})
            const float dl0 = mean0 - bf_lo(mb0), dl1 = mean1 - bf_lo(mb1);
            const float rs0 = rsq(fmaxf(quad_sum(ss0 + ss2) * (1.f / kD) - dl0 * dl0, 0.f) + kEps);
            const float rs1 = rsq(fmaxf(quad_sum(ss1 + ss3) * (1.f / kD) - dl1 * dl1, 0.f) + kEps);
            float rk[3][2];
            rk[1][0] = __shfl_sync(~0u, rs0, t * 8); rk[1][1] = __shfl_sync(~0u, rs0, t * 8 + 4);
            rk[2][0] = __shfl_sync(~0u, rs1, t * 8); rk[2][1] = __shfl_sync(~0u, rs1, t * 8 + 4);
            const uint32_t stg = sb + SM_STG + wg * 8192 + lane * 16;
            if (!qok) mbar_wait(BAR(B_WQF), 0);
            QCHUNK(0, QC0);
            wg_wait<1>();
            reg_fence(ak); reg_fence(av);
            uint32_t kf[3][7], vf[3][7];
            #pragma unroll
            for (int c = 0; c < 7; c++) {
                kf[2][c] = pack_bf16(ak[4 * c + 2], ak[4 * c + 3]);
                vf[2][c] = movm(pack_bf16(av[4 * c + 2], av[4 * c + 3]));
            }
            const uint32_t om = ~lane & 1;
            kf[2][0] = set_par(kf[2][0], om, tag); vf[2][0] = set_par(vf[2][0], om, tag);
            vf[2][1] = set_par(vf[2][1], om, tag); vf[2][5] = set_par(vf[2][5], om, tag);
            auto publish = [&](auto st) {
                st(0, kf[2][0], kf[2][1], kf[2][2], kf[2][3]);
                st(1, vf[2][0], kf[2][4], kf[2][5], kf[2][6]);
                st(2, vf[2][1], vf[2][2], vf[2][3], vf[2][4]);
                st(3, vf[2][5], vf[2][6], __float_as_uint(rk[2][0]), __float_as_uint(rk[2][1]));
            };
            if (w < 3 || rank) publish([&](int c, uint32_t x, uint32_t y, uint32_t z, uint32_t v) { st_gen4(hp + c * 32, x, y, z, v); });
            else publish([&](int c, uint32_t x, uint32_t y, uint32_t z, uint32_t v) {
                asm volatile("st.async.shared::cluster.mbarrier::complete_tx::bytes.v4.b32 [%0], {%2,%3,%4,%5}, [%1];"
                             :: "r"(pbar0 + (SM_STG + 3 * 2048 - SM_BAR) + wg * 8192 + lane * 16 + c * 512), "r"(pbar0 + (B_HL + wg) * 8),
                                "r"(x), "r"(y), "r"(z), "r"(v) : "memory");
            });
            pair_arrive(B_KVC);
            QCHUNK(QC0, QC1);
            #pragma unroll
            for (int c = 0; c < 7; c++) {
                kf[1][c] = pack_bf16(ak[4 * c], ak[4 * c + 1]);
                vf[1][c] = movm(pack_bf16(av[4 * c], av[4 * c + 1]));
            }
            QCHUNK(QC1, QC2);
            named_bar(1 + wg, 128);
            uint32_t* op = opaque_ptr((uint32_t*)&prm.sc->o[((ti * 2 + wg) * 56 + hg * 7) * 64] + w * 64 + lane);
            om0 = opaque((lane & 7) == w * 2); om1 = opaque((lane & 7) == w * 2 + 1);
            QCHUNK(QC2, 28);
            warp_arrive(BAR(B_QL));
            #undef QCHUNK
            const bool gt0 = 2 * t > g, gt1 = 2 * t + 1 > g, no_prev = ti == 0 && w == 0;
            const float kf0 = gt0 ? rk[1][0] : rk[2][0], kf1 = gt1 ? rk[1][1] : rk[2][1];
            constexpr float kScale = 0.18898223650461362f * 1.4426950408889634f;
            const float sq0 = rs0 * kScale, sf0 = kf0 * (rs1 * kScale), sf1 = kf1 * (rs1 * kScale);
            const float NEG = -__int_as_float(0x7f800000);
            const float nb0 = gt0 && no_prev ? NEG : 0.f, nb1 = gt1 && no_prev ? NEG : 0.f;
            const uint32_t mk = opaque((gt0 ? 0x0000ffffu : 0u) | (gt1 ? 0xffff0000u : 0u));
            const uint32_t nil = __shfl_sync(~0u, lane, 0);
            const uint32_t sr = stg + ((w + 3) & 3) * 2048, hbar = BAR(w == 0 ? B_HL + wg : B_EP);
            mbar_wait(BAR(B_EP), 0);
            wg_wait<0>();
            reg_fence(aq);
            warp_arrive(BAR(B_A1D));
            uint32_t qf[8][2];
            #pragma unroll
            for (int c = 0; c < 7; c++) {
                qf[c + (c > 3)][0] = pack_bf16(aq[4 * c], aq[4 * c + 1]);
                qf[c + (c > 3)][1] = pack_bf16(aq[4 * c + 2], aq[4 * c + 3]);
            }
            qf[4][0] = t >= 2 ? qf[3][0] : 0u; qf[4][1] = t >= 2 ? qf[3][1] : 0u;
            qf[3][0] = t < 2 ? qf[3][0] : 0u;  qf[3][1] = t < 2 ? qf[3][1] : 0u;
            float sc[2][3][4];
            auto scores = [&](int n) {
                #pragma unroll
                for (int hd = 0; hd < 2; hd++) {
                    sc[hd][n][0] = sc[hd][n][1] = sc[hd][n][2] = sc[hd][n][3] = 0.f;
                    mma16816(sc[hd][n], qf[4 * hd][0], qf[4 * hd][1], qf[4 * hd + 1][0], qf[4 * hd + 1][1], kf[n][3 * hd], kf[n][3 * hd + 1]);
                    mma16816(sc[hd][n], qf[4 * hd + 2][0], qf[4 * hd + 2][1], qf[4 * hd + 3][0], qf[4 * hd + 3][1], kf[n][3 * hd + 2], kf[n][3 * hd + 3]);
                }
            };
            scores(1); scores(2);
            mbar_wait(hbar, 0);
            {
                const uint4 u0 = lds4(sr), u1 = lds4(sr + 512), u3 = lds4(sr + 1536), u2 = lds4(sr + 1024);
                kf[0][0] = u0.x; kf[0][1] = u0.y; kf[0][2] = u0.z; kf[0][3] = u0.w;
                vf[0][0] = u1.x; kf[0][4] = u1.y; kf[0][5] = u1.z; kf[0][6] = u1.w;
                vf[0][1] = u2.x; vf[0][2] = u2.y; vf[0][3] = u2.z; vf[0][4] = u2.w;
                vf[0][5] = u3.x; vf[0][6] = u3.y; rk[0][0] = __uint_as_float(u3.z); rk[0][1] = __uint_as_float(u3.w);
            }
            scores(0);
            const float ke0 = gt0 ? rk[0][0] : rk[1][0], ke1 = gt1 ? rk[0][1] : rk[1][1];
            const float se0 = ke0 * sq0, se1 = ke1 * sq0;
            uint32_t ow[7][2];
            #pragma unroll
            for (int hd = 0; hd < 2; hd++) {
                const int c0 = hd * 3;
                float (&sc_)[3][4] = sc[hd];
                const float e0 = fmaf(gt0 ? sc_[0][0] : sc_[1][0], se0, nb0), e1 = fmaf(gt1 ? sc_[0][1] : sc_[1][1], se1, nb1);
                const float f0 = (gt0 ? sc_[1][2] : sc_[2][2]) * sf0, f1 = (gt1 ? sc_[1][3] : sc_[2][3]) * sf1;
                const float me = quad_max(fmaxf(e0, e1)), mf = quad_max(fmaxf(f0, f1));
                const float p0 = ex2(e0 - me), p1 = ex2(e1 - me), r0 = ex2(f0 - mf), r1 = ex2(f1 - mf);
                const float ie = rcp(quad_sum(p0 + p1)), jf = rcp(quad_sum(r0 + r1));
                const uint32_t pp = pack_bf16(p0 * ke0 * ie, p1 * ke1 * ie), rp = pack_bf16(r0 * kf0 * jf, r1 * kf1 * jf);
                const uint32_t a0 = pp & ~mk, a1 = rp & mk, a3 = rp & ~mk, a4 = pp & mk, zero = pp & nil, zero2 = rp & nil;
                #pragma unroll
                for (int c = 0; c < 4; c++) {
                    float o[4] = {0.f, 0.f, 0.f, 0.f};
                    mma16816(o, a0, a1, zero, a3, vf[1][c0 + c], vf[2][c0 + c]);
                    mma1688(o, a4, zero2, vf[0][c0 + c]);
                    const uint32_t lo = pack_bf16(o[0], o[1]), hi = pack_bf16(o[2], o[3]);
                    if (hd == 1 && c == 0) { if (t >= 2) { ow[3][0] = lo; ow[3][1] = hi; } }
                    else { ow[c0 + c][0] = lo; ow[c0 + c][1] = hi; }
                }
            }
            #pragma unroll
            for (int c = 0; c < 7; c++) {
                stg1(op + c * 256,      set_par(ow[c][0], om0, tag));
                stg1(op + c * 256 + 32, set_par(ow[c][1], om1, tag));
            }
        }
        float as[28], ac[28];
        uint32_t xch, peer_xch, *gp1, *gp2;
        const uint32_t *hp, *ht;
        const uint2* hq;
        uint64_t da0, db0;
        bool lead;
        {
            float acc2[28];
            mbar_wait(BAR(B_XRF), 0);
            const int cg = a2j * 2 + wg, cg2 = (g2j + 2 * wg) * 2 + (rank ^ 1), cg1 = (g1j + 2 * wg) * 2 + (rank ^ (g1f < 14));
            lead = elect_one();
            {
                const uint32_t xa = sb + SM_XR + wg * 8192 + (w * 16 + (lane & 15)) * 128;
                #pragma unroll
                for (int c = 0; c < 4; c++) {
                    uint32_t xr[4];
                    asm volatile("ldmatrix.sync.aligned.m8n8.x4.shared.b16 {%0,%1,%2,%3}, [%4];"
                                 : "=r"(xr[0]), "=r"(xr[1]), "=r"(xr[2]), "=r"(xr[3])
                                 : "r"(xa + ((((c * 2 + wg + (lane >> 4)) ^ lane) & 7) << 4)) : "memory");
                    #pragma unroll
                    for (int e = 0; e < (c < 3 ? 4 : 2); e++) { acc2[8 * c + 2 * e] = bf_lo(xr[e]); acc2[8 * c + 2 * e + 1] = bf_hi(xr[e]); }
                }
            }
            uint32_t* spw = opaque_ptr(&prm.sc->stats[((a2s * 8 + cg) * 4 + w) * 32 + lane]);
            const uint32_t* spr = opaque_ptr(&prm.sc->stats[(a2s * 32 + w) * 32 + lane]);
            uint32_t* rp = opaque_ptr((uint32_t*)&prm.sc->rows[a2s * 64 + w * 16 + (t >> 1) * 8 + g] + (t & 1));
            const int cgs = cg ^ (a2s >> 4);
            uint32_t* np = opaque_ptr((uint32_t*)&prm.sc->hn[(a2s * 56 + cgs * 7) * 64] + w * 64 + lane);
            const uint64_t dwo = make_desc(sb + SM_WKV + wg * (28672 + 16), 0, true);
            const uint64_t doa = make_desc(sb + SM_WQ, 1024, false, 128);
            bias1a = prm.b1[g1f * 64 + w * 16 + g]; bias1b = prm.b1[g1f * 64 + w * 16 + 8 + g];
            const __nv_bfloat16 bias2 = prm.b2[ti * 128 + (w * 16 + (t >> 1) * 8 + g) * 2 + a2p];
            reg_fence(acc2);
            fence_async_smem();
            warp_arrive(BAR(B_XD));
            mbar_wait2(BAR(B_WOF), 0, BAR(B_WOF + 1), 0);
            mbar_wait(BAR(B_OD), 0);
            const uint32_t order = __shfl_sync(~0u, lds1(sb + SM_ORD), 0);
            static_for<0, 4>([&](auto P_) {
                constexpr int P = decltype(P_)::value;
                const uint64_t dwp = dwo + ((order >> (2 * P + 1) & 1) * 3584 + (order >> 2 * P & 1) * 896);
                if (P == 0 && wg) mbar_wait(BAR(B_OF + 1), 0);
                mbar_wait(BAR(B_OF + P), 0);
                wg_fence();
                static_for<0, 7>([&](auto K_) { constexpr int k = decltype(K_)::value;
                    wgmma_ss_n56<P * 14336 + k * 2048, k * 2048, 0>(acc2, doa, dwp); });
                if (P) wg_commit();
                if (P == 2) { wg_wait<1>(); warp_arrive(BAR(B_OC)); }
            });
            wg_wait<0>();
            reg_fence(acc2);
            float s0 = 0.f, s1 = 0.f, q0 = 0.f, q1 = 0.f;
            #pragma unroll
            for (int c = 0; c < 7; c++) {
                s0 += acc2[4 * c] + acc2[4 * c + 1];     q0 = fmaf(acc2[4 * c], acc2[4 * c], fmaf(acc2[4 * c + 1], acc2[4 * c + 1], q0));
                s1 += acc2[4 * c + 2] + acc2[4 * c + 3]; q1 = fmaf(acc2[4 * c + 2], acc2[4 * c + 2], fmaf(acc2[4 * c + 3], acc2[4 * c + 3], q1));
            }
            const bool th = t >= 2, to = t & 1;
            const float sa = (th ? s1 : s0) + __shfl_xor_sync(~0u, th ? s0 : s1, 2), qa = (th ? q1 : q0) + __shfl_xor_sync(~0u, th ? q0 : q1, 2);
            const float part = (to ? qa : sa) + __shfl_xor_sync(~0u, to ? sa : qa, 1);
            stg1(spw, set_par(__float_as_uint(part), 1u, tag));
            const uint32_t tpoll = clk32() + SDELAY;
            warp_arrive(BAR(B_HD));
            uint32_t us[8];
            {
                xch = opaque(sb + SM_XCH + w * 1792 + lane * 16);
                asm volatile("mapa.shared::cluster.u32 %0, %1, %2;" : "=r"(peer_xch) : "r"(xch), "r"(rank ^ 1));
                const int hcg = cg2 ^ (g2s >> 4), hrg = (g2s & 1) * 4 + w;
                const uint32_t* hl = (const uint32_t*)&prm.sc->hn[((g2s >> 1) * 112 + hcg * 7) * 64 + hrg * 8];
                hp = opaque_ptr(hl + (g & 1) * 14336 + (g >> 1) * 4 + t);
                ht = opaque_ptr(hl + min(lane >> 2, 6) * 256 + (lane & 3) * 8 + hrg);
                hq = opaque_ptr(&prm.sc->rows[((g2s >> 1) * 2 + (g & 1)) * 64 + hrg * 8 + (g >> 1)]);
                gp1 = opaque_ptr((uint32_t*)&prm.sc->g[(g1f * 56 + cg1 * 7) * 64] + w * 64 + lane);
                gp2 = opaque_ptr((uint32_t*)(prm.out + (size_t)(g2s * 64 + w * 16 + lane / 7) * kD + cg2 * 56) + (lane % 7) * 4);
                da0 = make_desc(sb, 0, true); db0 = make_desc(sb + SM_B, 128, false);
            }
            spin_until(tpoll);
            #pragma unroll
            for (int i = 0; i < 8; i++) us[i] = ld_rlx(spr + i * 128);
            {
                int it = 0;
                while (true) {
                    uint32_t bad = 0;
                    #pragma unroll
                    for (int i = 0; i < 8; i++) bad |= us[i] ^ tag;
                    if (!__any_sync(~0u, bad & 1)) break;
                    if (++it > kSpinLimit) break;
                    #pragma unroll
                    for (int i = 0; i < 8; i++) us[i] = ld_rlx(spr + i * 128);
                }
            }
            const float tot = (((__uint_as_float(us[0]) + __uint_as_float(us[1])) + (__uint_as_float(us[2]) + __uint_as_float(us[3])))
                            + ((__uint_as_float(us[4]) + __uint_as_float(us[5])) + (__uint_as_float(us[6]) + __uint_as_float(us[7])))) * (1.f / kD);
            const float oth = __shfl_xor_sync(~0u, tot, 1);
            const float mean = to ? oth : tot;
            const float var = fmaxf(fmaf(-mean, mean, to ? tot : oth), 0.f);
            const float rra = rsq(fmaf(var, 4.f + 4.f * kEps, 4.f * kEps * kEps)), mra = -mean * rra;
            const float rrb = __shfl_xor_sync(~0u, rra, 2), mrb = __shfl_xor_sync(~0u, mra, 2);
            const float rr0 = th ? rrb : rra, mr0 = th ? mrb : mra, rr1 = th ? rra : rrb, mr1 = th ? mra : mrb;
            #pragma unroll
            for (int c = 0; c < 7; c++) {
                stg1(np + c * 256,      set_par(pack_bf16(fmaf(acc2[4 * c], rr0, mr0), fmaf(acc2[4 * c + 1], rr0, mr0)), om0, tag));
                stg1(np + c * 256 + 32, set_par(pack_bf16(fmaf(acc2[4 * c + 2], rr1, mr1), fmaf(acc2[4 * c + 3], rr1, mr1)), om1, tag));
            }
            if (cg == 0) stg1(rp, set_par(__float_as_uint(to ? mean + __bfloat162float(bias2) : rcp(rra)), 1u, tag));
            #pragma unroll
            for (int c = 0; c < 28; c++) { ac[c] = 0.5f * __bfloat162float(c & 2 ? bias1b : bias1a); as[c] = 0.f; }
            reg_fence(as); reg_fence(ac);
        }
        auto send = [&]() {
            const uint32_t rf = pbar0 + (B_RF + warp) * 8;
            #pragma unroll
            for (int c = 0; c < 4; c++) {
                const uint32_t p0 = pack_bf16(as[8 * c], as[8 * c + 1]), p1 = pack_bf16(as[8 * c + 2], as[8 * c + 3]);
                if (c < 3) {
                    const uint32_t p2 = pack_bf16(as[8 * c + 4], as[8 * c + 5]), p3 = pack_bf16(as[8 * c + 6], as[8 * c + 7]);
                    asm volatile("st.async.shared::cluster.mbarrier::complete_tx::bytes.v4.b32 [%0], {%1,%2,%3,%4}, [%5];"
                                 :: "r"(peer_xch + c * 512), "r"(p0), "r"(p1), "r"(p2), "r"(p3), "r"(rf) : "memory");
                } else {
                    asm volatile("st.async.shared::cluster.mbarrier::complete_tx::bytes.v2.b32 [%0], {%1,%2}, [%3];"
                                 :: "r"(peer_xch + 1536 - lane * 8), "r"(p0), "r"(p1), "r"(rf) : "memory");
                }
            }
        };
        auto receive = [&](uint32_t (&pk)[14], uint32_t phase) {
            mbar_wait(BAR(B_RF + warp), phase);
            #pragma unroll
            for (int c = 0; c < 3; c++) { const uint4 u = lds4(xch + c * 512); pk[4 * c] = u.x; pk[4 * c + 1] = u.y; pk[4 * c + 2] = u.z; pk[4 * c + 3] = u.w; }
            const uint2 u = lds2(xch + 1536 - lane * 8); pk[12] = u.x; pk[13] = u.y;
        };
        uint2 rw[2]; uint32_t tw, tx;
        auto load_rows = [&]() { tw = ld_rlx(ht); tx = ld_rlx(ht + 14336); rw[0] = ld_rlx2(hq); rw[1] = ld_rlx2(hq + 4); };
        rw[0] = rw[1] = make_uint2(0u, 0u); tw = tx = ~tag;
        #pragma unroll 1
        for (int ge = 0;; ge++) {
          if (ge || g1_on) {
            const int use = ge * 2 + wg;
            int entry = ge ? 1 : 2 * wg, stop = 0;
            uint64_t da = da0 + (ge ? -3 : wg ? NR - 10 : 0) * 512;
            bool rel = lead && use == 1;
            const uint32_t xfree = BAR(use > (g1_on ? 0 : 2) ? B_RE + use - 1 : B_PD);
            mbar_wait(BAR(B_AF), 0);
            if (ge && (wg || g1_on)) named_bar(5 - wg, 256);
            auto step = [&](auto I_) {
                constexpr int i = decltype(I_)::value, sl = i % NB, ao = i * 8192, bo = sl * 14336;
                mbar_wait_fast(BAR(B_BF + sl), i / NB);
                wg_fence();
                wgmma_ss_n112<ao,        bo,       1>(as, ac, da, db0);
                wgmma_ss_n112<ao + 2048, bo + 256, 1>(as, ac, da, db0);
                wgmma_ss_n112<ao + 4096, bo + 512, 1>(as, ac, da, db0);
                wgmma_ss_n112<ao + 6144, bo + 768, 1>(as, ac, da, db0);
                wg_commit();
                if (i == 1 && stop == 1) named_arrive(4, 256);
                if (i == 3 && (use == 1 || use == 2)) named_arrive(4 + wg, 256);
                wg_wait<1>();
                mbar_arrive_if(BAR(B_BE + (13 + i) % 14), rel);
                rel = lead;
            };
            #pragma unroll 1
            while (true) {
                if (entry < 1) {
                    static_for<0, 2>(step);
                    if (stop == 1) break;
                    static_for<2, 4>(step);
                    if (stop) break;
                }
                if (entry < 2) static_for<4, 10>(step);
                else {
                    uint32_t af[NR * 4][4];
                    mbar_wait(BAR(B_GO), 0);
                    const uint32_t tp = lds1(sb + SM_TG + 4) + PLOFF;
                    int it = 0;
                    while ((int)(gtime32() - tp) < 0 && ++it < 256) __nanosleep(20);
                    const uint32_t la = sb + ((lane >> 4) * 8 + (lane & 7)) * 128 + (((w * 2 + ((lane >> 3) & 1)) ^ (lane & 7)) << 4);
                    #pragma unroll
                    for (int k = 0; k < NR * 4; k++)
                        asm volatile("ldmatrix.sync.aligned.m8n8.x4.trans.shared.b16 {%0,%1,%2,%3}, [%4];"
                                     : "=r"(af[k][0]), "=r"(af[k][1]), "=r"(af[k][2]), "=r"(af[k][3]) : "r"(la + k * 2048) : "memory");
                    __syncwarp();
                    mbar_arrive_if(BAR(B_PL), lead);
                    if (w == 0) {
                        const char* p2 = (const char*)prm.w2 + ((b >> 6) * 896 + (b & 63) + PFW * 64) * 4096 + lane * 128;
                        #pragma unroll 1
                        for (int i = 0; i < 14 - PFW; i++) {
                            it = 0;
                            while ((int)(gtime32() - tp) < PF3OFF + i * PF3PACE && ++it < 256) __nanosleep(40);
                            asm volatile("prefetch.global.L2 [%0];" :: "l"(p2 + i * 64 * 4096));
                        }
                    }
                    named_bar(4, 256);
                    static_for<0, NR>([&](auto I_) {
                        constexpr int i = decltype(I_)::value, sl = (16 + i) % NB, o = sl * 14336;
                        mbar_wait_fast(BAR(B_BF + sl), (16 + i) / NB & 1);
                        wg_fence();
                        wgmma_rs_n112<o,       1>(as, ac, af[4 * i][0], af[4 * i][1], af[4 * i][2], af[4 * i][3], db0);
                        wgmma_rs_n112<o + 256, 1>(as, ac, af[4 * i + 1][0], af[4 * i + 1][1], af[4 * i + 1][2], af[4 * i + 1][3], db0);
                        wgmma_rs_n112<o + 512, 1>(as, ac, af[4 * i + 2][0], af[4 * i + 2][1], af[4 * i + 2][2], af[4 * i + 2][3], db0);
                        wgmma_rs_n112<o + 768, 1>(as, ac, af[4 * i + 3][0], af[4 * i + 3][1], af[4 * i + 3][2], af[4 * i + 3][3], db0);
                        wg_commit();
                        if (i) { wg_wait<1>(); mbar_arrive_if(BAR(B_BE + (15 + i) % (2 * NB)), lead); }
                    });
                }
                static_for<10, 14>(step);
                entry = 0; stop = use + 1; da += 14 * 512;
            }
            const uint32_t prev = BAR(B_BE + (use ? 3 : 1));
            const bool xok = mbar_test(xfree, 0);
            wg_wait<0>();
            reg_fence(as); reg_fence(ac);
            mbar_arrive_if(prev, lead);
            if (!xok) mbar_wait(xfree, 0);
            if (ge) break;
            send();
            load_rows();
            uint32_t pk[14];
            receive(pk, 0);
            #pragma unroll
            for (int c = 0; c < 14; c++) {
                float r[2];
                #pragma unroll
                for (int e = 0; e < 2; e++) {
                    const float u = ac[2 * c + e] + (e ? bf_hi(pk[c]) : bf_lo(pk[c]));
                    r[e] = fmaf(u, tanh_hw(u * fmaf(u * u, 8.f * 0.7978845608f * 0.044715f, 2.f * 0.7978845608f)), u);
                }
                stg1(gp1 + (c >> 1) * 256 + (c & 1) * 32, set_par(pack_bf16(r[0], r[1]), c & 1 ? om1 : om0, tag));
            }
            named_bar(1 + wg, 128);
            if (w == 0 && lane == 0) {
                asm volatile("st.shared.u32 [%0], %1;" :: "r"(sb + SM_TG + 8 + wg * 4), "r"(clk32() + (wg ? XSPECB : XSPEC)) : "memory");
                mbar_arrive(BAR(B_GD + wg));
            }
            if (lead) mbar_expect(BAR(B_RF + warp), 1792);
            mbar_arrive_remote_if(pbar0 + (B_RE + wg) * 8, lead);
          } else mbar_wait(BAR(B_GD), 0);
            {
                int it = 0;
                while (__any_sync(~0u, ((tw ^ tag) | (tx ^ tag) | (rw[0].x ^ tag) | (rw[0].y ^ tag) | (rw[1].x ^ tag) | (rw[1].y ^ tag)) & 1)) {
                    if (++it > kSpinLimit) break;
                    load_rows();
                }
                uint32_t hw[14];
                #pragma unroll
                for (int c = 0; c < 14; c++) hw[c] = ld_rlx(hp + (c >> 1) * 256 + (c & 1) * 16);
                #pragma unroll
                for (int c = 0; c < 14; c++) {
                    ac[2 * c]     = fmaf(bf_lo(hw[c]), __uint_as_float(rw[c & 1].x), __uint_as_float(rw[c & 1].y));
                    ac[2 * c + 1] = fmaf(bf_hi(hw[c]), __uint_as_float(rw[c & 1].x), __uint_as_float(rw[c & 1].y));
                    as[2 * c] = as[2 * c + 1] = 0.f;
                }
                reg_fence(as); reg_fence(ac);
            }
        }
        uint32_t po[14], pk[14];
        if (!wg) sleep_until(clk32() + w * STAG2);
        send();
        #pragma unroll
        for (int c = 0; c < 14; c++) po[c] = opaque(pack_bf16(ac[2 * c], ac[2 * c + 1]));
        receive(pk, g1_on);
        #pragma unroll
        for (int c = 0; c < 14; c++) pk[c] = add_bf16x2(po[c], pk[c]);
        __syncwarp();
        const uint32_t sa = xch - lane * 16 + (lane & 15) * 112 + (lane >> 4) * 16;
        #pragma unroll
        for (int m = 0; m < 3; m++)
            asm volatile("stmatrix.sync.aligned.m8n8.x4.shared.b16 [%0], {%1,%2,%3,%4};"
                         :: "r"(sa + m * 32), "r"(pk[4 * m]), "r"(pk[4 * m + 1]), "r"(pk[4 * m + 2]), "r"(pk[4 * m + 3]) : "memory");
        asm volatile("stmatrix.sync.aligned.m8n8.x2.shared.b16 [%0], {%1,%2};" :: "r"(sa + 96), "r"(pk[12]), "r"(pk[13]) : "memory");
        __syncwarp();
        if (lane < 28) {
            #pragma unroll
            for (int i = 0; i < 4; i++) { const uint4 u = lds4(xch + i * 448); stg4(gp2 + i * 896, u.x, u.y, u.z, u.w); }
        }
        __syncwarp();
        mbar_arrive_remote_if(pbar0 + (B_RE + 2) * 8, lead && wg == 0);
        if (b == 0 && tid == 128) prm.sc->epoch = tag;
    }
}

typedef CUresult (*EncodeFn)(CUtensorMap*, CUtensorMapDataType, cuuint32_t, void*, const cuuint64_t*, const cuuint64_t*,
                             const cuuint32_t*, const cuuint32_t*, CUtensorMapInterleave, CUtensorMapSwizzle,
                             CUtensorMapL2promotion, CUtensorMapFloatOOBfill);

void make_map(EncodeFn enc, CUtensorMap* m, const void* base, uint64_t cols, uint64_t rows, uint32_t box_rows) {
    cuuint64_t dims[2] = {cols, rows};
    cuuint64_t strides[1] = {cols * 2};
    cuuint32_t box[2] = {64, box_rows};
    cuuint32_t es[2] = {1, 1};
    enc(m, CU_TENSOR_MAP_DATA_TYPE_BFLOAT16, 2, const_cast<void*>(base), dims, strides, box, es, CU_TENSOR_MAP_INTERLEAVE_NONE,
        CU_TENSOR_MAP_SWIZZLE_128B, CU_TENSOR_MAP_L2_PROMOTION_L2_128B, CU_TENSOR_MAP_FLOAT_OOB_FILL_NONE);
}

}

extern "C" void kernel_launch(void* const* d_in, const int* in_sizes, int n_in, void* d_out, int out_size) {
    (void)in_sizes; (void)n_in; (void)out_size;
    void* fn = nullptr;
    cudaDriverEntryPointQueryResult qr;
    cudaGetDriverEntryPoint("cuTensorMapEncodeTiled", &fn, cudaEnableDefault, &qr);
    EncodeFn enc = (EncodeFn)fn;
    CUtensorMap mX2, mX, mWqkv, mWo, mW1, mW2;
    {
        cuuint64_t dims[3] = {kD, kS / 2, 2}, strides[2] = {4 * kD, 2 * kD};
        cuuint32_t box[3] = {64, 64, 2}, es[3] = {1, 1, 1};
        enc(&mX2, CU_TENSOR_MAP_DATA_TYPE_BFLOAT16, 3, d_in[0], dims, strides, box, es, CU_TENSOR_MAP_INTERLEAVE_NONE,
            CU_TENSOR_MAP_SWIZZLE_128B, CU_TENSOR_MAP_L2_PROMOTION_L2_128B, CU_TENSOR_MAP_FLOAT_OOB_FILL_NONE);
    }
    make_map(enc, &mX, d_in[0], 2 * kD, kS / 2, 64);
    make_map(enc, &mWqkv, d_in[1], 3 * kD, kD, 64);
    make_map(enc, &mWo, d_in[2], kD, kD, 112);
    make_map(enc, &mW1, d_in[4], 2 * kF, kS / 2, 64);
    make_map(enc, &mW2, d_in[6], kS, kF, 64);
    Params prm;
    prm.x = (const __nv_bfloat16*)d_in[0];
    prm.wqkv = (const __nv_bfloat16*)d_in[1];
    prm.wo = (const __nv_bfloat16*)d_in[2];
    prm.w1 = (const __nv_bfloat16*)d_in[4];
    prm.b1 = (const __nv_bfloat16*)d_in[5];
    prm.w2 = (const __nv_bfloat16*)d_in[6];
    prm.b2 = (const __nv_bfloat16*)d_in[7];
    prm.out = (__nv_bfloat16*)d_out;
    cudaGetSymbolAddress((void**)&prm.sc, g_scratch);
    cudaFuncSetAttribute(fused_kernel, cudaFuncAttributeMaxDynamicSharedMemorySize, SM_TOTAL);
    fused_kernel<<<128, 384, SM_TOTAL, cudaStreamPerThread>>>(prm, mX2, mX, mWqkv, mWo, mW1, mW2);
}
```
